```python
import torch

def _softmax(x, axis=-1):
    return torch.softmax(x, dim=axis)

def _gelu(x):
    return torch.nn.functional.gelu(x, approximate='tanh')

def _silu(x):
    return torch.nn.functional.silu(x)

def _sigmoid(x):
    return torch.sigmoid(x)

def _layernorm(x, axis=-1, eps=1e-05):
    m = x.mean(dim=axis, keepdim=True)
    v = x.var(dim=axis, keepdim=True, unbiased=False)
    return (x - m) / torch.sqrt(v + eps)

def _scatter_add(tgt, idx, src, axis=0):
    return tgt.clone().index_add_(axis, idx, src)

def _segment_sum(src, seg, n):
    out = torch.zeros((n,) + src.shape[1:], dtype=src.dtype)
    return out.index_add_(0, seg, src)

def _pad(x, pw):
    flat = tuple((v for pair in reversed(pw) for v in pair))
    return torch.nn.functional.pad(x, flat)
kernel_name = 'gated_mix__memory_aug_recurrent_mem_tr__swiglu_ffn__prompt'

def setup_inputs():

    _w = lambda a: (lambda t: t.to(torch.bfloat16) if t.is_floating_point() else t)(torch.as_tensor(a))

    def _A_setup():
        B, S, Dm = (1, 2048, 1024)
        H, Dh = (32, 128)
        M, seg = (8, 32)
        seg = min(seg, S)
        S = S // seg * seg
        return {'x': _w((lambda *s: torch.randn(*s, dtype=torch.bfloat16) * 0.05)(B, S, Dm)), 'mem0': _w((lambda *s: torch.randn(*s, dtype=torch.bfloat16) * 0.4)(B, M, Dm)), 'Wq': _w((lambda *s: torch.randn(*s, dtype=torch.bfloat16) * 6.4)(Dm, H, Dh) * Dm ** (-0.5)), 'Wk': _w((lambda *s: torch.randn(*s, dtype=torch.bfloat16) * 6.4)(Dm, H, Dh) * Dm ** (-0.5)), 'Wv': _w((lambda *s: torch.randn(*s, dtype=torch.bfloat16) * 0.4)(Dm, H, Dh) * Dm ** (-0.5)), 'Wo': _w((lambda *s: torch.randn(*s, dtype=torch.bfloat16) * 0.4)(H, Dh, Dm) * (H * Dh) ** (-0.5)), 'seg_len': seg}
    _A_in = _A_setup()

    def _B_setup():
        B, S, D, F = (1, 2048, 1024, 3584)
        return {'x': _w((lambda *s: torch.randn(*s, dtype=torch.bfloat16) * 0.05)(B, S, D)), 'w_gate': _w((lambda *s: torch.randn(*s, dtype=torch.bfloat16) * 0.05)(D, F)), 'w_up': _w((lambda *s: torch.randn(*s, dtype=torch.bfloat16) * 0.05)(D, F)), 'w_down': _w((lambda *s: torch.randn(*s, dtype=torch.bfloat16) * 0.05)(F, D))}
    _B_in = _B_setup()
    return {'A_x': _A_in['x'], 'A_mem0': _A_in['mem0'], 'A_Wq': _A_in['Wq'], 'A_Wk': _A_in['Wk'], 'A_Wv': _A_in['Wv'], 'A_Wo': _A_in['Wo'], 'A_seg_len': _A_in['seg_len'], 'B_x': _B_in['x'], 'B_w_gate': _B_in['w_gate'], 'B_w_up': _B_in['w_up'], 'B_w_down': _B_in['w_down'], 'gate_w': _w((lambda *s: torch.randn(*s, dtype=torch.bfloat16) * 0.05)(1024) * 16.0)}

def reference(A_x, A_mem0, A_Wq, A_Wk, A_Wv, A_Wo, A_seg_len, B_x, B_w_gate, B_w_up, B_w_down, gate_w):

    def _A_ref(x, mem0, Wq, Wk, Wv, Wo, seg_len):
        B, S, Dm = x.shape
        H, Dh = (Wq.shape[1], Wq.shape[2])
        M = mem0.shape[1]
        scale = Dh ** (-0.5)
        n_seg = S // seg_len
        L = M + seg_len
        idx = torch.arange(L)
        mask = (idx[:, None] < M) | (idx[:, None] >= idx[None, :])
        mem = mem0
        outs = []
        for s in range(n_seg):
            xs = x[:, s * seg_len:(s + 1) * seg_len, :].clone()
            h = torch.concatenate([mem, xs], axis=1)
            q = torch.einsum('btd,dhe->bhte', h, Wq)
            k = torch.einsum('btd,dhe->bhte', h, Wk)
            v = torch.einsum('btd,dhe->bhte', h, Wv)
            scores = torch.einsum('bhqe,bhke->bhqk', q, k) * scale
            scores = torch.where(mask[None, None], scores, -1000000000.0)
            p = _softmax(scores, axis=-1)
            o = torch.einsum('bhqk,bhke->bhqe', p, v)
            o = torch.einsum('bhte,hed->btd', o, Wo)
            mem = o[:, :M, :].clone()
            outs.append(o[:, M:, :])
        return torch.concatenate(outs, axis=1)

    def _B_ref(x, w_gate, w_up, w_down):
        g = _silu(x @ w_gate)
        u = x @ w_up
        return g * u @ w_down
    x = A_x
    g = _sigmoid((x * gate_w).sum(-1, keepdims=True))
    a = _A_ref(x, A_mem0, A_Wq, A_Wk, A_Wv, A_Wo, A_seg_len)
    b = _B_ref(x, B_w_gate, B_w_up, B_w_down)
    return g * a + (1 - g) * b
```

```cpp
#include <cuda_runtime.h>
#include <cuda_bf16.h>
#include <cuda.h>
#include <stdint.h>

typedef __nv_bfloat16 bf16;

constexpr int SEQ = 2048, DM = 1024, NH = 32, DH = 128, NMEM = 8, SEG = 32, NSEG = 64, FF = 3584;
constexpr int HD = NH * DH;

__device__ bf16 g_O[SEQ * HD];
__device__ bf16 g_H[SEQ * FF];
__device__ float g_gate[SEQ];
__device__ float g_part[256 * 32 * 32];
__device__ uint32_t g_mem[4][DM * 4];
__device__ float4 g_sk[128 * 16 * 256];
__device__ uint32_t g_skflag[128];

#define DEVINL __device__ __forceinline__
constexpr long long SPIN_LIMIT = 4000000000LL;

DEVINL uint32_t smem_u32(const void* p) { return (uint32_t)__cvta_generic_to_shared(p); }
DEVINL void mbar_init(uint32_t bar, uint32_t cnt) { asm volatile("mbarrier.init.shared::cta.b64 [%0], %1;" ::"r"(bar), "r"(cnt) : "memory"); }
DEVINL void mbar_arrive(uint32_t bar) { asm volatile("mbarrier.arrive.shared::cta.b64 _, [%0];" ::"r"(bar) : "memory"); }
DEVINL void mbar_expect(uint32_t bar, uint32_t bytes) { asm volatile("mbarrier.arrive.expect_tx.shared::cta.b64 _, [%0], %1;" ::"r"(bar), "r"(bytes) : "memory"); }
DEVINL void mbar_arrive_remote(uint32_t cbar) { asm volatile("mbarrier.arrive.relaxed.cluster.shared::cluster.b64 _, [%0];" ::"r"(cbar) : "memory"); }
DEVINL bool mbar_try(uint32_t bar, uint32_t par) {
    uint32_t ok;
    asm volatile("{ .reg .pred p; mbarrier.try_wait.parity.shared::cta.b64 p, [%1], %2; selp.u32 %0, 1, 0, p; }" : "=r"(ok) : "r"(bar), "r"(par) : "memory");
    return ok;
}
__device__ __noinline__ void mbar_wait_slow(uint32_t bar, uint32_t par) {
    long long t0 = clock64();
    while (!mbar_try(bar, par)) { if (clock64() - t0 > SPIN_LIMIT) __trap(); }
}
DEVINL void mbar_wait(uint32_t bar, uint32_t par) {
    uint32_t n = 0;
    while (!mbar_try(bar, par)) { if (++n > 200000000u) __trap(); }
}
DEVINL uint32_t mapa(uint32_t a, uint32_t r) { uint32_t o; asm volatile("mapa.shared::cluster.u32 %0, %1, %2;" : "=r"(o) : "r"(a), "r"(r)); return o; }
DEVINL void fence_async() { asm volatile("fence.proxy.async.shared::cta;" ::: "memory"); }
DEVINL void bar_sync(int id, int n) { asm volatile("bar.sync %0, %1;" ::"r"(id), "r"(n) : "memory"); }
DEVINL void cluster_sync() { asm volatile("barrier.cluster.arrive.aligned; barrier.cluster.wait.aligned;" ::: "memory"); }
DEVINL void tma_load(uint32_t dst, const CUtensorMap* tm, int c0, int c1, uint32_t bar) {
    asm volatile("cp.async.bulk.tensor.2d.shared::cluster.global.mbarrier::complete_tx::bytes [%0], [%1, {%3, %4}], [%2];"
                 ::"r"(dst), "l"(tm), "r"(bar), "r"(c0), "r"(c1) : "memory");
}
DEVINL void tma_prefetch(const CUtensorMap* tm, int c0, int c1) {
    asm volatile("cp.async.bulk.prefetch.tensor.2d.L2.global [%0, {%1, %2}];" ::"l"(tm), "r"(c0), "r"(c1) : "memory");
}
DEVINL void tma_store(const CUtensorMap* tm, uint32_t src, int c0, int c1) {
    asm volatile("cp.async.bulk.tensor.2d.global.shared::cta.bulk_group [%0, {%2, %3}], [%1];" ::"l"(tm), "r"(src), "r"(c0), "r"(c1) : "memory");
}
DEVINL void bulk_commit() { asm volatile("cp.async.bulk.commit_group;" ::: "memory"); }
DEVINL void bulk_wait_read() { asm volatile("cp.async.bulk.wait_group.read 0;" ::: "memory"); }
DEVINL void bulk_wait_all() { asm volatile("cp.async.bulk.wait_group 0;" ::: "memory"); }
DEVINL void bulk_s2s(uint32_t cdst, uint32_t src, uint32_t bytes, uint32_t cbar) {
    asm volatile("cp.async.bulk.shared::cluster.shared::cta.mbarrier::complete_tx::bytes [%0], [%1], %2, [%3];" ::"r"(cdst), "r"(src), "r"(bytes), "r"(cbar) : "memory");
}
DEVINL void st_async16(uint32_t cdst, uint4 v, uint32_t cbar) {
    asm volatile("st.async.shared::cluster.mbarrier::complete_tx::bytes.v4.b32 [%0], {%1,%2,%3,%4}, [%5];" ::"r"(cdst), "r"(v.x), "r"(v.y), "r"(v.z), "r"(v.w), "r"(cbar) : "memory");
}
DEVINL uint64_t mkdesc(uint32_t addr, uint32_t lbo, uint32_t sbo, uint32_t swz) {
    return (uint64_t)((addr & 0x3FFFF) >> 4) | ((uint64_t)(lbo >> 4) << 16) | ((uint64_t)(sbo >> 4) << 32) | ((uint64_t)swz << 62);
}
DEVINL void wg_fence() { asm volatile("wgmma.fence.sync.aligned;" ::: "memory"); }
DEVINL void wg_commit() { asm volatile("wgmma.commit_group.sync.aligned;" ::: "memory"); }
template <int N> DEVINL void wg_wait() { asm volatile("wgmma.wait_group.sync.aligned %0;" ::"n"(N) : "memory"); }
DEVINL uint32_t pack_bf16(float lo, float hi) { uint32_t r; asm("cvt.rn.bf16x2.f32 %0, %1, %2;" : "=r"(r) : "f"(hi), "f"(lo)); return r; }
DEVINL void ldsm4(uint32_t* r, uint32_t a) { asm volatile("ldmatrix.sync.aligned.m8n8.x4.shared.b16 {%0,%1,%2,%3}, [%4];" : "=r"(r[0]), "=r"(r[1]), "=r"(r[2]), "=r"(r[3]) : "r"(a) : "memory"); }
DEVINL void ldsm4t(uint32_t* r, uint32_t a) { asm volatile("ldmatrix.sync.aligned.m8n8.x4.trans.shared.b16 {%0,%1,%2,%3}, [%4];" : "=r"(r[0]), "=r"(r[1]), "=r"(r[2]), "=r"(r[3]) : "r"(a) : "memory"); }
DEVINL void stsm4(uint32_t a, uint32_t r0, uint32_t r1, uint32_t r2, uint32_t r3) { asm volatile("stmatrix.sync.aligned.m8n8.x4.shared.b16 [%0], {%1,%2,%3,%4};" ::"r"(a), "r"(r0), "r"(r1), "r"(r2), "r"(r3) : "memory"); }
DEVINL void sts32(uint32_t a, uint32_t v) { asm volatile("st.shared.b32 [%0], %1;" ::"r"(a), "r"(v) : "memory"); }
DEVINL void sts128(uint32_t a, uint4 v) { asm volatile("st.shared.v4.b32 [%0], {%1,%2,%3,%4};" ::"r"(a), "r"(v.x), "r"(v.y), "r"(v.z), "r"(v.w) : "memory"); }
DEVINL uint4 lds128(uint32_t a) { uint4 v; asm volatile("ld.shared.v4.b32 {%0,%1,%2,%3}, [%4];" : "=r"(v.x), "=r"(v.y), "=r"(v.z), "=r"(v.w) : "r"(a) : "memory"); return v; }
DEVINL uint4 ld_strong16(const void* p) { uint4 v; asm volatile("ld.relaxed.gpu.global.v4.u32 {%0,%1,%2,%3}, [%4];" : "=r"(v.x), "=r"(v.y), "=r"(v.z), "=r"(v.w) : "l"(p) : "memory"); return v; }
DEVINL void st_strong8(void* p, uint32_t a, uint32_t b) { asm volatile("st.relaxed.gpu.global.v2.u32 [%0], {%1,%2};" ::"l"(p), "r"(a), "r"(b) : "memory"); }
DEVINL void mma16816(float* d, uint32_t a0, uint32_t a1, uint32_t a2, uint32_t a3, uint32_t b0, uint32_t b1) {
    asm volatile("mma.sync.aligned.m16n8k16.row.col.f32.bf16.bf16.f32 {%0,%1,%2,%3}, {%4,%5,%6,%7}, {%8,%9}, {%0,%1,%2,%3};"
                 : "+f"(d[0]), "+f"(d[1]), "+f"(d[2]), "+f"(d[3]) : "r"(a0), "r"(a1), "r"(a2), "r"(a3), "r"(b0), "r"(b1));
}
DEVINL void mma1688(float* d, uint32_t a0, uint32_t a1, uint32_t b0) {
    asm volatile("mma.sync.aligned.m16n8k8.row.col.f32.bf16.bf16.f32 {%0,%1,%2,%3}, {%4,%5}, {%6}, {%0,%1,%2,%3};"
                 : "+f"(d[0]), "+f"(d[1]), "+f"(d[2]), "+f"(d[3]) : "r"(a0), "r"(a1), "r"(b0));
}
template <int TA, int TB> DEVINL void wg_ss8(float* d, uint64_t da, uint64_t db, int sc) {
    asm volatile("{ .reg .pred p; setp.ne.b32 p, %6, 0; wgmma.mma_async.sync.aligned.m64n8k16.f32.bf16.bf16 {%0,%1,%2,%3}, %4, %5, p, 1, 1, %7, %8; }"
                 : "+f"(d[0]), "+f"(d[1]), "+f"(d[2]), "+f"(d[3]) : "l"(da), "l"(db), "r"(sc), "n"(TA), "n"(TB));
}
template <int TB> DEVINL void wg_rs8(float* d, const uint32_t* a, uint64_t db, int sc) {
    asm volatile("{ .reg .pred p; setp.ne.b32 p, %9, 0; wgmma.mma_async.sync.aligned.m64n8k16.f32.bf16.bf16 {%0,%1,%2,%3}, {%4,%5,%6,%7}, %8, p, 1, 1, %10; }"
                 : "+f"(d[0]), "+f"(d[1]), "+f"(d[2]), "+f"(d[3]) : "r"(a[0]), "r"(a[1]), "r"(a[2]), "r"(a[3]), "l"(db), "r"(sc), "n"(TB));
}
#define ACC16(d) "+f"(d[0]), "+f"(d[1]), "+f"(d[2]), "+f"(d[3]), "+f"(d[4]), "+f"(d[5]), "+f"(d[6]), "+f"(d[7]), "+f"(d[8]), "+f"(d[9]), "+f"(d[10]), "+f"(d[11]), "+f"(d[12]), "+f"(d[13]), "+f"(d[14]), "+f"(d[15])
DEVINL void wg_ss32(float* d, uint64_t da, uint64_t db) {
    asm volatile("wgmma.mma_async.sync.aligned.m64n32k16.f32.bf16.bf16 {%0,%1,%2,%3,%4,%5,%6,%7,%8,%9,%10,%11,%12,%13,%14,%15}, %16, %17, 1, 1, 1, 1, 0;"
                 : ACC16(d) : "l"(da), "l"(db));
}
DEVINL void wg_rs32(float* d, const uint32_t* a, uint64_t db, int sc) {
    asm volatile("{ .reg .pred p; setp.ne.b32 p, %21, 0; wgmma.mma_async.sync.aligned.m64n32k16.f32.bf16.bf16 {%0,%1,%2,%3,%4,%5,%6,%7,%8,%9,%10,%11,%12,%13,%14,%15}, {%16,%17,%18,%19}, %20, p, 1, 1, 0; }"
                 : ACC16(d) : "r"(a[0]), "r"(a[1]), "r"(a[2]), "r"(a[3]), "l"(db), "r"(sc));
}
DEVINL void wg_ss40(float* d, uint64_t da, uint64_t db, int sc) {
    asm volatile("{ .reg .pred p; setp.ne.b32 p, %22, 0; wgmma.mma_async.sync.aligned.m64n40k16.f32.bf16.bf16 {%0,%1,%2,%3,%4,%5,%6,%7,%8,%9,%10,%11,%12,%13,%14,%15,%16,%17,%18,%19}, %20, %21, p, 1, 1, 1, 1; }"
                 : ACC16(d), "+f"(d[16]), "+f"(d[17]), "+f"(d[18]), "+f"(d[19]) : "l"(da), "l"(db), "r"(sc));
}
#define A8(d, o) "+f"(d[o]), "+f"(d[o + 1]), "+f"(d[o + 2]), "+f"(d[o + 3]), "+f"(d[o + 4]), "+f"(d[o + 5]), "+f"(d[o + 6]), "+f"(d[o + 7])
#define A32(d, o) A8(d, o), A8(d, o + 8), A8(d, o + 16), A8(d, o + 24)
DEVINL void wg_ss256(float* d, uint64_t da, uint64_t db, int sc) {
    asm volatile(
        "{ .reg .pred p; setp.ne.b32 p, %130, 0;\n"
        "wgmma.mma_async.sync.aligned.m64n256k16.f32.bf16.bf16 {"
        "%0,%1,%2,%3,%4,%5,%6,%7,%8,%9,%10,%11,%12,%13,%14,%15,%16,%17,%18,%19,%20,%21,%22,%23,%24,%25,%26,%27,%28,%29,%30,%31,"
        "%32,%33,%34,%35,%36,%37,%38,%39,%40,%41,%42,%43,%44,%45,%46,%47,%48,%49,%50,%51,%52,%53,%54,%55,%56,%57,%58,%59,%60,%61,%62,%63,"
        "%64,%65,%66,%67,%68,%69,%70,%71,%72,%73,%74,%75,%76,%77,%78,%79,%80,%81,%82,%83,%84,%85,%86,%87,%88,%89,%90,%91,%92,%93,%94,%95,"
        "%96,%97,%98,%99,%100,%101,%102,%103,%104,%105,%106,%107,%108,%109,%110,%111,%112,%113,%114,%115,%116,%117,%118,%119,%120,%121,%122,%123,%124,%125,%126,%127"
        "}, %128, %129, p, 1, 1, 0, 1; }"
        : A32(d, 0), A32(d, 32), A32(d, 64), A32(d, 96) : "l"(da), "l"(db), "r"(sc));
}

constexpr int KR = 44;
constexpr int KS = 64 - KR;
constexpr int R_W = 0;
constexpr int R_WO = KS * 4096;
constexpr int R_QX = R_WO + 65536;
constexpr int R_RING = R_WO + 98304;
constexpr int R_K = R_RING + 24576;
constexpr int R_V = R_K + 10240;
constexpr int R_QM = R_V + 10240;
constexpr int R_O = R_QM + 2048;
constexpr int R_BAR = R_O + 2048;
constexpr int R_SMEM = R_BAR + 256 + 1024;
enum { B_FULL = 0, B_EMPTY = 6, B_MEM = 12, B_HOP1, B_XT, B_TFREE, B_GATE, B_AFREE, B_PRO0, B_PRO1 };

#define PROF(i)

struct RMaps { CUtensorMap x, w[3], wo; };

__global__ void __launch_bounds__(384, 1) r_kernel(const __grid_constant__ RMaps tm, const bf16* __restrict__ mem0) {
    extern __shared__ unsigned char smem_raw[];
    const uint32_t sb = (smem_u32(smem_raw) + 1023) & ~1023u;
    const int tid = threadIdx.x, lane = tid & 31;
    const int wg = __shfl_sync(0xffffffffu, tid >> 7, 0);
    const int warp = __shfl_sync(0xffffffffu, (tid >> 5) & 3, 0);
    uint32_t role; asm volatile("mov.u32 %0, %%cluster_ctarank;" : "=r"(role));
    const int h = blockIdx.x / 3;
    const uint32_t bar = sb + R_BAR;
    const int wo_first = role == 0 ? 0 : (role == 1 ? 4 : 10);
    const int wo_n = role == 0 ? 4 : 6;
    asm volatile("griddepcontrol.launch_dependents;");

    if (tid == 0) {
        for (int i = 0; i < 6; i++) { mbar_init(bar + 8 * (B_FULL + i), 1); mbar_init(bar + 8 * (B_EMPTY + i), 2); }
        mbar_init(bar + 8 * B_MEM, 4);
        mbar_init(bar + 8 * B_HOP1, 9);
        mbar_init(bar + 8 * B_XT, 2);
        mbar_init(bar + 8 * B_TFREE, 12);
        mbar_init(bar + 8 * B_GATE, 4);
        mbar_init(bar + 8 * B_AFREE, 2);
        mbar_init(bar + 8 * B_PRO0, 1);
        mbar_init(bar + 8 * B_PRO1, 1);
        asm volatile("fence.mbarrier_init.release.cluster;" ::: "memory");
        fence_async();
        const CUtensorMap* tw = &tm.w[role];
        mbar_expect(bar + 8 * B_PRO0, KR * 4096);
        for (int rb = 0; rb < KR / 4; rb++)
            for (int t = 0; t < 2; t++) tma_load(sb + (rb * 2 + t) * 8192, tw, h * DH + t * 64, rb * 64, bar + 8 * B_PRO0);
        for (int c = 0; c < 6; c++) {
            int slot = (c + 4) % 6;
            mbar_expect(bar + 8 * (B_FULL + slot), 4096);
            tma_load(sb + R_RING + slot * 4096, &tm.x, c * 64, 0, bar + 8 * (B_FULL + slot));
        }
        for (int rb = KR / 4; rb < 16; rb++)
            for (int t = 0; t < 2; t++) tma_prefetch(tw, h * DH + t * 64, rb * 64);
        for (int i = 0; i < wo_n; i++) tma_prefetch(&tm.wo, (wo_first + i) * 64, h * DH);
        mbar_expect(bar + 8 * B_HOP1, 4096);
        mbar_expect(bar + 8 * B_XT, role == 0 ? 16384 : 8192);
    }
    __syncthreads();
    cluster_sync();

    if (wg < 2) {
        asm volatile("setmaxnreg.inc.sync.aligned.u32 224;");
        uint32_t a[KR][4];
        mbar_wait(bar + 8 * B_PRO0, 0);
        {
            const int krow = (lane & 7) + ((lane >> 4) << 3);
            const int chunk = warp * 2 + ((lane >> 3) & 1);
#pragma unroll
            for (int k = 0; k < KR; k++) {
                int row = (k & 3) * 16 + krow;
                ldsm4t(a[k], sb + ((k >> 2) * 2 + wg) * 8192 + row * 128 + ((chunk ^ (row & 7)) << 4));
            }
        }
        bar_sync(1, 256);
        if (tid == 0) {
            fence_async();
            const CUtensorMap* tw = &tm.w[role];
            mbar_expect(bar + 8 * B_PRO1, KS * 4096 + wo_n * 16384);
            for (int t = 0; t < 2; t++)
                for (int rb = 0; rb < KS / 4; rb++) tma_load(sb + R_W + t * (KS * 2048) + rb * 8192, tw, h * DH + t * 64, KR * 16 + rb * 64, bar + 8 * B_PRO1);
            for (int i = 0; i < wo_n; i++) tma_load(sb + R_WO + i * 16384, &tm.wo, (wo_first + i) * 64, h * DH, bar + 8 * B_PRO1);
        }
        mbar_wait(bar + 8 * B_PRO1, 0);

        uint64_t dW = mkdesc(sb + R_W + wg * (KS * 2048), 1024, 1024, 1);
        uint64_t dM = mkdesc(sb + R_RING, 128, 128, 0);
        uint64_t dX = mkdesc(sb + R_RING, 16, 1024, 1);
        const uint32_t tile = sb + (role == 0 ? R_QM : (role == 1 ? R_K : R_V));
        const uint32_t tilex = role == 0 ? sb + R_QX : tile + 2048;
        const uint32_t peer = (role + 1 + (lane >> 4)) % 3;
        const int frow = wg * 64 + warp * 16;

        for (int s = -1; s < NSEG; s++) {
            if (s >= 0) {
                mbar_wait(bar + 8 * B_MEM, s & 1);
                PROF(wg * 4 + 0);
                asm volatile("" : "+l"(dW), "+l"(dM));
                float d[4];
                wg_fence();
#pragma unroll
                for (int k = 0; k < KR; k++) wg_rs8<1>(d, a[k], dM + (uint64_t)(k * 16), k);
#pragma unroll
                for (int k = 0; k < KS; k++) wg_ss8<1, 1>(d, dW + (uint64_t)(k * 128), dM + (uint64_t)((KR + k) * 16), 1);
                wg_commit();
                wg_wait<0>();
                uint32_t la = tile + (frow + (lane >> 2)) * 16 + (lane & 3) * 4;
                sts32(la, pack_bf16(d[0], d[1]));
                sts32(la + 128, pack_bf16(d[2], d[3]));
                __syncwarp();
                uint32_t ra = tile + (frow + (lane & 15)) * 16;
                uint4 v = lds128(ra);
                st_async16(mapa(ra, peer), v, mapa(bar + 8 * B_HOP1, peer));
                fence_async();
                __syncwarp();
                if (lane == 0) mbar_arrive(bar + 8 * B_HOP1);
                PROF(wg * 4 + 1);
                if (s == NSEG - 1) break;
                bar_sync(1, 256);
                if (tid == 0) {
                    fence_async();
                    for (int c = 2; c < 6; c++) {
                        mbar_expect(bar + 8 * (B_FULL + c - 2), 4096);
                        tma_load(sb + R_RING + (c - 2) * 4096, &tm.x, c * 64, (s + 1) * SEG, bar + 8 * (B_FULL + c - 2));
                    }
                }
                mbar_wait(bar + 8 * B_GATE, s & 1);
                PROF(wg * 4 + 2);
            }
            const int seg = s + 1;
            asm volatile("" : "+l"(dW), "+l"(dX));
            float d[16];
#pragma unroll
            for (int c = 0; c < 16; c++) {
                const int slot = (c + 4) % 6;
                const int use = c / 6 + ((c % 6) < 2 ? 0 : 0);
                const uint32_t par = (slot == 2 || slot == 3) ? (uint32_t)(((c - 2) / 6) & 1) : (uint32_t)((seg + (slot >= 4 ? c / 6 : (c - 2) / 6)) & 1);
                (void)use;
                mbar_wait(bar + 8 * (B_FULL + slot), par);
                wg_fence();
#pragma unroll
                for (int k = 0; k < 4; k++) {
                    const int ks = c * 4 + k;
                    if (ks < KR) wg_rs32(d, a[ks < KR ? ks : 0], dX + (uint64_t)(slot * 256 + k * 2), ks);
                    else wg_ss32(d, dW + (uint64_t)((ks - KR) * 128), dX + (uint64_t)(slot * 256 + k * 2));
                }
                wg_commit();
                if (c >= 1 && c <= 10) {
                    wg_wait<1>();
                    const int pc = c - 1, ps = (pc + 4) % 6;
                    if ((tid & 127) == 0) {
                        mbar_arrive(bar + 8 * (B_EMPTY + ps));
                        if (wg == (pc & 1)) {
                            const uint32_t epar = (ps == 2 || ps == 3) ? (uint32_t)(seg & 1) : (uint32_t)(pc >= 6 ? 1 : 0);
                            mbar_wait(bar + 8 * (B_EMPTY + ps), epar);
                            mbar_expect(bar + 8 * (B_FULL + ps), 4096);
                            tma_load(sb + R_RING + ps * 4096, &tm.x, (pc + 6) * 64, seg * SEG, bar + 8 * (B_FULL + ps));
                        }
                    }
                    __syncwarp();
                }
            }
            wg_wait<0>();
            if ((tid & 127) == 0) mbar_arrive(bar + 8 * B_AFREE);
            if (s >= 0) mbar_wait(bar + 8 * B_TFREE, s & 1);
            {
                uint32_t sa = tilex + (lane >> 4) * 2048 + (frow + (lane & 15)) * 16;
                uint32_t p0 = pack_bf16(d[0], d[1]), p1 = pack_bf16(d[2], d[3]), p2 = pack_bf16(d[4], d[5]), p3 = pack_bf16(d[6], d[7]);
                uint32_t p4 = pack_bf16(d[8], d[9]), p5 = pack_bf16(d[10], d[11]), p6 = pack_bf16(d[12], d[13]), p7 = pack_bf16(d[14], d[15]);
                stsm4(sa, p0, p1, p2, p3);
                stsm4(sa + 4096, p4, p5, p6, p7);
                if (role == 0) { stsm4(sa + 8192, p0, p1, p2, p3); stsm4(sa + 12288, p4, p5, p6, p7); }
            }
            fence_async();
            bar_sync(1, 256);
            if (tid == 0) {
                if (role != 0) {
                    for (uint32_t p = 1; p < 3; p++) { uint32_t pr = (role + p) % 3; bulk_s2s(mapa(tilex, pr), tilex, 8192, mapa(bar + 8 * B_XT, pr)); }
                }
                mbar_arrive(bar + 8 * B_XT);
                if (seg + 1 < NSEG) {
                    for (int c = 0; c < 2; c++) {
                        mbar_expect(bar + 8 * (B_FULL + 4 + c), 4096);
                        tma_load(sb + R_RING + (4 + c) * 4096, &tm.x, c * 64, (seg + 1) * SEG, bar + 8 * (B_FULL + 4 + c));
                    }
                }
            }
        }
    } else {
        asm volatile("setmaxnreg.dec.sync.aligned.u32 56;");
        const int t = tid & 127, g = lane >> 2, c = lane & 3;
        const float sl2 = 0.08838834764831845f * 1.4426950408889634f;
        const float NEGM = -1000000000.0f * 1.4426950408889634f;
        const int cg = (h * 2 + (int)role - 1) * 4 + warp;
        if (role != 0 && lane < 8) st_strong8(&g_mem[3][cg * 16 + lane * 2], 0u, 0u);
        {
            uint4 v[8];
#pragma unroll
            for (int i = 0; i < 8; i++) {
                const unsigned short* p = (const unsigned short*)mem0 + i * 128 + t;
                v[i].x = p[0] | ((uint32_t)p[DM] << 16);
                v[i].y = p[2 * DM] | ((uint32_t)p[3 * DM] << 16);
                v[i].z = p[4 * DM] | ((uint32_t)p[5 * DM] << 16);
                v[i].w = p[6 * DM] | ((uint32_t)p[7 * DM] << 16);
            }
            mbar_wait(bar + 8 * B_AFREE, 0);
#pragma unroll
            for (int i = 0; i < 8; i++) sts128(sb + R_RING + (i * 128 + t) * 16, v[i]);
            fence_async();
            __syncwarp();
            if (lane == 0) mbar_arrive(bar + 8 * B_MEM);
        }
        mbar_wait(bar + 8 * B_PRO1, 0);
        uint64_t dQm = mkdesc(sb + R_QM, 128, 0, 0);
        uint64_t dQx = mkdesc(sb + R_QX, 128, 2048, 0);
        uint64_t dK = mkdesc(sb + R_K, 128, 2048, 0);
        uint64_t dWo = mkdesc(sb + R_WO, 1024, 1024, 1);
        uint64_t dO = mkdesc(sb + R_O, 128, 128, 0);
        const uint32_t tfree = mapa(bar + 8 * B_TFREE, lane < 3 ? lane : 0);

        for (int s = 0; s < NSEG; s++) {
            mbar_wait(bar + 8 * B_XT, s & 1);
            mbar_wait(bar + 8 * B_HOP1, s & 1);
            PROF(8);
            if (t == 0) { mbar_expect(bar + 8 * B_HOP1, 4096); mbar_expect(bar + 8 * B_XT, role == 0 ? 16384 : 8192); }
            fence_async();
            asm volatile("" : "+l"(dQm), "+l"(dK), "+l"(dWo), "+l"(dO), "+l"(dQx));
            if (s < NSEG - 1) {
                float sc[20];
                wg_fence();
#pragma unroll
                for (int k = 0; k < 8; k++) wg_ss40(sc, dQm + (uint64_t)(k * 16), dK + (uint64_t)(k * 16), k);
                wg_commit();
                uint32_t vf[5][4];
#pragma unroll
                for (int j = 0; j < 5; j++) ldsm4(vf[j], sb + R_V + j * 2048 + warp * 512 + lane * 16);
                wg_wait<0>();
                float m = fmaxf(sc[0], sc[1]);
#pragma unroll
                for (int j = 1; j < 5; j++) m = fmaxf(m, fmaxf(sc[4 * j], sc[4 * j + 1]));
                m = fmaxf(m, __shfl_xor_sync(0xffffffffu, m, 1));
                m = fmaxf(m, __shfl_xor_sync(0xffffffffu, m, 2));
                const float mb = m * sl2;
                uint32_t pk[5];
                float l = 0.f;
#pragma unroll
                for (int j = 0; j < 5; j++) {
                    float p0 = exp2f(fmaf(sc[4 * j], sl2, -mb)), p1 = exp2f(fmaf(sc[4 * j + 1], sl2, -mb));
                    l += p0 + p1;
                    pk[j] = pack_bf16(p0, p1);
                }
                float o[4][4];
#pragma unroll
                for (int n = 0; n < 4; n++) {
                    o[n][0] = o[n][1] = o[n][2] = o[n][3] = 0.f;
                    mma16816(o[n], pk[0], 0u, pk[1], 0u, vf[0][n], vf[1][n]);
                    mma16816(o[n], pk[2], 0u, pk[3], 0u, vf[2][n], vf[3][n]);
                    mma1688(o[n], pk[4], 0u, vf[4][n]);
                }
                l += __shfl_xor_sync(0xffffffffu, l, 1);
                l += __shfl_xor_sync(0xffffffffu, l, 2);
                const float inv = 1.0f / l;
#pragma unroll
                for (int n = 0; n < 4; n++) sts32(sb + R_O + (warp * 4 + n) * 128 + g * 16 + c * 4, pack_bf16(o[n][0] * inv, o[n][1] * inv));
                fence_async();
                bar_sync(2, 128);
                PROF(9);
                const uint32_t tag = (uint32_t)(s % 3) + 1u;
                float* pp = g_part + (size_t)h * 32 + (size_t)((wo_first * 16 + warp * 4 + (g >> 2)) * 1024) + (g & 3) * 8 + c * 2;
                float w[6][4];
                wg_fence();
#pragma unroll
                for (int i = 0; i < 6; i++) {
                    if (i < wo_n) {
#pragma unroll
                        for (int k = 0; k < 8; k++) wg_ss8<1, 0>(w[i], dWo + (uint64_t)(i * 1024 + k * 128), dO + (uint64_t)(k * 16), k);
                    }
                    wg_commit();
                }
#define WO_OUT(i) do { wg_wait<5 - i>(); if (i < wo_n) { \
                    st_strong8(pp + i * 16384, (__float_as_uint(w[i][0]) & ~3u) | tag, (__float_as_uint(w[i][1]) & ~3u) | tag); \
                    st_strong8(pp + i * 16384 + 2048, (__float_as_uint(w[i][2]) & ~3u) | tag, (__float_as_uint(w[i][3]) & ~3u) | tag); } } while (0)
                WO_OUT(0); WO_OUT(1); WO_OUT(2); WO_OUT(3); WO_OUT(4); WO_OUT(5);
                if (role != 0 && lane == 0) mbar_arrive(bar + 8 * B_GATE);
                PROF(10);
            }
            if (role == 0) {
                float sc[20];
                wg_fence();
#pragma unroll
                for (int k = 0; k < 8; k++) wg_ss40(sc, dQx + (uint64_t)(k * 16), dK + (uint64_t)(k * 16), k);
                wg_commit();
                wg_wait<0>();
                const int t0 = (warp & 1) * 16 + g;
                float m0 = NEGM, m1 = NEGM;
#pragma unroll
                for (int j = 0; j < 5; j++) {
#pragma unroll
                    for (int e = 0; e < 2; e++) {
                        const int key = (j - 1) * 8 + c * 2 + e;
                        sc[4 * j + e] = (key <= t0) ? sc[4 * j + e] * sl2 : NEGM;
                        sc[4 * j + 2 + e] = (key <= t0 + 8) ? sc[4 * j + 2 + e] * sl2 : NEGM;
                        m0 = fmaxf(m0, sc[4 * j + e]);
                        m1 = fmaxf(m1, sc[4 * j + 2 + e]);
                    }
                }
                m0 = fmaxf(m0, __shfl_xor_sync(0xffffffffu, m0, 1)); m0 = fmaxf(m0, __shfl_xor_sync(0xffffffffu, m0, 2));
                m1 = fmaxf(m1, __shfl_xor_sync(0xffffffffu, m1, 1)); m1 = fmaxf(m1, __shfl_xor_sync(0xffffffffu, m1, 2));
                uint32_t pk[10];
                float l0 = 0.f, l1 = 0.f;
#pragma unroll
                for (int j = 0; j < 5; j++) {
                    float p0 = exp2f(sc[4 * j] - m0), p1 = exp2f(sc[4 * j + 1] - m0), p2 = exp2f(sc[4 * j + 2] - m1), p3 = exp2f(sc[4 * j + 3] - m1);
                    l0 += p0 + p1; l1 += p2 + p3;
                    pk[2 * j] = pack_bf16(p0, p1); pk[2 * j + 1] = pack_bf16(p2, p3);
                }
                l0 += __shfl_xor_sync(0xffffffffu, l0, 1); l0 += __shfl_xor_sync(0xffffffffu, l0, 2);
                l1 += __shfl_xor_sync(0xffffffffu, l1, 1); l1 += __shfl_xor_sync(0xffffffffu, l1, 2);
                const float i0 = 1.0f / l0, i1 = 1.0f / l1;
                uint32_t* op = (uint32_t*)(g_O + (size_t)(s * SEG + t0) * HD + h * DH + (warp >> 1) * 64 + c * 2);
#pragma unroll
                for (int half = 0; half < 2; half++) {
                    float o[4][4];
#pragma unroll
                    for (int n = 0; n < 4; n++) o[n][0] = o[n][1] = o[n][2] = o[n][3] = 0.f;
                    const uint32_t va = sb + R_V + ((warp >> 1) * 2 + half) * 512 + lane * 16;
                    uint32_t v0[4], v1[4];
                    ldsm4(v0, va); ldsm4(v1, va + 2048);
#pragma unroll
                    for (int n = 0; n < 4; n++) mma16816(o[n], pk[0], pk[1], pk[2], pk[3], v0[n], v1[n]);
                    ldsm4(v0, va + 4096); ldsm4(v1, va + 6144);
#pragma unroll
                    for (int n = 0; n < 4; n++) mma16816(o[n], pk[4], pk[5], pk[6], pk[7], v0[n], v1[n]);
                    ldsm4(v0, va + 8192);
#pragma unroll
                    for (int n = 0; n < 4; n++) mma1688(o[n], pk[8], pk[9], v0[n]);
#pragma unroll
                    for (int n = 0; n < 4; n++) {
                        op[half * 16 + n * 4] = pack_bf16(o[n][0] * i0, o[n][1] * i0);
                        op[half * 16 + n * 4 + 4 * HD] = pack_bf16(o[n][2] * i1, o[n][3] * i1);
                    }
                }
                if (s < NSEG - 1 && lane == 0) mbar_arrive(bar + 8 * B_GATE);
            }
            if (s == NSEG - 1) break;
            __syncwarp();
            if (lane < 3) mbar_arrive_remote(tfree);
            PROF(11);
            if (role != 0) {
                const uint32_t tag = (uint32_t)(s % 3) + 1u;
                const float* rp = g_part + (size_t)cg * 1024 + lane * 4;
                uint4 v[8];
#pragma unroll
                for (int i = 0; i < 8; i++) v[i] = ld_strong16(rp + i * 128);
                uint32_t n = 0;
                while (true) {
                    bool ok = true;
#pragma unroll
                    for (int i = 0; i < 8; i++) {
                        if ((((v[i].x ^ tag) | (v[i].y ^ tag) | (v[i].z ^ tag) | (v[i].w ^ tag)) & 3u) != 0u) { v[i] = ld_strong16(rp + i * 128); ok = false; }
                    }
                    if (ok) break;
                    if (++n > 20000000u) __trap();
                }
                float x0 = 0.f, x1 = 0.f, x2 = 0.f, x3 = 0.f;
#pragma unroll
                for (int i = 0; i < 8; i++) {
                    x0 += __uint_as_float(v[i].x & ~3u); x1 += __uint_as_float(v[i].y & ~3u);
                    x2 += __uint_as_float(v[i].z & ~3u); x3 += __uint_as_float(v[i].w & ~3u);
                }
                x0 += __shfl_xor_sync(0xffffffffu, x0, 8); x1 += __shfl_xor_sync(0xffffffffu, x1, 8);
                x2 += __shfl_xor_sync(0xffffffffu, x2, 8); x3 += __shfl_xor_sync(0xffffffffu, x3, 8);
                x0 += __shfl_xor_sync(0xffffffffu, x0, 16); x1 += __shfl_xor_sync(0xffffffffu, x1, 16);
                x2 += __shfl_xor_sync(0xffffffffu, x2, 16); x3 += __shfl_xor_sync(0xffffffffu, x3, 16);
                if (lane < 8) {
                    st_strong8(&g_mem[(s + 1) & 3][cg * 16 + lane * 2], ~pack_bf16(x0, x1), ~pack_bf16(x2, x3));
                    st_strong8(&g_mem[s & 3][cg * 16 + lane * 2], 0u, 0u);
                }
            }
            PROF(12);
            {
                const uint32_t* rp = &g_mem[(s + 1) & 3][t * 4];
                uint4 v[8];
#pragma unroll
                for (int i = 0; i < 8; i++) v[i] = ld_strong16(rp + i * 512);
                uint32_t n = 0;
                while (true) {
                    bool ok = true;
#pragma unroll
                    for (int i = 0; i < 8; i++) {
                        if (v[i].x == 0u || v[i].y == 0u || v[i].z == 0u || v[i].w == 0u) { v[i] = ld_strong16(rp + i * 512); ok = false; }
                    }
                    if (ok) break;
                    if (++n > 20000000u) __trap();
                }
                PROF(13);
                mbar_wait(bar + 8 * B_AFREE, (s + 1) & 1);
#pragma unroll
                for (int i = 0; i < 8; i++) sts128(sb + R_RING + (i * 128 + t) * 16, make_uint4(~v[i].x, ~v[i].y, ~v[i].z, ~v[i].w));
                fence_async();
                __syncwarp();
                if (lane == 0) mbar_arrive(bar + 8 * B_MEM);
                PROF(14);
            }
        }
    }
    __syncwarp();
    asm volatile("barrier.cluster.arrive; barrier.cluster.wait;" ::: "memory");
}

constexpr int G_ST = 4;
constexpr int G_STAGE = 16384 + 32768;
constexpr int G_EPI = G_ST * G_STAGE;
constexpr int G_GATE = G_EPI + 32768;
constexpr int G_BAR = G_GATE + 1024;
constexpr int G_SMEM = G_BAR + 128 + 1024;

struct G1Maps { CUtensorMap x, wg, wu, h; };
constexpr int G1_NB = FF / 128;
constexpr int G1_TILES = 16 * G1_NB;

__global__ void __launch_bounds__(384, 1) g1_kernel(const __grid_constant__ G1Maps tm, const bf16* __restrict__ x, const bf16* __restrict__ gate_w) {
    extern __shared__ unsigned char smem_raw[];
    const uint32_t sb = (smem_u32(smem_raw) + 1023) & ~1023u;
    float* sgate = (float*)(smem_raw + (sb - smem_u32(smem_raw)) + G_GATE);
    const int tid = threadIdx.x, lane = tid & 31;
    const int wg = __shfl_sync(0xffffffffu, tid >> 7, 0);
    const int warp = __shfl_sync(0xffffffffu, (tid >> 5) & 3, 0);
    const uint32_t bar = sb + G_BAR;
    const int t_begin = (int)(((long long)blockIdx.x * G1_TILES) / gridDim.x);
    const int t_end = (int)(((long long)(blockIdx.x + 1) * G1_TILES) / gridDim.x);
    const int mb0 = t_begin / G1_NB;
    if (tid == 0) {
        for (int i = 0; i < G_ST; i++) { mbar_init(bar + 8 * i, 1); mbar_init(bar + 8 * (G_ST + i), 2); }
        mbar_init(bar + 8 * 2 * G_ST, 3);
        fence_async();
    }
    __syncthreads();
    if (wg == 2) {
        asm volatile("setmaxnreg.dec.sync.aligned.u32 40;");
        if (warp == 0) {
            if (lane == 0) {
                int it = 0;
                for (int tile = t_begin; tile < t_end; tile++) {
                    const int mb = tile / G1_NB, nb = tile % G1_NB;
                    for (int kb = 0; kb < 16; kb++, it++) {
                        const int st = it % G_ST;
                        mbar_wait(bar + 8 * (G_ST + st), ((it / G_ST) & 1) ^ 1);
                        const uint32_t fb = bar + 8 * st, sa = sb + st * G_STAGE;
                        mbar_expect(fb, G_STAGE);
                        tma_load(sa, &tm.x, kb * 64, mb * 128, fb);
                        tma_load(sa + 16384, &tm.wg, nb * 128, kb * 64, fb);
                        tma_load(sa + 16384 + 8192, &tm.wg, nb * 128 + 64, kb * 64, fb);
                        tma_load(sa + 16384 + 16384, &tm.wu, nb * 128, kb * 64, fb);
                        tma_load(sa + 16384 + 24576, &tm.wu, nb * 128 + 64, kb * 64, fb);
                    }
                }
            }
        } else {
            const int nrows = ((t_end - 1) / G1_NB - mb0 + 1) * 128;
            for (int r = warp - 1; r < nrows; r += 3) {
                const uint4* xp = (const uint4*)(x + (size_t)(mb0 * 128 + r) * DM);
                const uint4* gp = (const uint4*)gate_w;
                float acc = 0.f;
#pragma unroll
                for (int i = 0; i < 4; i++) {
                    uint4 xv = xp[i * 32 + lane], gv = gp[i * 32 + lane];
                    const uint32_t xa[4] = {xv.x, xv.y, xv.z, xv.w}, ga[4] = {gv.x, gv.y, gv.z, gv.w};
#pragma unroll
                    for (int e = 0; e < 4; e++) {
                        acc = fmaf(__uint_as_float(xa[e] << 16), __uint_as_float(ga[e] << 16), acc);
                        acc = fmaf(__uint_as_float(xa[e] & 0xffff0000u), __uint_as_float(ga[e] & 0xffff0000u), acc);
                    }
                }
#pragma unroll
                for (int o = 16; o > 0; o >>= 1) acc += __shfl_xor_sync(0xffffffffu, acc, o);
                if (lane == 0) { float gt = 1.0f / (1.0f + __expf(-acc)); sgate[r] = gt; g_gate[mb0 * 128 + r] = gt; }
            }
            __syncwarp();
            if (lane == 0) mbar_arrive(bar + 8 * 2 * G_ST);
        }
    } else {
        asm volatile("setmaxnreg.inc.sync.aligned.u32 232;");
        float d[128];
        int it = 0;
        const uint32_t epi = sb + G_EPI + wg * 16384;
        for (int tile = t_begin; tile < t_end; tile++) {
            const int mb = tile / G1_NB, nb = tile % G1_NB;
            for (int kb = 0; kb < 16; kb++, it++) {
                const int st = it % G_ST;
                mbar_wait(bar + 8 * st, (it / G_ST) & 1);
                const uint64_t da = mkdesc(sb + st * G_STAGE + wg * 8192, 16, 1024, 1);
                const uint64_t db = mkdesc(sb + st * G_STAGE + 16384, 8192, 1024, 1);
                wg_fence();
#pragma unroll
                for (int k = 0; k < 4; k++) wg_ss256(d, da + (uint64_t)(k * 2), db + (uint64_t)(k * 128), kb | k);
                wg_commit();
                if (kb > 0) { wg_wait<1>(); if ((tid & 127) == 0) mbar_arrive(bar + 8 * (G_ST + (it - 1) % G_ST)); }
            }
            wg_wait<0>();
            if ((tid & 127) == 0) { mbar_arrive(bar + 8 * (G_ST + (it - 1) % G_ST)); bulk_wait_read(); }
            if (tile == t_begin) mbar_wait(bar + 8 * 2 * G_ST, 0);
            bar_sync(1 + wg, 128);
            const int r0 = (mb - mb0) * 128 + wg * 64 + warp * 16 + (lane >> 2);
            const float s0 = 1.0f - sgate[r0], s1 = 1.0f - sgate[r0 + 8];
            const int row = warp * 16 + ((lane >> 3) & 1) * 8 + (lane & 7);
#pragma unroll
            for (int j = 0; j < 16; j += 2) {
                uint32_t p[4];
#pragma unroll
                for (int q = 0; q < 4; q++) {
                    const int i = (j + (q >> 1)) * 4 + (q & 1) * 2;
                    const float sc = (q & 1) ? s1 : s0;
                    const float g0 = d[i], g1 = d[i + 1];
                    const float h0 = __fdividef(g0, 1.0f + __expf(-g0)) * d[64 + i] * sc;
                    const float h1 = __fdividef(g1, 1.0f + __expf(-g1)) * d[64 + i + 1] * sc;
                    p[q] = pack_bf16(h0, h1);
                }
                const int cgp = j + (lane >> 4);
                stsm4(epi + (cgp >> 3) * 8192 + row * 128 + (((cgp & 7) ^ (row & 7)) << 4), p[0], p[1], p[2], p[3]);
            }
            fence_async();
            bar_sync(1 + wg, 128);
            if ((tid & 127) == 0) {
                tma_store(&tm.h, epi, nb * 128, mb * 128 + wg * 64);
                tma_store(&tm.h, epi + 8192, nb * 128 + 64, mb * 128 + wg * 64);
                bulk_commit();
            }
        }
        if ((tid & 127) == 0) bulk_wait_all();
    }
    asm volatile("griddepcontrol.wait;" ::: "memory");
}

struct G2Maps { CUtensorMap o, h, wo, wd, out; };

__global__ void __launch_bounds__(384, 1) g2_kernel(const __grid_constant__ G2Maps tm) {
    extern __shared__ unsigned char smem_raw[];
    const uint32_t sb = (smem_u32(smem_raw) + 1023) & ~1023u;
    const int tid = threadIdx.x, lane = tid & 31;
    const int wg = __shfl_sync(0xffffffffu, tid >> 7, 0);
    const int warp = __shfl_sync(0xffffffffu, (tid >> 5) & 3, 0);
    const uint32_t bar = sb + G_BAR;
    const int kh = blockIdx.x & 1, nb = (blockIdx.x >> 1) & 3, mb = blockIdx.x >> 3;
    if (tid == 0) {
        for (int i = 0; i < G_ST; i++) { mbar_init(bar + 8 * i, 1); mbar_init(bar + 8 * (G_ST + i), 2); }
        fence_async();
    }
    __syncthreads();
    if (wg == 2) {
        asm volatile("setmaxnreg.dec.sync.aligned.u32 40;");
        if (warp == 0 && lane == 0) {
            for (int it = 0; it < 60; it++) {
                const int kb = kh * 60 + it, st = it % G_ST;
                mbar_wait(bar + 8 * (G_ST + st), ((it / G_ST) & 1) ^ 1);
                const uint32_t fb = bar + 8 * st, sa = sb + st * G_STAGE;
                mbar_expect(fb, G_STAGE);
                const CUtensorMap* ta = kb < 64 ? &tm.o : &tm.h;
                const CUtensorMap* tb = kb < 64 ? &tm.wo : &tm.wd;
                const int k0 = (kb < 64 ? kb : kb - 64) * 64;
                tma_load(sa, ta, k0, mb * 128, fb);
#pragma unroll
                for (int q = 0; q < 4; q++) tma_load(sa + 16384 + q * 8192, tb, nb * 256 + q * 64, k0, fb);
            }
        }
    } else {
        asm volatile("setmaxnreg.inc.sync.aligned.u32 232;");
        float d[128];
        const int r0 = mb * 128 + wg * 64 + warp * 16 + (lane >> 2);
        const float s0 = g_gate[r0], s1 = g_gate[r0 + 8];
        const int o_last = kh == 0 ? 59 : 3;
        for (int it = 0; it < 60; it++) {
            const int st = it % G_ST;
            mbar_wait(bar + 8 * st, (it / G_ST) & 1);
            const uint64_t da = mkdesc(sb + st * G_STAGE + wg * 8192, 16, 1024, 1);
            const uint64_t db = mkdesc(sb + st * G_STAGE + 16384, 8192, 1024, 1);
            wg_fence();
#pragma unroll
            for (int k = 0; k < 4; k++) wg_ss256(d, da + (uint64_t)(k * 2), db + (uint64_t)(k * 128), it | k);
            wg_commit();
            if (it == o_last) {
                wg_wait<0>();
#pragma unroll
                for (int i = 0; i < 128; i++) d[i] *= (i & 2) ? s1 : s0;
            } else {
                wg_wait<1>();
            }
            if (it > 0 && (tid & 127) == 0) mbar_arrive(bar + 8 * (G_ST + (it - 1) % G_ST));
        }
        wg_wait<0>();
        float4* mine = g_sk + (size_t)blockIdx.x * 4096 + tid;
        const float4* theirs = g_sk + (size_t)(blockIdx.x ^ 1) * 4096 + tid;
        if (kh == 0) {
#pragma unroll
            for (int i = 0; i < 16; i++) __stcg(mine + i * 256, make_float4(d[64 + 4 * i], d[64 + 4 * i + 1], d[64 + 4 * i + 2], d[64 + 4 * i + 3]));
        } else {
#pragma unroll
            for (int i = 0; i < 16; i++) __stcg(mine + i * 256, make_float4(d[4 * i], d[4 * i + 1], d[4 * i + 2], d[4 * i + 3]));
#pragma unroll
            for (int i = 0; i < 64; i++) d[i] = d[64 + i];
        }
        __threadfence();
        bar_sync(1, 256);
        if (tid == 0) {
            asm volatile("st.release.gpu.global.u32 [%0], %1;" ::"l"(&g_skflag[blockIdx.x]), "r"(1u) : "memory");
            uint32_t v, n = 0;
            do {
                asm volatile("ld.acquire.gpu.global.u32 %0, [%1];" : "=r"(v) : "l"(&g_skflag[blockIdx.x ^ 1]) : "memory");
                if (++n > 200000000u) __trap();
            } while (v == 0u);
            g_skflag[blockIdx.x ^ 1] = 0u;
        }
        bar_sync(1, 256);
        const uint32_t epi = sb + G_EPI + wg * 16384;
        const int row = warp * 16 + ((lane >> 3) & 1) * 8 + (lane & 7);
#pragma unroll
        for (int j = 0; j < 16; j += 2) {
            float4 u = __ldcg(theirs + j * 256), v = __ldcg(theirs + (j + 1) * 256);
            const int cgp = j + (lane >> 4);
            stsm4(epi + (cgp >> 3) * 8192 + row * 128 + (((cgp & 7) ^ (row & 7)) << 4),
                  pack_bf16(d[4 * j] + u.x, d[4 * j + 1] + u.y), pack_bf16(d[4 * j + 2] + u.z, d[4 * j + 3] + u.w),
                  pack_bf16(d[4 * j + 4] + v.x, d[4 * j + 5] + v.y), pack_bf16(d[4 * j + 6] + v.z, d[4 * j + 7] + v.w));
        }
        fence_async();
        bar_sync(2 + wg, 128);
        if ((tid & 127) == 0) {
            tma_store(&tm.out, epi, nb * 256 + kh * 128, mb * 128 + wg * 64);
            tma_store(&tm.out, epi + 8192, nb * 256 + kh * 128 + 64, mb * 128 + wg * 64);
            bulk_commit();
            bulk_wait_all();
        }
    }
}

typedef CUresult (*EncodeFn)(CUtensorMap*, CUtensorMapDataType, cuuint32_t, void*, const cuuint64_t*, const cuuint64_t*, const cuuint32_t*,
                             const cuuint32_t*, CUtensorMapInterleave, CUtensorMapSwizzle, CUtensorMapL2promotion, CUtensorMapFloatOOBfill);

static void make_map(EncodeFn enc, CUtensorMap* m, const void* ptr, uint64_t rows, uint64_t cols, uint32_t box_rows) {
    cuuint64_t dims[2] = {cols, rows};
    cuuint64_t strides[1] = {cols * 2};
    cuuint32_t box[2] = {64, box_rows};
    cuuint32_t es[2] = {1, 1};
    enc(m, CU_TENSOR_MAP_DATA_TYPE_BFLOAT16, 2, (void*)ptr, dims, strides, box, es, CU_TENSOR_MAP_INTERLEAVE_NONE,
        CU_TENSOR_MAP_SWIZZLE_128B, CU_TENSOR_MAP_L2_PROMOTION_L2_256B, CU_TENSOR_MAP_FLOAT_OOB_FILL_NONE);
}

extern "C" void kernel_launch(void* const* d_in, const int* in_sizes, int n_in, void* d_out, int out_size) {
    (void)in_sizes; (void)n_in; (void)out_size;
    const bf16* x = (const bf16*)d_in[0];
    const bf16* mem0 = (const bf16*)d_in[1];
    const bf16* gate_w = (const bf16*)d_in[11];
    static EncodeFn enc = nullptr;
    static int n_sm = 0;
    static void *pO = nullptr, *pH = nullptr;
    if (!enc) {
        void* fn = nullptr;
        cudaDriverEntryPointQueryResult qr;
        cudaGetDriverEntryPoint("cuTensorMapEncodeTiled", &fn, cudaEnableDefault, &qr);
        enc = (EncodeFn)fn;
        cudaDeviceGetAttribute(&n_sm, cudaDevAttrMultiProcessorCount, 0);
        cudaFuncSetAttribute(r_kernel, cudaFuncAttributeMaxDynamicSharedMemorySize, R_SMEM);
        cudaFuncSetAttribute(g1_kernel, cudaFuncAttributeMaxDynamicSharedMemorySize, G_SMEM);
        cudaFuncSetAttribute(g2_kernel, cudaFuncAttributeMaxDynamicSharedMemorySize, G_SMEM);
        cudaGetSymbolAddress(&pO, g_O);
        cudaGetSymbolAddress(&pH, g_H);
    }
    RMaps rm; G1Maps m1; G2Maps m2;
    make_map(enc, &rm.x, x, SEQ, DM, 32);
    for (int i = 0; i < 3; i++) make_map(enc, &rm.w[i], d_in[2 + i], DM, HD, 64);
    make_map(enc, &rm.wo, d_in[5], HD, DM, 128);
    make_map(enc, &m1.x, x, SEQ, DM, 128);
    make_map(enc, &m1.wg, d_in[8], DM, FF, 64);
    make_map(enc, &m1.wu, d_in[9], DM, FF, 64);
    make_map(enc, &m1.h, pH, SEQ, FF, 64);
    make_map(enc, &m2.o, pO, SEQ, HD, 128);
    make_map(enc, &m2.h, pH, SEQ, FF, 128);
    make_map(enc, &m2.wo, d_in[5], HD, DM, 64);
    make_map(enc, &m2.wd, d_in[10], FF, DM, 64);
    make_map(enc, &m2.out, d_out, SEQ, DM, 64);

    cudaStream_t st = cudaStreamPerThread;
    {
        cudaLaunchConfig_t cfg = {};
        cfg.gridDim = dim3(96); cfg.blockDim = dim3(384); cfg.dynamicSmemBytes = R_SMEM; cfg.stream = st;
        cudaLaunchAttribute at[1];
        at[0].id = cudaLaunchAttributeClusterDimension; at[0].val.clusterDim.x = 3; at[0].val.clusterDim.y = 1; at[0].val.clusterDim.z = 1;
        cfg.attrs = at; cfg.numAttrs = 1;
        cudaLaunchKernelEx(&cfg, r_kernel, rm, mem0);
    }
    {
        cudaLaunchConfig_t cfg = {};
        cfg.gridDim = dim3(n_sm - 96); cfg.blockDim = dim3(384); cfg.dynamicSmemBytes = G_SMEM; cfg.stream = st;
        cudaLaunchAttribute at[1];
        at[0].id = cudaLaunchAttributeProgrammaticStreamSerialization; at[0].val.programmaticStreamSerializationAllowed = 1;
        cfg.attrs = at; cfg.numAttrs = 1;
        cudaLaunchKernelEx(&cfg, g1_kernel, m1, x, gate_w);
    }
    g2_kernel<<<128, 384, G_SMEM, st>>>(m2);
}
```

```cpp
#include <cuda_runtime.h>
#include <cuda_bf16.h>
#include <cuda.h>
#include <stdint.h>

typedef __nv_bfloat16 bf16;

constexpr int SEQ = 2048, DM = 1024, NH = 32, DH = 128, NMEM = 8, SEG = 32, NSEG = 64, FF = 3584;
constexpr int HD = NH * DH;

__device__ bf16 g_O[SEQ * HD];
__device__ bf16 g_H[SEQ * FF];
__device__ float g_gate[SEQ];
__device__ uint32_t g_part[2][128 * 32 * 32];
__device__ uint32_t g_mem[4][DM * 4];
__device__ float4 g_sk[128 * 16 * 256];
__device__ uint32_t g_skflag[128];
#define KT(k, i)

#define DEVINL __device__ __forceinline__
constexpr long long SPIN_LIMIT = 4000000000LL;

DEVINL uint32_t smem_u32(const void* p) { return (uint32_t)__cvta_generic_to_shared(p); }
DEVINL void mbar_init(uint32_t bar, uint32_t cnt) { asm volatile("mbarrier.init.shared::cta.b64 [%0], %1;" ::"r"(bar), "r"(cnt) : "memory"); }
DEVINL void mbar_arrive(uint32_t bar) { asm volatile("mbarrier.arrive.shared::cta.b64 _, [%0];" ::"r"(bar) : "memory"); }
DEVINL void mbar_expect(uint32_t bar, uint32_t bytes) { asm volatile("mbarrier.arrive.expect_tx.shared::cta.b64 _, [%0], %1;" ::"r"(bar), "r"(bytes) : "memory"); }
DEVINL void mbar_arrive_remote(uint32_t cbar) { asm volatile("mbarrier.arrive.relaxed.cluster.shared::cluster.b64 _, [%0];" ::"r"(cbar) : "memory"); }
DEVINL bool mbar_try(uint32_t bar, uint32_t par) {
    uint32_t ok;
    asm volatile("{ .reg .pred p; mbarrier.try_wait.parity.shared::cta.b64 p, [%1], %2; selp.u32 %0, 1, 0, p; }" : "=r"(ok) : "r"(bar), "r"(par) : "memory");
    return ok;
}
__device__ __noinline__ void mbar_wait_slow(uint32_t bar, uint32_t par) {
    long long t0 = clock64();
    while (!mbar_try(bar, par)) { if (clock64() - t0 > SPIN_LIMIT) __trap(); }
}
DEVINL void mbar_wait(uint32_t bar, uint32_t par) {
    uint32_t n = 0;
    while (!mbar_try(bar, par)) { if (++n > 200000000u) __trap(); }
}
DEVINL uint32_t mapa(uint32_t a, uint32_t r) { uint32_t o; asm volatile("mapa.shared::cluster.u32 %0, %1, %2;" : "=r"(o) : "r"(a), "r"(r)); return o; }
DEVINL void fence_async() { asm volatile("fence.proxy.async.shared::cta;" ::: "memory"); }
DEVINL void bar_sync(int id, int n) { asm volatile("bar.sync %0, %1;" ::"r"(id), "r"(n) : "memory"); }
DEVINL void cluster_sync() { asm volatile("barrier.cluster.arrive.aligned; barrier.cluster.wait.aligned;" ::: "memory"); }
DEVINL void tma_load(uint32_t dst, const CUtensorMap* tm, int c0, int c1, uint32_t bar) {
    asm volatile("cp.async.bulk.tensor.2d.shared::cluster.global.mbarrier::complete_tx::bytes [%0], [%1, {%3, %4}], [%2];"
                 ::"r"(dst), "l"(tm), "r"(bar), "r"(c0), "r"(c1) : "memory");
}
DEVINL void tma_prefetch(const CUtensorMap* tm, int c0, int c1) {
    asm volatile("cp.async.bulk.prefetch.tensor.2d.L2.global [%0, {%1, %2}];" ::"l"(tm), "r"(c0), "r"(c1) : "memory");
}
DEVINL void tma_store(const CUtensorMap* tm, uint32_t src, int c0, int c1) {
    asm volatile("cp.async.bulk.tensor.2d.global.shared::cta.bulk_group [%0, {%2, %3}], [%1];" ::"l"(tm), "r"(src), "r"(c0), "r"(c1) : "memory");
}
DEVINL void bulk_commit() { asm volatile("cp.async.bulk.commit_group;" ::: "memory"); }
DEVINL void bulk_wait_read() { asm volatile("cp.async.bulk.wait_group.read 0;" ::: "memory"); }
DEVINL void bulk_wait_all() { asm volatile("cp.async.bulk.wait_group 0;" ::: "memory"); }
DEVINL void bulk_s2s(uint32_t cdst, uint32_t src, uint32_t bytes, uint32_t cbar) {
    asm volatile("cp.async.bulk.shared::cluster.shared::cta.mbarrier::complete_tx::bytes [%0], [%1], %2, [%3];" ::"r"(cdst), "r"(src), "r"(bytes), "r"(cbar) : "memory");
}
DEVINL void st_async16(uint32_t cdst, uint4 v, uint32_t cbar) {
    asm volatile("st.async.shared::cluster.mbarrier::complete_tx::bytes.v4.b32 [%0], {%1,%2,%3,%4}, [%5];" ::"r"(cdst), "r"(v.x), "r"(v.y), "r"(v.z), "r"(v.w), "r"(cbar) : "memory");
}
DEVINL uint64_t mkdesc(uint32_t addr, uint32_t lbo, uint32_t sbo, uint32_t swz) {
    return (uint64_t)((addr & 0x3FFFF) >> 4) | ((uint64_t)(lbo >> 4) << 16) | ((uint64_t)(sbo >> 4) << 32) | ((uint64_t)swz << 62);
}
constexpr uint32_t SB0 = 1024;
__host__ __device__ constexpr uint64_t cdesc(uint32_t off, uint32_t lbo, uint32_t sbo, uint32_t swz) {
    return (uint64_t)(((SB0 + off) & 0x3FFFF) >> 4) | ((uint64_t)(lbo >> 4) << 16) | ((uint64_t)(sbo >> 4) << 32) | ((uint64_t)swz << 62);
}
DEVINL float ex2(float x) { float y; asm("ex2.approx.ftz.f32 %0, %1;" : "=f"(y) : "f"(x)); return y; }
DEVINL void spin_clk(int d) { uint32_t t0, t1; asm volatile("mov.u32 %0, %%clock;" : "=r"(t0)); do { asm volatile("mov.u32 %0, %%clock;" : "=r"(t1)); } while ((int)(t1 - t0) < d); }
#define PROBE_GAP 150
#define OPAQUE(x) asm volatile("" : "+r"(x))
DEVINL void wg_fence() { asm volatile("wgmma.fence.sync.aligned;" ::: "memory"); }
DEVINL void wg_commit() { asm volatile("wgmma.commit_group.sync.aligned;" ::: "memory"); }
template <int N> DEVINL void wg_wait() { asm volatile("wgmma.wait_group.sync.aligned %0;" ::"n"(N) : "memory"); }
DEVINL uint32_t pack_bf16(float lo, float hi) { uint32_t r; asm("cvt.rn.bf16x2.f32 %0, %1, %2;" : "=r"(r) : "f"(hi), "f"(lo)); return r; }
DEVINL void ldsm4(uint32_t* r, uint32_t a) { asm volatile("ldmatrix.sync.aligned.m8n8.x4.shared.b16 {%0,%1,%2,%3}, [%4];" : "=r"(r[0]), "=r"(r[1]), "=r"(r[2]), "=r"(r[3]) : "r"(a) : "memory"); }
DEVINL void ldsm4t(uint32_t* r, uint32_t a) { asm volatile("ldmatrix.sync.aligned.m8n8.x4.trans.shared.b16 {%0,%1,%2,%3}, [%4];" : "=r"(r[0]), "=r"(r[1]), "=r"(r[2]), "=r"(r[3]) : "r"(a) : "memory"); }
DEVINL void stsm4(uint32_t a, uint32_t r0, uint32_t r1, uint32_t r2, uint32_t r3) { asm volatile("stmatrix.sync.aligned.m8n8.x4.shared.b16 [%0], {%1,%2,%3,%4};" ::"r"(a), "r"(r0), "r"(r1), "r"(r2), "r"(r3) : "memory"); }
DEVINL void stsm4t(uint32_t a, uint32_t r0, uint32_t r1, uint32_t r2, uint32_t r3) { asm volatile("stmatrix.sync.aligned.m8n8.x4.trans.shared.b16 [%0], {%1,%2,%3,%4};" ::"r"(a), "r"(r0), "r"(r1), "r"(r2), "r"(r3) : "memory"); }
DEVINL void sts32(uint32_t a, uint32_t v) { asm volatile("st.shared.b32 [%0], %1;" ::"r"(a), "r"(v) : "memory"); }
DEVINL void sts128(uint32_t a, uint4 v) { asm volatile("st.shared.v4.b32 [%0], {%1,%2,%3,%4};" ::"r"(a), "r"(v.x), "r"(v.y), "r"(v.z), "r"(v.w) : "memory"); }
DEVINL uint4 lds128(uint32_t a) { uint4 v; asm volatile("ld.shared.v4.b32 {%0,%1,%2,%3}, [%4];" : "=r"(v.x), "=r"(v.y), "=r"(v.z), "=r"(v.w) : "r"(a) : "memory"); return v; }
DEVINL uint4 ld_strong16(const void* p) { uint4 v; asm volatile("ld.relaxed.gpu.global.v4.u32 {%0,%1,%2,%3}, [%4];" : "=r"(v.x), "=r"(v.y), "=r"(v.z), "=r"(v.w) : "l"(p) : "memory"); return v; }
DEVINL void st_strong8(void* p, uint32_t a, uint32_t b) { asm volatile("st.relaxed.gpu.global.v2.u32 [%0], {%1,%2};" ::"l"(p), "r"(a), "r"(b) : "memory"); }
DEVINL void st_strong4(void* p, uint32_t a) { asm volatile("st.relaxed.gpu.global.u32 [%0], %1;" ::"l"(p), "r"(a) : "memory"); }
DEVINL void st_strong16(void* p, uint4 v) { asm volatile("st.relaxed.gpu.global.v4.u32 [%0], {%1,%2,%3,%4};" ::"l"(p), "r"(v.x), "r"(v.y), "r"(v.z), "r"(v.w) : "memory"); }
DEVINL uint32_t pack_nz(float lo, float hi) { uint32_t r = pack_bf16(lo, hi); return r == 0u ? 0x8000u : r; }
DEVINL void mma16816(float* d, uint32_t a0, uint32_t a1, uint32_t a2, uint32_t a3, uint32_t b0, uint32_t b1) {
    asm volatile("mma.sync.aligned.m16n8k16.row.col.f32.bf16.bf16.f32 {%0,%1,%2,%3}, {%4,%5,%6,%7}, {%8,%9}, {%0,%1,%2,%3};"
                 : "+f"(d[0]), "+f"(d[1]), "+f"(d[2]), "+f"(d[3]) : "r"(a0), "r"(a1), "r"(a2), "r"(a3), "r"(b0), "r"(b1));
}
DEVINL void mma1688(float* d, uint32_t a0, uint32_t a1, uint32_t b0) {
    asm volatile("mma.sync.aligned.m16n8k8.row.col.f32.bf16.bf16.f32 {%0,%1,%2,%3}, {%4,%5}, {%6}, {%0,%1,%2,%3};"
                 : "+f"(d[0]), "+f"(d[1]), "+f"(d[2]), "+f"(d[3]) : "r"(a0), "r"(a1), "r"(b0));
}
template <int TA, int TB> DEVINL void wg_ss8(float* d, uint64_t da, uint64_t db, int sc) {
    asm volatile("{ .reg .pred p; setp.ne.b32 p, %6, 0; wgmma.mma_async.sync.aligned.m64n8k16.f32.bf16.bf16 {%0,%1,%2,%3}, %4, %5, p, 1, 1, %7, %8; }"
                 : "+f"(d[0]), "+f"(d[1]), "+f"(d[2]), "+f"(d[3]) : "l"(da), "l"(db), "r"(sc), "n"(TA), "n"(TB));
}
template <int TB> DEVINL void wg_rs8(float* d, const uint32_t* a, uint64_t db, int sc) {
    asm volatile("{ .reg .pred p; setp.ne.b32 p, %9, 0; wgmma.mma_async.sync.aligned.m64n8k16.f32.bf16.bf16 {%0,%1,%2,%3}, {%4,%5,%6,%7}, %8, p, 1, 1, %10; }"
                 : "+f"(d[0]), "+f"(d[1]), "+f"(d[2]), "+f"(d[3]) : "r"(a[0]), "r"(a[1]), "r"(a[2]), "r"(a[3]), "l"(db), "r"(sc), "n"(TB));
}
#define ACC16(d) "+f"(d[0]), "+f"(d[1]), "+f"(d[2]), "+f"(d[3]), "+f"(d[4]), "+f"(d[5]), "+f"(d[6]), "+f"(d[7]), "+f"(d[8]), "+f"(d[9]), "+f"(d[10]), "+f"(d[11]), "+f"(d[12]), "+f"(d[13]), "+f"(d[14]), "+f"(d[15])
template <int TA> DEVINL void wg_ss32(float* d, uint64_t da, uint64_t db, int sc) {
    asm volatile("{ .reg .pred p; setp.ne.b32 p, %18, 0; wgmma.mma_async.sync.aligned.m64n32k16.f32.bf16.bf16 {%0,%1,%2,%3,%4,%5,%6,%7,%8,%9,%10,%11,%12,%13,%14,%15}, %16, %17, p, 1, 1, %19, 0; }"
                 : ACC16(d) : "l"(da), "l"(db), "r"(sc), "n"(TA));
}
DEVINL void wg_rs32(float* d, const uint32_t* a, uint64_t db, int sc) {
    asm volatile("{ .reg .pred p; setp.ne.b32 p, %21, 0; wgmma.mma_async.sync.aligned.m64n32k16.f32.bf16.bf16 {%0,%1,%2,%3,%4,%5,%6,%7,%8,%9,%10,%11,%12,%13,%14,%15}, {%16,%17,%18,%19}, %20, p, 1, 1, 0; }"
                 : ACC16(d) : "r"(a[0]), "r"(a[1]), "r"(a[2]), "r"(a[3]), "l"(db), "r"(sc));
}
DEVINL void wg_ss40(float* d, uint64_t da, uint64_t db, int sc) {
    asm volatile("{ .reg .pred p; setp.ne.b32 p, %22, 0; wgmma.mma_async.sync.aligned.m64n40k16.f32.bf16.bf16 {%0,%1,%2,%3,%4,%5,%6,%7,%8,%9,%10,%11,%12,%13,%14,%15,%16,%17,%18,%19}, %20, %21, p, 1, 1, 1, 1; }"
                 : ACC16(d), "+f"(d[16]), "+f"(d[17]), "+f"(d[18]), "+f"(d[19]) : "l"(da), "l"(db), "r"(sc));
}
#define A8(d, o) "+f"(d[o]), "+f"(d[o + 1]), "+f"(d[o + 2]), "+f"(d[o + 3]), "+f"(d[o + 4]), "+f"(d[o + 5]), "+f"(d[o + 6]), "+f"(d[o + 7])
#define A32(d, o) A8(d, o), A8(d, o + 8), A8(d, o + 16), A8(d, o + 24)
DEVINL void wg_ss256(float* d, uint64_t da, uint64_t db, int sc) {
    asm volatile(
        "{ .reg .pred p; setp.ne.b32 p, %130, 0;\n"
        "wgmma.mma_async.sync.aligned.m64n256k16.f32.bf16.bf16 {"
        "%0,%1,%2,%3,%4,%5,%6,%7,%8,%9,%10,%11,%12,%13,%14,%15,%16,%17,%18,%19,%20,%21,%22,%23,%24,%25,%26,%27,%28,%29,%30,%31,"
        "%32,%33,%34,%35,%36,%37,%38,%39,%40,%41,%42,%43,%44,%45,%46,%47,%48,%49,%50,%51,%52,%53,%54,%55,%56,%57,%58,%59,%60,%61,%62,%63,"
        "%64,%65,%66,%67,%68,%69,%70,%71,%72,%73,%74,%75,%76,%77,%78,%79,%80,%81,%82,%83,%84,%85,%86,%87,%88,%89,%90,%91,%92,%93,%94,%95,"
        "%96,%97,%98,%99,%100,%101,%102,%103,%104,%105,%106,%107,%108,%109,%110,%111,%112,%113,%114,%115,%116,%117,%118,%119,%120,%121,%122,%123,%124,%125,%126,%127"
        "}, %128, %129, p, 1, 1, 0, 1; }"
        : A32(d, 0), A32(d, 32), A32(d, 64), A32(d, 96) : "l"(da), "l"(db), "r"(sc));
}

constexpr int KR = 44;
constexpr int KS = 64 - KR;
constexpr int R_W = 0;
constexpr int R_WO = KS * 4096;
constexpr int R_QX = R_WO + 65536;
constexpr int R_RING = R_WO + 98304;
constexpr int R_K = R_RING + 24576;
constexpr int R_V = R_K + 10240;
constexpr int R_QM = R_V + 10240;
constexpr int R_O = R_QM + 2048;
constexpr int R_BAR = R_O + 2048;
constexpr int R_SMEM = R_BAR + 256 + 512 + 256 + 128;
enum { B_FULL = 0, B_EMPTY = 5, B_MEM = 8, B_HOP1 = 12, B_XT, B_TFREE, B_O, B_AFREE0, B_AFREE1, B_PRO0, B_PRO1, B_XRECV, B_P };
#define D2_BASE 700
#define D2_STEP 200
#define DQ 800
#define D3 300

DEVINL uint32_t clk32() { uint32_t c_; asm volatile("mov.u32 %0, %%clock;" : "=r"(c_)); return c_; }
DEVINL void spin_until(uint32_t t) { while ((int)(clk32() - t) < 0) {} }
#define PROF(i)
#define PROF2(i)
#define PROF3(i, val)
DEVINL void e_arrive(uint32_t bar) { asm volatile("{ .reg .pred p; elect.sync _|p, 0xffffffff; @p mbarrier.arrive.shared::cta.b64 _, [%0]; }" ::"r"(bar) : "memory"); }
DEVINL void e_arrive_remote(uint32_t cbar) { asm volatile("{ .reg .pred p; elect.sync _|p, 0xffffffff; @p mbarrier.arrive.relaxed.cluster.shared::cluster.b64 _, [%0]; }" ::"r"(cbar) : "memory"); }
DEVINL void e_expect(uint32_t bar, uint32_t bytes) { asm volatile("{ .reg .pred p; elect.sync _|p, 0xffffffff; @p mbarrier.arrive.expect_tx.shared::cta.b64 _, [%0], %1; }" ::"r"(bar), "r"(bytes) : "memory"); }
DEVINL void e_tma_load(uint32_t dst, const CUtensorMap* tm, int c0, int c1, uint32_t bar) {
    asm volatile("{ .reg .pred p; elect.sync _|p, 0xffffffff; @p cp.async.bulk.tensor.2d.shared::cluster.global.mbarrier::complete_tx::bytes [%0], [%1, {%3, %4}], [%2]; }"
                 ::"r"(dst), "l"(tm), "r"(bar), "r"(c0), "r"(c1) : "memory");
}
DEVINL void e_tma_store(const CUtensorMap* tm, uint32_t src, int c0, int c1) {
    asm volatile("{ .reg .pred p; elect.sync _|p, 0xffffffff; @p cp.async.bulk.tensor.2d.global.shared::cta.bulk_group [%0, {%2, %3}], [%1]; }" ::"l"(tm), "r"(src), "r"(c0), "r"(c1) : "memory");
}
DEVINL void e_bulk_s2s(uint32_t cdst, uint32_t src, uint32_t bytes, uint32_t cbar) {
    asm volatile("{ .reg .pred p; elect.sync _|p, 0xffffffff; @p cp.async.bulk.shared::cluster.shared::cta.mbarrier::complete_tx::bytes [%0], [%1], %2, [%3]; }" ::"r"(cdst), "r"(src), "r"(bytes), "r"(cbar) : "memory");
}

struct RMaps { CUtensorMap x, w[3], wo, o; };
#define KC(c) ((c) * 64)

#define XORD 3
__host__ __device__ constexpr int xo(int i) {
    return XORD == 0 ? i : XORD == 1 ? (i + 14) % 16 : XORD == 2 ? (i + 11) % 16
         : XORD == 3 ? (i < 10 ? ((i & 1) ? i / 2 : 11 + i / 2) : i - 5) : (i < 6 ? i : ((i & 1) ? 6 + (i - 6) / 2 : 11 + (i - 6) / 2));
}
#define XC(i) (xo(i) * 64)
DEVINL void x_load_pair(uint32_t dst, const CUtensorMap* tmx, int h, int p, int seg, uint32_t fbar) {
    e_expect(fbar, 8192);
    e_tma_load(dst, tmx, XC(2 * p), seg * SEG, fbar);
    e_tma_load(dst + 4096, tmx, XC(2 * p + 1), seg * SEG, fbar);
}
__host__ __device__ constexpr int wo_tile(int role, int i) { return i < 4 ? role + 3 * i : 11 + role + 2 * (i - 4); }

DEVINL void wo_issue(float* w, uint64_t dWo) {
    constexpr uint64_t dO = cdesc(R_O, 128, 128, 0);
    wg_fence();
#pragma unroll
    for (int k = 0; k < 8; k++) wg_ss8<1, 1>(w, dWo + (uint64_t)(k * 128), dO + (uint64_t)(k * 16), k);
    wg_commit();
}
template <int N> DEVINL void wo_store(float* w, uint32_t* q) {
    asm volatile("wgmma.wait_group.sync.aligned %4;" : "+f"(w[0]), "+f"(w[1]), "+f"(w[2]), "+f"(w[3]) : "n"(N) : "memory");
    st_strong4(q, pack_nz(w[0], w[1]));
    st_strong4(q + 1024, pack_nz(w[2], w[3]));
}

template <uint32_t role> DEVINL void r_big(const RMaps& tm, const int wid) {
    extern __shared__ __align__(1024) unsigned char smem_raw[];
    const uint32_t sb = smem_u32(smem_raw);
    const uint32_t bar = sb + R_BAR;
    const int tid = threadIdx.x;
    int h; asm("mov.u32 %0, %%clusterid.x;" : "=r"(h));
        uint32_t a[KR][4];
        mbar_wait(bar + 8 * B_PRO0, 0);
        {
            const int lane = tid & 31;
            const int krow = (lane & 7) + ((lane >> 4) << 3);
            const int chunk = (wid & 3) * 2 + ((lane >> 3) & 1);
            const uint32_t la = sb + (wid >> 2) * 8192 + krow * 128 + ((chunk ^ (krow & 7)) << 4);
#pragma unroll
            for (int k = 0; k < KR; k++) ldsm4t(a[k], la + (k >> 2) * 16384 + (k & 3) * 2048);
        }
        bar_sync(1, 256);
        if (tid == 0) {
            fence_async();
            const CUtensorMap* tw = &tm.w[role];
            mbar_expect(bar + 8 * B_PRO1, KS * 4096 + (role == 0 ? 4 : 6) * 16384);
#pragma unroll 1
            for (int rb = 0; rb < KS / 2; rb++) tma_load(sb + R_W + (rb & 1) * (KS * 2048) + (rb >> 1) * 8192, tw, h * DH + (rb & 1) * 64, KC(KR / 4 + (rb >> 1)), bar + 8 * B_PRO1);
#pragma unroll 1
            for (int i = 0; i < (role == 0 ? 4 : 6); i++) tma_load(sb + R_WO + i * 16384, &tm.wo, wo_tile(role, i) * 64, h * DH, bar + 8 * B_PRO1);
        }
        __syncwarp();
        constexpr uint32_t e0 = role == 0 ? R_QX + 16384 : R_K + 2048, e1 = role == 0 ? R_QX + 24576 : R_V + 2048;
        if (wid == 1) x_load_pair(sb + e0, &tm.x, h, 3, 0, bar + 8 * (B_FULL + 3));
        if (wid == 2) x_load_pair(sb + e1, &tm.x, h, 4, 0, bar + 8 * (B_FULL + 4));
        mbar_wait(bar + 8 * B_PRO1, 0);

        constexpr uint64_t dW0 = cdesc(R_W, 1024, 1024, 1);
        constexpr uint64_t dWo0 = cdesc(R_WO, 1024, 1024, 1);
        constexpr uint64_t dM = cdesc(R_RING, 128, 128, 0);
        constexpr uint64_t dX = cdesc(R_RING, 16, 1024, 1);
        constexpr uint64_t dX0 = cdesc(0, 16, 1024, 1);
        int tb = tid;
        int wq = wid;

        float d[16];
        for (int s = -1; s < NSEG; s++) {
            if (s >= 0) {
                OPAQUE(wq);
                const uint64_t dW = dW0 + (uint64_t)((wq >> 2) * (KS * 128));
                float y[4] = {0.f, 0.f, 0.f, 0.f};
                {
                    OPAQUE(tb);
                    const uint32_t ma = sb + R_RING + (tb & 31) * 16;
                    float z[4] = {0.f, 0.f, 0.f, 0.f};
#pragma unroll
                    for (int k = 0; k < KR; k += 2) {
                        if (k % 16 == 0) mbar_wait(bar + 8 * (B_MEM + k / 16), s & 1);
                        if (k == 0) {
                            PROF((wq >> 2) * 4 + 0);
                        }
                        uint32_t b[4];
                        ldsm4t(b, ma + k * 256);
                        mma16816(y, a[k][0], a[k][1], a[k][2], a[k][3], b[0], b[1]);
                        mma16816(z, a[k + 1][0], a[k + 1][1], a[k + 1][2], a[k + 1][3], b[2], b[3]);
                    }
                    y[0] += z[0]; y[1] += z[1]; y[2] += z[2]; y[3] += z[3];
                }
                PROF2(8);
                mbar_wait(bar + 8 * (B_MEM + 3), s & 1);
                wg_fence();
#pragma unroll
                for (int k = KR; k < 64; k++) wg_ss8<1, 1>(y, dW + (uint64_t)((k - KR) * 128), dM + (uint64_t)(k * 16), 1);
                wg_commit();
                asm volatile("wgmma.wait_group.sync.aligned 0;" : "+f"(y[0]), "+f"(y[1]), "+f"(y[2]), "+f"(y[3])::"memory");
                OPAQUE(tb);
                {
                    const uint32_t wo_ = (tb >> 5) * 256;
                    const uint32_t tile = sb + (role == 0 ? R_QX : (role == 1 ? R_K : R_V)) + wo_;
                    const uint32_t u0 = pack_bf16(y[0], y[1]), u1 = pack_bf16(y[2], y[3]);
                    sts32(tile + (tb & 31) * 4, u0);
                    sts32(tile + (tb & 31) * 4 + 128, u1);
                    __syncwarp();
                    uint4 v = lds128(tile + (tb & 15) * 16);
                    uint32_t peer = role + 1 + ((tb >> 4) & 1);
                    peer = peer >= 3 ? peer - 3 : peer;
                    const uint32_t rt = sb + (role == 0 ? R_QM : (role == 1 ? R_K : R_V)) + wo_ + (tb & 15) * 16;
                    st_async16(mapa(rt, peer), v, mapa(bar + 8 * B_HOP1, peer));
                    if (role == 0) {
                        sts128(tile + 4096 + ((tb >> 4) & 1) * 4096 + (tb & 15) * 16, v);
                        sts32(tile + 12288 + (tb & 31) * 4, u0);
                        sts32(tile + 12288 + (tb & 31) * 4 + 128, u1);
                        __syncwarp();
                    }
                    e_arrive(bar + 8 * B_HOP1);
                }
                PROF((wq >> 2) * 4 + 1);
                if (s < NSEG - 1) {
                    bar_sync(1, 256);
                    if (wq < 2) { fence_async(); x_load_pair(sb + R_RING + wq * 8192, &tm.x, h, wq, s + 1, bar + 8 * (B_FULL + wq)); }
                    OPAQUE(tb);
                    uint32_t* pp = g_part[s & 1] + (h * 32 + ((int)role + 3 * (tb >> 7)) * 8192 + ((tb >> 5) & 3) * 2048 + (tb & 31));
                    const uint64_t dWo = dWo0 + (uint64_t)((wq >> 2) * 1024);
                    if (role != 0 && (wq & 3) == 3) mbar_wait(bar + 8 * B_XRECV, s & 1);
                    mbar_wait(bar + 8 * B_O, s & 1);
                    PROF((wq >> 2) * 4 + 2);
                    float w0[4];
                    wo_issue(w0, dWo);
                    wo_store<0>(w0, pp);
                    wo_issue(w0, dWo + 2048);
                    if (role != 0 && (wq & 3) == 3) x_load_pair(sb + (wq == 3 ? e0 : e1), &tm.x, h, 3 + (wq >> 2), s + 1, bar + 8 * (B_FULL + 3 + (wq >> 2)));
                    wo_store<0>(w0, pp + 6 * 8192);
                    if (role != 0) {
                        wo_issue(w0, dWo + 4096);
                        wo_store<0>(w0, pp + (11 - (tb >> 7)) * 8192);
                    }
                    if (wq == 0) PROF(10);
                }
                if (role == 0) {
                    constexpr uint64_t dV = cdesc(R_V, 2048, 128, 0);
                    constexpr uint64_t dP = cdesc(R_QX, 128, 4096, 0);
                    mbar_wait(bar + 8 * B_P, s & 1);
                    wg_fence();
#pragma unroll
                    for (int k = 0; k < 3; k++) wg_ss32<0>(d, dV + (uint64_t)((wq >> 2) * 64 + k * 256), dP + (uint64_t)(k * 16), k);
                    wg_commit();
                    wg_wait<0>();
                    OPAQUE(tb);
                    const uint32_t r = ((tb >> 4) & 1) * 8 + (tb & 7), ch = ((tb >> 5) & 3) * 2 + ((tb >> 3) & 1);
                    const uint32_t ob = sb + R_QX + 2048 + (tb >> 7) * 8192;
                    const uint32_t oa = ob + r * 128 + ((ch ^ (r & 7)) << 4);
                    stsm4t(oa, pack_bf16(d[0], d[1]), pack_bf16(d[2], d[3]), pack_bf16(d[4], d[5]), pack_bf16(d[6], d[7]));
                    stsm4t(oa + 4096, pack_bf16(d[8], d[9]), pack_bf16(d[10], d[11]), pack_bf16(d[12], d[13]), pack_bf16(d[14], d[15]));
                    fence_async();
                    bar_sync(2 + (wq >> 2), 128);
                    if ((wq & 3) == 0) {
                        const uint32_t src = sb + R_QX + 2048 + (wq >> 2) * 8192;
                        e_tma_store(&tm.o, src, h * DH + (wq >> 2) * 64, s * SEG);
                        e_tma_store(&tm.o, src + 4096, h * DH + (wq >> 2) * 64, s * SEG + 16);
                        bulk_commit();
                    }
                }
                if (s == NSEG - 1) { bulk_wait_all(); break; }
            }
            const int seg = s + 1;
            OPAQUE(wq);
            const uint64_t dW = dW0 + (uint64_t)((wq >> 2) * (KS * 128));
#pragma unroll
            for (int p = 0; p < 8; p++) {
                const int slot = p % 5;
                mbar_wait(bar + 8 * (B_FULL + slot), slot < 3 ? (uint32_t)(p / 5) : (uint32_t)(seg & 1));
                PROF2(p);
                const uint64_t db = slot < 3 ? dX + (uint64_t)(slot * 512) : dX0 + (uint64_t)((slot == 3 ? e0 : e1) >> 4);
                wg_fence();
#pragma unroll
                for (int kk = 0; kk < 8; kk++) {
                    const int k = XORD >= 3 ? (kk & 1) * 4 + (kk >> 1) : kk;
                    const int ks = xo(2 * p + (k >> 2)) * 4 + (k & 3);
                    if (ks >= KR) wg_ss32<1>(d, dW + (uint64_t)((ks - KR) * 128), db + (uint64_t)((k >> 2) * 256 + (k & 3) * 2), p + k);
                    else wg_rs32(d, a[ks < KR ? ks : 0], db + (uint64_t)((k >> 2) * 256 + (k & 3) * 2), p + k);
                }
                wg_commit();
                if (p >= 1) {
                    wg_wait<1>();
                    if (p <= 3) {
                        if ((wq & 3) == p) e_arrive(bar + 8 * (B_EMPTY + p - 1));
                        if (wq == p + (p & 1) * 4) {
                            mbar_wait(bar + 8 * (B_EMPTY + p - 1), seg & 1);
                            x_load_pair(sb + R_RING + (p - 1) * 8192, &tm.x, h, p + 4, seg, bar + 8 * (B_FULL + p - 1));
                        }
                    }
                    if (p == 5 && (wq & 3) < 3) { bulk_wait_read(); e_arrive_remote(mapa(bar + 8 * B_TFREE, wq & 3)); }
                    if (p == 6 && (wq & 3) == 1) e_arrive(bar + 8 * B_AFREE0);
                    if (p == 7 && (wq & 3) == 2) e_arrive(bar + 8 * B_AFREE1);
                }
            }
            asm volatile("wgmma.wait_group.sync.aligned 0;" : ACC16(d)::"memory");
            PROF2(16);
            mbar_wait(bar + 8 * B_TFREE, seg & 1);
            const uint32_t tilex = sb + (role == 0 ? R_QX + 2048 : (role == 1 ? R_K + 2048 : R_V + 2048));
            {
                OPAQUE(tb);
                const uint32_t gs = role == 0 ? 4096 : 2048;
                const uint32_t sa = tilex + ((tb >> 4) & 1) * gs + (tb >> 5) * 256 + (tb & 15) * 16;
                stsm4(sa, pack_bf16(d[0], d[1]), pack_bf16(d[2], d[3]), pack_bf16(d[4], d[5]), pack_bf16(d[6], d[7]));
                stsm4(sa + 2 * gs, pack_bf16(d[8], d[9]), pack_bf16(d[10], d[11]), pack_bf16(d[12], d[13]), pack_bf16(d[14], d[15]));
            }
            fence_async();
            bar_sync(1, 256);
            if (wq < 2) {
                if (role != 0) { uint32_t pr = role + 1 + wq; pr = pr >= 3 ? pr - 3 : pr; e_bulk_s2s(mapa(tilex, pr), tilex, 8192, mapa(bar + 8 * B_XT, pr)); }
            } else if (wq == 4) {
                e_arrive(bar + 8 * B_XT);
            } else if (seg + 1 < NSEG) {
                if (wq == 2) x_load_pair(sb + R_RING + 16384, &tm.x, h, 2, seg + 1, bar + 8 * (B_FULL + 2));
                if (role == 0 && (wq & 3) == 3) x_load_pair(sb + (wq == 3 ? e0 : e1), &tm.x, h, 3 + (wq >> 2), seg + 1, bar + 8 * (B_FULL + 3 + (wq >> 2)));
            }
        }
}

template <uint32_t role> DEVINL void r_chain(const bf16* __restrict__ mem0, const int wid) {
    extern __shared__ __align__(1024) unsigned char smem_raw[];
    const uint32_t sb = smem_u32(smem_raw);
    const uint32_t bar = sb + R_BAR;
    const int tid = threadIdx.x;
    int h; asm("mov.u32 %0, %%clusterid.x;" : "=r"(h));
        int t = tid & 127;
        const float sl2 = 0.08838834764831845f * 1.4426950408889634f;
        const float NEGM = -1000000000.0f * 1.4426950408889634f;
        const int rg0 = ((int)role - 1) * 32 + h;
        if (role != 0 && (t & 63) < 8) st_strong16(&g_mem[3][(rg0 + (t >> 6) * 64) * 32 + (t & 63) * 4], make_uint4(0u, 0u, 0u, 0u));
        if (role == 0) sts128(sb + R_QM + t * 16, make_uint4(0u, 0u, 0u, 0u));
        {
            mbar_wait(bar + 8 * B_AFREE0, 0);
            mbar_wait(bar + 8 * B_AFREE1, 0);
#pragma unroll 2
            for (int i = 0; i < 8; i++) {
                const int col = (t >> 5) * 256 + i * 32 + (t & 31);
                const unsigned short* p = (const unsigned short*)mem0 + col;
                uint4 v;
                v.x = p[0] | ((uint32_t)p[DM] << 16);
                v.y = p[2 * DM] | ((uint32_t)p[3 * DM] << 16);
                v.z = p[4 * DM] | ((uint32_t)p[5 * DM] << 16);
                v.w = p[6 * DM] | ((uint32_t)p[7 * DM] << 16);
                sts128(sb + R_RING + (KC(col >> 6) + (col & 63)) * 16, v);
            }
            fence_async();
            __syncwarp();
            e_arrive(bar + 8 * B_MEM + (t >> 5) * 8);
        }
        constexpr uint64_t dQ = role == 0 ? cdesc(R_QX, 128, 2048, 0) : cdesc(R_QM, 128, 0, 0);
        constexpr uint64_t dK = cdesc(R_K, 128, 2048, 0);

        for (int s = 0; s < NSEG; s++) {
            mbar_wait(bar + 8 * B_XT, s & 1);
            if (t >= 1 && t < 3) { uint32_t pr = role + t; pr = pr >= 3 ? pr - 3 : pr; mbar_arrive_remote(mapa(bar + 8 * B_XRECV, pr)); }
            __syncwarp();
            mbar_wait(bar + 8 * B_HOP1, s & 1);
            PROF(8);
            fence_async();
            OPAQUE(t);
            if (s == NSEG - 1 && role != 0) break;
            float sc[20];
            wg_fence();
#pragma unroll
            for (int k = 0; k < 8; k++) wg_ss40(sc, dQ + (uint64_t)(k * 16), dK + (uint64_t)(k * 16), k);
            wg_commit();
            uint32_t t_o = 0;
            {
                const uint32_t va = sb + R_V + (t >> 5) * 512 + ((t >> 4) & 1) * 2048 + (t & 15) * 16;
                uint32_t v0[4], v1[4];
                ldsm4(v0, va); ldsm4(v1, va + 256);
                wg_wait<0>();
                float m = fmaxf(sc[0], sc[1]);
#pragma unroll
                for (int j = 1; j < 5; j++) m = fmaxf(m, fmaxf(sc[4 * j], sc[4 * j + 1]));
                m = fmaxf(m, __shfl_xor_sync(0xffffffffu, m, 1));
                m = fmaxf(m, __shfl_xor_sync(0xffffffffu, m, 2));
                const float mb = m * sl2;
                uint32_t pk[5];
#pragma unroll
                for (int j = 0; j < 5; j++) pk[j] = pack_bf16(ex2(fmaf(sc[4 * j], sl2, -mb)), ex2(fmaf(sc[4 * j + 1], sl2, -mb)));
                float o0[4] = {0.f, 0.f, 0.f, 0.f}, o1[4] = {0.f, 0.f, 0.f, 0.f}, ls[4] = {0.f, 0.f, 0.f, 0.f};
                constexpr uint32_t ONE = 0x3F803F80u;
                mma16816(o0, v0[0], v0[1], v0[2], v0[3], pk[0], pk[1]);
                mma16816(o1, v1[0], v1[1], v1[2], v1[3], pk[0], pk[1]);
                ldsm4(v0, va + 4096); ldsm4(v1, va + 4096 + 256);
                mma16816(ls, ONE, ONE, ONE, ONE, pk[0], pk[1]);
                mma16816(ls, ONE, ONE, ONE, ONE, pk[2], pk[3]);
                mma1688(ls, ONE, ONE, pk[4]);
                mma16816(o0, v0[0], v0[1], v0[2], v0[3], pk[2], pk[3]);
                mma16816(o1, v1[0], v1[1], v1[2], v1[3], pk[2], pk[3]);
                ldsm4(v0, sb + R_V + 8192 + t * 16);
                mma1688(o0, v0[0], v0[1], pk[4]);
                mma1688(o1, v0[2], v0[3], pk[4]);
                const float i0 = __fdividef(1.0f, ls[0]), i1 = __fdividef(1.0f, ls[1]);
                const uint32_t oa = sb + R_O + (t >> 5) * 512 + (t & 31) * 4;
                sts32(oa, pack_bf16(o0[0] * i0, o0[1] * i1));
                sts32(oa + 128, pack_bf16(o0[2] * i0, o0[3] * i1));
                sts32(oa + 256, pack_bf16(o1[0] * i0, o1[1] * i1));
                sts32(oa + 384, pack_bf16(o1[2] * i0, o1[3] * i1));
                fence_async();
                __syncwarp();
                e_arrive(bar + 8 * B_O);
                t_o = clk32();
                PROF(9);
            }
            if (t < 32) { e_expect(bar + 8 * B_HOP1, 4096); e_expect(bar + 8 * B_XT, role == 0 ? 16384 : 8192); }
            if (role == 0) {
                OPAQUE(t);
                const int t0 = t >> 2, c = t & 3;
                float m1 = NEGM;
#pragma unroll
                for (int j = 0; j < 5; j++) {
#pragma unroll
                    for (int e = 0; e < 2; e++) {
                        const int key = (j - 1) * 8 + c * 2 + e;
                        sc[4 * j + 2 + e] = (key <= t0) ? sc[4 * j + 2 + e] * sl2 : NEGM;
                        m1 = fmaxf(m1, sc[4 * j + 2 + e]);
                    }
                }
                m1 = fmaxf(m1, __shfl_xor_sync(0xffffffffu, m1, 1)); m1 = fmaxf(m1, __shfl_xor_sync(0xffffffffu, m1, 2));
                float l1 = 0.f;
#pragma unroll
                for (int j = 0; j < 5; j++) {
                    sc[4 * j + 2] = ex2(sc[4 * j + 2] - m1); sc[4 * j + 3] = ex2(sc[4 * j + 3] - m1);
                    l1 += sc[4 * j + 2] + sc[4 * j + 3];
                }
                l1 += __shfl_xor_sync(0xffffffffu, l1, 1); l1 += __shfl_xor_sync(0xffffffffu, l1, 2);
                const float i1 = __fdividef(1.0f, l1);
                const uint32_t pa = sb + R_QX + (t >> 5) * 4096 + (t & 31) * 4;
#pragma unroll
                for (int j = 0; j < 5; j++) sts32(pa + j * 128, pack_bf16(sc[4 * j + 2] * i1, sc[4 * j + 3] * i1));
                sts32(pa + 5 * 128, 0u);
                fence_async();
                __syncwarp();
                e_arrive(bar + 8 * B_P);
            }
            if (s == NSEG - 1) break;
            OPAQUE(t);
            PROF(11);
            if (role != 0) {
                const uint32_t* rp = g_part[s & 1] + ((rg0 + (t >> 6) * 64) * 1024 + ((t >> 2) & 7) * 32 + ((t >> 5) & 1) * 16 + (t & 3) * 4);
                uint4 v[4];
                uint32_t n = 0;
                spin_until(t_o + D2_BASE + (role - 1 + (t >> 6) * 2) * D2_STEP);
                PROF3(0, clk32());
#pragma unroll
                for (int i = 0; i < 4; i++) v[i] = ld_strong16(rp + i * 256);
                while (true) {
                    bool ok = true;
#pragma unroll
                    for (int i = 0; i < 4; i++) {
                        if (v[i].x == 0u || v[i].y == 0u || v[i].z == 0u || v[i].w == 0u) { v[i] = ld_strong16(rp + i * 256); ok = false; }
                    }
                    if (__all_sync(0xffffffffu, ok)) break;
                    if (++n > 20000000u) __trap();
                }
                PROF3(1, clk32()); PROF3(8, n);
                float f[8];
#define LO(u) __uint_as_float((u) << 16)
#define HI(u) __uint_as_float((u) & 0xffff0000u)
                f[0] = (LO(v[0].x) + LO(v[1].x)) + (LO(v[2].x) + LO(v[3].x)); f[1] = (HI(v[0].x) + HI(v[1].x)) + (HI(v[2].x) + HI(v[3].x));
                f[2] = (LO(v[0].y) + LO(v[1].y)) + (LO(v[2].y) + LO(v[3].y)); f[3] = (HI(v[0].y) + HI(v[1].y)) + (HI(v[2].y) + HI(v[3].y));
                f[4] = (LO(v[0].z) + LO(v[1].z)) + (LO(v[2].z) + LO(v[3].z)); f[5] = (HI(v[0].z) + HI(v[1].z)) + (HI(v[2].z) + HI(v[3].z));
                f[6] = (LO(v[0].w) + LO(v[1].w)) + (LO(v[2].w) + LO(v[3].w)); f[7] = (HI(v[0].w) + HI(v[1].w)) + (HI(v[2].w) + HI(v[3].w));
                const bool b4 = t & 16, b3 = t & 8;
                float g4[4], g2[2];
#pragma unroll
                for (int i = 0; i < 4; i++) g4[i] = (b4 ? f[4 + i] : f[i]) + __shfl_xor_sync(0xffffffffu, b4 ? f[i] : f[4 + i], 16);
#pragma unroll
                for (int i = 0; i < 2; i++) g2[i] = (b3 ? g4[2 + i] : g4[i]) + __shfl_xor_sync(0xffffffffu, b3 ? g4[i] : g4[2 + i], 8);
                g2[0] += __shfl_xor_sync(0xffffffffu, g2[0], 4);
                g2[1] += __shfl_xor_sync(0xffffffffu, g2[1], 4);
                OPAQUE(t);
                if (!(t & 4)) st_strong4(&g_mem[(s + 1) & 3][(rg0 + (t >> 6) * 64) * 32 + ((t >> 5) & 1) * 16 + (t & 3) * 4 + ((t >> 3) & 3)], pack_nz(g2[0], g2[1]));
                __syncwarp();
            }
            t_o += D2_BASE + DQ + D3 + (t >> 5) * D2_STEP;
            OPAQUE(t);
            PROF(12);
            {
                const uint32_t* rp = &g_mem[(s + 1) & 3][((t >> 5) * 256 + (t & 31)) * 4];
                uint4 v[8];
                uint32_t n = 0;
                spin_until(t_o);
                PROF3(2, clk32());
#pragma unroll
                for (int i = 0; i < 8; i++) v[i] = ld_strong16(rp + i * 128);
                while (true) {
                    bool ok = true;
#pragma unroll
                    for (int i = 0; i < 8; i++) {
                        if (v[i].x == 0u || v[i].y == 0u || v[i].z == 0u || v[i].w == 0u) { v[i] = ld_strong16(rp + i * 128); ok = false; }
                    }
                    if (__all_sync(0xffffffffu, ok)) break;
                    if (++n > 20000000u) __trap();
                }
                PROF(13);
                PROF3(3, clk32()); PROF3(9, n);
                mbar_wait(bar + 8 * B_AFREE0 + (t >> 6) * 8, (s + 1) & 1);
                PROF3(4, clk32());
#pragma unroll
                for (int i = 0; i < 8; i++) sts128(sb + R_RING + ((t >> 5) * 256 + KC(i >> 1) + (i & 1) * 32 + (t & 31)) * 16, v[i]);
                fence_async();
                __syncwarp();
                e_arrive(bar + 8 * B_MEM + (t >> 5) * 8);
                PROF(14);
                PROF3(5, clk32());
            }
            if (role != 0) {
                OPAQUE(t);
                uint32_t* zp = g_part[s & 1] + ((rg0 + (t >> 6) * 64) * 1024 + ((t >> 2) & 7) * 32 + ((t >> 5) & 1) * 16 + (t & 3) * 4);
#pragma unroll
                for (int i = 0; i < 4; i++) st_strong16(zp + i * 256, make_uint4(0u, 0u, 0u, 0u));
                if ((t & 31) < 4) st_strong16(&g_mem[s & 3][(rg0 + (t >> 6) * 64) * 32 + ((t >> 5) & 1) * 16 + (t & 3) * 4], make_uint4(0u, 0u, 0u, 0u));
                asm volatile("fence.acq_rel.gpu;" ::: "memory");
            }
        }
}

__global__ void __launch_bounds__(384, 1) r_kernel(const __grid_constant__ RMaps tm, const bf16* __restrict__ mem0) {
    extern __shared__ __align__(1024) unsigned char smem_raw[];
    const uint32_t sb = smem_u32(smem_raw);
    if ((sb & 0x3FFFFu) != SB0) __trap();
    const int tid = threadIdx.x;
    const int wid = __shfl_sync(0xffffffffu, tid >> 5, 0);
    uint32_t role; asm("mov.u32 %0, %%cluster_ctarank;" : "=r"(role));
    int h; asm("mov.u32 %0, %%clusterid.x;" : "=r"(h));
    const uint32_t bar = sb + R_BAR;
    asm volatile("griddepcontrol.launch_dependents;");
    KT(0, 0);

    if (tid == 0) {
        for (int i = 0; i < 5; i++) mbar_init(bar + 8 * (B_FULL + i), 1);
        for (int i = 0; i < 3; i++) mbar_init(bar + 8 * (B_EMPTY + i), 2);
        for (int i = 0; i < 4; i++) mbar_init(bar + 8 * (B_MEM + i), 1);
        mbar_init(bar + 8 * B_HOP1, 9);
        mbar_init(bar + 8 * B_XT, 2);
        mbar_init(bar + 8 * B_TFREE, 6);
        mbar_init(bar + 8 * B_P, 4);
        mbar_init(bar + 8 * B_XRECV, 2);
        mbar_init(bar + 8 * B_O, 4);
        mbar_init(bar + 8 * B_AFREE0, 2);
        mbar_init(bar + 8 * B_AFREE1, 2);
        mbar_init(bar + 8 * B_PRO0, 1);
        mbar_init(bar + 8 * B_PRO1, 1);
        asm volatile("fence.mbarrier_init.release.cluster;" ::: "memory");
        fence_async();
        const CUtensorMap* tw = &tm.w[role];
        mbar_expect(bar + 8 * B_PRO0, KR * 4096);
#pragma unroll 1
        for (int rb = 0; rb < KR / 2; rb++) tma_load(sb + rb * 8192, tw, h * DH + (rb & 1) * 64, KC(rb >> 1), bar + 8 * B_PRO0);
#pragma unroll 1
        for (int c = 0; c < 6; c++) {
            if (!(c & 1)) mbar_expect(bar + 8 * (B_FULL + (c >> 1)), 8192);
            tma_load(sb + R_RING + c * 4096, &tm.x, XC(c), 0, bar + 8 * (B_FULL + (c >> 1)));
        }
#pragma unroll 1
        for (int rb = KR / 2; rb < 32; rb++) tma_prefetch(tw, h * DH + (rb & 1) * 64, KC(rb >> 1));
#pragma unroll 1
        for (int i = 0; i < (role == 0 ? 4 : 6); i++) tma_prefetch(&tm.wo, wo_tile(role, i) * 64, h * DH);
        if (blockIdx.x < NSEG) {
#pragma unroll 1
            for (int c = 0; c < 16; c++) tma_prefetch(&tm.x, c * 64, blockIdx.x * SEG);
        }
        mbar_expect(bar + 8 * B_HOP1, 4096);
        mbar_expect(bar + 8 * B_XT, role == 0 ? 16384 : 8192);
    }
    __syncthreads();
    cluster_sync();

    if (wid < 8) {
        asm volatile("setmaxnreg.inc.sync.aligned.u32 224;");
        if (role == 0) r_big<0>(tm, wid); else if (role == 1) r_big<1>(tm, wid); else r_big<2>(tm, wid);
    } else {
        asm volatile("setmaxnreg.dec.sync.aligned.u32 56;");
        if (role == 0) r_chain<0>(mem0, wid); else if (role == 1) r_chain<1>(mem0, wid); else r_chain<2>(mem0, wid);
    }
    __syncwarp();
    asm volatile("barrier.cluster.arrive; barrier.cluster.wait;" ::: "memory");
    KT(0, 1);
}

constexpr int G_ST = 4;
constexpr int G_STAGE = 16384 + 32768;
constexpr int G_EPI = G_ST * G_STAGE;
constexpr int G_GATE = G_EPI + 32768;
constexpr int G_BAR = G_GATE + 1024;
constexpr int G_SMEM = G_BAR + 128 + 1024;

struct G1Maps { CUtensorMap x, wg, wu, h; };
constexpr int G1_NB = FF / 128;
constexpr int G1_TILES = 16 * G1_NB;

__global__ void __launch_bounds__(384, 1) g1_kernel(const __grid_constant__ G1Maps tm, const bf16* __restrict__ x, const bf16* __restrict__ gate_w) {
    extern __shared__ __align__(1024) unsigned char smem_raw[];
    const uint32_t sb = (smem_u32(smem_raw) + 1023) & ~1023u;
    float* sgate = (float*)(smem_raw + (sb - smem_u32(smem_raw)) + G_GATE);
    const int tid = threadIdx.x, lane = tid & 31;
    const int wg = __shfl_sync(0xffffffffu, tid >> 7, 0);
    const int warp = __shfl_sync(0xffffffffu, (tid >> 5) & 3, 0);
    const uint32_t bar = sb + G_BAR;
    const int t_begin = (int)(((long long)blockIdx.x * G1_TILES) / gridDim.x);
    const int t_end = (int)(((long long)(blockIdx.x + 1) * G1_TILES) / gridDim.x);
    const int mb0 = t_begin / G1_NB;
    KT(1, 0);
    if (tid == 0) {
        for (int i = 0; i < G_ST; i++) { mbar_init(bar + 8 * i, 1); mbar_init(bar + 8 * (G_ST + i), 2); }
        mbar_init(bar + 8 * 2 * G_ST, 3);
        fence_async();
    }
    __syncthreads();
    if (wg == 2) {
        asm volatile("setmaxnreg.dec.sync.aligned.u32 40;");
        if (warp == 0) {
            if (lane == 0) {
                int it = 0;
                for (int tile = t_begin; tile < t_end; tile++) {
                    const int mb = tile / G1_NB, nb = tile % G1_NB;
                    for (int kb = 0; kb < 16; kb++, it++) {
                        const int st = it % G_ST;
                        mbar_wait(bar + 8 * (G_ST + st), ((it / G_ST) & 1) ^ 1);
                        const uint32_t fb = bar + 8 * st, sa = sb + st * G_STAGE;
                        mbar_expect(fb, G_STAGE);
                        tma_load(sa, &tm.x, kb * 64, mb * 128, fb);
                        tma_load(sa + 16384, &tm.wg, nb * 128, kb * 64, fb);
                        tma_load(sa + 16384 + 8192, &tm.wg, nb * 128 + 64, kb * 64, fb);
                        tma_load(sa + 16384 + 16384, &tm.wu, nb * 128, kb * 64, fb);
                        tma_load(sa + 16384 + 24576, &tm.wu, nb * 128 + 64, kb * 64, fb);
                    }
                }
            }
        } else {
            const int nrows = ((t_end - 1) / G1_NB - mb0 + 1) * 128;
            for (int r = warp - 1; r < nrows; r += 3) {
                const uint4* xp = (const uint4*)(x + (size_t)(mb0 * 128 + r) * DM);
                const uint4* gp = (const uint4*)gate_w;
                float acc = 0.f;
#pragma unroll
                for (int i = 0; i < 4; i++) {
                    uint4 xv = xp[i * 32 + lane], gv = gp[i * 32 + lane];
                    const uint32_t xa[4] = {xv.x, xv.y, xv.z, xv.w}, ga[4] = {gv.x, gv.y, gv.z, gv.w};
#pragma unroll
                    for (int e = 0; e < 4; e++) {
                        acc = fmaf(__uint_as_float(xa[e] << 16), __uint_as_float(ga[e] << 16), acc);
                        acc = fmaf(__uint_as_float(xa[e] & 0xffff0000u), __uint_as_float(ga[e] & 0xffff0000u), acc);
                    }
                }
#pragma unroll
                for (int o = 16; o > 0; o >>= 1) acc += __shfl_xor_sync(0xffffffffu, acc, o);
                if (lane == 0) { float gt = 1.0f / (1.0f + __expf(-acc)); sgate[r] = gt; g_gate[mb0 * 128 + r] = gt; }
            }
            __syncwarp();
            if (lane == 0) mbar_arrive(bar + 8 * 2 * G_ST);
        }
    } else {
        asm volatile("setmaxnreg.inc.sync.aligned.u32 232;");
        float d[128];
        int it = 0;
        const uint32_t epi = sb + G_EPI + wg * 16384;
        for (int tile = t_begin; tile < t_end; tile++) {
            const int mb = tile / G1_NB, nb = tile % G1_NB;
            for (int kb = 0; kb < 16; kb++, it++) {
                const int st = it % G_ST;
                mbar_wait(bar + 8 * st, (it / G_ST) & 1);
                const uint64_t da = mkdesc(sb + st * G_STAGE + wg * 8192, 16, 1024, 1);
                const uint64_t db = mkdesc(sb + st * G_STAGE + 16384, 8192, 1024, 1);
                wg_fence();
#pragma unroll
                for (int k = 0; k < 4; k++) wg_ss256(d, da + (uint64_t)(k * 2), db + (uint64_t)(k * 128), kb | k);
                wg_commit();
                if (kb > 0) { wg_wait<1>(); if ((tid & 127) == 0) mbar_arrive(bar + 8 * (G_ST + (it - 1) % G_ST)); }
            }
            wg_wait<0>();
            if ((tid & 127) == 0) { mbar_arrive(bar + 8 * (G_ST + (it - 1) % G_ST)); bulk_wait_read(); }
            if (tile == t_begin) mbar_wait(bar + 8 * 2 * G_ST, 0);
            bar_sync(1 + wg, 128);
            const int r0 = (mb - mb0) * 128 + wg * 64 + warp * 16 + (lane >> 2);
            const float s0 = 1.0f - sgate[r0], s1 = 1.0f - sgate[r0 + 8];
            const int row = warp * 16 + ((lane >> 3) & 1) * 8 + (lane & 7);
#pragma unroll
            for (int j = 0; j < 16; j += 2) {
                uint32_t p[4];
#pragma unroll
                for (int q = 0; q < 4; q++) {
                    const int i = (j + (q >> 1)) * 4 + (q & 1) * 2;
                    const float sc = (q & 1) ? s1 : s0;
                    const float g0 = d[i], g1 = d[i + 1];
                    const float h0 = __fdividef(g0, 1.0f + __expf(-g0)) * d[64 + i] * sc;
                    const float h1 = __fdividef(g1, 1.0f + __expf(-g1)) * d[64 + i + 1] * sc;
                    p[q] = pack_bf16(h0, h1);
                }
                const int cgp = j + (lane >> 4);
                stsm4(epi + (cgp >> 3) * 8192 + row * 128 + (((cgp & 7) ^ (row & 7)) << 4), p[0], p[1], p[2], p[3]);
            }
            fence_async();
            bar_sync(1 + wg, 128);
            if ((tid & 127) == 0) {
                tma_store(&tm.h, epi, nb * 128, mb * 128 + wg * 64);
                tma_store(&tm.h, epi + 8192, nb * 128 + 64, mb * 128 + wg * 64);
                bulk_commit();
            }
        }
        if ((tid & 127) == 0) bulk_wait_all();
        KT(1, 1);
    }
    __syncwarp();
    asm volatile("griddepcontrol.wait;" ::: "memory");
}

struct G2Maps { CUtensorMap o, h, wo, wd, out; };

__global__ void __launch_bounds__(384, 1) g2_kernel(const __grid_constant__ G2Maps tm) {
    extern __shared__ __align__(1024) unsigned char smem_raw[];
    const uint32_t sb = (smem_u32(smem_raw) + 1023) & ~1023u;
    const int tid = threadIdx.x, lane = tid & 31;
    const int wg = __shfl_sync(0xffffffffu, tid >> 7, 0);
    const int warp = __shfl_sync(0xffffffffu, (tid >> 5) & 3, 0);
    const uint32_t bar = sb + G_BAR;
    const int kh = blockIdx.x & 1, nb = (blockIdx.x >> 1) & 3, mb = blockIdx.x >> 3;
    KT(2, 0);
    if (tid == 0) {
        for (int i = 0; i < G_ST; i++) { mbar_init(bar + 8 * i, 1); mbar_init(bar + 8 * (G_ST + i), 2); }
        fence_async();
    }
    __syncthreads();
    if (wg == 2) {
        asm volatile("setmaxnreg.dec.sync.aligned.u32 40;");
        if (warp == 0 && lane == 0) {
            for (int it = 0; it < 60; it++) {
                const int kb = kh * 60 + it, st = it % G_ST;
                mbar_wait(bar + 8 * (G_ST + st), ((it / G_ST) & 1) ^ 1);
                const uint32_t fb = bar + 8 * st, sa = sb + st * G_STAGE;
                mbar_expect(fb, G_STAGE);
                const CUtensorMap* ta = kb < 64 ? &tm.o : &tm.h;
                const CUtensorMap* tb = kb < 64 ? &tm.wo : &tm.wd;
                const int k0 = (kb < 64 ? kb : kb - 64) * 64;
                tma_load(sa, ta, k0, mb * 128, fb);
#pragma unroll
                for (int q = 0; q < 4; q++) tma_load(sa + 16384 + q * 8192, tb, nb * 256 + q * 64, k0, fb);
            }
        }
    } else {
        asm volatile("setmaxnreg.inc.sync.aligned.u32 232;");
        float d[128];
        const int r0 = mb * 128 + wg * 64 + warp * 16 + (lane >> 2);
        const float s0 = g_gate[r0], s1 = g_gate[r0 + 8];
        const int o_last = kh == 0 ? 59 : 3;
        for (int it = 0; it < 60; it++) {
            const int st = it % G_ST;
            mbar_wait(bar + 8 * st, (it / G_ST) & 1);
            const uint64_t da = mkdesc(sb + st * G_STAGE + wg * 8192, 16, 1024, 1);
            const uint64_t db = mkdesc(sb + st * G_STAGE + 16384, 8192, 1024, 1);
            wg_fence();
#pragma unroll
            for (int k = 0; k < 4; k++) wg_ss256(d, da + (uint64_t)(k * 2), db + (uint64_t)(k * 128), it | k);
            wg_commit();
            if (it == o_last) {
                wg_wait<0>();
#pragma unroll
                for (int i = 0; i < 128; i++) d[i] *= (i & 2) ? s1 : s0;
            } else {
                wg_wait<1>();
            }
            if (it > 0 && (tid & 127) == 0) mbar_arrive(bar + 8 * (G_ST + (it - 1) % G_ST));
        }
        wg_wait<0>();
        float4* mine = g_sk + (size_t)blockIdx.x * 4096 + tid;
        const float4* theirs = g_sk + (size_t)(blockIdx.x ^ 1) * 4096 + tid;
        if (kh == 0) {
#pragma unroll
            for (int i = 0; i < 16; i++) __stcg(mine + i * 256, make_float4(d[64 + 4 * i], d[64 + 4 * i + 1], d[64 + 4 * i + 2], d[64 + 4 * i + 3]));
        } else {
#pragma unroll
            for (int i = 0; i < 16; i++) __stcg(mine + i * 256, make_float4(d[4 * i], d[4 * i + 1], d[4 * i + 2], d[4 * i + 3]));
#pragma unroll
            for (int i = 0; i < 64; i++) d[i] = d[64 + i];
        }
        __threadfence();
        bar_sync(1, 256);
        if (tid == 0) {
            asm volatile("st.release.gpu.global.u32 [%0], %1;" ::"l"(&g_skflag[blockIdx.x]), "r"(1u) : "memory");
            uint32_t v, n = 0;
            do {
                asm volatile("ld.acquire.gpu.global.u32 %0, [%1];" : "=r"(v) : "l"(&g_skflag[blockIdx.x ^ 1]) : "memory");
                if (++n > 200000000u) __trap();
            } while (v == 0u);
            g_skflag[blockIdx.x ^ 1] = 0u;
        }
        bar_sync(1, 256);
        const uint32_t epi = sb + G_EPI + wg * 16384;
        const int row = warp * 16 + ((lane >> 3) & 1) * 8 + (lane & 7);
#pragma unroll
        for (int j = 0; j < 16; j += 2) {
            float4 u = __ldcg(theirs + j * 256), v = __ldcg(theirs + (j + 1) * 256);
            const int cgp = j + (lane >> 4);
            stsm4(epi + (cgp >> 3) * 8192 + row * 128 + (((cgp & 7) ^ (row & 7)) << 4),
                  pack_bf16(d[4 * j] + u.x, d[4 * j + 1] + u.y), pack_bf16(d[4 * j + 2] + u.z, d[4 * j + 3] + u.w),
                  pack_bf16(d[4 * j + 4] + v.x, d[4 * j + 5] + v.y), pack_bf16(d[4 * j + 6] + v.z, d[4 * j + 7] + v.w));
        }
        fence_async();
        bar_sync(2 + wg, 128);
        if ((tid & 127) == 0) {
            tma_store(&tm.out, epi, nb * 256 + kh * 128, mb * 128 + wg * 64);
            tma_store(&tm.out, epi + 8192, nb * 256 + kh * 128 + 64, mb * 128 + wg * 64);
            bulk_commit();
            bulk_wait_all();
        }
        KT(2, 1);
    }
}

typedef CUresult (*EncodeFn)(CUtensorMap*, CUtensorMapDataType, cuuint32_t, void*, const cuuint64_t*, const cuuint64_t*, const cuuint32_t*,
                             const cuuint32_t*, CUtensorMapInterleave, CUtensorMapSwizzle, CUtensorMapL2promotion, CUtensorMapFloatOOBfill);

static void make_map(EncodeFn enc, CUtensorMap* m, const void* ptr, uint64_t rows, uint64_t cols, uint32_t box_rows) {
    cuuint64_t dims[2] = {cols, rows};
    cuuint64_t strides[1] = {cols * 2};
    cuuint32_t box[2] = {64, box_rows};
    cuuint32_t es[2] = {1, 1};
    enc(m, CU_TENSOR_MAP_DATA_TYPE_BFLOAT16, 2, (void*)ptr, dims, strides, box, es, CU_TENSOR_MAP_INTERLEAVE_NONE,
        CU_TENSOR_MAP_SWIZZLE_128B, CU_TENSOR_MAP_L2_PROMOTION_L2_256B, CU_TENSOR_MAP_FLOAT_OOB_FILL_NONE);
}

extern "C" void kernel_launch(void* const* d_in, const int* in_sizes, int n_in, void* d_out, int out_size) {
    (void)in_sizes; (void)n_in; (void)out_size;
    const bf16* x = (const bf16*)d_in[0];
    const bf16* mem0 = (const bf16*)d_in[1];
    const bf16* gate_w = (const bf16*)d_in[11];
    static EncodeFn enc = nullptr;
    static int n_sm = 0;
    static void *pO = nullptr, *pH = nullptr;
    if (!enc) {
        void* fn = nullptr;
        cudaDriverEntryPointQueryResult qr;
        cudaGetDriverEntryPoint("cuTensorMapEncodeTiled", &fn, cudaEnableDefault, &qr);
        enc = (EncodeFn)fn;
        cudaDeviceGetAttribute(&n_sm, cudaDevAttrMultiProcessorCount, 0);
        cudaFuncSetAttribute(r_kernel, cudaFuncAttributeMaxDynamicSharedMemorySize, R_SMEM);
        cudaFuncSetAttribute(g1_kernel, cudaFuncAttributeMaxDynamicSharedMemorySize, G_SMEM);
        cudaFuncSetAttribute(g2_kernel, cudaFuncAttributeMaxDynamicSharedMemorySize, G_SMEM);
        cudaGetSymbolAddress(&pO, g_O);
        cudaGetSymbolAddress(&pH, g_H);
    }
    RMaps rm; G1Maps m1; G2Maps m2;
    make_map(enc, &rm.x, x, SEQ, DM, 32);
    for (int i = 0; i < 3; i++) make_map(enc, &rm.w[i], d_in[2 + i], DM, HD, 64);
    make_map(enc, &rm.wo, d_in[5], HD, DM, 128);
    make_map(enc, &rm.o, pO, SEQ, HD, 16);
    make_map(enc, &m1.x, x, SEQ, DM, 128);
    make_map(enc, &m1.wg, d_in[8], DM, FF, 64);
    make_map(enc, &m1.wu, d_in[9], DM, FF, 64);
    make_map(enc, &m1.h, pH, SEQ, FF, 64);
    make_map(enc, &m2.o, pO, SEQ, HD, 128);
    make_map(enc, &m2.h, pH, SEQ, FF, 128);
    make_map(enc, &m2.wo, d_in[5], HD, DM, 64);
    make_map(enc, &m2.wd, d_in[10], FF, DM, 64);
    make_map(enc, &m2.out, d_out, SEQ, DM, 64);

    cudaStream_t st = cudaStreamPerThread;
    {
        cudaLaunchConfig_t cfg = {};
        cfg.gridDim = dim3(96); cfg.blockDim = dim3(384); cfg.dynamicSmemBytes = R_SMEM; cfg.stream = st;
        cudaLaunchAttribute at[1];
        at[0].id = cudaLaunchAttributeClusterDimension; at[0].val.clusterDim.x = 3; at[0].val.clusterDim.y = 1; at[0].val.clusterDim.z = 1;
        cfg.attrs = at; cfg.numAttrs = 1;
        cudaLaunchKernelEx(&cfg, r_kernel, rm, mem0);
    }
    {
        cudaLaunchConfig_t cfg = {};
        cfg.gridDim = dim3(n_sm - 96); cfg.blockDim = dim3(384); cfg.dynamicSmemBytes = G_SMEM; cfg.stream = st;
        cudaLaunchAttribute at[1];
        at[0].id = cudaLaunchAttributeProgrammaticStreamSerialization; at[0].val.programmaticStreamSerializationAllowed = 1;
        cfg.attrs = at; cfg.numAttrs = 1;
        cudaLaunchKernelEx(&cfg, g1_kernel, m1, x, gate_w);
    }
    g2_kernel<<<128, 384, G_SMEM, st>>>(m2);
}
```

```cpp
#include <cuda_runtime.h>
#include <cuda_bf16.h>
#include <cuda.h>
#include <stdint.h>

typedef __nv_bfloat16 bf16;

constexpr int SEQ = 2048, DM = 1024, NH = 32, DH = 128, NMEM = 8, SEG = 32, NSEG = 64, FF = 3584;
constexpr int HD = NH * DH;

__device__ bf16 g_O[SEQ * HD];
__device__ bf16 g_H[SEQ * FF];
__device__ uint32_t g_gate[SEQ];
__device__ uint32_t g_part[4][128 * 32 * 32];
__device__ uint32_t g_mem[4][DM * 4];
constexpr int NFULL = 36;
constexpr int NLATE = 64 - NFULL;
__device__ float4 g_pre[NLATE * 32 * 256];
__device__ float4 g_sk[NLATE * 4 * 32 * 256];
__device__ uint32_t g_skcnt[NLATE], g_skdone[NLATE];
__device__ uint32_t g_hcnt[16], g_ocnt[16];
#define KT(k, i)
#define PT(i)

#define DEVINL __device__ __forceinline__
constexpr long long SPIN_LIMIT = 4000000000LL;

DEVINL uint32_t smem_u32(const void* p) { return (uint32_t)__cvta_generic_to_shared(p); }
DEVINL void mbar_init(uint32_t bar, uint32_t cnt) { asm volatile("mbarrier.init.shared::cta.b64 [%0], %1;" ::"r"(bar), "r"(cnt) : "memory"); }
DEVINL void mbar_arrive(uint32_t bar) { asm volatile("mbarrier.arrive.shared::cta.b64 _, [%0];" ::"r"(bar) : "memory"); }
DEVINL void mbar_expect(uint32_t bar, uint32_t bytes) { asm volatile("mbarrier.arrive.expect_tx.shared::cta.b64 _, [%0], %1;" ::"r"(bar), "r"(bytes) : "memory"); }
DEVINL void mbar_arrive_remote(uint32_t cbar) { asm volatile("mbarrier.arrive.relaxed.cluster.shared::cluster.b64 _, [%0];" ::"r"(cbar) : "memory"); }
DEVINL bool mbar_try(uint32_t bar, uint32_t par) {
    uint32_t ok;
    asm volatile("{ .reg .pred p; mbarrier.try_wait.parity.shared::cta.b64 p, [%1], %2; selp.u32 %0, 1, 0, p; }" : "=r"(ok) : "r"(bar), "r"(par) : "memory");
    return ok;
}
__device__ __noinline__ void mbar_wait_slow(uint32_t bar, uint32_t par) {
    long long t0 = clock64();
    while (!mbar_try(bar, par)) { if (clock64() - t0 > SPIN_LIMIT) __trap(); }
}
DEVINL void mbar_wait(uint32_t bar, uint32_t par) {
    uint32_t n = 0;
    while (!mbar_try(bar, par)) { if (++n > 200000000u) __trap(); }
}
DEVINL uint32_t mapa(uint32_t a, uint32_t r) { uint32_t o; asm volatile("mapa.shared::cluster.u32 %0, %1, %2;" : "=r"(o) : "r"(a), "r"(r)); return o; }
DEVINL void fence_async() { asm volatile("fence.proxy.async.shared::cta;" ::: "memory"); }
DEVINL void bar_sync(int id, int n) { asm volatile("bar.sync %0, %1;" ::"r"(id), "r"(n) : "memory"); }
DEVINL void cluster_sync() { asm volatile("barrier.cluster.arrive.aligned; barrier.cluster.wait.aligned;" ::: "memory"); }
DEVINL void tma_load(uint32_t dst, const CUtensorMap* tm, int c0, int c1, uint32_t bar) {
    asm volatile("cp.async.bulk.tensor.2d.shared::cluster.global.mbarrier::complete_tx::bytes [%0], [%1, {%3, %4}], [%2];"
                 ::"r"(dst), "l"(tm), "r"(bar), "r"(c0), "r"(c1) : "memory");
}
DEVINL void tma_prefetch(const CUtensorMap* tm, int c0, int c1) {
    asm volatile("cp.async.bulk.prefetch.tensor.2d.L2.global [%0, {%1, %2}];" ::"l"(tm), "r"(c0), "r"(c1) : "memory");
}
DEVINL void tma_store(const CUtensorMap* tm, uint32_t src, int c0, int c1) {
    asm volatile("cp.async.bulk.tensor.2d.global.shared::cta.bulk_group [%0, {%2, %3}], [%1];" ::"l"(tm), "r"(src), "r"(c0), "r"(c1) : "memory");
}
DEVINL void bulk_commit() { asm volatile("cp.async.bulk.commit_group;" ::: "memory"); }
DEVINL void bulk_wait_read() { asm volatile("cp.async.bulk.wait_group.read 0;" ::: "memory"); }
DEVINL void bulk_wait_all() { asm volatile("cp.async.bulk.wait_group 0;" ::: "memory"); }
DEVINL void bulk_s2s(uint32_t cdst, uint32_t src, uint32_t bytes, uint32_t cbar) {
    asm volatile("cp.async.bulk.shared::cluster.shared::cta.mbarrier::complete_tx::bytes [%0], [%1], %2, [%3];" ::"r"(cdst), "r"(src), "r"(bytes), "r"(cbar) : "memory");
}
DEVINL void st_async16(uint32_t cdst, uint4 v, uint32_t cbar) {
    asm volatile("st.async.shared::cluster.mbarrier::complete_tx::bytes.v4.b32 [%0], {%1,%2,%3,%4}, [%5];" ::"r"(cdst), "r"(v.x), "r"(v.y), "r"(v.z), "r"(v.w), "r"(cbar) : "memory");
}
DEVINL uint64_t mkdesc(uint32_t addr, uint32_t lbo, uint32_t sbo, uint32_t swz) {
    return (uint64_t)((addr & 0x3FFFF) >> 4) | ((uint64_t)(lbo >> 4) << 16) | ((uint64_t)(sbo >> 4) << 32) | ((uint64_t)swz << 62);
}
constexpr uint32_t SB0 = 1024;
__host__ __device__ constexpr uint64_t cdesc(uint32_t off, uint32_t lbo, uint32_t sbo, uint32_t swz) {
    return (uint64_t)(((SB0 + off) & 0x3FFFF) >> 4) | ((uint64_t)(lbo >> 4) << 16) | ((uint64_t)(sbo >> 4) << 32) | ((uint64_t)swz << 62);
}
DEVINL float ex2(float x) { float y; asm("ex2.approx.ftz.f32 %0, %1;" : "=f"(y) : "f"(x)); return y; }
DEVINL void spin_clk(int d) { uint32_t t0, t1; asm volatile("mov.u32 %0, %%clock;" : "=r"(t0)); do { asm volatile("mov.u32 %0, %%clock;" : "=r"(t1)); } while ((int)(t1 - t0) < d); }
#define PROBE_GAP 150
#define OPAQUE(x) asm volatile("" : "+r"(x))
DEVINL void wg_fence() { asm volatile("wgmma.fence.sync.aligned;" ::: "memory"); }
DEVINL void wg_commit() { asm volatile("wgmma.commit_group.sync.aligned;" ::: "memory"); }
template <int N> DEVINL void wg_wait() { asm volatile("wgmma.wait_group.sync.aligned %0;" ::"n"(N) : "memory"); }
DEVINL uint32_t pack_bf16(float lo, float hi) { uint32_t r; asm("cvt.rn.bf16x2.f32 %0, %1, %2;" : "=r"(r) : "f"(hi), "f"(lo)); return r; }
DEVINL void ldsm4(uint32_t* r, uint32_t a) { asm volatile("ldmatrix.sync.aligned.m8n8.x4.shared.b16 {%0,%1,%2,%3}, [%4];" : "=r"(r[0]), "=r"(r[1]), "=r"(r[2]), "=r"(r[3]) : "r"(a) : "memory"); }
DEVINL void ldsm4t(uint32_t* r, uint32_t a) { asm volatile("ldmatrix.sync.aligned.m8n8.x4.trans.shared.b16 {%0,%1,%2,%3}, [%4];" : "=r"(r[0]), "=r"(r[1]), "=r"(r[2]), "=r"(r[3]) : "r"(a) : "memory"); }
DEVINL void stsm4(uint32_t a, uint32_t r0, uint32_t r1, uint32_t r2, uint32_t r3) { asm volatile("stmatrix.sync.aligned.m8n8.x4.shared.b16 [%0], {%1,%2,%3,%4};" ::"r"(a), "r"(r0), "r"(r1), "r"(r2), "r"(r3) : "memory"); }
DEVINL void stsm4t(uint32_t a, uint32_t r0, uint32_t r1, uint32_t r2, uint32_t r3) { asm volatile("stmatrix.sync.aligned.m8n8.x4.trans.shared.b16 [%0], {%1,%2,%3,%4};" ::"r"(a), "r"(r0), "r"(r1), "r"(r2), "r"(r3) : "memory"); }
DEVINL void sts32(uint32_t a, uint32_t v) { asm volatile("st.shared.b32 [%0], %1;" ::"r"(a), "r"(v) : "memory"); }
DEVINL void sts128(uint32_t a, uint4 v) { asm volatile("st.shared.v4.b32 [%0], {%1,%2,%3,%4};" ::"r"(a), "r"(v.x), "r"(v.y), "r"(v.z), "r"(v.w) : "memory"); }
DEVINL uint4 lds128(uint32_t a) { uint4 v; asm volatile("ld.shared.v4.b32 {%0,%1,%2,%3}, [%4];" : "=r"(v.x), "=r"(v.y), "=r"(v.z), "=r"(v.w) : "r"(a) : "memory"); return v; }
DEVINL uint4 ld_strong16(const void* p) { uint4 v; asm volatile("ld.relaxed.gpu.global.v4.u32 {%0,%1,%2,%3}, [%4];" : "=r"(v.x), "=r"(v.y), "=r"(v.z), "=r"(v.w) : "l"(p) : "memory"); return v; }
DEVINL void st_strong8(void* p, uint32_t a, uint32_t b) { asm volatile("st.relaxed.gpu.global.v2.u32 [%0], {%1,%2};" ::"l"(p), "r"(a), "r"(b) : "memory"); }
DEVINL void st_strong4(void* p, uint32_t a) { asm volatile("st.relaxed.gpu.global.u32 [%0], %1;" ::"l"(p), "r"(a) : "memory"); }
DEVINL void st_strong16(void* p, uint4 v) { asm volatile("st.relaxed.gpu.global.v4.u32 [%0], {%1,%2,%3,%4};" ::"l"(p), "r"(v.x), "r"(v.y), "r"(v.z), "r"(v.w) : "memory"); }
DEVINL uint32_t pack_nz(float lo, float hi) { uint32_t r = pack_bf16(lo, hi); return r == 0u ? 0x8000u : r; }
DEVINL uint32_t min4(uint4 v, uint32_t m) { return __vimin3_u32(__vimin3_u32(v.x, v.y, m), v.z, v.w); }
DEVINL void mma16816(float* d, uint32_t a0, uint32_t a1, uint32_t a2, uint32_t a3, uint32_t b0, uint32_t b1) {
    asm volatile("mma.sync.aligned.m16n8k16.row.col.f32.bf16.bf16.f32 {%0,%1,%2,%3}, {%4,%5,%6,%7}, {%8,%9}, {%0,%1,%2,%3};"
                 : "+f"(d[0]), "+f"(d[1]), "+f"(d[2]), "+f"(d[3]) : "r"(a0), "r"(a1), "r"(a2), "r"(a3), "r"(b0), "r"(b1));
}
DEVINL void mma1688(float* d, uint32_t a0, uint32_t a1, uint32_t b0) {
    asm volatile("mma.sync.aligned.m16n8k8.row.col.f32.bf16.bf16.f32 {%0,%1,%2,%3}, {%4,%5}, {%6}, {%0,%1,%2,%3};"
                 : "+f"(d[0]), "+f"(d[1]), "+f"(d[2]), "+f"(d[3]) : "r"(a0), "r"(a1), "r"(b0));
}
template <int TA, int TB> DEVINL void wg_ss8(float* d, uint64_t da, uint64_t db, int sc) {
    asm volatile("{ .reg .pred p; setp.ne.b32 p, %6, 0; wgmma.mma_async.sync.aligned.m64n8k16.f32.bf16.bf16 {%0,%1,%2,%3}, %4, %5, p, 1, 1, %7, %8; }"
                 : "+f"(d[0]), "+f"(d[1]), "+f"(d[2]), "+f"(d[3]) : "l"(da), "l"(db), "r"(sc), "n"(TA), "n"(TB));
}
template <int TB> DEVINL void wg_rs8(float* d, const uint32_t* a, uint64_t db, int sc) {
    asm volatile("{ .reg .pred p; setp.ne.b32 p, %9, 0; wgmma.mma_async.sync.aligned.m64n8k16.f32.bf16.bf16 {%0,%1,%2,%3}, {%4,%5,%6,%7}, %8, p, 1, 1, %10; }"
                 : "+f"(d[0]), "+f"(d[1]), "+f"(d[2]), "+f"(d[3]) : "r"(a[0]), "r"(a[1]), "r"(a[2]), "r"(a[3]), "l"(db), "r"(sc), "n"(TB));
}
#define ACC16(d) "+f"(d[0]), "+f"(d[1]), "+f"(d[2]), "+f"(d[3]), "+f"(d[4]), "+f"(d[5]), "+f"(d[6]), "+f"(d[7]), "+f"(d[8]), "+f"(d[9]), "+f"(d[10]), "+f"(d[11]), "+f"(d[12]), "+f"(d[13]), "+f"(d[14]), "+f"(d[15])
template <int TA> DEVINL void wg_ss32(float* d, uint64_t da, uint64_t db, int sc) {
    asm volatile("{ .reg .pred p; setp.ne.b32 p, %18, 0; wgmma.mma_async.sync.aligned.m64n32k16.f32.bf16.bf16 {%0,%1,%2,%3,%4,%5,%6,%7,%8,%9,%10,%11,%12,%13,%14,%15}, %16, %17, p, 1, 1, %19, 0; }"
                 : ACC16(d) : "l"(da), "l"(db), "r"(sc), "n"(TA));
}
DEVINL void wg_rs32(float* d, const uint32_t* a, uint64_t db, int sc) {
    asm volatile("{ .reg .pred p; setp.ne.b32 p, %21, 0; wgmma.mma_async.sync.aligned.m64n32k16.f32.bf16.bf16 {%0,%1,%2,%3,%4,%5,%6,%7,%8,%9,%10,%11,%12,%13,%14,%15}, {%16,%17,%18,%19}, %20, p, 1, 1, 0; }"
                 : ACC16(d) : "r"(a[0]), "r"(a[1]), "r"(a[2]), "r"(a[3]), "l"(db), "r"(sc));
}
DEVINL void wg_ss40(float* d, uint64_t da, uint64_t db, int sc) {
    asm volatile("{ .reg .pred p; setp.ne.b32 p, %22, 0; wgmma.mma_async.sync.aligned.m64n40k16.f32.bf16.bf16 {%0,%1,%2,%3,%4,%5,%6,%7,%8,%9,%10,%11,%12,%13,%14,%15,%16,%17,%18,%19}, %20, %21, p, 1, 1, 1, 1; }"
                 : ACC16(d), "+f"(d[16]), "+f"(d[17]), "+f"(d[18]), "+f"(d[19]) : "l"(da), "l"(db), "r"(sc));
}
#define A8(d, o) "+f"(d[o]), "+f"(d[o + 1]), "+f"(d[o + 2]), "+f"(d[o + 3]), "+f"(d[o + 4]), "+f"(d[o + 5]), "+f"(d[o + 6]), "+f"(d[o + 7])
#define A32(d, o) A8(d, o), A8(d, o + 8), A8(d, o + 16), A8(d, o + 24)
DEVINL void wg_ss256(float* d, uint64_t da, uint64_t db, int sc) {
    asm volatile(
        "{ .reg .pred p; setp.ne.b32 p, %130, 0;\n"
        "wgmma.mma_async.sync.aligned.m64n256k16.f32.bf16.bf16 {"
        "%0,%1,%2,%3,%4,%5,%6,%7,%8,%9,%10,%11,%12,%13,%14,%15,%16,%17,%18,%19,%20,%21,%22,%23,%24,%25,%26,%27,%28,%29,%30,%31,"
        "%32,%33,%34,%35,%36,%37,%38,%39,%40,%41,%42,%43,%44,%45,%46,%47,%48,%49,%50,%51,%52,%53,%54,%55,%56,%57,%58,%59,%60,%61,%62,%63,"
        "%64,%65,%66,%67,%68,%69,%70,%71,%72,%73,%74,%75,%76,%77,%78,%79,%80,%81,%82,%83,%84,%85,%86,%87,%88,%89,%90,%91,%92,%93,%94,%95,"
        "%96,%97,%98,%99,%100,%101,%102,%103,%104,%105,%106,%107,%108,%109,%110,%111,%112,%113,%114,%115,%116,%117,%118,%119,%120,%121,%122,%123,%124,%125,%126,%127"
        "}, %128, %129, p, 1, 1, 0, 1; }"
        : A32(d, 0), A32(d, 32), A32(d, 64), A32(d, 96) : "l"(da), "l"(db), "r"(sc));
}

DEVINL float gate_row(const bf16* __restrict__ xr, const bf16* __restrict__ gate_w, int lane) {
    float acc = 0.f;
#pragma unroll
    for (int i = 0; i < 4; i++) {
        const uint4 xv = __ldg((const uint4*)xr + i * 32 + lane), gv = __ldg((const uint4*)gate_w + i * 32 + lane);
        const uint32_t xa[4] = {xv.x, xv.y, xv.z, xv.w}, ga[4] = {gv.x, gv.y, gv.z, gv.w};
#pragma unroll
        for (int e = 0; e < 4; e++) {
            acc = fmaf(__uint_as_float(xa[e] << 16), __uint_as_float(ga[e] << 16), acc);
            acc = fmaf(__uint_as_float(xa[e] & 0xffff0000u), __uint_as_float(ga[e] & 0xffff0000u), acc);
        }
    }
#pragma unroll
    for (int o = 16; o > 0; o >>= 1) acc += __shfl_xor_sync(0xffffffffu, acc, o);
    return 1.0f / (1.0f + __expf(-acc));
}
DEVINL uint32_t ld_strong4(const void* p) { uint32_t v; asm volatile("ld.relaxed.gpu.global.u32 %0, [%1];" : "=r"(v) : "l"(p) : "memory"); return v; }
DEVINL void wait_count(const uint32_t* p, uint32_t want) {
    uint32_t v, n = 0;
    while (true) {
        asm volatile("ld.acquire.gpu.global.u32 %0, [%1];" : "=r"(v) : "l"(p) : "memory");
        if (v >= want) break;
        __nanosleep(200);
        if (++n > 10000000u) __trap();
    }
}

constexpr int KR = 44;
constexpr int KS = 64 - KR;
constexpr int R_W = 0;
constexpr int R_WO = KS * 4096;
constexpr int R_QX = R_WO + 65536;
constexpr int R_RING = R_WO + 98304;
constexpr int R_K = R_RING + 24576;
constexpr int R_V = R_K + 10240;
constexpr int R_QM = R_V + 10240;
constexpr int R_O = R_QM + 2048;
constexpr int R_BAR = R_O + 2048;
constexpr int R_G = R_BAR + 256 + 512 + 256 + 128;
constexpr int R_SMEM = R_G + 512;
enum { B_FULL = 0, B_EMPTY = 5, B_MEM = 8, B_HOP1 = 12, B_XT, B_TFREE, B_O, B_AFREE0, B_AFREE1, B_PRO0, B_PRO1, B_XRECV, B_P };
#define D2_BASE 1200
#define D2_STEP 200
#define PD2 6
#define DQ 1700
#define D3 0

DEVINL uint32_t clk32() { uint32_t c_; asm volatile("mov.u32 %0, %%clock;" : "=r"(c_)); return c_; }
DEVINL void spin_until(uint32_t t) { while ((uint32_t)(t - clk32() - 1u) < 100000u) {} }
#define PROF(i)
#define PROF2(i)
#define PROF3(i, val)
DEVINL void e_arrive(uint32_t bar) { asm volatile("{ .reg .pred p; elect.sync _|p, 0xffffffff; @p mbarrier.arrive.shared::cta.b64 _, [%0]; }" ::"r"(bar) : "memory"); }
DEVINL void e_arrive_remote(uint32_t cbar) { asm volatile("{ .reg .pred p; elect.sync _|p, 0xffffffff; @p mbarrier.arrive.relaxed.cluster.shared::cluster.b64 _, [%0]; }" ::"r"(cbar) : "memory"); }
DEVINL void e_count(uint32_t* p) { asm volatile("{ .reg .pred p; elect.sync _|p, 0xffffffff; @p red.relaxed.gpu.global.add.u32 [%0], 1; }" ::"l"(p) : "memory"); }
DEVINL void e_expect(uint32_t bar, uint32_t bytes) { asm volatile("{ .reg .pred p; elect.sync _|p, 0xffffffff; @p mbarrier.arrive.expect_tx.shared::cta.b64 _, [%0], %1; }" ::"r"(bar), "r"(bytes) : "memory"); }
DEVINL void e_tma_load(uint32_t dst, const CUtensorMap* tm, int c0, int c1, uint32_t bar) {
    asm volatile("{ .reg .pred p; elect.sync _|p, 0xffffffff; @p cp.async.bulk.tensor.2d.shared::cluster.global.mbarrier::complete_tx::bytes [%0], [%1, {%3, %4}], [%2]; }"
                 ::"r"(dst), "l"(tm), "r"(bar), "r"(c0), "r"(c1) : "memory");
}
DEVINL void e_tma_store(const CUtensorMap* tm, uint32_t src, int c0, int c1) {
    asm volatile("{ .reg .pred p; elect.sync _|p, 0xffffffff; @p cp.async.bulk.tensor.2d.global.shared::cta.bulk_group [%0, {%2, %3}], [%1]; }" ::"l"(tm), "r"(src), "r"(c0), "r"(c1) : "memory");
}
DEVINL void e_bulk_s2s(uint32_t cdst, uint32_t src, uint32_t bytes, uint32_t cbar) {
    asm volatile("{ .reg .pred p; elect.sync _|p, 0xffffffff; @p cp.async.bulk.shared::cluster.shared::cta.mbarrier::complete_tx::bytes [%0], [%1], %2, [%3]; }" ::"r"(cdst), "r"(src), "r"(bytes), "r"(cbar) : "memory");
}

#define SLOT 0
#define PH3 0
#define PHQ 0
DEVINL void wait_slot(uint32_t phase) {
    if (SLOT) {
        uint32_t c; asm volatile("mov.u32 %0, %%globaltimer_lo;" : "=r"(c));
        const uint32_t tgt = c + (SLOT ? SLOT : 1) - ((c - phase) % (SLOT ? SLOT : 1));
        do { asm volatile("mov.u32 %0, %%globaltimer_lo;" : "=r"(c)); } while ((uint32_t)(tgt - c - 1u) < 100000u);
    }
}
template <int N> DEVINL uint32_t poll_set(uint4 (&v)[N], const uint32_t* rp, int stride, uint32_t phase) {
    wait_slot(phase);
#pragma unroll
    for (int i = 0; i < N; i++) v[i] = ld_strong16(rp + i * stride);
    uint32_t n = 0;
    while (true) {
        uint32_t m = 0xffffffffu;
#pragma unroll
        for (int i = 0; i < N; i++) m = min4(v[i], m);
        if (__all_sync(0xffffffffu, m != 0u)) return n;
        wait_slot(phase);
#pragma unroll
        for (int i = 0; i < N; i++)
            asm volatile("{ .reg .pred p; setp.eq.u32 p, %5, 0; @p ld.relaxed.gpu.global.v4.u32 {%0,%1,%2,%3}, [%4]; }"
                         : "+r"(v[i].x), "+r"(v[i].y), "+r"(v[i].z), "+r"(v[i].w) : "l"(rp + i * stride), "r"(min4(v[i], 0xffffffffu)) : "memory");
        if (++n > 20000000u) __trap();
    }
}

struct RMaps { CUtensorMap x, w[3], wo, o; };
#define KC(c) ((c) * 64)

#define XORD 3
__host__ __device__ constexpr int xo(int i) {
    return XORD == 0 ? i : XORD == 1 ? (i + 14) % 16 : XORD == 2 ? (i + 11) % 16
         : XORD == 3 ? (i < 10 ? ((i & 1) ? i / 2 : 11 + i / 2) : i - 5) : (i < 6 ? i : ((i & 1) ? 6 + (i - 6) / 2 : 11 + (i - 6) / 2));
}
#define XC(i) (xo(i) * 64)
DEVINL void x_load_pair(uint32_t dst, const CUtensorMap* tmx, int h, int p, int seg, uint32_t fbar) {
    e_expect(fbar, 8192);
    e_tma_load(dst, tmx, XC(2 * p), seg * SEG, fbar);
    e_tma_load(dst + 4096, tmx, XC(2 * p + 1), seg * SEG, fbar);
}
__host__ __device__ constexpr int wo_tile(int role, int i) { return i < 4 ? role + 3 * i : 11 + role + 2 * (i - 4); }

DEVINL void wo_issue(float* w, uint64_t dWo) {
    constexpr uint64_t dO = cdesc(R_O, 128, 128, 0);
    wg_fence();
#pragma unroll
    for (int k = 0; k < 8; k++) wg_ss8<1, 1>(w, dWo + (uint64_t)(k * 128), dO + (uint64_t)(k * 16), k);
    wg_commit();
}
template <int N> DEVINL void wo_store(float* w, uint32_t* q) {
    asm volatile("wgmma.wait_group.sync.aligned %4;" : "+f"(w[0]), "+f"(w[1]), "+f"(w[2]), "+f"(w[3]) : "n"(N) : "memory");
    st_strong4(q, pack_nz(w[0], w[1]));
    st_strong4(q + 1024, pack_nz(w[2], w[3]));
}

template <uint32_t role> DEVINL void r_big(const RMaps& tm, const int wid) {
    extern __shared__ __align__(1024) unsigned char smem_raw[];
    const uint32_t sb = smem_u32(smem_raw);
    const uint32_t bar = sb + R_BAR;
    const int tid = threadIdx.x;
    int h; asm("mov.u32 %0, %%clusterid.x;" : "=r"(h));
        uint32_t a[KR][4];
        mbar_wait(bar + 8 * B_PRO0, 0);
        PT(0);
        {
            const int lane = tid & 31;
            const int krow = (lane & 7) + ((lane >> 4) << 3);
            const int chunk = (wid & 3) * 2 + ((lane >> 3) & 1);
            const uint32_t la = sb + (wid >> 2) * 8192 + krow * 128 + ((chunk ^ (krow & 7)) << 4);
#pragma unroll
            for (int k = 0; k < KR; k++) ldsm4t(a[k], la + (k >> 2) * 16384 + (k & 3) * 2048);
        }
        bar_sync(1, 256);
        {
            fence_async();
            const CUtensorMap* tw = &tm.w[role];
            e_expect(bar + 8 * B_PRO1, (wid < 5 ? 16384 : 0) + (wid < (role == 0 ? 4 : 6) ? 16384 : 0));
            if (wid < 5) {
                e_tma_load(sb + R_W + wid * 8192, tw, h * DH, KC(KR / 4 + wid), bar + 8 * B_PRO1);
                e_tma_load(sb + R_W + KS * 2048 + wid * 8192, tw, h * DH + 64, KC(KR / 4 + wid), bar + 8 * B_PRO1);
            }
            if (wid < (role == 0 ? 4 : 6)) e_tma_load(sb + R_WO + wid * 16384, &tm.wo, wo_tile(role, wid) * 64, h * DH, bar + 8 * B_PRO1);
        }
        constexpr uint32_t e0 = role == 0 ? R_QX + 16384 : R_K + 2048, e1 = role == 0 ? R_QX + 24576 : R_V + 2048;
        if (wid == 6) x_load_pair(sb + e0, &tm.x, h, 3, 0, bar + 8 * (B_FULL + 3));
        if (wid == 7) x_load_pair(sb + e1, &tm.x, h, 4, 0, bar + 8 * (B_FULL + 4));
        PT(1);
        mbar_wait(bar + 8 * B_PRO1, 0);
        PT(2);

        constexpr uint64_t dW0 = cdesc(R_W, 1024, 1024, 1);
        constexpr uint64_t dWo0 = cdesc(R_WO, 1024, 1024, 1);
        constexpr uint64_t dM = cdesc(R_RING, 128, 128, 0);
        constexpr uint64_t dX = cdesc(R_RING, 16, 1024, 1);
        constexpr uint64_t dX0 = cdesc(0, 16, 1024, 1);
        int tb = tid;
        int wq = wid;

        float d[16];
        for (int s = -1; s < NSEG; s++) {
            if (s >= 0) {
                OPAQUE(wq);
                const uint64_t dW = dW0 + (uint64_t)((wq >> 2) * (KS * 128));
                float y[4] = {0.f, 0.f, 0.f, 0.f};
                {
                    OPAQUE(tb);
                    const uint32_t ma = sb + R_RING + (tb & 31) * 16;
                    float z[4] = {0.f, 0.f, 0.f, 0.f}, u[4] = {0.f, 0.f, 0.f, 0.f};
                    uint32_t b[4][4];
                    mbar_wait(bar + 8 * B_MEM, s & 1);
                    PROF((wq >> 2) * 4 + 0);
                    if (s == 0) PT(3);
                    if (s == 1) PT(4);
#pragma unroll
                    for (int g = 0; g < 4; g++) ldsm4t(b[g], ma + g * 512);
#pragma unroll
                    for (int g = 0; g < KR / 2; g++) {
                        float* c0 = (g % 3 == 0) ? y : (g % 3 == 1) ? u : z;
                        float* c1 = (g % 3 == 0) ? z : (g % 3 == 1) ? y : u;
                        mma16816(c0, a[2 * g][0], a[2 * g][1], a[2 * g][2], a[2 * g][3], b[g & 3][0], b[g & 3][1]);
                        mma16816(c1, a[2 * g + 1][0], a[2 * g + 1][1], a[2 * g + 1][2], a[2 * g + 1][3], b[g & 3][2], b[g & 3][3]);
                        if (g + 4 < KR / 2) {
                            if ((g + 4) % 8 == 0) mbar_wait(bar + 8 * (B_MEM + (g + 4) / 8), s & 1);
                            ldsm4t(b[g & 3], ma + (g + 4) * 512);
                        }
                    }
                    y[0] += z[0] + u[0]; y[1] += z[1] + u[1]; y[2] += z[2] + u[2]; y[3] += z[3] + u[3];
                }
                PROF2(8);
                mbar_wait(bar + 8 * (B_MEM + 3), s & 1);
                wg_fence();
#pragma unroll
                for (int k = KR; k < 64; k++) wg_ss8<1, 1>(y, dW + (uint64_t)((k - KR) * 128), dM + (uint64_t)(k * 16), 1);
                wg_commit();
                asm volatile("wgmma.wait_group.sync.aligned 0;" : "+f"(y[0]), "+f"(y[1]), "+f"(y[2]), "+f"(y[3])::"memory");
                OPAQUE(tb);
                {
                    const uint32_t wo_ = (tb >> 5) * 256;
                    const uint32_t tile = sb + (role == 0 ? R_QX : (role == 1 ? R_K : R_V)) + wo_;
                    const uint32_t u0 = pack_bf16(y[0], y[1]), u1 = pack_bf16(y[2], y[3]);
                    sts32(tile + (tb & 31) * 4, u0);
                    sts32(tile + (tb & 31) * 4 + 128, u1);
                    __syncwarp();
                    uint4 v = lds128(tile + (tb & 15) * 16);
                    uint32_t peer = role + 1 + ((tb >> 4) & 1);
                    peer = peer >= 3 ? peer - 3 : peer;
                    const uint32_t rt = sb + (role == 0 ? R_QM : (role == 1 ? R_K : R_V)) + wo_ + (tb & 15) * 16;
                    st_async16(mapa(rt, peer), v, mapa(bar + 8 * B_HOP1, peer));
                    if (role == 0) {
                        sts128(tile + 4096 + ((tb >> 4) & 1) * 4096 + (tb & 15) * 16, v);
                        sts32(tile + 12288 + (tb & 31) * 4, u0);
                        sts32(tile + 12288 + (tb & 31) * 4 + 128, u1);
                        __syncwarp();
                    }
                    e_arrive(bar + 8 * B_HOP1);
                }
                PROF((wq >> 2) * 4 + 1);
                if (s < NSEG - 1) {
                    bar_sync(1, 256);
                    if (wq < 2) { fence_async(); x_load_pair(sb + R_RING + wq * 8192, &tm.x, h, wq, s + 1, bar + 8 * (B_FULL + wq)); }
                    OPAQUE(tb);
                    uint32_t* pp = g_part[s & 3] + (h * 32 + ((int)role + 3 * (tb >> 7)) * 8192 + ((tb >> 5) & 3) * 2048 + (tb & 31));
                    const uint64_t dWo = dWo0 + (uint64_t)((wq >> 2) * 1024);
                    if (role != 0 && (wq & 3) == 3) mbar_wait(bar + 8 * B_XRECV, s & 1);
                    mbar_wait(bar + 8 * B_O, s & 1);
                    PROF((wq >> 2) * 4 + 2);
                    float w0[4];
                    wo_issue(w0, dWo);
                    wo_store<0>(w0, pp);
                    wo_issue(w0, dWo + 2048);
                    if (role != 0 && (wq & 3) == 3) x_load_pair(sb + (wq == 3 ? e0 : e1), &tm.x, h, 3 + (wq >> 2), s + 1, bar + 8 * (B_FULL + 3 + (wq >> 2)));
                    wo_store<0>(w0, pp + 6 * 8192);
                    if (role != 0) {
                        wo_issue(w0, dWo + 4096);
                        wo_store<0>(w0, pp + (11 - (tb >> 7)) * 8192);
                    }
                    if (wq == 0) PROF(10);
                }
                if (role == 0) {
                    constexpr uint64_t dV = cdesc(R_V, 2048, 128, 0);
                    constexpr uint64_t dP = cdesc(R_QX, 128, 4096, 0);
                    mbar_wait(bar + 8 * B_P, s & 1);
                    wg_fence();
#pragma unroll
                    for (int k = 0; k < 3; k++) wg_ss32<0>(d, dV + (uint64_t)((wq >> 2) * 64 + k * 256), dP + (uint64_t)(k * 16), k);
                    wg_commit();
                    wg_wait<0>();
                    OPAQUE(tb);
                    const uint32_t r = ((tb >> 4) & 1) * 8 + (tb & 7), ch = ((tb >> 5) & 3) * 2 + ((tb >> 3) & 1);
                    const uint32_t ob = sb + R_QX + 2048 + (tb >> 7) * 8192;
                    const uint32_t oa = ob + r * 128 + ((ch ^ (r & 7)) << 4);
                    stsm4t(oa, pack_bf16(d[0], d[1]), pack_bf16(d[2], d[3]), pack_bf16(d[4], d[5]), pack_bf16(d[6], d[7]));
                    stsm4t(oa + 4096, pack_bf16(d[8], d[9]), pack_bf16(d[10], d[11]), pack_bf16(d[12], d[13]), pack_bf16(d[14], d[15]));
                    fence_async();
                    bar_sync(2 + (wq >> 2), 128);
                    if ((wq & 3) == 0) {
                        const uint32_t src = sb + R_QX + 2048 + (wq >> 2) * 8192;
                        e_tma_store(&tm.o, src, h * DH + (wq >> 2) * 64, s * SEG);
                        e_tma_store(&tm.o, src + 4096, h * DH + (wq >> 2) * 64, s * SEG + 16);
                        bulk_commit();
                    }
                }
                if (s == NSEG - 1) { bulk_wait_all(); break; }
            }
            const int seg = s + 1;
            OPAQUE(wq);
            const uint64_t dW = dW0 + (uint64_t)((wq >> 2) * (KS * 128));
#pragma unroll
            for (int p = 0; p < 8; p++) {
                const int slot = p % 5;
                mbar_wait(bar + 8 * (B_FULL + slot), slot < 3 ? (uint32_t)(p / 5) : (uint32_t)(seg & 1));
                PROF2(p);
                const uint64_t db = slot < 3 ? dX + (uint64_t)(slot * 512) : dX0 + (uint64_t)((slot == 3 ? e0 : e1) >> 4);
                wg_fence();
#pragma unroll
                for (int kk = 0; kk < 8; kk++) {
                    const int k = XORD >= 3 ? (kk & 1) * 4 + (kk >> 1) : kk;
                    const int ks = xo(2 * p + (k >> 2)) * 4 + (k & 3);
                    if (ks >= KR) wg_ss32<1>(d, dW + (uint64_t)((ks - KR) * 128), db + (uint64_t)((k >> 2) * 256 + (k & 3) * 2), p + k);
                    else wg_rs32(d, a[ks < KR ? ks : 0], db + (uint64_t)((k >> 2) * 256 + (k & 3) * 2), p + k);
                }
                wg_commit();
                if (p >= 1) {
                    wg_wait<1>();
                    if (p <= 3) {
                        if ((wq & 3) == p) e_arrive(bar + 8 * (B_EMPTY + p - 1));
                        if (wq == p + (p & 1) * 4) {
                            mbar_wait(bar + 8 * (B_EMPTY + p - 1), seg & 1);
                            x_load_pair(sb + R_RING + (p - 1) * 8192, &tm.x, h, p + 4, seg, bar + 8 * (B_FULL + p - 1));
                        }
                    }
                    if (p == 5 && (wq & 3) < 3) {
                        if (role == 0) {
                            bulk_wait_all();
                            if ((wq & 3) == 0 && s >= 0) e_count(&g_ocnt[s >> 2]);
                        }
                        e_arrive_remote(mapa(bar + 8 * B_TFREE, wq & 3));
                    }
                    if (p == 6 && (wq & 3) == 1) e_arrive(bar + 8 * B_AFREE0);
                    if (p == 7 && (wq & 3) == 2) e_arrive(bar + 8 * B_AFREE1);
                }
            }
            asm volatile("wgmma.wait_group.sync.aligned 0;" : ACC16(d)::"memory");
            PROF2(16);
            mbar_wait(bar + 8 * B_TFREE, seg & 1);
            const uint32_t tilex = sb + (role == 0 ? R_QX + 2048 : (role == 1 ? R_K + 2048 : R_V + 2048));
            {
                OPAQUE(tb);
                const uint32_t gs = role == 0 ? 4096 : 2048;
                const uint32_t sa = tilex + ((tb >> 4) & 1) * gs + (tb >> 5) * 256 + (tb & 15) * 16;
                stsm4(sa, pack_bf16(d[0], d[1]), pack_bf16(d[2], d[3]), pack_bf16(d[4], d[5]), pack_bf16(d[6], d[7]));
                stsm4(sa + 2 * gs, pack_bf16(d[8], d[9]), pack_bf16(d[10], d[11]), pack_bf16(d[12], d[13]), pack_bf16(d[14], d[15]));
            }
            fence_async();
            bar_sync(1, 256);
            if (wq < 2) {
                if (role != 0) { uint32_t pr = role + 1 + wq; pr = pr >= 3 ? pr - 3 : pr; e_bulk_s2s(mapa(tilex, pr), tilex, 8192, mapa(bar + 8 * B_XT, pr)); }
            } else if (wq == 4) {
                e_arrive(bar + 8 * B_XT);
            } else if (seg + 1 < NSEG) {
                if (wq == 2) x_load_pair(sb + R_RING + 16384, &tm.x, h, 2, seg + 1, bar + 8 * (B_FULL + 2));
                if (role == 0 && (wq & 3) == 3) x_load_pair(sb + (wq == 3 ? e0 : e1), &tm.x, h, 3 + (wq >> 2), seg + 1, bar + 8 * (B_FULL + 3 + (wq >> 2)));
            }
        }
}

template <uint32_t role> DEVINL void r_chain(const bf16* __restrict__ mem0, const bf16* __restrict__ x, const bf16* __restrict__ gate_w, const int wid) {
    extern __shared__ __align__(1024) unsigned char smem_raw[];
    const uint32_t sb = smem_u32(smem_raw);
    const uint32_t bar = sb + R_BAR;
    const int tid = threadIdx.x;
    int h; asm("mov.u32 %0, %%clusterid.x;" : "=r"(h));
        int t = tid & 127;
        const float sl2 = 0.08838834764831845f * 1.4426950408889634f;
        const float NEGM = -1000000000.0f * 1.4426950408889634f;
        const int rg0 = ((int)role - 1) * 32 + h;
        if (role != 0) {
#pragma unroll 1
            for (int r = 0; r < 4; r++) {
                uint32_t* zp = g_part[r] + ((rg0 + (t >> 6) * 64) * 1024 + (t & 63) * 4);
#pragma unroll
                for (int i = 0; i < 4; i++) st_strong16(zp + i * 256, make_uint4(0u, 0u, 0u, 0u));
                if ((t & 63) < 8) st_strong16(&g_mem[r][(rg0 + (t >> 6) * 64) * 32 + (t & 63) * 4], make_uint4(0u, 0u, 0u, 0u));
            }
            __threadfence();
        }
        {
#pragma unroll 1
            for (int r = (h * 3 + (int)role) * 4 + (t >> 5); r < SEQ; r += 384) {
                const uint32_t gb = __float_as_uint(gate_row(x + r * DM, gate_w, t & 31));
                if ((t & 31) == 0) st_strong4(&g_gate[r], gb ? gb : 0x80000000u);
            }
        }
        if (role == 0) sts128(sb + R_QM + t * 16, make_uint4(0u, 0u, 0u, 0u));
        {
            uint4 v[8];
#pragma unroll
            for (int r = 0; r < 8; r++) v[r] = __ldg((const uint4*)(mem0 + r * DM) + t);
            mbar_wait(bar + 8 * B_AFREE0, 0);
            mbar_wait(bar + 8 * B_AFREE1, 0);
#define TR2(f, c) \
            sts128(sb + R_RING + t * 128 + (c) * 16, make_uint4(__byte_perm(v[0].f, v[1].f, 0x5410), __byte_perm(v[2].f, v[3].f, 0x5410), __byte_perm(v[4].f, v[5].f, 0x5410), __byte_perm(v[6].f, v[7].f, 0x5410))); \
            sts128(sb + R_RING + t * 128 + (c) * 16 + 16, make_uint4(__byte_perm(v[0].f, v[1].f, 0x7632), __byte_perm(v[2].f, v[3].f, 0x7632), __byte_perm(v[4].f, v[5].f, 0x7632), __byte_perm(v[6].f, v[7].f, 0x7632)));
            TR2(x, 0) TR2(y, 2) TR2(z, 4) TR2(w, 6)
            fence_async();
            __syncwarp();
            e_arrive(bar + 8 * B_MEM + (t >> 5) * 8);
        }
        constexpr uint64_t dQ = role == 0 ? cdesc(R_QX, 128, 2048, 0) : cdesc(R_QM, 128, 0, 0);
        constexpr uint64_t dK = cdesc(R_K, 128, 2048, 0);

        for (int s = 0; s < NSEG; s++) {
            if (role == 0) {
                uint32_t n = 0, gate;
                do { gate = ld_strong4(&g_gate[s * SEG + (t >> 2)]); if (++n > 20000000u) __trap(); } while (gate == 0u);
                sts32(sb + R_G + t * 4, gate);
                __syncwarp();
            }
            mbar_wait(bar + 8 * B_XT, s & 1);
            if (t >= 1 && t < 3) { uint32_t pr = role + t; pr = pr >= 3 ? pr - 3 : pr; mbar_arrive_remote(mapa(bar + 8 * B_XRECV, pr)); }
            __syncwarp();
            mbar_wait(bar + 8 * B_HOP1, s & 1);
            PROF(8);
            fence_async();
            OPAQUE(t);
            if (s == NSEG - 1 && role != 0) break;
            float sc[20];
            wg_fence();
#pragma unroll
            for (int k = 0; k < 8; k++) wg_ss40(sc, dQ + (uint64_t)(k * 16), dK + (uint64_t)(k * 16), k);
            wg_commit();
            uint32_t t_o = 0;
            {
                const uint32_t va = sb + R_V + (t >> 5) * 512 + ((t >> 4) & 1) * 2048 + (t & 15) * 16;
                uint32_t v0[4], v1[4];
                ldsm4(v0, va); ldsm4(v1, va + 256);
                wg_wait<0>();
                float m = fmaxf(sc[0], sc[1]);
#pragma unroll
                for (int j = 1; j < 5; j++) m = fmaxf(m, fmaxf(sc[4 * j], sc[4 * j + 1]));
                m = fmaxf(m, __shfl_xor_sync(0xffffffffu, m, 1));
                m = fmaxf(m, __shfl_xor_sync(0xffffffffu, m, 2));
                const float mb = m * sl2;
                uint32_t pk[5];
#pragma unroll
                for (int j = 0; j < 5; j++) pk[j] = pack_bf16(ex2(fmaf(sc[4 * j], sl2, -mb)), ex2(fmaf(sc[4 * j + 1], sl2, -mb)));
                float o0[4] = {0.f, 0.f, 0.f, 0.f}, o1[4] = {0.f, 0.f, 0.f, 0.f}, ls[4] = {0.f, 0.f, 0.f, 0.f};
                constexpr uint32_t ONE = 0x3F803F80u;
                mma16816(o0, v0[0], v0[1], v0[2], v0[3], pk[0], pk[1]);
                mma16816(o1, v1[0], v1[1], v1[2], v1[3], pk[0], pk[1]);
                ldsm4(v0, va + 4096); ldsm4(v1, va + 4096 + 256);
                mma16816(ls, ONE, ONE, ONE, ONE, pk[0], pk[1]);
                mma16816(ls, ONE, ONE, ONE, ONE, pk[2], pk[3]);
                mma1688(ls, ONE, ONE, pk[4]);
                mma16816(o0, v0[0], v0[1], v0[2], v0[3], pk[2], pk[3]);
                mma16816(o1, v1[0], v1[1], v1[2], v1[3], pk[2], pk[3]);
                ldsm4(v0, sb + R_V + 8192 + t * 16);
                mma1688(o0, v0[0], v0[1], pk[4]);
                mma1688(o1, v0[2], v0[3], pk[4]);
                const float i0 = __fdividef(1.0f, ls[0]), i1 = __fdividef(1.0f, ls[1]);
                const uint32_t oa = sb + R_O + (t >> 5) * 512 + (t & 31) * 4;
                sts32(oa, pack_bf16(o0[0] * i0, o0[1] * i1));
                sts32(oa + 128, pack_bf16(o0[2] * i0, o0[3] * i1));
                sts32(oa + 256, pack_bf16(o1[0] * i0, o1[1] * i1));
                sts32(oa + 384, pack_bf16(o1[2] * i0, o1[3] * i1));
                fence_async();
                __syncwarp();
                e_arrive(bar + 8 * B_O);
                t_o = clk32();
                PROF(9);
            }
            if (t < 32) { e_expect(bar + 8 * B_HOP1, 4096); e_expect(bar + 8 * B_XT, role == 0 ? 16384 : 8192); }
            if (role == 0) {
                OPAQUE(t);
                const int t0 = t >> 2, c = t & 3;
                uint32_t gate; asm volatile("ld.shared.b32 %0, [%1];" : "=r"(gate) : "r"(sb + R_G + t * 4) : "memory");
                float m1 = NEGM;
#pragma unroll
                for (int j = 0; j < 5; j++) {
#pragma unroll
                    for (int e = 0; e < 2; e++) {
                        const int key = (j - 1) * 8 + c * 2 + e;
                        sc[4 * j + 2 + e] = (key <= t0) ? sc[4 * j + 2 + e] * sl2 : NEGM;
                        m1 = fmaxf(m1, sc[4 * j + 2 + e]);
                    }
                }
                m1 = fmaxf(m1, __shfl_xor_sync(0xffffffffu, m1, 1)); m1 = fmaxf(m1, __shfl_xor_sync(0xffffffffu, m1, 2));
                float l1 = 0.f;
#pragma unroll
                for (int j = 0; j < 5; j++) {
                    sc[4 * j + 2] = ex2(sc[4 * j + 2] - m1); sc[4 * j + 3] = ex2(sc[4 * j + 3] - m1);
                    l1 += sc[4 * j + 2] + sc[4 * j + 3];
                }
                l1 += __shfl_xor_sync(0xffffffffu, l1, 1); l1 += __shfl_xor_sync(0xffffffffu, l1, 2);
                const float i1 = __fdividef(__uint_as_float(gate), l1);
                const uint32_t pa = sb + R_QX + (t >> 5) * 4096 + (t & 31) * 4;
#pragma unroll
                for (int j = 0; j < 5; j++) sts32(pa + j * 128, pack_bf16(sc[4 * j + 2] * i1, sc[4 * j + 3] * i1));
                sts32(pa + 5 * 128, 0u);
                fence_async();
                __syncwarp();
                e_arrive(bar + 8 * B_P);
            }
            if (s == NSEG - 1) break;
            OPAQUE(t);
            PROF(11);
            if (role != 0) {
                const uint32_t* rp = g_part[s & 3] + ((rg0 + (t >> 6) * 64) * 1024 + ((t >> 2) & 7) * 32 + ((t >> 5) & 1) * 16 + (t & 3) * 4);
                uint32_t* wp = &g_mem[(s + 1) & 3][(rg0 + (t >> 6) * 64) * 32 + ((t >> 5) & 1) * 16 + (t & 3) * 4 + ((t >> 3) & 3)];
                spin_until(t_o + D2_BASE + (role - 1 + (t >> 6) * 2) * D2_STEP);
                PROF3(0, clk32());
#define LO(u) __uint_as_float((u) << 16)
#define HI(u) __uint_as_float((u) & 0xffff0000u)
                uint4 v[4];
                uint32_t n = poll_set<4>(v, rp, 256, (role - 1 + (t >> 6) * 2) * PHQ);
                {
                    PROF3(1, clk32());
                    float f[8];
                    f[0] = (LO(v[0].x) + LO(v[1].x)) + (LO(v[2].x) + LO(v[3].x)); f[1] = (HI(v[0].x) + HI(v[1].x)) + (HI(v[2].x) + HI(v[3].x));
                    f[2] = (LO(v[0].y) + LO(v[1].y)) + (LO(v[2].y) + LO(v[3].y)); f[3] = (HI(v[0].y) + HI(v[1].y)) + (HI(v[2].y) + HI(v[3].y));
                    f[4] = (LO(v[0].z) + LO(v[1].z)) + (LO(v[2].z) + LO(v[3].z)); f[5] = (HI(v[0].z) + HI(v[1].z)) + (HI(v[2].z) + HI(v[3].z));
                    f[6] = (LO(v[0].w) + LO(v[1].w)) + (LO(v[2].w) + LO(v[3].w)); f[7] = (HI(v[0].w) + HI(v[1].w)) + (HI(v[2].w) + HI(v[3].w));
                    const bool b4 = t & 16, b3 = t & 8;
                    float g4[4], g2[2];
#pragma unroll
                    for (int i = 0; i < 4; i++) g4[i] = (b4 ? f[4 + i] : f[i]) + __shfl_xor_sync(0xffffffffu, b4 ? f[i] : f[4 + i], 16);
#pragma unroll
                    for (int i = 0; i < 2; i++) g2[i] = (b3 ? g4[2 + i] : g4[i]) + __shfl_xor_sync(0xffffffffu, b3 ? g4[i] : g4[2 + i], 8);
                    g2[0] += __shfl_xor_sync(0xffffffffu, g2[0], 4);
                    g2[1] += __shfl_xor_sync(0xffffffffu, g2[1], 4);
                    st_strong4(wp, pack_nz(g2[0], g2[1]));
                }
                PROF3(8, n); (void)n;
            }
            t_o += D2_BASE + DQ + D3 + (t >> 5) * D2_STEP;
            OPAQUE(t);
            PROF(12);
            {
                const uint32_t* rp = &g_mem[(s + 1) & 3][((t >> 5) * 256 + (t & 31)) * 4];
                const uint32_t da = sb + R_RING + ((t >> 5) * 256 + (t & 31)) * 16;
                uint4 v[8];
                spin_until(t_o);
                PROF3(2, clk32());
                uint32_t n = poll_set<8>(v, rp, 128, PH3 + (t >> 5) * PHQ);
                PROF(13);
                PROF3(3, clk32()); PROF3(9, n); (void)n;
                mbar_wait(bar + 8 * B_AFREE0 + (t >> 6) * 8, (s + 1) & 1);
                PROF3(4, clk32());
#pragma unroll
                for (int i = 0; i < 8; i++) sts128(da + i * 512, v[i]);
                if (t >= 64) fence_async();
                __syncwarp();
                e_arrive(bar + 8 * B_MEM + (t >> 5) * 8);
                PROF(14);
                PROF3(5, clk32());
            }
            if (role != 0) {
                OPAQUE(t);
                uint32_t* zp = g_part[s & 3] + ((rg0 + (t >> 6) * 64) * 1024 + ((t >> 2) & 7) * 32 + ((t >> 5) & 1) * 16 + (t & 3) * 4);
#pragma unroll
                for (int i = 0; i < 4; i++) st_strong16(zp + i * 256, make_uint4(0u, 0u, 0u, 0u));
                if ((t & 31) < 4) st_strong16(&g_mem[s & 3][(rg0 + (t >> 6) * 64) * 32 + ((t >> 5) & 1) * 16 + (t & 3) * 4], make_uint4(0u, 0u, 0u, 0u));
            }
        }
}

__global__ void __launch_bounds__(384, 1) r_kernel(const __grid_constant__ RMaps tm, const bf16* __restrict__ mem0, const bf16* __restrict__ x, const bf16* __restrict__ gate_w) {
    extern __shared__ __align__(1024) unsigned char smem_raw[];
    const uint32_t sb = smem_u32(smem_raw);
    if ((sb & 0x3FFFFu) != SB0) __trap();
    const int tid = threadIdx.x;
    const int wid = __shfl_sync(0xffffffffu, tid >> 5, 0);
    uint32_t role; asm("mov.u32 %0, %%cluster_ctarank;" : "=r"(role));
    int h; asm("mov.u32 %0, %%clusterid.x;" : "=r"(h));
    const uint32_t bar = sb + R_BAR;
    asm volatile("griddepcontrol.launch_dependents;");
    KT(0, 0);

    if (tid == 0) {
        for (int i = 0; i < 5; i++) mbar_init(bar + 8 * (B_FULL + i), 1);
        for (int i = 0; i < 3; i++) mbar_init(bar + 8 * (B_EMPTY + i), 2);
        for (int i = 0; i < 4; i++) mbar_init(bar + 8 * (B_MEM + i), 1);
        mbar_init(bar + 8 * B_HOP1, 9);
        mbar_init(bar + 8 * B_XT, 2);
        mbar_init(bar + 8 * B_TFREE, 6);
        mbar_init(bar + 8 * B_P, 4);
        mbar_init(bar + 8 * B_XRECV, 2);
        mbar_init(bar + 8 * B_O, 4);
        mbar_init(bar + 8 * B_AFREE0, 2);
        mbar_init(bar + 8 * B_AFREE1, 2);
        mbar_init(bar + 8 * B_PRO0, 1);
        mbar_init(bar + 8 * B_PRO1, 8);
        asm volatile("fence.mbarrier_init.release.cluster;" ::: "memory");
        fence_async();
        mbar_expect(bar + 8 * B_PRO0, KR * 4096);
        for (int i = 0; i < 3; i++) mbar_expect(bar + 8 * (B_FULL + i), 8192);
        mbar_expect(bar + 8 * B_HOP1, 4096);
        mbar_expect(bar + 8 * B_XT, role == 0 ? 16384 : 8192);
    }
    __syncthreads();
    asm volatile("barrier.cluster.arrive.relaxed.aligned;" ::: "memory");
    {
        const CUtensorMap* tw = &tm.w[role];
        if (wid < 11) {
            e_tma_load(sb + wid * 16384, tw, h * DH, KC(wid), bar + 8 * B_PRO0);
            e_tma_load(sb + wid * 16384 + 8192, tw, h * DH + 64, KC(wid), bar + 8 * B_PRO0);
        }
        if (wid < 6) e_tma_load(sb + R_RING + wid * 4096, &tm.x, XC(wid), 0, bar + 8 * (B_FULL + (wid >> 1)));
        if ((tid & 31) == 0) {
            if (wid < 10) tma_prefetch(tw, h * DH + (wid & 1) * 64, KC(KR / 4 + (wid >> 1)));
            if (wid >= 6 && wid - 6 < (role == 0 ? 4 : 6)) tma_prefetch(&tm.wo, wo_tile(role, wid - 6) * 64, h * DH);
            if (blockIdx.x < NSEG && wid < 8) { tma_prefetch(&tm.x, wid * 128, blockIdx.x * SEG); tma_prefetch(&tm.x, wid * 128 + 64, blockIdx.x * SEG); }
        }
        __syncwarp();
    }
    asm volatile("barrier.cluster.wait.aligned;" ::: "memory");

    if (wid < 8) {
        asm volatile("setmaxnreg.inc.sync.aligned.u32 224;");
        if (role == 0) r_big<0>(tm, wid); else if (role == 1) r_big<1>(tm, wid); else r_big<2>(tm, wid);
    } else {
        asm volatile("setmaxnreg.dec.sync.aligned.u32 56;");
        if (role == 0) r_chain<0>(mem0, x, gate_w, wid); else if (role == 1) r_chain<1>(mem0, x, gate_w, wid); else r_chain<2>(mem0, x, gate_w, wid);
    }
    __syncwarp();
    asm volatile("barrier.cluster.arrive; barrier.cluster.wait;" ::: "memory");
    KT(0, 1);
}

constexpr int G_ST = 4;
constexpr int G_STAGE = 16384 + 32768;
constexpr int G_EPI = G_ST * G_STAGE;
constexpr int G_GATE = G_EPI + 32768;
constexpr int G_BAR = G_GATE + 1024;
constexpr int G_SMEM = G_BAR + 128 + 1024;

struct G1Maps { CUtensorMap x, wg, wu, hs, o, h, wo, wd, out; };
constexpr int G1_NB = FF / 128;
constexpr int G1_TILES = 16 * G1_NB;

DEVINL void g_mma_block(float* d, uint32_t sb, uint32_t bar, int it, int wg, int tid, bool first) {
    const int st = it % G_ST;
    mbar_wait(bar + 8 * st, (it / G_ST) & 1);
    const uint64_t da = mkdesc(sb + st * G_STAGE + wg * 8192, 16, 1024, 1);
    const uint64_t db = mkdesc(sb + st * G_STAGE + 16384, 8192, 1024, 1);
    wg_fence();
#pragma unroll
    for (int k = 0; k < 4; k++) wg_ss256(d, da + (uint64_t)(k * 2), db + (uint64_t)(k * 128), (first ? 0 : 1) | k);
    wg_commit();
    if (!first) { wg_wait<1>(); if ((tid & 127) == 0) mbar_arrive(bar + 8 * (G_ST + (it - 1) % G_ST)); }
}
DEVINL void g_load_block(uint32_t sb, uint32_t bar, int it, const CUtensorMap* ta, int k0, int m0, const CUtensorMap* tb, int n0) {
    const int st = it % G_ST;
    mbar_wait(bar + 8 * (G_ST + st), ((it / G_ST) & 1) ^ 1);
    const uint32_t fb = bar + 8 * st, sa = sb + st * G_STAGE;
    mbar_expect(fb, G_STAGE);
    tma_load(sa, ta, k0, m0, fb);
#pragma unroll
    for (int q = 0; q < 4; q++) tma_load(sa + 16384 + q * 8192, tb, n0 + q * 64, k0, fb);
}

__global__ void __launch_bounds__(384, 1) g1_kernel(const __grid_constant__ G1Maps tm, const bf16* __restrict__ x, const bf16* __restrict__ gate_w) {
    extern __shared__ __align__(1024) unsigned char smem_raw[];
    const uint32_t sb = (smem_u32(smem_raw) + 1023) & ~1023u;
    float* sgate = (float*)(smem_raw + (sb - smem_u32(smem_raw)) + G_GATE);
    const int tid = threadIdx.x, lane = tid & 31;
    const int wg = __shfl_sync(0xffffffffu, tid >> 7, 0);
    const int warp = __shfl_sync(0xffffffffu, (tid >> 5) & 3, 0);
    const uint32_t bar = sb + G_BAR;
    const int t_begin = (blockIdx.x * G1_TILES) / gridDim.x;
    const int t_end = ((blockIdx.x + 1) * G1_TILES) / gridDim.x;
    const int mb0 = t_begin / G1_NB;
    KT(1, 0);
    if (tid == 0) {
        for (int i = 0; i < G_ST; i++) { mbar_init(bar + 8 * i, 1); mbar_init(bar + 8 * (G_ST + i), 2); }
        mbar_init(bar + 8 * 2 * G_ST, 3);
        fence_async();
    }
    __syncthreads();
    if (wg == 2) {
        asm volatile("setmaxnreg.dec.sync.aligned.u32 56;");
        if (warp == 0) {
            if (lane == 0) {
                int it = 0;
                for (int tile = t_begin; tile < t_end; tile++) {
                    const int mb = tile / G1_NB, nb = tile % G1_NB;
                    for (int kb = 0; kb < 16; kb++, it++) {
                        const int st = it % G_ST;
                        mbar_wait(bar + 8 * (G_ST + st), ((it / G_ST) & 1) ^ 1);
                        const uint32_t fb = bar + 8 * st, sa = sb + st * G_STAGE;
                        mbar_expect(fb, G_STAGE);
                        tma_load(sa, &tm.x, kb * 64, mb * 128, fb);
                        tma_load(sa + 16384, &tm.wg, nb * 128, kb * 64, fb);
                        tma_load(sa + 16384 + 8192, &tm.wg, nb * 128 + 64, kb * 64, fb);
                        tma_load(sa + 16384 + 16384, &tm.wu, nb * 128, kb * 64, fb);
                        tma_load(sa + 16384 + 24576, &tm.wu, nb * 128 + 64, kb * 64, fb);
                    }
                }
                for (int pass = 0; pass < 2; pass++) {
                    for (int i = blockIdx.x; i < (pass ? NFULL : NLATE); i += gridDim.x) {
                        const int tile = pass ? i : NFULL + i, mb = tile >> 2, nb = tile & 3;
                        wait_count(&g_hcnt[mb], 2 * G1_NB);
                        asm volatile("fence.proxy.async;" ::: "memory");
                        for (int kb = 0; kb < FF / 64; kb++, it++) g_load_block(sb, bar, it, &tm.h, kb * 64, mb * 128, &tm.wd, nb * 256);
                        if (pass) {
                            wait_count(&g_ocnt[mb], NH * 4 * 2);
                            asm volatile("fence.proxy.async;" ::: "memory");
                            for (int kb = 0; kb < HD / 64; kb++, it++) g_load_block(sb, bar, it, &tm.o, kb * 64, mb * 128, &tm.wo, nb * 256);
                        }
                    }
                }
            }
        } else {
            const int nrows = ((t_end - 1) / G1_NB - mb0 + 1) * 128;
#pragma unroll 2
            for (int r = warp - 1; r < nrows; r += 3) {
                const float gt = gate_row(x + (mb0 * 128 + r) * DM, gate_w, lane);
                if (lane == 0) sgate[r] = gt;
            }
            __syncwarp();
            if (lane == 0) mbar_arrive(bar + 8 * 2 * G_ST);
        }
    } else {
        asm volatile("setmaxnreg.inc.sync.aligned.u32 224;");
        float d[128];
        int it = 0;
        const uint32_t epi = sb + G_EPI + wg * 16384;
        const int row = warp * 16 + ((lane >> 3) & 1) * 8 + (lane & 7);
        for (int tile = t_begin; tile < t_end; tile++) {
            const int mb = tile / G1_NB, nb = tile % G1_NB;
            for (int kb = 0; kb < 16; kb++, it++) g_mma_block(d, sb, bar, it, wg, tid, kb == 0);
            wg_wait<0>();
            if ((tid & 127) == 0) { mbar_arrive(bar + 8 * (G_ST + (it - 1) % G_ST)); bulk_wait_read(); }
            if (tile == t_begin) mbar_wait(bar + 8 * 2 * G_ST, 0);
            bar_sync(1 + wg, 128);
            const int r0 = (mb - mb0) * 128 + wg * 64 + warp * 16 + (lane >> 2);
            const float s0 = 1.0f - sgate[r0], s1 = 1.0f - sgate[r0 + 8];
#pragma unroll
            for (int j = 0; j < 16; j += 2) {
                uint32_t p[4];
#pragma unroll
                for (int q = 0; q < 4; q++) {
                    const int i = (j + (q >> 1)) * 4 + (q & 1) * 2;
                    const float sc = (q & 1) ? s1 : s0;
                    const float g0 = d[i], g1 = d[i + 1];
                    const float h0 = __fdividef(g0, 1.0f + __expf(-g0)) * d[64 + i] * sc;
                    const float h1 = __fdividef(g1, 1.0f + __expf(-g1)) * d[64 + i + 1] * sc;
                    p[q] = pack_bf16(h0, h1);
                }
                const int cgp = j + (lane >> 4);
                stsm4(epi + (cgp >> 3) * 8192 + row * 128 + (((cgp & 7) ^ (row & 7)) << 4), p[0], p[1], p[2], p[3]);
            }
            fence_async();
            bar_sync(1 + wg, 128);
            if ((tid & 127) == 0) {
                tma_store(&tm.hs, epi, nb * 128, mb * 128 + wg * 64);
                tma_store(&tm.hs, epi + 8192, nb * 128 + 64, mb * 128 + wg * 64);
                bulk_commit();
            }
        }
        if ((tid & 127) == 0) {
            bulk_wait_all();
            __threadfence();
            const int n0 = min(t_end, (mb0 + 1) * G1_NB) - t_begin;
            atomicAdd(&g_hcnt[mb0], (uint32_t)n0);
            if (t_end - t_begin > n0) atomicAdd(&g_hcnt[mb0 + 1], (uint32_t)(t_end - t_begin - n0));
        }
        for (int pass = 0; pass < 2; pass++) {
            for (int i = blockIdx.x; i < (pass ? NFULL : NLATE); i += gridDim.x) {
                const int nkb = pass ? (FF + HD) / 64 : FF / 64;
                for (int kb = 0; kb < nkb; kb++, it++) g_mma_block(d, sb, bar, it, wg, tid, kb == 0);
                wg_wait<0>();
                if ((tid & 127) == 0) mbar_arrive(bar + 8 * (G_ST + (it - 1) % G_ST));
                if (pass == 0) {
                    float4* pre = g_pre + i * (32 * 256) + tid;
#pragma unroll
                    for (int q = 0; q < 32; q++) __stcg(pre + q * 256, make_float4(d[4 * q], d[4 * q + 1], d[4 * q + 2], d[4 * q + 3]));
                } else {
                    const int mb = i >> 2, nb = i & 3;
#pragma unroll
                    for (int half = 0; half < 2; half++) {
                        if ((tid & 127) == 0) bulk_wait_read();
                        bar_sync(1 + wg, 128);
#pragma unroll
                        for (int j = 0; j < 16; j += 2) {
                            const float* e = d + half * 64 + 4 * j;
                            const int cgp = j + (lane >> 4);
                            stsm4(epi + (cgp >> 3) * 8192 + row * 128 + (((cgp & 7) ^ (row & 7)) << 4),
                                  pack_bf16(e[0], e[1]), pack_bf16(e[2], e[3]), pack_bf16(e[4], e[5]), pack_bf16(e[6], e[7]));
                        }
                        fence_async();
                        bar_sync(1 + wg, 128);
                        if ((tid & 127) == 0) {
                            tma_store(&tm.out, epi, nb * 256 + half * 128, mb * 128 + wg * 64);
                            tma_store(&tm.out, epi + 8192, nb * 256 + half * 128 + 64, mb * 128 + wg * 64);
                            bulk_commit();
                        }
                    }
                }
            }
        }
        if ((tid & 127) == 0) bulk_wait_all();
        KT(1, 1);
    }
    __syncwarp();
    asm volatile("griddepcontrol.wait;" ::: "memory");
}

struct G2Maps { CUtensorMap o, wo, out; };

__global__ void __launch_bounds__(384, 1) g2_kernel(const __grid_constant__ G2Maps tm) {
    extern __shared__ __align__(1024) unsigned char smem_raw[];
    const uint32_t sb = (smem_u32(smem_raw) + 1023) & ~1023u;
    const int tid = threadIdx.x, lane = tid & 31;
    const int wg = __shfl_sync(0xffffffffu, tid >> 7, 0);
    const int warp = __shfl_sync(0xffffffffu, (tid >> 5) & 3, 0);
    const uint32_t bar = sb + G_BAR;
    const int ks = blockIdx.x & 3, lt = blockIdx.x >> 2, nb = (NFULL + lt) & 3, mb = (NFULL + lt) >> 2;
    KT(2, 0);
    if (tid == 0) {
        for (int i = 0; i < G_ST; i++) { mbar_init(bar + 8 * i, 1); mbar_init(bar + 8 * (G_ST + i), 2); }
        fence_async();
    }
    __syncthreads();
    if (wg == 2) {
        asm volatile("setmaxnreg.dec.sync.aligned.u32 40;");
        if (warp == 0 && lane == 0) {
            for (int it = 0; it < 16; it++) g_load_block(sb, bar, it, &tm.o, (ks * 16 + it) * 64, mb * 128, &tm.wo, nb * 256);
        } else if (warp == 1) {
            if (blockIdx.x < SEQ / 32) g_gate[blockIdx.x * 32 + lane] = 0u;
            if (blockIdx.x == 0 && lane < 16) { g_hcnt[lane] = 0u; g_ocnt[lane] = 0u; }
        }
    } else {
        asm volatile("setmaxnreg.inc.sync.aligned.u32 232;");
        float d[128];
        float4 r[8];
        const float4* pre = g_pre + (lt * 32 + ks * 8) * 256 + tid;
#pragma unroll
        for (int q = 0; q < 8; q++) r[q] = __ldcg(pre + q * 256);
        for (int it = 0; it < 16; it++) g_mma_block(d, sb, bar, it, wg, tid, it == 0);
        wg_wait<0>();
        float4* mine = g_sk + blockIdx.x * (32 * 256) + tid;
#pragma unroll
        for (int c = 0; c < 4; c++) {
            if (c != ks) {
#pragma unroll
                for (int q = c * 8; q < c * 8 + 8; q++) __stcg(mine + q * 256, make_float4(d[4 * q], d[4 * q + 1], d[4 * q + 2], d[4 * q + 3]));
            } else {
#pragma unroll
                for (int q = 0; q < 8; q++) { r[q].x += d[c * 32 + 4 * q]; r[q].y += d[c * 32 + 4 * q + 1]; r[q].z += d[c * 32 + 4 * q + 2]; r[q].w += d[c * 32 + 4 * q + 3]; }
            }
        }
        __threadfence();
        bar_sync(1, 256);
        if (tid == 0) {
            atomicAdd(&g_skcnt[lt], 1u);
            uint32_t v, n = 0;
            do {
                asm volatile("ld.acquire.gpu.global.u32 %0, [%1];" : "=r"(v) : "l"(&g_skcnt[lt]) : "memory");
                if (++n > 200000000u) __trap();
            } while (v < 4u);
            if (atomicAdd(&g_skdone[lt], 1u) == 3u) { g_skcnt[lt] = 0u; g_skdone[lt] = 0u; }
        }
        bar_sync(1, 256);
#pragma unroll
        for (int c = 1; c < 4; c++) {
            const float4* th = g_sk + ((lt * 4 + ((ks + c) & 3)) * 32 + ks * 8) * 256 + tid;
#pragma unroll
            for (int q = 0; q < 8; q++) { const float4 u = __ldcg(th + q * 256); r[q].x += u.x; r[q].y += u.y; r[q].z += u.z; r[q].w += u.w; }
        }
        const uint32_t epi = sb + G_EPI + wg * 16384;
        const int row = warp * 16 + ((lane >> 3) & 1) * 8 + (lane & 7);
#pragma unroll
        for (int j = 0; j < 8; j += 2) {
            const int cgp = j + (lane >> 4);
            stsm4(epi + row * 128 + ((cgp ^ (row & 7)) << 4), pack_bf16(r[j].x, r[j].y), pack_bf16(r[j].z, r[j].w),
                  pack_bf16(r[j + 1].x, r[j + 1].y), pack_bf16(r[j + 1].z, r[j + 1].w));
        }
        fence_async();
        bar_sync(2 + wg, 128);
        if ((tid & 127) == 0) {
            tma_store(&tm.out, epi, nb * 256 + ks * 64, mb * 128 + wg * 64);
            bulk_commit();
            bulk_wait_all();
        }
        KT(2, 1);
    }
}

typedef CUresult (*EncodeFn)(CUtensorMap*, CUtensorMapDataType, cuuint32_t, void*, const cuuint64_t*, const cuuint64_t*, const cuuint32_t*,
                             const cuuint32_t*, CUtensorMapInterleave, CUtensorMapSwizzle, CUtensorMapL2promotion, CUtensorMapFloatOOBfill);

static void make_map(EncodeFn enc, CUtensorMap* m, const void* ptr, uint64_t rows, uint64_t cols, uint32_t box_rows) {
    cuuint64_t dims[2] = {cols, rows};
    cuuint64_t strides[1] = {cols * 2};
    cuuint32_t box[2] = {64, box_rows};
    cuuint32_t es[2] = {1, 1};
    enc(m, CU_TENSOR_MAP_DATA_TYPE_BFLOAT16, 2, (void*)ptr, dims, strides, box, es, CU_TENSOR_MAP_INTERLEAVE_NONE,
        CU_TENSOR_MAP_SWIZZLE_128B, CU_TENSOR_MAP_L2_PROMOTION_L2_256B, CU_TENSOR_MAP_FLOAT_OOB_FILL_NONE);
}

extern "C" void kernel_launch(void* const* d_in, const int* in_sizes, int n_in, void* d_out, int out_size) {
    (void)in_sizes; (void)n_in; (void)out_size;
    const bf16* x = (const bf16*)d_in[0];
    const bf16* mem0 = (const bf16*)d_in[1];
    const bf16* gate_w = (const bf16*)d_in[11];
    static EncodeFn enc = nullptr;
    static int n_sm = 0;
    static void *pO = nullptr, *pH = nullptr;
    if (!enc) {
        void* fn = nullptr;
        cudaDriverEntryPointQueryResult qr;
        cudaGetDriverEntryPoint("cuTensorMapEncodeTiled", &fn, cudaEnableDefault, &qr);
        enc = (EncodeFn)fn;
        cudaDeviceGetAttribute(&n_sm, cudaDevAttrMultiProcessorCount, 0);
        cudaFuncSetAttribute(r_kernel, cudaFuncAttributeMaxDynamicSharedMemorySize, R_SMEM);
        cudaFuncSetAttribute(g1_kernel, cudaFuncAttributeMaxDynamicSharedMemorySize, G_SMEM);
        cudaFuncSetAttribute(g2_kernel, cudaFuncAttributeMaxDynamicSharedMemorySize, G_SMEM);
        cudaGetSymbolAddress(&pO, g_O);
        cudaGetSymbolAddress(&pH, g_H);
    }
    RMaps rm; G1Maps m1; G2Maps m2;
    make_map(enc, &rm.x, x, SEQ, DM, 32);
    for (int i = 0; i < 3; i++) make_map(enc, &rm.w[i], d_in[2 + i], DM, HD, 64);
    make_map(enc, &rm.wo, d_in[5], HD, DM, 128);
    make_map(enc, &rm.o, pO, SEQ, HD, 16);
    make_map(enc, &m1.x, x, SEQ, DM, 128);
    make_map(enc, &m1.wg, d_in[8], DM, FF, 64);
    make_map(enc, &m1.wu, d_in[9], DM, FF, 64);
    make_map(enc, &m1.hs, pH, SEQ, FF, 64);
    make_map(enc, &m1.o, pO, SEQ, HD, 128);
    make_map(enc, &m1.h, pH, SEQ, FF, 128);
    make_map(enc, &m1.wo, d_in[5], HD, DM, 64);
    make_map(enc, &m1.wd, d_in[10], FF, DM, 64);
    make_map(enc, &m1.out, d_out, SEQ, DM, 64);
    m2.o = m1.o; m2.wo = m1.wo; m2.out = m1.out;

    cudaStream_t st = cudaStreamPerThread;
    {
        cudaLaunchConfig_t cfg = {};
        cfg.gridDim = dim3(96); cfg.blockDim = dim3(384); cfg.dynamicSmemBytes = R_SMEM; cfg.stream = st;
        cudaLaunchAttribute at[1];
        at[0].id = cudaLaunchAttributeClusterDimension; at[0].val.clusterDim.x = 3; at[0].val.clusterDim.y = 1; at[0].val.clusterDim.z = 1;
        cfg.attrs = at; cfg.numAttrs = 1;
        cudaLaunchKernelEx(&cfg, r_kernel, rm, mem0, x, gate_w);
    }
    {
        cudaLaunchConfig_t cfg = {};
        cfg.gridDim = dim3(n_sm - 96); cfg.blockDim = dim3(384); cfg.dynamicSmemBytes = G_SMEM; cfg.stream = st;
        cudaLaunchAttribute at[1];
        at[0].id = cudaLaunchAttributeProgrammaticStreamSerialization; at[0].val.programmaticStreamSerializationAllowed = 1;
        cfg.attrs = at; cfg.numAttrs = 1;
        cudaLaunchKernelEx(&cfg, g1_kernel, m1, x, gate_w);
    }
    g2_kernel<<<NLATE * 4, 384, G_SMEM, st>>>(m2);
}
```

```cpp
#include <cuda_runtime.h>
#include <cuda_bf16.h>
#include <cuda.h>
#include <stdint.h>

typedef __nv_bfloat16 bf16;

constexpr int SEQ = 2048, DM = 1024, NH = 32, DH = 128, NMEM = 8, SEG = 32, NSEG = 64, FF = 3584;
constexpr int HD = NH * DH;

__device__ bf16 g_O[SEQ * HD];
__device__ bf16 g_H[SEQ * FF];
__device__ uint32_t g_gate[SEQ];
__device__ uint32_t g_part[4][128 * 32 * 32];
__device__ uint32_t g_mem[4][DM * 4];
constexpr int NFULL = 36;
constexpr int NLATE = 64 - NFULL;
__device__ float4 g_pre[NLATE * 32 * 256];
__device__ float4 g_sk[NLATE * 4 * 32 * 256];
__device__ uint32_t g_skcnt[NLATE], g_skdone[NLATE];
__device__ uint32_t g_hcnt[16], g_ocnt[16];
#define KT(k, i)
#define PT(i)

#define DEVINL __device__ __forceinline__
constexpr long long SPIN_LIMIT = 4000000000LL;

DEVINL uint32_t smem_u32(const void* p) { return (uint32_t)__cvta_generic_to_shared(p); }
DEVINL void mbar_init(uint32_t bar, uint32_t cnt) { asm volatile("mbarrier.init.shared::cta.b64 [%0], %1;" ::"r"(bar), "r"(cnt) : "memory"); }
DEVINL void mbar_arrive(uint32_t bar) { asm volatile("mbarrier.arrive.shared::cta.b64 _, [%0];" ::"r"(bar) : "memory"); }
DEVINL void mbar_expect(uint32_t bar, uint32_t bytes) { asm volatile("mbarrier.arrive.expect_tx.shared::cta.b64 _, [%0], %1;" ::"r"(bar), "r"(bytes) : "memory"); }
DEVINL void mbar_arrive_remote(uint32_t cbar) { asm volatile("mbarrier.arrive.relaxed.cluster.shared::cluster.b64 _, [%0];" ::"r"(cbar) : "memory"); }
DEVINL bool mbar_try(uint32_t bar, uint32_t par) {
    uint32_t ok;
    asm volatile("{ .reg .pred p; mbarrier.try_wait.parity.shared::cta.b64 p, [%1], %2; selp.u32 %0, 1, 0, p; }" : "=r"(ok) : "r"(bar), "r"(par) : "memory");
    return ok;
}
__device__ __noinline__ void mbar_wait_slow(uint32_t bar, uint32_t par) {
    long long t0 = clock64();
    while (!mbar_try(bar, par)) { if (clock64() - t0 > SPIN_LIMIT) __trap(); }
}
DEVINL void mbar_wait(uint32_t bar, uint32_t par) {
    uint32_t n = 0;
    while (!mbar_try(bar, par)) { if (++n > 200000000u) __trap(); }
}
DEVINL uint32_t mapa(uint32_t a, uint32_t r) { uint32_t o; asm volatile("mapa.shared::cluster.u32 %0, %1, %2;" : "=r"(o) : "r"(a), "r"(r)); return o; }
DEVINL void fence_async() { asm volatile("fence.proxy.async.shared::cta;" ::: "memory"); }
DEVINL void bar_sync(int id, int n) { asm volatile("bar.sync %0, %1;" ::"r"(id), "r"(n) : "memory"); }
DEVINL void cluster_sync() { asm volatile("barrier.cluster.arrive.aligned; barrier.cluster.wait.aligned;" ::: "memory"); }
DEVINL void tma_load(uint32_t dst, const CUtensorMap* tm, int c0, int c1, uint32_t bar) {
    asm volatile("cp.async.bulk.tensor.2d.shared::cluster.global.mbarrier::complete_tx::bytes [%0], [%1, {%3, %4}], [%2];"
                 ::"r"(dst), "l"(tm), "r"(bar), "r"(c0), "r"(c1) : "memory");
}
DEVINL void tma_prefetch(const CUtensorMap* tm, int c0, int c1) {
    asm volatile("cp.async.bulk.prefetch.tensor.2d.L2.global [%0, {%1, %2}];" ::"l"(tm), "r"(c0), "r"(c1) : "memory");
}
DEVINL void tma_store(const CUtensorMap* tm, uint32_t src, int c0, int c1) {
    asm volatile("cp.async.bulk.tensor.2d.global.shared::cta.bulk_group [%0, {%2, %3}], [%1];" ::"l"(tm), "r"(src), "r"(c0), "r"(c1) : "memory");
}
DEVINL void bulk_commit() { asm volatile("cp.async.bulk.commit_group;" ::: "memory"); }
DEVINL void bulk_wait_read() { asm volatile("cp.async.bulk.wait_group.read 0;" ::: "memory"); }
DEVINL void bulk_wait_all() { asm volatile("cp.async.bulk.wait_group 0;" ::: "memory"); }
DEVINL void bulk_s2s(uint32_t cdst, uint32_t src, uint32_t bytes, uint32_t cbar) {
    asm volatile("cp.async.bulk.shared::cluster.shared::cta.mbarrier::complete_tx::bytes [%0], [%1], %2, [%3];" ::"r"(cdst), "r"(src), "r"(bytes), "r"(cbar) : "memory");
}
DEVINL void st_async16(uint32_t cdst, uint4 v, uint32_t cbar) {
    asm volatile("st.async.shared::cluster.mbarrier::complete_tx::bytes.v4.b32 [%0], {%1,%2,%3,%4}, [%5];" ::"r"(cdst), "r"(v.x), "r"(v.y), "r"(v.z), "r"(v.w), "r"(cbar) : "memory");
}
DEVINL uint64_t mkdesc(uint32_t addr, uint32_t lbo, uint32_t sbo, uint32_t swz) {
    return (uint64_t)((addr & 0x3FFFF) >> 4) | ((uint64_t)(lbo >> 4) << 16) | ((uint64_t)(sbo >> 4) << 32) | ((uint64_t)swz << 62);
}
constexpr uint32_t SB0 = 1024;
__host__ __device__ constexpr uint64_t cdesc(uint32_t off, uint32_t lbo, uint32_t sbo, uint32_t swz) {
    return (uint64_t)(((SB0 + off) & 0x3FFFF) >> 4) | ((uint64_t)(lbo >> 4) << 16) | ((uint64_t)(sbo >> 4) << 32) | ((uint64_t)swz << 62);
}
DEVINL float ex2(float x) { float y; asm("ex2.approx.ftz.f32 %0, %1;" : "=f"(y) : "f"(x)); return y; }
DEVINL void spin_clk(int d) { uint32_t t0, t1; asm volatile("mov.u32 %0, %%clock;" : "=r"(t0)); do { asm volatile("mov.u32 %0, %%clock;" : "=r"(t1)); } while ((int)(t1 - t0) < d); }
#define PROBE_GAP 150
#define OPAQUE(x) asm volatile("" : "+r"(x))
DEVINL void wg_fence() { asm volatile("wgmma.fence.sync.aligned;" ::: "memory"); }
DEVINL void wg_commit() { asm volatile("wgmma.commit_group.sync.aligned;" ::: "memory"); }
template <int N> DEVINL void wg_wait() { asm volatile("wgmma.wait_group.sync.aligned %0;" ::"n"(N) : "memory"); }
DEVINL uint32_t pack_bf16(float lo, float hi) { uint32_t r; asm("cvt.rn.bf16x2.f32 %0, %1, %2;" : "=r"(r) : "f"(hi), "f"(lo)); return r; }
DEVINL void ldsm4(uint32_t* r, uint32_t a) { asm volatile("ldmatrix.sync.aligned.m8n8.x4.shared.b16 {%0,%1,%2,%3}, [%4];" : "=r"(r[0]), "=r"(r[1]), "=r"(r[2]), "=r"(r[3]) : "r"(a) : "memory"); }
DEVINL void ldsm4t(uint32_t* r, uint32_t a) { asm volatile("ldmatrix.sync.aligned.m8n8.x4.trans.shared.b16 {%0,%1,%2,%3}, [%4];" : "=r"(r[0]), "=r"(r[1]), "=r"(r[2]), "=r"(r[3]) : "r"(a) : "memory"); }
DEVINL void stsm4(uint32_t a, uint32_t r0, uint32_t r1, uint32_t r2, uint32_t r3) { asm volatile("stmatrix.sync.aligned.m8n8.x4.shared.b16 [%0], {%1,%2,%3,%4};" ::"r"(a), "r"(r0), "r"(r1), "r"(r2), "r"(r3) : "memory"); }
DEVINL void stsm4t(uint32_t a, uint32_t r0, uint32_t r1, uint32_t r2, uint32_t r3) { asm volatile("stmatrix.sync.aligned.m8n8.x4.trans.shared.b16 [%0], {%1,%2,%3,%4};" ::"r"(a), "r"(r0), "r"(r1), "r"(r2), "r"(r3) : "memory"); }
DEVINL void sts32(uint32_t a, uint32_t v) { asm volatile("st.shared.b32 [%0], %1;" ::"r"(a), "r"(v) : "memory"); }
DEVINL void sts128(uint32_t a, uint4 v) { asm volatile("st.shared.v4.b32 [%0], {%1,%2,%3,%4};" ::"r"(a), "r"(v.x), "r"(v.y), "r"(v.z), "r"(v.w) : "memory"); }
DEVINL uint4 lds128(uint32_t a) { uint4 v; asm volatile("ld.shared.v4.b32 {%0,%1,%2,%3}, [%4];" : "=r"(v.x), "=r"(v.y), "=r"(v.z), "=r"(v.w) : "r"(a) : "memory"); return v; }
DEVINL uint4 ld_strong16(const void* p) { uint4 v; asm volatile("ld.relaxed.gpu.global.v4.u32 {%0,%1,%2,%3}, [%4];" : "=r"(v.x), "=r"(v.y), "=r"(v.z), "=r"(v.w) : "l"(p) : "memory"); return v; }
DEVINL void st_strong8(void* p, uint32_t a, uint32_t b) { asm volatile("st.relaxed.gpu.global.v2.u32 [%0], {%1,%2};" ::"l"(p), "r"(a), "r"(b) : "memory"); }
DEVINL void st_strong4(void* p, uint32_t a) { asm volatile("st.relaxed.gpu.global.u32 [%0], %1;" ::"l"(p), "r"(a) : "memory"); }
DEVINL void st_strong16(void* p, uint4 v) { asm volatile("st.relaxed.gpu.global.v4.u32 [%0], {%1,%2,%3,%4};" ::"l"(p), "r"(v.x), "r"(v.y), "r"(v.z), "r"(v.w) : "memory"); }
DEVINL uint32_t pack_nz(float lo, float hi) { uint32_t r = pack_bf16(lo, hi); return r == 0u ? 0x8000u : r; }
DEVINL uint32_t min4(uint4 v, uint32_t m) { return __vimin3_u32(__vimin3_u32(v.x, v.y, m), v.z, v.w); }
DEVINL void mma16816(float* d, uint32_t a0, uint32_t a1, uint32_t a2, uint32_t a3, uint32_t b0, uint32_t b1) {
    asm volatile("mma.sync.aligned.m16n8k16.row.col.f32.bf16.bf16.f32 {%0,%1,%2,%3}, {%4,%5,%6,%7}, {%8,%9}, {%0,%1,%2,%3};"
                 : "+f"(d[0]), "+f"(d[1]), "+f"(d[2]), "+f"(d[3]) : "r"(a0), "r"(a1), "r"(a2), "r"(a3), "r"(b0), "r"(b1));
}
DEVINL void mma1688(float* d, uint32_t a0, uint32_t a1, uint32_t b0) {
    asm volatile("mma.sync.aligned.m16n8k8.row.col.f32.bf16.bf16.f32 {%0,%1,%2,%3}, {%4,%5}, {%6}, {%0,%1,%2,%3};"
                 : "+f"(d[0]), "+f"(d[1]), "+f"(d[2]), "+f"(d[3]) : "r"(a0), "r"(a1), "r"(b0));
}
template <int TA, int TB> DEVINL void wg_ss8(float* d, uint64_t da, uint64_t db, int sc) {
    asm volatile("{ .reg .pred p; setp.ne.b32 p, %6, 0; wgmma.mma_async.sync.aligned.m64n8k16.f32.bf16.bf16 {%0,%1,%2,%3}, %4, %5, p, 1, 1, %7, %8; }"
                 : "+f"(d[0]), "+f"(d[1]), "+f"(d[2]), "+f"(d[3]) : "l"(da), "l"(db), "r"(sc), "n"(TA), "n"(TB));
}
template <int TB> DEVINL void wg_rs8(float* d, const uint32_t* a, uint64_t db, int sc) {
    asm volatile("{ .reg .pred p; setp.ne.b32 p, %9, 0; wgmma.mma_async.sync.aligned.m64n8k16.f32.bf16.bf16 {%0,%1,%2,%3}, {%4,%5,%6,%7}, %8, p, 1, 1, %10; }"
                 : "+f"(d[0]), "+f"(d[1]), "+f"(d[2]), "+f"(d[3]) : "r"(a[0]), "r"(a[1]), "r"(a[2]), "r"(a[3]), "l"(db), "r"(sc), "n"(TB));
}
#define ACC16(d) "+f"(d[0]), "+f"(d[1]), "+f"(d[2]), "+f"(d[3]), "+f"(d[4]), "+f"(d[5]), "+f"(d[6]), "+f"(d[7]), "+f"(d[8]), "+f"(d[9]), "+f"(d[10]), "+f"(d[11]), "+f"(d[12]), "+f"(d[13]), "+f"(d[14]), "+f"(d[15])
template <int TA> DEVINL void wg_ss32(float* d, uint64_t da, uint64_t db, int sc) {
    asm volatile("{ .reg .pred p; setp.ne.b32 p, %18, 0; wgmma.mma_async.sync.aligned.m64n32k16.f32.bf16.bf16 {%0,%1,%2,%3,%4,%5,%6,%7,%8,%9,%10,%11,%12,%13,%14,%15}, %16, %17, p, 1, 1, %19, 0; }"
                 : ACC16(d) : "l"(da), "l"(db), "r"(sc), "n"(TA));
}
DEVINL void wg_rs32(float* d, const uint32_t* a, uint64_t db, int sc) {
    asm volatile("{ .reg .pred p; setp.ne.b32 p, %21, 0; wgmma.mma_async.sync.aligned.m64n32k16.f32.bf16.bf16 {%0,%1,%2,%3,%4,%5,%6,%7,%8,%9,%10,%11,%12,%13,%14,%15}, {%16,%17,%18,%19}, %20, p, 1, 1, 0; }"
                 : ACC16(d) : "r"(a[0]), "r"(a[1]), "r"(a[2]), "r"(a[3]), "l"(db), "r"(sc));
}
DEVINL void wg_ss40(float* d, uint64_t da, uint64_t db, int sc) {
    asm volatile("{ .reg .pred p; setp.ne.b32 p, %22, 0; wgmma.mma_async.sync.aligned.m64n40k16.f32.bf16.bf16 {%0,%1,%2,%3,%4,%5,%6,%7,%8,%9,%10,%11,%12,%13,%14,%15,%16,%17,%18,%19}, %20, %21, p, 1, 1, 1, 1; }"
                 : ACC16(d), "+f"(d[16]), "+f"(d[17]), "+f"(d[18]), "+f"(d[19]) : "l"(da), "l"(db), "r"(sc));
}
#define A8(d, o) "+f"(d[o]), "+f"(d[o + 1]), "+f"(d[o + 2]), "+f"(d[o + 3]), "+f"(d[o + 4]), "+f"(d[o + 5]), "+f"(d[o + 6]), "+f"(d[o + 7])
#define A32(d, o) A8(d, o), A8(d, o + 8), A8(d, o + 16), A8(d, o + 24)
DEVINL void wg_ss256(float* d, uint64_t da, uint64_t db, int sc) {
    asm volatile(
        "{ .reg .pred p; setp.ne.b32 p, %130, 0;\n"
        "wgmma.mma_async.sync.aligned.m64n256k16.f32.bf16.bf16 {"
        "%0,%1,%2,%3,%4,%5,%6,%7,%8,%9,%10,%11,%12,%13,%14,%15,%16,%17,%18,%19,%20,%21,%22,%23,%24,%25,%26,%27,%28,%29,%30,%31,"
        "%32,%33,%34,%35,%36,%37,%38,%39,%40,%41,%42,%43,%44,%45,%46,%47,%48,%49,%50,%51,%52,%53,%54,%55,%56,%57,%58,%59,%60,%61,%62,%63,"
        "%64,%65,%66,%67,%68,%69,%70,%71,%72,%73,%74,%75,%76,%77,%78,%79,%80,%81,%82,%83,%84,%85,%86,%87,%88,%89,%90,%91,%92,%93,%94,%95,"
        "%96,%97,%98,%99,%100,%101,%102,%103,%104,%105,%106,%107,%108,%109,%110,%111,%112,%113,%114,%115,%116,%117,%118,%119,%120,%121,%122,%123,%124,%125,%126,%127"
        "}, %128, %129, p, 1, 1, 0, 1; }"
        : A32(d, 0), A32(d, 32), A32(d, 64), A32(d, 96) : "l"(da), "l"(db), "r"(sc));
}

DEVINL float gate_row(const bf16* __restrict__ xr, const bf16* __restrict__ gate_w, int lane) {
    float acc = 0.f;
#pragma unroll
    for (int i = 0; i < 4; i++) {
        const uint4 xv = __ldg((const uint4*)xr + i * 32 + lane), gv = __ldg((const uint4*)gate_w + i * 32 + lane);
        const uint32_t xa[4] = {xv.x, xv.y, xv.z, xv.w}, ga[4] = {gv.x, gv.y, gv.z, gv.w};
#pragma unroll
        for (int e = 0; e < 4; e++) {
            acc = fmaf(__uint_as_float(xa[e] << 16), __uint_as_float(ga[e] << 16), acc);
            acc = fmaf(__uint_as_float(xa[e] & 0xffff0000u), __uint_as_float(ga[e] & 0xffff0000u), acc);
        }
    }
#pragma unroll
    for (int o = 16; o > 0; o >>= 1) acc += __shfl_xor_sync(0xffffffffu, acc, o);
    return 1.0f / (1.0f + __expf(-acc));
}
DEVINL uint32_t ld_strong4(const void* p) { uint32_t v; asm volatile("ld.relaxed.gpu.global.u32 %0, [%1];" : "=r"(v) : "l"(p) : "memory"); return v; }
DEVINL void wait_count(const uint32_t* p, uint32_t want) {
    uint32_t v, n = 0;
    while (true) {
        asm volatile("ld.acquire.gpu.global.u32 %0, [%1];" : "=r"(v) : "l"(p) : "memory");
        if (v >= want) break;
        __nanosleep(200);
        if (++n > 10000000u) __trap();
    }
}

constexpr int KR = 44;
constexpr int KS = 64 - KR;
constexpr int R_W = 0;
constexpr int R_WO = KS * 4096;
constexpr int R_QX = R_WO + 65536;
constexpr int R_RING = R_WO + 98304;
constexpr int R_K = R_RING + 24576;
constexpr int R_V = R_K + 10240;
constexpr int R_QM = R_V + 10240;
constexpr int R_O = R_QM + 2048;
constexpr int R_BAR = R_O + 2048;
constexpr int R_G = R_BAR + 256 + 512 + 256 + 128;
constexpr int R_SMEM = R_G + 512;
enum { B_FULL = 0, B_EMPTY = 5, B_MEM = 8, B_HOP1 = 12, B_XT, B_TFREE, B_O, B_AFREE0, B_AFREE1, B_PRO0, B_PRO1, B_XRECV, B_P };
#define D2_BASE 1200
#define D2_STEP 200
#define PD2 6
#define DQ 1700
#define D3 0

DEVINL uint32_t clk32() { uint32_t c_; asm volatile("mov.u32 %0, %%clock;" : "=r"(c_)); return c_; }
DEVINL void spin_until(uint32_t t) { while ((uint32_t)(t - clk32() - 1u) < 100000u) {} }
#define PROF(i)
#define PROF2(i)
#define PROF3(i, val)
DEVINL void e_arrive(uint32_t bar) { asm volatile("{ .reg .pred p; elect.sync _|p, 0xffffffff; @p mbarrier.arrive.shared::cta.b64 _, [%0]; }" ::"r"(bar) : "memory"); }
DEVINL void e_arrive_remote(uint32_t cbar) { asm volatile("{ .reg .pred p; elect.sync _|p, 0xffffffff; @p mbarrier.arrive.relaxed.cluster.shared::cluster.b64 _, [%0]; }" ::"r"(cbar) : "memory"); }
DEVINL void e_count(uint32_t* p) { asm volatile("{ .reg .pred p; elect.sync _|p, 0xffffffff; @p red.relaxed.gpu.global.add.u32 [%0], 1; }" ::"l"(p) : "memory"); }
DEVINL void e_expect(uint32_t bar, uint32_t bytes) { asm volatile("{ .reg .pred p; elect.sync _|p, 0xffffffff; @p mbarrier.arrive.expect_tx.shared::cta.b64 _, [%0], %1; }" ::"r"(bar), "r"(bytes) : "memory"); }
DEVINL void e_tma_load(uint32_t dst, const CUtensorMap* tm, int c0, int c1, uint32_t bar) {
    asm volatile("{ .reg .pred p; elect.sync _|p, 0xffffffff; @p cp.async.bulk.tensor.2d.shared::cluster.global.mbarrier::complete_tx::bytes [%0], [%1, {%3, %4}], [%2]; }"
                 ::"r"(dst), "l"(tm), "r"(bar), "r"(c0), "r"(c1) : "memory");
}
DEVINL void e_tma_store(const CUtensorMap* tm, uint32_t src, int c0, int c1) {
    asm volatile("{ .reg .pred p; elect.sync _|p, 0xffffffff; @p cp.async.bulk.tensor.2d.global.shared::cta.bulk_group [%0, {%2, %3}], [%1]; }" ::"l"(tm), "r"(src), "r"(c0), "r"(c1) : "memory");
}
DEVINL void e_bulk_s2s(uint32_t cdst, uint32_t src, uint32_t bytes, uint32_t cbar) {
    asm volatile("{ .reg .pred p; elect.sync _|p, 0xffffffff; @p cp.async.bulk.shared::cluster.shared::cta.mbarrier::complete_tx::bytes [%0], [%1], %2, [%3]; }" ::"r"(cdst), "r"(src), "r"(bytes), "r"(cbar) : "memory");
}

#define SLOT 0
#define PH3 0
#define PHQ 0
DEVINL void wait_slot(uint32_t phase) {
    if (SLOT) {
        uint32_t c; asm volatile("mov.u32 %0, %%globaltimer_lo;" : "=r"(c));
        const uint32_t tgt = c + (SLOT ? SLOT : 1) - ((c - phase) % (SLOT ? SLOT : 1));
        do { asm volatile("mov.u32 %0, %%globaltimer_lo;" : "=r"(c)); } while ((uint32_t)(tgt - c - 1u) < 100000u);
    }
}
template <int N> DEVINL uint32_t poll_set(uint4 (&v)[N], const uint32_t* rp, int stride, uint32_t phase) {
    wait_slot(phase);
#pragma unroll
    for (int i = 0; i < N; i++) v[i] = ld_strong16(rp + i * stride);
    uint32_t n = 0;
    while (true) {
        uint32_t m = 0xffffffffu;
#pragma unroll
        for (int i = 0; i < N; i++) m = min4(v[i], m);
        if (__all_sync(0xffffffffu, m != 0u)) return n;
        wait_slot(phase);
#pragma unroll
        for (int i = 0; i < N; i++)
            asm volatile("{ .reg .pred p; setp.eq.u32 p, %5, 0; @p ld.relaxed.gpu.global.v4.u32 {%0,%1,%2,%3}, [%4]; }"
                         : "+r"(v[i].x), "+r"(v[i].y), "+r"(v[i].z), "+r"(v[i].w) : "l"(rp + i * stride), "r"(min4(v[i], 0xffffffffu)) : "memory");
        if (++n > 20000000u) __trap();
    }
}

struct RMaps { CUtensorMap x, w[3], wo, o; };
#define KC(c) ((c) * 64)

#define XORD 3
__host__ __device__ constexpr int xo(int i) {
    return XORD == 0 ? i : XORD == 1 ? (i + 14) % 16 : XORD == 2 ? (i + 11) % 16
         : XORD == 3 ? (i < 10 ? ((i & 1) ? i / 2 : 11 + i / 2) : i - 5) : (i < 6 ? i : ((i & 1) ? 6 + (i - 6) / 2 : 11 + (i - 6) / 2));
}
#define XC(i) (xo(i) * 64)
DEVINL void x_load_pair(uint32_t dst, const CUtensorMap* tmx, int h, int p, int seg, uint32_t fbar) {
    e_expect(fbar, 8192);
    e_tma_load(dst, tmx, XC(2 * p), seg * SEG, fbar);
    e_tma_load(dst + 4096, tmx, XC(2 * p + 1), seg * SEG, fbar);
}
__host__ __device__ constexpr int wo_tile(int role, int i) { return i < 4 ? role + 3 * i : 11 + role + 2 * (i - 4); }

DEVINL void wo_issue(float* w, uint64_t dWo) {
    constexpr uint64_t dO = cdesc(R_O, 128, 128, 0);
    wg_fence();
#pragma unroll
    for (int k = 0; k < 8; k++) wg_ss8<1, 1>(w, dWo + (uint64_t)(k * 128), dO + (uint64_t)(k * 16), k);
    wg_commit();
}
template <int N> DEVINL void wo_store(float* w, uint32_t* q) {
    asm volatile("wgmma.wait_group.sync.aligned %4;" : "+f"(w[0]), "+f"(w[1]), "+f"(w[2]), "+f"(w[3]) : "n"(N) : "memory");
    st_strong4(q, pack_nz(w[0], w[1]));
    st_strong4(q + 1024, pack_nz(w[2], w[3]));
}

template <uint32_t role> DEVINL void r_big(const RMaps& tm, const int wid) {
    extern __shared__ __align__(1024) unsigned char smem_raw[];
    const uint32_t sb = smem_u32(smem_raw);
    const uint32_t bar = sb + R_BAR;
    const int tid = threadIdx.x;
    int h; asm("mov.u32 %0, %%clusterid.x;" : "=r"(h));
        uint32_t a[KR][4];
        mbar_wait(bar + 8 * B_PRO0, 0);
        PT(0);
        {
            const int lane = tid & 31;
            const int krow = (lane & 7) + ((lane >> 4) << 3);
            const int chunk = (wid & 3) * 2 + ((lane >> 3) & 1);
            const uint32_t la = sb + (wid >> 2) * 8192 + krow * 128 + ((chunk ^ (krow & 7)) << 4);
#pragma unroll
            for (int k = 0; k < KR; k++) ldsm4t(a[k], la + (k >> 2) * 16384 + (k & 3) * 2048);
        }
        bar_sync(1, 256);
        {
            fence_async();
            const CUtensorMap* tw = &tm.w[role];
            e_expect(bar + 8 * B_PRO1, (wid < 5 ? 16384 : 0) + (wid < (role == 0 ? 4 : 6) ? 16384 : 0));
            if (wid < 5) {
                e_tma_load(sb + R_W + wid * 8192, tw, h * DH, KC(KR / 4 + wid), bar + 8 * B_PRO1);
                e_tma_load(sb + R_W + KS * 2048 + wid * 8192, tw, h * DH + 64, KC(KR / 4 + wid), bar + 8 * B_PRO1);
            }
            if (wid < (role == 0 ? 4 : 6)) e_tma_load(sb + R_WO + wid * 16384, &tm.wo, wo_tile(role, wid) * 64, h * DH, bar + 8 * B_PRO1);
        }
        constexpr uint32_t e0 = role == 0 ? R_QX + 16384 : R_K + 2048, e1 = role == 0 ? R_QX + 24576 : R_V + 2048;
        if (wid == 6) x_load_pair(sb + e0, &tm.x, h, 3, 0, bar + 8 * (B_FULL + 3));
        if (wid == 7) x_load_pair(sb + e1, &tm.x, h, 4, 0, bar + 8 * (B_FULL + 4));
        PT(1);
        mbar_wait(bar + 8 * B_PRO1, 0);
        PT(2);

        constexpr uint64_t dW0 = cdesc(R_W, 1024, 1024, 1);
        constexpr uint64_t dWo0 = cdesc(R_WO, 1024, 1024, 1);
        constexpr uint64_t dM = cdesc(R_RING, 128, 128, 0);
        constexpr uint64_t dX = cdesc(R_RING, 16, 1024, 1);
        constexpr uint64_t dX0 = cdesc(0, 16, 1024, 1);
        int tb = tid;
        int wq = wid;

        float d[16];
        for (int s = -1; s < NSEG; s++) {
            if (s >= 0) {
                OPAQUE(wq);
                const uint64_t dW = dW0 + (uint64_t)((wq >> 2) * (KS * 128));
                float y[4] = {0.f, 0.f, 0.f, 0.f};
                {
                    OPAQUE(tb);
                    const uint32_t ma = sb + R_RING + (tb & 31) * 16;
                    float z[4] = {0.f, 0.f, 0.f, 0.f}, u[4] = {0.f, 0.f, 0.f, 0.f};
                    uint32_t b[4][4];
                    mbar_wait(bar + 8 * B_MEM, s & 1);
                    PROF((wq >> 2) * 4 + 0);
                    if (s == 0) PT(3);
                    if (s == 1) PT(4);
#pragma unroll
                    for (int g = 0; g < 4; g++) ldsm4t(b[g], ma + g * 512);
#pragma unroll
                    for (int g = 0; g < KR / 2; g++) {
                        float* c0 = (g % 3 == 0) ? y : (g % 3 == 1) ? u : z;
                        float* c1 = (g % 3 == 0) ? z : (g % 3 == 1) ? y : u;
                        mma16816(c0, a[2 * g][0], a[2 * g][1], a[2 * g][2], a[2 * g][3], b[g & 3][0], b[g & 3][1]);
                        mma16816(c1, a[2 * g + 1][0], a[2 * g + 1][1], a[2 * g + 1][2], a[2 * g + 1][3], b[g & 3][2], b[g & 3][3]);
                        if (g + 4 < KR / 2) {
                            if ((g + 4) % 8 == 0) mbar_wait(bar + 8 * (B_MEM + (g + 4) / 8), s & 1);
                            ldsm4t(b[g & 3], ma + (g + 4) * 512);
                        }
                    }
                    y[0] += z[0] + u[0]; y[1] += z[1] + u[1]; y[2] += z[2] + u[2]; y[3] += z[3] + u[3];
                }
                PROF2(8);
                mbar_wait(bar + 8 * (B_MEM + 3), s & 1);
                wg_fence();
#pragma unroll
                for (int k = KR; k < 64; k++) wg_ss8<1, 1>(y, dW + (uint64_t)((k - KR) * 128), dM + (uint64_t)(k * 16), 1);
                wg_commit();
                asm volatile("wgmma.wait_group.sync.aligned 0;" : "+f"(y[0]), "+f"(y[1]), "+f"(y[2]), "+f"(y[3])::"memory");
                OPAQUE(tb);
                {
                    const uint32_t wo_ = (tb >> 5) * 256;
                    const uint32_t tile = sb + (role == 0 ? R_QX : (role == 1 ? R_K : R_V)) + wo_;
                    const uint32_t u0 = pack_bf16(y[0], y[1]), u1 = pack_bf16(y[2], y[3]);
                    sts32(tile + (tb & 31) * 4, u0);
                    sts32(tile + (tb & 31) * 4 + 128, u1);
                    __syncwarp();
                    uint4 v = lds128(tile + (tb & 15) * 16);
                    uint32_t peer = role + 1 + ((tb >> 4) & 1);
                    peer = peer >= 3 ? peer - 3 : peer;
                    const uint32_t rt = sb + (role == 0 ? R_QM : (role == 1 ? R_K : R_V)) + wo_ + (tb & 15) * 16;
                    st_async16(mapa(rt, peer), v, mapa(bar + 8 * B_HOP1, peer));
                    if (role == 0) {
                        sts128(tile + 4096 + ((tb >> 4) & 1) * 4096 + (tb & 15) * 16, v);
                        sts32(tile + 12288 + (tb & 31) * 4, u0);
                        sts32(tile + 12288 + (tb & 31) * 4 + 128, u1);
                        __syncwarp();
                    }
                    e_arrive(bar + 8 * B_HOP1);
                }
                PROF((wq >> 2) * 4 + 1);
                if (s < NSEG - 1) {
                    bar_sync(1, 256);
                    if (wq < 2) { fence_async(); x_load_pair(sb + R_RING + wq * 8192, &tm.x, h, wq, s + 1, bar + 8 * (B_FULL + wq)); }
                    OPAQUE(tb);
                    uint32_t* pp = g_part[s & 3] + (h * 32 + ((int)role + 3 * (tb >> 7)) * 8192 + ((tb >> 5) & 3) * 2048 + (tb & 31));
                    const uint64_t dWo = dWo0 + (uint64_t)((wq >> 2) * 1024);
                    if (role != 0 && (wq & 3) == 3) mbar_wait(bar + 8 * B_XRECV, s & 1);
                    mbar_wait(bar + 8 * B_O, s & 1);
                    PROF((wq >> 2) * 4 + 2);
                    float w0[4];
                    wo_issue(w0, dWo);
                    wo_store<0>(w0, pp);
                    wo_issue(w0, dWo + 2048);
                    if (role != 0 && (wq & 3) == 3) x_load_pair(sb + (wq == 3 ? e0 : e1), &tm.x, h, 3 + (wq >> 2), s + 1, bar + 8 * (B_FULL + 3 + (wq >> 2)));
                    wo_store<0>(w0, pp + 6 * 8192);
                    if (role != 0) {
                        wo_issue(w0, dWo + 4096);
                        wo_store<0>(w0, pp + (11 - (tb >> 7)) * 8192);
                    }
                    if (wq == 0) PROF(10);
                }
                if (role == 0) {
                    constexpr uint64_t dV = cdesc(R_V, 2048, 128, 0);
                    constexpr uint64_t dP = cdesc(R_QX, 128, 4096, 0);
                    mbar_wait(bar + 8 * B_P, s & 1);
                    wg_fence();
#pragma unroll
                    for (int k = 0; k < 3; k++) wg_ss32<0>(d, dV + (uint64_t)((wq >> 2) * 64 + k * 256), dP + (uint64_t)(k * 16), k);
                    wg_commit();
                    wg_wait<0>();
                    OPAQUE(tb);
                    const uint32_t r = ((tb >> 4) & 1) * 8 + (tb & 7), ch = ((tb >> 5) & 3) * 2 + ((tb >> 3) & 1);
                    const uint32_t ob = sb + R_QX + 2048 + (tb >> 7) * 8192;
                    const uint32_t oa = ob + r * 128 + ((ch ^ (r & 7)) << 4);
                    stsm4t(oa, pack_bf16(d[0], d[1]), pack_bf16(d[2], d[3]), pack_bf16(d[4], d[5]), pack_bf16(d[6], d[7]));
                    stsm4t(oa + 4096, pack_bf16(d[8], d[9]), pack_bf16(d[10], d[11]), pack_bf16(d[12], d[13]), pack_bf16(d[14], d[15]));
                    fence_async();
                    bar_sync(2 + (wq >> 2), 128);
                    if ((wq & 3) == 0) {
                        const uint32_t src = sb + R_QX + 2048 + (wq >> 2) * 8192;
                        e_tma_store(&tm.o, src, h * DH + (wq >> 2) * 64, s * SEG);
                        e_tma_store(&tm.o, src + 4096, h * DH + (wq >> 2) * 64, s * SEG + 16);
                        bulk_commit();
                    }
                }
                if (s == NSEG - 1) { bulk_wait_all(); break; }
            }
            const int seg = s + 1;
            OPAQUE(wq);
            const uint64_t dW = dW0 + (uint64_t)((wq >> 2) * (KS * 128));
#pragma unroll
            for (int p = 0; p < 8; p++) {
                const int slot = p % 5;
                mbar_wait(bar + 8 * (B_FULL + slot), slot < 3 ? (uint32_t)(p / 5) : (uint32_t)(seg & 1));
                PROF2(p);
                const uint64_t db = slot < 3 ? dX + (uint64_t)(slot * 512) : dX0 + (uint64_t)((slot == 3 ? e0 : e1) >> 4);
                wg_fence();
#pragma unroll
                for (int kk = 0; kk < 8; kk++) {
                    const int k = XORD >= 3 ? (kk & 1) * 4 + (kk >> 1) : kk;
                    const int ks = xo(2 * p + (k >> 2)) * 4 + (k & 3);
                    if (ks >= KR) wg_ss32<1>(d, dW + (uint64_t)((ks - KR) * 128), db + (uint64_t)((k >> 2) * 256 + (k & 3) * 2), p + k);
                    else wg_rs32(d, a[ks < KR ? ks : 0], db + (uint64_t)((k >> 2) * 256 + (k & 3) * 2), p + k);
                }
                wg_commit();
                if (p >= 1) {
                    wg_wait<1>();
                    if (p <= 3) {
                        if ((wq & 3) == p) e_arrive(bar + 8 * (B_EMPTY + p - 1));
                        if (wq == p + (p & 1) * 4) {
                            mbar_wait(bar + 8 * (B_EMPTY + p - 1), seg & 1);
                            x_load_pair(sb + R_RING + (p - 1) * 8192, &tm.x, h, p + 4, seg, bar + 8 * (B_FULL + p - 1));
                        }
                    }
                    if (p == 5 && (wq & 3) < 3) {
                        if (role == 0) {
                            bulk_wait_all();
                            if ((wq & 3) == 0 && s >= 0) e_count(&g_ocnt[s >> 2]);
                        }
                        e_arrive_remote(mapa(bar + 8 * B_TFREE, wq & 3));
                    }
                    if (p == 6 && (wq & 3) == 1) e_arrive(bar + 8 * B_AFREE0);
                    if (p == 7 && (wq & 3) == 2) e_arrive(bar + 8 * B_AFREE1);
                }
            }
            asm volatile("wgmma.wait_group.sync.aligned 0;" : ACC16(d)::"memory");
            PROF2(16);
            mbar_wait(bar + 8 * B_TFREE, seg & 1);
            const uint32_t tilex = sb + (role == 0 ? R_QX + 2048 : (role == 1 ? R_K + 2048 : R_V + 2048));
            {
                OPAQUE(tb);
                const uint32_t gs = role == 0 ? 4096 : 2048;
                const uint32_t sa = tilex + ((tb >> 4) & 1) * gs + (tb >> 5) * 256 + (tb & 15) * 16;
                stsm4(sa, pack_bf16(d[0], d[1]), pack_bf16(d[2], d[3]), pack_bf16(d[4], d[5]), pack_bf16(d[6], d[7]));
                stsm4(sa + 2 * gs, pack_bf16(d[8], d[9]), pack_bf16(d[10], d[11]), pack_bf16(d[12], d[13]), pack_bf16(d[14], d[15]));
            }
            fence_async();
            bar_sync(1, 256);
            if (wq < 2) {
                if (role != 0) { uint32_t pr = role + 1 + wq; pr = pr >= 3 ? pr - 3 : pr; e_bulk_s2s(mapa(tilex, pr), tilex, 8192, mapa(bar + 8 * B_XT, pr)); }
            } else if (wq == 4) {
                e_arrive(bar + 8 * B_XT);
            } else if (seg + 1 < NSEG) {
                if (wq == 2) x_load_pair(sb + R_RING + 16384, &tm.x, h, 2, seg + 1, bar + 8 * (B_FULL + 2));
                if (role == 0 && (wq & 3) == 3) x_load_pair(sb + (wq == 3 ? e0 : e1), &tm.x, h, 3 + (wq >> 2), seg + 1, bar + 8 * (B_FULL + 3 + (wq >> 2)));
            }
        }
}

template <uint32_t role> DEVINL void r_chain(const bf16* __restrict__ mem0, const bf16* __restrict__ x, const bf16* __restrict__ gate_w, const int wid) {
    extern __shared__ __align__(1024) unsigned char smem_raw[];
    const uint32_t sb = smem_u32(smem_raw);
    const uint32_t bar = sb + R_BAR;
    const int tid = threadIdx.x;
    int h; asm("mov.u32 %0, %%clusterid.x;" : "=r"(h));
        int t = tid & 127;
        const float sl2 = 0.08838834764831845f * 1.4426950408889634f;
        const float NEGM = -1000000000.0f * 1.4426950408889634f;
        const int rg0 = ((int)role - 1) * 32 + h;
        if (role != 0) {
#pragma unroll 1
            for (int r = 0; r < 4; r++) {
                uint32_t* zp = g_part[r] + ((rg0 + (t >> 6) * 64) * 1024 + (t & 63) * 4);
#pragma unroll
                for (int i = 0; i < 4; i++) st_strong16(zp + i * 256, make_uint4(0u, 0u, 0u, 0u));
                if ((t & 63) < 8) st_strong16(&g_mem[r][(rg0 + (t >> 6) * 64) * 32 + (t & 63) * 4], make_uint4(0u, 0u, 0u, 0u));
            }
            __threadfence();
        }
        {
#pragma unroll 1
            for (int r = (h * 3 + (int)role) * 4 + (t >> 5); r < SEQ; r += 384) {
                const uint32_t gb = __float_as_uint(gate_row(x + r * DM, gate_w, t & 31));
                if ((t & 31) == 0) st_strong4(&g_gate[r], gb ? gb : 0x80000000u);
            }
        }
        if (role == 0) sts128(sb + R_QM + t * 16, make_uint4(0u, 0u, 0u, 0u));
        {
            uint4 v[8];
#pragma unroll
            for (int r = 0; r < 8; r++) v[r] = __ldg((const uint4*)(mem0 + r * DM) + t);
            mbar_wait(bar + 8 * B_AFREE0, 0);
            mbar_wait(bar + 8 * B_AFREE1, 0);
#define TR2(f, c) \
            sts128(sb + R_RING + t * 128 + (c) * 16, make_uint4(__byte_perm(v[0].f, v[1].f, 0x5410), __byte_perm(v[2].f, v[3].f, 0x5410), __byte_perm(v[4].f, v[5].f, 0x5410), __byte_perm(v[6].f, v[7].f, 0x5410))); \
            sts128(sb + R_RING + t * 128 + (c) * 16 + 16, make_uint4(__byte_perm(v[0].f, v[1].f, 0x7632), __byte_perm(v[2].f, v[3].f, 0x7632), __byte_perm(v[4].f, v[5].f, 0x7632), __byte_perm(v[6].f, v[7].f, 0x7632)));
            TR2(x, 0) TR2(y, 2) TR2(z, 4) TR2(w, 6)
            fence_async();
            __syncwarp();
            e_arrive(bar + 8 * B_MEM + (t >> 5) * 8);
        }
        constexpr uint64_t dQ = role == 0 ? cdesc(R_QX, 128, 2048, 0) : cdesc(R_QM, 128, 0, 0);
        constexpr uint64_t dK = cdesc(R_K, 128, 2048, 0);

        for (int s = 0; s < NSEG; s++) {
            if (role == 0) {
                uint32_t n = 0, gate;
                do { gate = ld_strong4(&g_gate[s * SEG + (t >> 2)]); if (++n > 20000000u) __trap(); } while (gate == 0u);
                sts32(sb + R_G + t * 4, gate);
                __syncwarp();
            }
            mbar_wait(bar + 8 * B_XT, s & 1);
            if (t >= 1 && t < 3) { uint32_t pr = role + t; pr = pr >= 3 ? pr - 3 : pr; mbar_arrive_remote(mapa(bar + 8 * B_XRECV, pr)); }
            __syncwarp();
            mbar_wait(bar + 8 * B_HOP1, s & 1);
            PROF(8);
            fence_async();
            OPAQUE(t);
            if (s == NSEG - 1 && role != 0) break;
            float sc[20];
            wg_fence();
#pragma unroll
            for (int k = 0; k < 8; k++) wg_ss40(sc, dQ + (uint64_t)(k * 16), dK + (uint64_t)(k * 16), k);
            wg_commit();
            uint32_t t_o = 0;
            {
                const uint32_t va = sb + R_V + (t >> 5) * 512 + ((t >> 4) & 1) * 2048 + (t & 15) * 16;
                uint32_t v0[4], v1[4];
                ldsm4(v0, va); ldsm4(v1, va + 256);
                wg_wait<0>();
                if (role == 0) {
#pragma unroll
                    for (int j = 0; j < 5; j++)
                        asm volatile("st.shared.v2.f32 [%0], {%1,%2};" ::"r"(sb + R_QX + 768 + (t >> 5) * 4096 + j * 256 + (t & 31) * 8), "f"(sc[4 * j + 2]), "f"(sc[4 * j + 3]) : "memory");
                }
                float m = fmaxf(sc[0], sc[1]);
#pragma unroll
                for (int j = 1; j < 5; j++) m = fmaxf(m, fmaxf(sc[4 * j], sc[4 * j + 1]));
                m = fmaxf(m, __shfl_xor_sync(0xffffffffu, m, 1));
                m = fmaxf(m, __shfl_xor_sync(0xffffffffu, m, 2));
                const float mb = m * sl2;
                uint32_t pk[5];
#pragma unroll
                for (int j = 0; j < 5; j++) pk[j] = pack_bf16(ex2(fmaf(sc[4 * j], sl2, -mb)), ex2(fmaf(sc[4 * j + 1], sl2, -mb)));
                float o0[4] = {0.f, 0.f, 0.f, 0.f}, o1[4] = {0.f, 0.f, 0.f, 0.f}, ls[4] = {0.f, 0.f, 0.f, 0.f};
                constexpr uint32_t ONE = 0x3F803F80u;
                mma16816(o0, v0[0], v0[1], v0[2], v0[3], pk[0], pk[1]);
                mma16816(o1, v1[0], v1[1], v1[2], v1[3], pk[0], pk[1]);
                ldsm4(v0, va + 4096); ldsm4(v1, va + 4096 + 256);
                mma16816(ls, ONE, ONE, ONE, ONE, pk[0], pk[1]);
                mma16816(ls, ONE, ONE, ONE, ONE, pk[2], pk[3]);
                mma1688(ls, ONE, ONE, pk[4]);
                mma16816(o0, v0[0], v0[1], v0[2], v0[3], pk[2], pk[3]);
                mma16816(o1, v1[0], v1[1], v1[2], v1[3], pk[2], pk[3]);
                ldsm4(v0, sb + R_V + 8192 + t * 16);
                mma1688(o0, v0[0], v0[1], pk[4]);
                mma1688(o1, v0[2], v0[3], pk[4]);
                const float i0 = __fdividef(1.0f, ls[0]), i1 = __fdividef(1.0f, ls[1]);
                const uint32_t oa = sb + R_O + (t >> 5) * 512 + (t & 31) * 4;
                sts32(oa, pack_bf16(o0[0] * i0, o0[1] * i1));
                sts32(oa + 128, pack_bf16(o0[2] * i0, o0[3] * i1));
                sts32(oa + 256, pack_bf16(o1[0] * i0, o1[1] * i1));
                sts32(oa + 384, pack_bf16(o1[2] * i0, o1[3] * i1));
                fence_async();
                __syncwarp();
                e_arrive(bar + 8 * B_O);
                t_o = clk32();
                PROF(9);
            }
            if (t < 32) { e_expect(bar + 8 * B_HOP1, 4096); e_expect(bar + 8 * B_XT, role == 0 ? 16384 : 8192); }
            if (role == 0) {
                OPAQUE(t);
                const int t0 = t >> 2, c = t & 3;
                uint32_t gate; asm volatile("ld.shared.b32 %0, [%1];" : "=r"(gate) : "r"(sb + R_G + t * 4) : "memory");
                float m1 = NEGM;
#pragma unroll
                for (int j = 0; j < 5; j++)
                    asm volatile("ld.shared.v2.f32 {%0,%1}, [%2];" : "=f"(sc[4 * j + 2]), "=f"(sc[4 * j + 3]) : "r"(sb + R_QX + 768 + (t >> 5) * 4096 + j * 256 + (t & 31) * 8) : "memory");
#pragma unroll
                for (int j = 0; j < 5; j++) {
#pragma unroll
                    for (int e = 0; e < 2; e++) {
                        const int key = (j - 1) * 8 + c * 2 + e;
                        sc[4 * j + 2 + e] = (key <= t0) ? sc[4 * j + 2 + e] * sl2 : NEGM;
                        m1 = fmaxf(m1, sc[4 * j + 2 + e]);
                    }
                }
                m1 = fmaxf(m1, __shfl_xor_sync(0xffffffffu, m1, 1)); m1 = fmaxf(m1, __shfl_xor_sync(0xffffffffu, m1, 2));
                float l1 = 0.f;
#pragma unroll
                for (int j = 0; j < 5; j++) {
                    sc[4 * j + 2] = ex2(sc[4 * j + 2] - m1); sc[4 * j + 3] = ex2(sc[4 * j + 3] - m1);
                    l1 += sc[4 * j + 2] + sc[4 * j + 3];
                }
                l1 += __shfl_xor_sync(0xffffffffu, l1, 1); l1 += __shfl_xor_sync(0xffffffffu, l1, 2);
                const float i1 = __fdividef(__uint_as_float(gate), l1);
                const uint32_t pa = sb + R_QX + (t >> 5) * 4096 + (t & 31) * 4;
#pragma unroll
                for (int j = 0; j < 5; j++) sts32(pa + j * 128, pack_bf16(sc[4 * j + 2] * i1, sc[4 * j + 3] * i1));
                sts32(pa + 5 * 128, 0u);
                fence_async();
                __syncwarp();
                e_arrive(bar + 8 * B_P);
            }
            if (s == NSEG - 1) break;
            OPAQUE(t);
            PROF(11);
            if (role != 0) {
                const uint32_t* rp = g_part[s & 3] + ((rg0 + (t >> 6) * 64) * 1024 + ((t >> 2) & 7) * 32 + ((t >> 5) & 1) * 16 + (t & 3) * 4);
                uint32_t* wp = &g_mem[(s + 1) & 3][(rg0 + (t >> 6) * 64) * 32 + ((t >> 5) & 1) * 16 + (t & 3) * 4 + ((t >> 3) & 3)];
                spin_until(t_o + D2_BASE + (role - 1 + (t >> 6) * 2) * D2_STEP);
                PROF3(0, clk32());
#define LO(u) __uint_as_float((u) << 16)
#define HI(u) __uint_as_float((u) & 0xffff0000u)
                uint4 v[4];
                uint32_t n = poll_set<4>(v, rp, 256, (role - 1 + (t >> 6) * 2) * PHQ);
                {
                    PROF3(1, clk32());
                    float f[8];
                    f[0] = (LO(v[0].x) + LO(v[1].x)) + (LO(v[2].x) + LO(v[3].x)); f[1] = (HI(v[0].x) + HI(v[1].x)) + (HI(v[2].x) + HI(v[3].x));
                    f[2] = (LO(v[0].y) + LO(v[1].y)) + (LO(v[2].y) + LO(v[3].y)); f[3] = (HI(v[0].y) + HI(v[1].y)) + (HI(v[2].y) + HI(v[3].y));
                    f[4] = (LO(v[0].z) + LO(v[1].z)) + (LO(v[2].z) + LO(v[3].z)); f[5] = (HI(v[0].z) + HI(v[1].z)) + (HI(v[2].z) + HI(v[3].z));
                    f[6] = (LO(v[0].w) + LO(v[1].w)) + (LO(v[2].w) + LO(v[3].w)); f[7] = (HI(v[0].w) + HI(v[1].w)) + (HI(v[2].w) + HI(v[3].w));
                    const bool b4 = t & 16, b3 = t & 8;
                    float g4[4], g2[2];
#pragma unroll
                    for (int i = 0; i < 4; i++) g4[i] = (b4 ? f[4 + i] : f[i]) + __shfl_xor_sync(0xffffffffu, b4 ? f[i] : f[4 + i], 16);
#pragma unroll
                    for (int i = 0; i < 2; i++) g2[i] = (b3 ? g4[2 + i] : g4[i]) + __shfl_xor_sync(0xffffffffu, b3 ? g4[i] : g4[2 + i], 8);
                    g2[0] += __shfl_xor_sync(0xffffffffu, g2[0], 4);
                    g2[1] += __shfl_xor_sync(0xffffffffu, g2[1], 4);
                    st_strong4(wp, pack_nz(g2[0], g2[1]));
                }
                PROF3(8, n); (void)n;
            }
            t_o += D2_BASE + DQ + D3 + (t >> 5) * D2_STEP;
            OPAQUE(t);
            PROF(12);
            {
                const uint32_t* rp = &g_mem[(s + 1) & 3][((t >> 5) * 256 + (t & 31)) * 4];
                const uint32_t da = sb + R_RING + ((t >> 5) * 256 + (t & 31)) * 16;
                uint4 v[8];
                spin_until(t_o);
                PROF3(2, clk32());
                uint32_t n = poll_set<8>(v, rp, 128, PH3 + (t >> 5) * PHQ);
                PROF(13);
                PROF3(3, clk32()); PROF3(9, n); (void)n;
                mbar_wait(bar + 8 * B_AFREE0 + (t >> 6) * 8, (s + 1) & 1);
                PROF3(4, clk32());
#pragma unroll
                for (int i = 0; i < 8; i++) sts128(da + i * 512, v[i]);
                if (t >= 64) fence_async();
                __syncwarp();
                e_arrive(bar + 8 * B_MEM + (t >> 5) * 8);
                PROF(14);
                PROF3(5, clk32());
            }
            if (role != 0) {
                OPAQUE(t);
                uint32_t* zp = g_part[s & 3] + ((rg0 + (t >> 6) * 64) * 1024 + ((t >> 2) & 7) * 32 + ((t >> 5) & 1) * 16 + (t & 3) * 4);
#pragma unroll
                for (int i = 0; i < 4; i++) st_strong16(zp + i * 256, make_uint4(0u, 0u, 0u, 0u));
                if ((t & 31) < 4) st_strong16(&g_mem[s & 3][(rg0 + (t >> 6) * 64) * 32 + ((t >> 5) & 1) * 16 + (t & 3) * 4], make_uint4(0u, 0u, 0u, 0u));
            }
        }
}

__global__ void __launch_bounds__(384, 1) r_kernel(const __grid_constant__ RMaps tm, const bf16* __restrict__ mem0, const bf16* __restrict__ x, const bf16* __restrict__ gate_w) {
    extern __shared__ __align__(1024) unsigned char smem_raw[];
    const uint32_t sb = smem_u32(smem_raw);
    if ((sb & 0x3FFFFu) != SB0) __trap();
    const int tid = threadIdx.x;
    const int wid = __shfl_sync(0xffffffffu, tid >> 5, 0);
    uint32_t role; asm("mov.u32 %0, %%cluster_ctarank;" : "=r"(role));
    int h; asm("mov.u32 %0, %%clusterid.x;" : "=r"(h));
    const uint32_t bar = sb + R_BAR;
    asm volatile("griddepcontrol.launch_dependents;");
    KT(0, 0);

    if (tid == 0) {
        for (int i = 0; i < 5; i++) mbar_init(bar + 8 * (B_FULL + i), 1);
        for (int i = 0; i < 3; i++) mbar_init(bar + 8 * (B_EMPTY + i), 2);
        for (int i = 0; i < 4; i++) mbar_init(bar + 8 * (B_MEM + i), 1);
        mbar_init(bar + 8 * B_HOP1, 9);
        mbar_init(bar + 8 * B_XT, 2);
        mbar_init(bar + 8 * B_TFREE, 6);
        mbar_init(bar + 8 * B_P, 4);
        mbar_init(bar + 8 * B_XRECV, 2);
        mbar_init(bar + 8 * B_O, 4);
        mbar_init(bar + 8 * B_AFREE0, 2);
        mbar_init(bar + 8 * B_AFREE1, 2);
        mbar_init(bar + 8 * B_PRO0, 1);
        mbar_init(bar + 8 * B_PRO1, 8);
        asm volatile("fence.mbarrier_init.release.cluster;" ::: "memory");
        fence_async();
        mbar_expect(bar + 8 * B_PRO0, KR * 4096);
        for (int i = 0; i < 3; i++) mbar_expect(bar + 8 * (B_FULL + i), 8192);
        mbar_expect(bar + 8 * B_HOP1, 4096);
        mbar_expect(bar + 8 * B_XT, role == 0 ? 16384 : 8192);
    }
    __syncthreads();
    asm volatile("barrier.cluster.arrive.relaxed.aligned;" ::: "memory");
    {
        const CUtensorMap* tw = &tm.w[role];
        if (wid < 11) {
            e_tma_load(sb + wid * 16384, tw, h * DH, KC(wid), bar + 8 * B_PRO0);
            e_tma_load(sb + wid * 16384 + 8192, tw, h * DH + 64, KC(wid), bar + 8 * B_PRO0);
        }
        if (wid < 6) e_tma_load(sb + R_RING + wid * 4096, &tm.x, XC(wid), 0, bar + 8 * (B_FULL + (wid >> 1)));
        if ((tid & 31) == 0) {
            if (wid < 10) tma_prefetch(tw, h * DH + (wid & 1) * 64, KC(KR / 4 + (wid >> 1)));
            if (wid >= 6 && wid - 6 < (role == 0 ? 4 : 6)) tma_prefetch(&tm.wo, wo_tile(role, wid - 6) * 64, h * DH);
            if (blockIdx.x < NSEG && wid < 8) { tma_prefetch(&tm.x, wid * 128, blockIdx.x * SEG); tma_prefetch(&tm.x, wid * 128 + 64, blockIdx.x * SEG); }
        }
        __syncwarp();
    }
    asm volatile("barrier.cluster.wait.aligned;" ::: "memory");

    if (wid < 8) {
        asm volatile("setmaxnreg.inc.sync.aligned.u32 224;");
        if (role == 0) r_big<0>(tm, wid); else if (role == 1) r_big<1>(tm, wid); else r_big<2>(tm, wid);
    } else {
        asm volatile("setmaxnreg.dec.sync.aligned.u32 56;");
        if (role == 0) r_chain<0>(mem0, x, gate_w, wid); else if (role == 1) r_chain<1>(mem0, x, gate_w, wid); else r_chain<2>(mem0, x, gate_w, wid);
    }
    __syncwarp();
    asm volatile("barrier.cluster.arrive; barrier.cluster.wait;" ::: "memory");
    KT(0, 1);
}

constexpr int G_ST = 4;
constexpr int G_STAGE = 16384 + 32768;
constexpr int G_EPI = G_ST * G_STAGE;
constexpr int G_GATE = G_EPI + 32768;
constexpr int G_BAR = G_GATE + 1024;
constexpr int G_SMEM = G_BAR + 128 + 1024;

struct G1Maps { CUtensorMap x, wg, wu, hs, o, h, wo, wd, out; };
constexpr int G1_NB = FF / 128;
constexpr int G1_TILES = 16 * G1_NB;

DEVINL void g_mma_block(float* d, uint32_t sb, uint32_t bar, int it, int wg, int tid, bool first) {
    const int st = it % G_ST;
    mbar_wait(bar + 8 * st, (it / G_ST) & 1);
    const uint64_t da = mkdesc(sb + st * G_STAGE + wg * 8192, 16, 1024, 1);
    const uint64_t db = mkdesc(sb + st * G_STAGE + 16384, 8192, 1024, 1);
    wg_fence();
#pragma unroll
    for (int k = 0; k < 4; k++) wg_ss256(d, da + (uint64_t)(k * 2), db + (uint64_t)(k * 128), (first ? 0 : 1) | k);
    wg_commit();
    if (!first) { wg_wait<1>(); if ((tid & 127) == 0) mbar_arrive(bar + 8 * (G_ST + (it - 1) % G_ST)); }
}
DEVINL void g_load_block(uint32_t sb, uint32_t bar, int it, const CUtensorMap* ta, int k0, int m0, const CUtensorMap* tb, int n0) {
    const int st = it % G_ST;
    mbar_wait(bar + 8 * (G_ST + st), ((it / G_ST) & 1) ^ 1);
    const uint32_t fb = bar + 8 * st, sa = sb + st * G_STAGE;
    mbar_expect(fb, G_STAGE);
    tma_load(sa, ta, k0, m0, fb);
#pragma unroll
    for (int q = 0; q < 4; q++) tma_load(sa + 16384 + q * 8192, tb, n0 + q * 64, k0, fb);
}

__global__ void __launch_bounds__(384, 1) g1_kernel(const __grid_constant__ G1Maps tm) {
    extern __shared__ __align__(1024) unsigned char smem_raw[];
    const uint32_t sb = (smem_u32(smem_raw) + 1023) & ~1023u;
    const int tid = threadIdx.x, lane = tid & 31;
    const int wg = __shfl_sync(0xffffffffu, tid >> 7, 0);
    const int warp = __shfl_sync(0xffffffffu, (tid >> 5) & 3, 0);
    const uint32_t bar = sb + G_BAR;
    const int t_begin = (blockIdx.x * G1_TILES) / gridDim.x;
    const int t_end = ((blockIdx.x + 1) * G1_TILES) / gridDim.x;
    const int mb0 = t_begin / G1_NB;
    KT(1, 0);
    if (tid == 0) {
        for (int i = 0; i < G_ST; i++) { mbar_init(bar + 8 * i, 1); mbar_init(bar + 8 * (G_ST + i), 2); }
        fence_async();
    }
    __syncthreads();
    if (wg == 2) {
        asm volatile("setmaxnreg.dec.sync.aligned.u32 56;");
        if (warp == 0) {
            if (lane == 0) {
                int it = 0;
                for (int tile = t_begin; tile < t_end; tile++) {
                    const int mb = tile / G1_NB, nb = tile % G1_NB;
                    for (int kb = 0; kb < 16; kb++, it++) {
                        const int st = it % G_ST;
                        mbar_wait(bar + 8 * (G_ST + st), ((it / G_ST) & 1) ^ 1);
                        const uint32_t fb = bar + 8 * st, sa = sb + st * G_STAGE;
                        mbar_expect(fb, G_STAGE);
                        tma_load(sa, &tm.x, kb * 64, mb * 128, fb);
                        tma_load(sa + 16384, &tm.wg, nb * 128, kb * 64, fb);
                        tma_load(sa + 16384 + 8192, &tm.wg, nb * 128 + 64, kb * 64, fb);
                        tma_load(sa + 16384 + 16384, &tm.wu, nb * 128, kb * 64, fb);
                        tma_load(sa + 16384 + 24576, &tm.wu, nb * 128 + 64, kb * 64, fb);
                    }
                }
                for (int pass = 0; pass < 2; pass++) {
                    for (int i = blockIdx.x; i < (pass ? NFULL : NLATE); i += gridDim.x) {
                        const int tile = pass ? i : NFULL + i, mb = tile >> 2, nb = tile & 3;
                        wait_count(&g_hcnt[mb], 2 * G1_NB);
                        asm volatile("fence.proxy.async;" ::: "memory");
                        for (int kb = 0; kb < FF / 64; kb++, it++) g_load_block(sb, bar, it, &tm.h, kb * 64, mb * 128, &tm.wd, nb * 256);
                        if (pass) {
                            wait_count(&g_ocnt[mb], NH * 4 * 2);
                            asm volatile("fence.proxy.async;" ::: "memory");
                            for (int kb = 0; kb < HD / 64; kb++, it++) g_load_block(sb, bar, it, &tm.o, kb * 64, mb * 128, &tm.wo, nb * 256);
                        }
                    }
                }
            }
        }
    } else {
        asm volatile("setmaxnreg.inc.sync.aligned.u32 224;");
        float d[128];
        int it = 0;
        float s0 = 0.f, s1 = 0.f;
        const uint32_t epi = sb + G_EPI + wg * 16384;
        const int row = warp * 16 + ((lane >> 3) & 1) * 8 + (lane & 7);
        for (int tile = t_begin; tile < t_end; tile++) {
            const int mb = tile / G1_NB, nb = tile % G1_NB;
            for (int kb = 0; kb < 16; kb++, it++) g_mma_block(d, sb, bar, it, wg, tid, kb == 0);
            if (tile == t_begin || nb == 0) {
                const uint32_t* gp = &g_gate[mb * 128 + wg * 64 + warp * 16 + (lane >> 2)];
                uint32_t u0, u1, n = 0;
                do { u0 = ld_strong4(gp); u1 = ld_strong4(gp + 8); if (++n > 20000000u) __trap(); } while (u0 == 0u || u1 == 0u);
                s0 = 1.0f - __uint_as_float(u0); s1 = 1.0f - __uint_as_float(u1);
                __syncwarp();
            }
            wg_wait<0>();
            if ((tid & 127) == 0) { mbar_arrive(bar + 8 * (G_ST + (it - 1) % G_ST)); bulk_wait_read(); }
            bar_sync(1 + wg, 128);
#pragma unroll
            for (int j = 0; j < 16; j += 2) {
                uint32_t p[4];
#pragma unroll
                for (int q = 0; q < 4; q++) {
                    const int i = (j + (q >> 1)) * 4 + (q & 1) * 2;
                    const float sc = (q & 1) ? s1 : s0;
                    const float g0 = d[i], g1 = d[i + 1];
                    const float h0 = __fdividef(g0, 1.0f + __expf(-g0)) * d[64 + i] * sc;
                    const float h1 = __fdividef(g1, 1.0f + __expf(-g1)) * d[64 + i + 1] * sc;
                    p[q] = pack_bf16(h0, h1);
                }
                const int cgp = j + (lane >> 4);
                stsm4(epi + (cgp >> 3) * 8192 + row * 128 + (((cgp & 7) ^ (row & 7)) << 4), p[0], p[1], p[2], p[3]);
            }
            fence_async();
            bar_sync(1 + wg, 128);
            if ((tid & 127) == 0) {
                tma_store(&tm.hs, epi, nb * 128, mb * 128 + wg * 64);
                tma_store(&tm.hs, epi + 8192, nb * 128 + 64, mb * 128 + wg * 64);
                bulk_commit();
            }
        }
        if ((tid & 127) == 0) {
            bulk_wait_all();
            __threadfence();
            const int n0 = min(t_end, (mb0 + 1) * G1_NB) - t_begin;
            atomicAdd(&g_hcnt[mb0], (uint32_t)n0);
            if (t_end - t_begin > n0) atomicAdd(&g_hcnt[mb0 + 1], (uint32_t)(t_end - t_begin - n0));
        }
        for (int pass = 0; pass < 2; pass++) {
            for (int i = blockIdx.x; i < (pass ? NFULL : NLATE); i += gridDim.x) {
                const int nkb = pass ? (FF + HD) / 64 : FF / 64;
                for (int kb = 0; kb < nkb; kb++, it++) g_mma_block(d, sb, bar, it, wg, tid, kb == 0);
                wg_wait<0>();
                if ((tid & 127) == 0) mbar_arrive(bar + 8 * (G_ST + (it - 1) % G_ST));
                if (pass == 0) {
                    float4* pre = g_pre + i * (32 * 256) + tid;
#pragma unroll
                    for (int q = 0; q < 32; q++) __stcg(pre + q * 256, make_float4(d[4 * q], d[4 * q + 1], d[4 * q + 2], d[4 * q + 3]));
                } else {
                    const int mb = i >> 2, nb = i & 3;
#pragma unroll
                    for (int half = 0; half < 2; half++) {
                        if ((tid & 127) == 0) bulk_wait_read();
                        bar_sync(1 + wg, 128);
#pragma unroll
                        for (int j = 0; j < 16; j += 2) {
                            const float* e = d + half * 64 + 4 * j;
                            const int cgp = j + (lane >> 4);
                            stsm4(epi + (cgp >> 3) * 8192 + row * 128 + (((cgp & 7) ^ (row & 7)) << 4),
                                  pack_bf16(e[0], e[1]), pack_bf16(e[2], e[3]), pack_bf16(e[4], e[5]), pack_bf16(e[6], e[7]));
                        }
                        fence_async();
                        bar_sync(1 + wg, 128);
                        if ((tid & 127) == 0) {
                            tma_store(&tm.out, epi, nb * 256 + half * 128, mb * 128 + wg * 64);
                            tma_store(&tm.out, epi + 8192, nb * 256 + half * 128 + 64, mb * 128 + wg * 64);
                            bulk_commit();
                        }
                    }
                }
            }
        }
        if ((tid & 127) == 0) bulk_wait_all();
        KT(1, 1);
    }
    __syncwarp();
    asm volatile("griddepcontrol.wait;" ::: "memory");
}

struct G2Maps { CUtensorMap o, wo, out; };

__global__ void __launch_bounds__(384, 1) g2_kernel(const __grid_constant__ G2Maps tm) {
    extern __shared__ __align__(1024) unsigned char smem_raw[];
    const uint32_t sb = (smem_u32(smem_raw) + 1023) & ~1023u;
    const int tid = threadIdx.x, lane = tid & 31;
    const int wg = __shfl_sync(0xffffffffu, tid >> 7, 0);
    const int warp = __shfl_sync(0xffffffffu, (tid >> 5) & 3, 0);
    const uint32_t bar = sb + G_BAR;
    const int ks = blockIdx.x & 3, lt = blockIdx.x >> 2, nb = (NFULL + lt) & 3, mb = (NFULL + lt) >> 2;
    KT(2, 0);
    if (tid == 0) {
        for (int i = 0; i < G_ST; i++) { mbar_init(bar + 8 * i, 1); mbar_init(bar + 8 * (G_ST + i), 2); }
        fence_async();
    }
    __syncthreads();
    if (wg == 2) {
        asm volatile("setmaxnreg.dec.sync.aligned.u32 40;");
        if (warp == 0 && lane == 0) {
            for (int it = 0; it < 16; it++) g_load_block(sb, bar, it, &tm.o, (ks * 16 + it) * 64, mb * 128, &tm.wo, nb * 256);
        } else if (warp == 1) {
            if (blockIdx.x < SEQ / 32) g_gate[blockIdx.x * 32 + lane] = 0u;
            if (blockIdx.x == 0 && lane < 16) { g_hcnt[lane] = 0u; g_ocnt[lane] = 0u; }
        }
    } else {
        asm volatile("setmaxnreg.inc.sync.aligned.u32 232;");
        float d[128];
        float4 r[8];
        const float4* pre = g_pre + (lt * 32 + ks * 8) * 256 + tid;
#pragma unroll
        for (int q = 0; q < 8; q++) r[q] = __ldcg(pre + q * 256);
        for (int it = 0; it < 16; it++) g_mma_block(d, sb, bar, it, wg, tid, it == 0);
        wg_wait<0>();
        float4* mine = g_sk + blockIdx.x * (32 * 256) + tid;
#pragma unroll
        for (int c = 0; c < 4; c++) {
            if (c != ks) {
#pragma unroll
                for (int q = c * 8; q < c * 8 + 8; q++) __stcg(mine + q * 256, make_float4(d[4 * q], d[4 * q + 1], d[4 * q + 2], d[4 * q + 3]));
            } else {
#pragma unroll
                for (int q = 0; q < 8; q++) { r[q].x += d[c * 32 + 4 * q]; r[q].y += d[c * 32 + 4 * q + 1]; r[q].z += d[c * 32 + 4 * q + 2]; r[q].w += d[c * 32 + 4 * q + 3]; }
            }
        }
        __threadfence();
        bar_sync(1, 256);
        if (tid == 0) {
            atomicAdd(&g_skcnt[lt], 1u);
            uint32_t v, n = 0;
            do {
                asm volatile("ld.acquire.gpu.global.u32 %0, [%1];" : "=r"(v) : "l"(&g_skcnt[lt]) : "memory");
                if (++n > 200000000u) __trap();
            } while (v < 4u);
            if (atomicAdd(&g_skdone[lt], 1u) == 3u) { g_skcnt[lt] = 0u; g_skdone[lt] = 0u; }
        }
        bar_sync(1, 256);
#pragma unroll
        for (int c = 1; c < 4; c++) {
            const float4* th = g_sk + ((lt * 4 + ((ks + c) & 3)) * 32 + ks * 8) * 256 + tid;
#pragma unroll
            for (int q = 0; q < 8; q++) { const float4 u = __ldcg(th + q * 256); r[q].x += u.x; r[q].y += u.y; r[q].z += u.z; r[q].w += u.w; }
        }
        const uint32_t epi = sb + G_EPI + wg * 16384;
        const int row = warp * 16 + ((lane >> 3) & 1) * 8 + (lane & 7);
#pragma unroll
        for (int j = 0; j < 8; j += 2) {
            const int cgp = j + (lane >> 4);
            stsm4(epi + row * 128 + ((cgp ^ (row & 7)) << 4), pack_bf16(r[j].x, r[j].y), pack_bf16(r[j].z, r[j].w),
                  pack_bf16(r[j + 1].x, r[j + 1].y), pack_bf16(r[j + 1].z, r[j + 1].w));
        }
        fence_async();
        bar_sync(2 + wg, 128);
        if ((tid & 127) == 0) {
            tma_store(&tm.out, epi, nb * 256 + ks * 64, mb * 128 + wg * 64);
            bulk_commit();
            bulk_wait_all();
        }
        KT(2, 1);
    }
}

typedef CUresult (*EncodeFn)(CUtensorMap*, CUtensorMapDataType, cuuint32_t, void*, const cuuint64_t*, const cuuint64_t*, const cuuint32_t*,
                             const cuuint32_t*, CUtensorMapInterleave, CUtensorMapSwizzle, CUtensorMapL2promotion, CUtensorMapFloatOOBfill);

static void make_map(EncodeFn enc, CUtensorMap* m, const void* ptr, uint64_t rows, uint64_t cols, uint32_t box_rows) {
    cuuint64_t dims[2] = {cols, rows};
    cuuint64_t strides[1] = {cols * 2};
    cuuint32_t box[2] = {64, box_rows};
    cuuint32_t es[2] = {1, 1};
    enc(m, CU_TENSOR_MAP_DATA_TYPE_BFLOAT16, 2, (void*)ptr, dims, strides, box, es, CU_TENSOR_MAP_INTERLEAVE_NONE,
        CU_TENSOR_MAP_SWIZZLE_128B, CU_TENSOR_MAP_L2_PROMOTION_L2_256B, CU_TENSOR_MAP_FLOAT_OOB_FILL_NONE);
}

extern "C" void kernel_launch(void* const* d_in, const int* in_sizes, int n_in, void* d_out, int out_size) {
    (void)in_sizes; (void)n_in; (void)out_size;
    const bf16* x = (const bf16*)d_in[0];
    const bf16* mem0 = (const bf16*)d_in[1];
    const bf16* gate_w = (const bf16*)d_in[11];
    static EncodeFn enc = nullptr;
    static int n_sm = 0;
    static void *pO = nullptr, *pH = nullptr;
    if (!enc) {
        void* fn = nullptr;
        cudaDriverEntryPointQueryResult qr;
        cudaGetDriverEntryPoint("cuTensorMapEncodeTiled", &fn, cudaEnableDefault, &qr);
        enc = (EncodeFn)fn;
        cudaDeviceGetAttribute(&n_sm, cudaDevAttrMultiProcessorCount, 0);
        cudaFuncSetAttribute(r_kernel, cudaFuncAttributeMaxDynamicSharedMemorySize, R_SMEM);
        cudaFuncSetAttribute(g1_kernel, cudaFuncAttributeMaxDynamicSharedMemorySize, G_SMEM);
        cudaFuncSetAttribute(g2_kernel, cudaFuncAttributeMaxDynamicSharedMemorySize, G_SMEM);
        cudaGetSymbolAddress(&pO, g_O);
        cudaGetSymbolAddress(&pH, g_H);
    }
    RMaps rm; G1Maps m1; G2Maps m2;
    make_map(enc, &rm.x, x, SEQ, DM, 32);
    for (int i = 0; i < 3; i++) make_map(enc, &rm.w[i], d_in[2 + i], DM, HD, 64);
    make_map(enc, &rm.wo, d_in[5], HD, DM, 128);
    make_map(enc, &rm.o, pO, SEQ, HD, 16);
    make_map(enc, &m1.x, x, SEQ, DM, 128);
    make_map(enc, &m1.wg, d_in[8], DM, FF, 64);
    make_map(enc, &m1.wu, d_in[9], DM, FF, 64);
    make_map(enc, &m1.hs, pH, SEQ, FF, 64);
    make_map(enc, &m1.o, pO, SEQ, HD, 128);
    make_map(enc, &m1.h, pH, SEQ, FF, 128);
    make_map(enc, &m1.wo, d_in[5], HD, DM, 64);
    make_map(enc, &m1.wd, d_in[10], FF, DM, 64);
    make_map(enc, &m1.out, d_out, SEQ, DM, 64);
    m2.o = m1.o; m2.wo = m1.wo; m2.out = m1.out;

    cudaStream_t st = cudaStreamPerThread;
    {
        cudaLaunchConfig_t cfg = {};
        cfg.gridDim = dim3(96); cfg.blockDim = dim3(384); cfg.dynamicSmemBytes = R_SMEM; cfg.stream = st;
        cudaLaunchAttribute at[1];
        at[0].id = cudaLaunchAttributeClusterDimension; at[0].val.clusterDim.x = 3; at[0].val.clusterDim.y = 1; at[0].val.clusterDim.z = 1;
        cfg.attrs = at; cfg.numAttrs = 1;
        cudaLaunchKernelEx(&cfg, r_kernel, rm, mem0, x, gate_w);
    }
    {
        cudaLaunchConfig_t cfg = {};
        cfg.gridDim = dim3(n_sm - 96); cfg.blockDim = dim3(384); cfg.dynamicSmemBytes = G_SMEM; cfg.stream = st;
        cudaLaunchAttribute at[1];
        at[0].id = cudaLaunchAttributeProgrammaticStreamSerialization; at[0].val.programmaticStreamSerializationAllowed = 1;
        cfg.attrs = at; cfg.numAttrs = 1;
        cudaLaunchKernelEx(&cfg, g1_kernel, m1);
    }
    g2_kernel<<<NLATE * 4, 384, G_SMEM, st>>>(m2);
}
```

```cpp
#include <cuda_runtime.h>
#include <cuda_bf16.h>
#include <cuda.h>
#include <stdint.h>

typedef __nv_bfloat16 bf16;

constexpr int SEQ = 2048, DM = 1024, NH = 32, DH = 128, NMEM = 8, SEG = 32, NSEG = 64, FF = 3584;
constexpr int HD = NH * DH;

__device__ bf16 g_O[SEQ * HD];
__device__ bf16 g_H[SEQ * FF];
__device__ uint32_t g_gate[SEQ];
__device__ uint32_t g_part[4][128 * 32 * 32];
__device__ uint32_t g_mem[4][DM * 4];
constexpr int NFULL = 36;
constexpr int NLATE = 64 - NFULL;
__device__ float4 g_pre[NLATE * 32 * 256];
__device__ float4 g_sk[NLATE * 4 * 32 * 256];
__device__ uint32_t g_skcnt[NLATE], g_skdone[NLATE];
__device__ uint32_t g_hcnt[16], g_ocnt[16];
#define KT(k, i)
#define PT(i)

#define DEVINL __device__ __forceinline__
constexpr long long SPIN_LIMIT = 4000000000LL;

DEVINL uint32_t smem_u32(const void* p) { return (uint32_t)__cvta_generic_to_shared(p); }
DEVINL void mbar_init(uint32_t bar, uint32_t cnt) { asm volatile("mbarrier.init.shared::cta.b64 [%0], %1;" ::"r"(bar), "r"(cnt) : "memory"); }
DEVINL void mbar_arrive(uint32_t bar) { asm volatile("mbarrier.arrive.shared::cta.b64 _, [%0];" ::"r"(bar) : "memory"); }
DEVINL void mbar_expect(uint32_t bar, uint32_t bytes) { asm volatile("mbarrier.arrive.expect_tx.shared::cta.b64 _, [%0], %1;" ::"r"(bar), "r"(bytes) : "memory"); }
DEVINL void mbar_arrive_remote(uint32_t cbar) { asm volatile("mbarrier.arrive.relaxed.cluster.shared::cluster.b64 _, [%0];" ::"r"(cbar) : "memory"); }
DEVINL bool mbar_try(uint32_t bar, uint32_t par) {
    uint32_t ok;
    asm volatile("{ .reg .pred p; mbarrier.try_wait.parity.shared::cta.b64 p, [%1], %2; selp.u32 %0, 1, 0, p; }" : "=r"(ok) : "r"(bar), "r"(par) : "memory");
    return ok;
}
__device__ __noinline__ void mbar_wait_slow(uint32_t bar, uint32_t par) {
    long long t0 = clock64();
    while (!mbar_try(bar, par)) { if (clock64() - t0 > SPIN_LIMIT) __trap(); }
}
DEVINL void mbar_wait(uint32_t bar, uint32_t par) {
    uint32_t n = 0;
    while (!mbar_try(bar, par)) { if (++n > 200000000u) __trap(); }
}
DEVINL uint32_t mapa(uint32_t a, uint32_t r) { uint32_t o; asm volatile("mapa.shared::cluster.u32 %0, %1, %2;" : "=r"(o) : "r"(a), "r"(r)); return o; }
DEVINL void fence_async() { asm volatile("fence.proxy.async.shared::cta;" ::: "memory"); }
DEVINL void bar_sync(int id, int n) { asm volatile("bar.sync %0, %1;" ::"r"(id), "r"(n) : "memory"); }
DEVINL void cluster_sync() { asm volatile("barrier.cluster.arrive.aligned; barrier.cluster.wait.aligned;" ::: "memory"); }
DEVINL void tma_load(uint32_t dst, const CUtensorMap* tm, int c0, int c1, uint32_t bar) {
    asm volatile("cp.async.bulk.tensor.2d.shared::cluster.global.mbarrier::complete_tx::bytes [%0], [%1, {%3, %4}], [%2];"
                 ::"r"(dst), "l"(tm), "r"(bar), "r"(c0), "r"(c1) : "memory");
}
DEVINL void tma_prefetch(const CUtensorMap* tm, int c0, int c1) {
    asm volatile("cp.async.bulk.prefetch.tensor.2d.L2.global [%0, {%1, %2}];" ::"l"(tm), "r"(c0), "r"(c1) : "memory");
}
DEVINL void tma_store(const CUtensorMap* tm, uint32_t src, int c0, int c1) {
    asm volatile("cp.async.bulk.tensor.2d.global.shared::cta.bulk_group [%0, {%2, %3}], [%1];" ::"l"(tm), "r"(src), "r"(c0), "r"(c1) : "memory");
}
DEVINL void bulk_commit() { asm volatile("cp.async.bulk.commit_group;" ::: "memory"); }
DEVINL void bulk_wait_read() { asm volatile("cp.async.bulk.wait_group.read 0;" ::: "memory"); }
DEVINL void bulk_wait_all() { asm volatile("cp.async.bulk.wait_group 0;" ::: "memory"); }
DEVINL void bulk_s2s(uint32_t cdst, uint32_t src, uint32_t bytes, uint32_t cbar) {
    asm volatile("cp.async.bulk.shared::cluster.shared::cta.mbarrier::complete_tx::bytes [%0], [%1], %2, [%3];" ::"r"(cdst), "r"(src), "r"(bytes), "r"(cbar) : "memory");
}
DEVINL void st_async16(uint32_t cdst, uint4 v, uint32_t cbar) {
    asm volatile("st.async.shared::cluster.mbarrier::complete_tx::bytes.v4.b32 [%0], {%1,%2,%3,%4}, [%5];" ::"r"(cdst), "r"(v.x), "r"(v.y), "r"(v.z), "r"(v.w), "r"(cbar) : "memory");
}
DEVINL uint64_t mkdesc(uint32_t addr, uint32_t lbo, uint32_t sbo, uint32_t swz) {
    return (uint64_t)((addr & 0x3FFFF) >> 4) | ((uint64_t)(lbo >> 4) << 16) | ((uint64_t)(sbo >> 4) << 32) | ((uint64_t)swz << 62);
}
constexpr uint32_t SB0 = 1024;
__host__ __device__ constexpr uint64_t cdesc(uint32_t off, uint32_t lbo, uint32_t sbo, uint32_t swz) {
    return (uint64_t)(((SB0 + off) & 0x3FFFF) >> 4) | ((uint64_t)(lbo >> 4) << 16) | ((uint64_t)(sbo >> 4) << 32) | ((uint64_t)swz << 62);
}
DEVINL float ex2(float x) { float y; asm("ex2.approx.ftz.f32 %0, %1;" : "=f"(y) : "f"(x)); return y; }
DEVINL void spin_clk(int d) { uint32_t t0, t1; asm volatile("mov.u32 %0, %%clock;" : "=r"(t0)); do { asm volatile("mov.u32 %0, %%clock;" : "=r"(t1)); } while ((int)(t1 - t0) < d); }
#define PROBE_GAP 150
#define OPAQUE(x) asm volatile("" : "+r"(x))
DEVINL void wg_fence() { asm volatile("wgmma.fence.sync.aligned;" ::: "memory"); }
DEVINL void wg_commit() { asm volatile("wgmma.commit_group.sync.aligned;" ::: "memory"); }
template <int N> DEVINL void wg_wait() { asm volatile("wgmma.wait_group.sync.aligned %0;" ::"n"(N) : "memory"); }
DEVINL uint32_t pack_bf16(float lo, float hi) { uint32_t r; asm("cvt.rn.bf16x2.f32 %0, %1, %2;" : "=r"(r) : "f"(hi), "f"(lo)); return r; }
DEVINL void ldsm4(uint32_t* r, uint32_t a) { asm volatile("ldmatrix.sync.aligned.m8n8.x4.shared.b16 {%0,%1,%2,%3}, [%4];" : "=r"(r[0]), "=r"(r[1]), "=r"(r[2]), "=r"(r[3]) : "r"(a) : "memory"); }
DEVINL void ldsm4t(uint32_t* r, uint32_t a) { asm volatile("ldmatrix.sync.aligned.m8n8.x4.trans.shared.b16 {%0,%1,%2,%3}, [%4];" : "=r"(r[0]), "=r"(r[1]), "=r"(r[2]), "=r"(r[3]) : "r"(a) : "memory"); }
DEVINL void stsm4(uint32_t a, uint32_t r0, uint32_t r1, uint32_t r2, uint32_t r3) { asm volatile("stmatrix.sync.aligned.m8n8.x4.shared.b16 [%0], {%1,%2,%3,%4};" ::"r"(a), "r"(r0), "r"(r1), "r"(r2), "r"(r3) : "memory"); }
DEVINL void stsm4t(uint32_t a, uint32_t r0, uint32_t r1, uint32_t r2, uint32_t r3) { asm volatile("stmatrix.sync.aligned.m8n8.x4.trans.shared.b16 [%0], {%1,%2,%3,%4};" ::"r"(a), "r"(r0), "r"(r1), "r"(r2), "r"(r3) : "memory"); }
DEVINL void sts32(uint32_t a, uint32_t v) { asm volatile("st.shared.b32 [%0], %1;" ::"r"(a), "r"(v) : "memory"); }
DEVINL void sts128(uint32_t a, uint4 v) { asm volatile("st.shared.v4.b32 [%0], {%1,%2,%3,%4};" ::"r"(a), "r"(v.x), "r"(v.y), "r"(v.z), "r"(v.w) : "memory"); }
DEVINL uint4 lds128(uint32_t a) { uint4 v; asm volatile("ld.shared.v4.b32 {%0,%1,%2,%3}, [%4];" : "=r"(v.x), "=r"(v.y), "=r"(v.z), "=r"(v.w) : "r"(a) : "memory"); return v; }
DEVINL uint4 ld_strong16(const void* p) { uint4 v; asm volatile("ld.relaxed.gpu.global.v4.u32 {%0,%1,%2,%3}, [%4];" : "=r"(v.x), "=r"(v.y), "=r"(v.z), "=r"(v.w) : "l"(p) : "memory"); return v; }
DEVINL void st_strong8(void* p, uint32_t a, uint32_t b) { asm volatile("st.relaxed.gpu.global.v2.u32 [%0], {%1,%2};" ::"l"(p), "r"(a), "r"(b) : "memory"); }
DEVINL void st_strong4(void* p, uint32_t a) { asm volatile("st.relaxed.gpu.global.u32 [%0], %1;" ::"l"(p), "r"(a) : "memory"); }
DEVINL void st_strong16(void* p, uint4 v) { asm volatile("st.relaxed.gpu.global.v4.u32 [%0], {%1,%2,%3,%4};" ::"l"(p), "r"(v.x), "r"(v.y), "r"(v.z), "r"(v.w) : "memory"); }
DEVINL uint32_t pack_nz(float lo, float hi) { uint32_t r = pack_bf16(lo, hi); return r == 0u ? 0x8000u : r; }
DEVINL uint32_t min4(uint4 v, uint32_t m) { return __vimin3_u32(__vimin3_u32(v.x, v.y, m), v.z, v.w); }
DEVINL void mma16816(float* d, uint32_t a0, uint32_t a1, uint32_t a2, uint32_t a3, uint32_t b0, uint32_t b1) {
    asm volatile("mma.sync.aligned.m16n8k16.row.col.f32.bf16.bf16.f32 {%0,%1,%2,%3}, {%4,%5,%6,%7}, {%8,%9}, {%0,%1,%2,%3};"
                 : "+f"(d[0]), "+f"(d[1]), "+f"(d[2]), "+f"(d[3]) : "r"(a0), "r"(a1), "r"(a2), "r"(a3), "r"(b0), "r"(b1));
}
DEVINL void mma1688(float* d, uint32_t a0, uint32_t a1, uint32_t b0) {
    asm volatile("mma.sync.aligned.m16n8k8.row.col.f32.bf16.bf16.f32 {%0,%1,%2,%3}, {%4,%5}, {%6}, {%0,%1,%2,%3};"
                 : "+f"(d[0]), "+f"(d[1]), "+f"(d[2]), "+f"(d[3]) : "r"(a0), "r"(a1), "r"(b0));
}
template <int TA, int TB> DEVINL void wg_ss8(float* d, uint64_t da, uint64_t db, int sc) {
    asm volatile("{ .reg .pred p; setp.ne.b32 p, %6, 0; wgmma.mma_async.sync.aligned.m64n8k16.f32.bf16.bf16 {%0,%1,%2,%3}, %4, %5, p, 1, 1, %7, %8; }"
                 : "+f"(d[0]), "+f"(d[1]), "+f"(d[2]), "+f"(d[3]) : "l"(da), "l"(db), "r"(sc), "n"(TA), "n"(TB));
}
template <int TB> DEVINL void wg_rs8(float* d, const uint32_t* a, uint64_t db, int sc) {
    asm volatile("{ .reg .pred p; setp.ne.b32 p, %9, 0; wgmma.mma_async.sync.aligned.m64n8k16.f32.bf16.bf16 {%0,%1,%2,%3}, {%4,%5,%6,%7}, %8, p, 1, 1, %10; }"
                 : "+f"(d[0]), "+f"(d[1]), "+f"(d[2]), "+f"(d[3]) : "r"(a[0]), "r"(a[1]), "r"(a[2]), "r"(a[3]), "l"(db), "r"(sc), "n"(TB));
}
#define ACC16(d) "+f"(d[0]), "+f"(d[1]), "+f"(d[2]), "+f"(d[3]), "+f"(d[4]), "+f"(d[5]), "+f"(d[6]), "+f"(d[7]), "+f"(d[8]), "+f"(d[9]), "+f"(d[10]), "+f"(d[11]), "+f"(d[12]), "+f"(d[13]), "+f"(d[14]), "+f"(d[15])
template <int TA> DEVINL void wg_ss32(float* d, uint64_t da, uint64_t db, int sc) {
    asm volatile("{ .reg .pred p; setp.ne.b32 p, %18, 0; wgmma.mma_async.sync.aligned.m64n32k16.f32.bf16.bf16 {%0,%1,%2,%3,%4,%5,%6,%7,%8,%9,%10,%11,%12,%13,%14,%15}, %16, %17, p, 1, 1, %19, 0; }"
                 : ACC16(d) : "l"(da), "l"(db), "r"(sc), "n"(TA));
}
DEVINL void wg_rs32(float* d, const uint32_t* a, uint64_t db, int sc) {
    asm volatile("{ .reg .pred p; setp.ne.b32 p, %21, 0; wgmma.mma_async.sync.aligned.m64n32k16.f32.bf16.bf16 {%0,%1,%2,%3,%4,%5,%6,%7,%8,%9,%10,%11,%12,%13,%14,%15}, {%16,%17,%18,%19}, %20, p, 1, 1, 0; }"
                 : ACC16(d) : "r"(a[0]), "r"(a[1]), "r"(a[2]), "r"(a[3]), "l"(db), "r"(sc));
}
DEVINL void wg_ss40(float* d, uint64_t da, uint64_t db, int sc) {
    asm volatile("{ .reg .pred p; setp.ne.b32 p, %22, 0; wgmma.mma_async.sync.aligned.m64n40k16.f32.bf16.bf16 {%0,%1,%2,%3,%4,%5,%6,%7,%8,%9,%10,%11,%12,%13,%14,%15,%16,%17,%18,%19}, %20, %21, p, 1, 1, 1, 1; }"
                 : ACC16(d), "+f"(d[16]), "+f"(d[17]), "+f"(d[18]), "+f"(d[19]) : "l"(da), "l"(db), "r"(sc));
}
#define A8(d, o) "+f"(d[o]), "+f"(d[o + 1]), "+f"(d[o + 2]), "+f"(d[o + 3]), "+f"(d[o + 4]), "+f"(d[o + 5]), "+f"(d[o + 6]), "+f"(d[o + 7])
#define A32(d, o) A8(d, o), A8(d, o + 8), A8(d, o + 16), A8(d, o + 24)
DEVINL void wg_ss256(float* d, uint64_t da, uint64_t db, int sc) {
    asm volatile(
        "{ .reg .pred p; setp.ne.b32 p, %130, 0;\n"
        "wgmma.mma_async.sync.aligned.m64n256k16.f32.bf16.bf16 {"
        "%0,%1,%2,%3,%4,%5,%6,%7,%8,%9,%10,%11,%12,%13,%14,%15,%16,%17,%18,%19,%20,%21,%22,%23,%24,%25,%26,%27,%28,%29,%30,%31,"
        "%32,%33,%34,%35,%36,%37,%38,%39,%40,%41,%42,%43,%44,%45,%46,%47,%48,%49,%50,%51,%52,%53,%54,%55,%56,%57,%58,%59,%60,%61,%62,%63,"
        "%64,%65,%66,%67,%68,%69,%70,%71,%72,%73,%74,%75,%76,%77,%78,%79,%80,%81,%82,%83,%84,%85,%86,%87,%88,%89,%90,%91,%92,%93,%94,%95,"
        "%96,%97,%98,%99,%100,%101,%102,%103,%104,%105,%106,%107,%108,%109,%110,%111,%112,%113,%114,%115,%116,%117,%118,%119,%120,%121,%122,%123,%124,%125,%126,%127"
        "}, %128, %129, p, 1, 1, 0, 1; }"
        : A32(d, 0), A32(d, 32), A32(d, 64), A32(d, 96) : "l"(da), "l"(db), "r"(sc));
}

DEVINL float gate_row(const bf16* __restrict__ xr, const bf16* __restrict__ gate_w, int lane) {
    float acc = 0.f;
#pragma unroll
    for (int i = 0; i < 4; i++) {
        const uint4 xv = __ldg((const uint4*)xr + i * 32 + lane), gv = __ldg((const uint4*)gate_w + i * 32 + lane);
        const uint32_t xa[4] = {xv.x, xv.y, xv.z, xv.w}, ga[4] = {gv.x, gv.y, gv.z, gv.w};
#pragma unroll
        for (int e = 0; e < 4; e++) {
            acc = fmaf(__uint_as_float(xa[e] << 16), __uint_as_float(ga[e] << 16), acc);
            acc = fmaf(__uint_as_float(xa[e] & 0xffff0000u), __uint_as_float(ga[e] & 0xffff0000u), acc);
        }
    }
#pragma unroll
    for (int o = 16; o > 0; o >>= 1) acc += __shfl_xor_sync(0xffffffffu, acc, o);
    return 1.0f / (1.0f + __expf(-acc));
}
DEVINL uint32_t ld_strong4(const void* p) { uint32_t v; asm volatile("ld.relaxed.gpu.global.u32 %0, [%1];" : "=r"(v) : "l"(p) : "memory"); return v; }
DEVINL void wait_count(const uint32_t* p, uint32_t want) {
    uint32_t v, n = 0;
    while (true) {
        asm volatile("ld.acquire.gpu.global.u32 %0, [%1];" : "=r"(v) : "l"(p) : "memory");
        if (v >= want) break;
        __nanosleep(200);
        if (++n > 10000000u) __trap();
    }
}

constexpr int KR = 44;
constexpr int KS = 64 - KR;
constexpr int R_W = 0;
constexpr int R_WO = KS * 4096;
constexpr int R_QX = R_WO + 65536;
constexpr int R_RING = R_WO + 98304;
constexpr int R_K = R_RING + 24576;
constexpr int R_V = R_K + 10240;
constexpr int R_QM = R_V + 10240;
constexpr int R_O = R_QM + 2048;
constexpr int R_BAR = R_O + 2048;
constexpr int R_G = R_BAR + 256 + 512 + 256 + 128;
constexpr int R_SMEM = R_G + 512;
enum { B_FULL = 0, B_EMPTY = 5, B_MEM = 8, B_HOP1 = 12, B_XT, B_TFREE, B_O, B_AFREE0, B_AFREE1, B_PRO0, B_PRO1, B_XRECV, B_P, B_XDONE, B_OST0, B_OST1, B_HOPV };
#define D2_BASE 1100
#define D2_STEP 200
#define PD2 6
#define DQ 1800
#define D3 0

DEVINL uint32_t clk32() { uint32_t c_; asm volatile("mov.u32 %0, %%clock;" : "=r"(c_)); return c_; }
DEVINL void spin_until(uint32_t t) { while ((uint32_t)(t - clk32() - 1u) < 100000u) {} }
#define PROF(i)
#define PROF2(i)
#define PROF3(i, val)
DEVINL void e_arrive(uint32_t bar) { asm volatile("{ .reg .pred p; elect.sync _|p, 0xffffffff; @p mbarrier.arrive.shared::cta.b64 _, [%0]; }" ::"r"(bar) : "memory"); }
DEVINL void e_arrive_remote(uint32_t cbar) { asm volatile("{ .reg .pred p; elect.sync _|p, 0xffffffff; @p mbarrier.arrive.relaxed.cluster.shared::cluster.b64 _, [%0]; }" ::"r"(cbar) : "memory"); }
DEVINL void e_count(uint32_t* p) { asm volatile("{ .reg .pred p; elect.sync _|p, 0xffffffff; @p red.relaxed.gpu.global.add.u32 [%0], 1; }" ::"l"(p) : "memory"); }
DEVINL void e_expect(uint32_t bar, uint32_t bytes) { asm volatile("{ .reg .pred p; elect.sync _|p, 0xffffffff; @p mbarrier.arrive.expect_tx.shared::cta.b64 _, [%0], %1; }" ::"r"(bar), "r"(bytes) : "memory"); }
DEVINL void e_tma_load(uint32_t dst, const CUtensorMap* tm, int c0, int c1, uint32_t bar) {
    asm volatile("{ .reg .pred p; elect.sync _|p, 0xffffffff; @p cp.async.bulk.tensor.2d.shared::cluster.global.mbarrier::complete_tx::bytes [%0], [%1, {%3, %4}], [%2]; }"
                 ::"r"(dst), "l"(tm), "r"(bar), "r"(c0), "r"(c1) : "memory");
}
DEVINL void e_tma_store(const CUtensorMap* tm, uint32_t src, int c0, int c1) {
    asm volatile("{ .reg .pred p; elect.sync _|p, 0xffffffff; @p cp.async.bulk.tensor.2d.global.shared::cta.bulk_group [%0, {%2, %3}], [%1]; }" ::"l"(tm), "r"(src), "r"(c0), "r"(c1) : "memory");
}
DEVINL void e_bulk_s2s(uint32_t cdst, uint32_t src, uint32_t bytes, uint32_t cbar) {
    asm volatile("{ .reg .pred p; elect.sync _|p, 0xffffffff; @p cp.async.bulk.shared::cluster.shared::cta.mbarrier::complete_tx::bytes [%0], [%1], %2, [%3]; }" ::"r"(cdst), "r"(src), "r"(bytes), "r"(cbar) : "memory");
}

#define SLOT 0
#define PH3 0
#define PHQ 0
DEVINL void wait_slot(uint32_t phase) {
    if (SLOT) {
        uint32_t c; asm volatile("mov.u32 %0, %%globaltimer_lo;" : "=r"(c));
        const uint32_t tgt = c + (SLOT ? SLOT : 1) - ((c - phase) % (SLOT ? SLOT : 1));
        do { asm volatile("mov.u32 %0, %%globaltimer_lo;" : "=r"(c)); } while ((uint32_t)(tgt - c - 1u) < 100000u);
    }
}
template <int N> DEVINL uint32_t poll_set(uint4 (&v)[N], const uint32_t* rp, int stride, uint32_t phase) {
    wait_slot(phase);
#pragma unroll
    for (int i = 0; i < N; i++) v[i] = ld_strong16(rp + i * stride);
    uint32_t n = 0;
    while (true) {
        uint32_t m = 0xffffffffu;
#pragma unroll
        for (int i = 0; i < N; i++) m = min4(v[i], m);
        if (__all_sync(0xffffffffu, m != 0u)) return n;
        wait_slot(phase);
#pragma unroll
        for (int i = 0; i < N; i++)
            asm volatile("{ .reg .pred p; setp.eq.u32 p, %5, 0; @p ld.relaxed.gpu.global.v4.u32 {%0,%1,%2,%3}, [%4]; }"
                         : "+r"(v[i].x), "+r"(v[i].y), "+r"(v[i].z), "+r"(v[i].w) : "l"(rp + i * stride), "r"(min4(v[i], 0xffffffffu)) : "memory");
        if (++n > 20000000u) __trap();
    }
}

struct RMaps { CUtensorMap x, w[3], wo, o; };
#define KC(c) ((c) * 64)

#define XORD 4
__host__ __device__ constexpr int xo(int i) {
    return XORD == 0 ? i : XORD == 1 ? (i + 14) % 16 : XORD == 2 ? (i + 11) % 16
         : XORD == 3 ? (i < 10 ? ((i & 1) ? i / 2 : 11 + i / 2) : i - 5) : (i < 6 ? i : ((i & 1) ? 6 + (i - 6) / 2 : 11 + (i - 6) / 2));
}
#define XC(i) (xo(i) * 64)
DEVINL void x_load_pair(uint32_t dst, const CUtensorMap* tmx, int h, int p, int seg, uint32_t fbar) {
    e_expect(fbar, 8192);
    e_tma_load(dst, tmx, XC(2 * p), seg * SEG, fbar);
    e_tma_load(dst + 4096, tmx, XC(2 * p + 1), seg * SEG, fbar);
}
__host__ __device__ constexpr int wo_tile(int role, int i) {
    return role == 0 ? (i < 2 ? 4 + i : 8 + i) : (i >> 1) * 6 + (role - 1) * 2 + (i & 1);
}

DEVINL void wo_issue(float* w, uint64_t dWo) {
    constexpr uint64_t dO = cdesc(R_O, 128, 128, 0);
    wg_fence();
#pragma unroll
    for (int k = 0; k < 8; k++) wg_ss8<1, 1>(w, dWo + (uint64_t)(k * 128), dO + (uint64_t)(k * 16), k);
    wg_commit();
}
template <int N> DEVINL void wo_store(float* w, uint32_t* q) {
    asm volatile("wgmma.wait_group.sync.aligned %4;" : "+f"(w[0]), "+f"(w[1]), "+f"(w[2]), "+f"(w[3]) : "n"(N) : "memory");
    st_strong4(q, pack_nz(w[0], w[1]));
    st_strong4(q + 1024, pack_nz(w[2], w[3]));
}

DEVINL void o_store(const RMaps& tm, uint32_t sb, uint32_t bar, int wq, int h, int s) {
    mbar_wait(bar + 8 * B_OST0 + (wq >> 2) * 8, s & 1);
    const uint32_t src = sb + R_QX + 2048 + (wq >> 2) * 8192;
    e_tma_store(&tm.o, src, h * DH + (wq >> 2) * 64, s * SEG);
    e_tma_store(&tm.o, src + 4096, h * DH + (wq >> 2) * 64, s * SEG + 16);
    bulk_commit();
}

template <uint32_t role> DEVINL void r_big(const RMaps& tm, const int wid) {
    extern __shared__ __align__(1024) unsigned char smem_raw[];
    const uint32_t sb = smem_u32(smem_raw);
    const uint32_t bar = sb + R_BAR;
    const int tid = threadIdx.x;
    int h; asm("mov.u32 %0, %%clusterid.x;" : "=r"(h));
        uint32_t a[KR][4];
        mbar_wait(bar + 8 * B_PRO0, 0);
        PT(0);
        {
            const int lane = tid & 31;
            const int krow = (lane & 7) + ((lane >> 4) << 3);
            const int chunk = (wid & 3) * 2 + ((lane >> 3) & 1);
            const uint32_t la = sb + (wid >> 2) * 8192 + krow * 128 + ((chunk ^ (krow & 7)) << 4);
#pragma unroll
            for (int k = 0; k < KR; k++) ldsm4t(a[k], la + (k >> 2) * 16384 + (k & 3) * 2048);
        }
        bar_sync(1, 256);
        {
            fence_async();
            const CUtensorMap* tw = &tm.w[role];
            e_expect(bar + 8 * B_PRO1, (wid < 5 ? 16384 : 0) + (wid < (role == 0 ? 4 : 6) ? 16384 : 0));
            if (wid < 5) {
                e_tma_load(sb + R_W + wid * 8192, tw, h * DH, KC(KR / 4 + wid), bar + 8 * B_PRO1);
                e_tma_load(sb + R_W + KS * 2048 + wid * 8192, tw, h * DH + 64, KC(KR / 4 + wid), bar + 8 * B_PRO1);
            }
            if (wid < (role == 0 ? 4 : 6)) e_tma_load(sb + R_WO + wid * 16384, &tm.wo, wo_tile(role, wid) * 64, h * DH, bar + 8 * B_PRO1);
        }
        constexpr uint32_t e0 = role == 0 ? R_QX + 16384 : R_K + 2048, e1 = role == 0 ? R_QX + 24576 : R_V + 2048;
        if (wid == 6) x_load_pair(sb + e0, &tm.x, h, 3, 0, bar + 8 * (B_FULL + 3));
        if (wid == 7) x_load_pair(sb + e1, &tm.x, h, 4, 0, bar + 8 * (B_FULL + 4));
        PT(1);
        mbar_wait(bar + 8 * B_PRO1, 0);
        PT(2);

        constexpr uint64_t dW0 = cdesc(R_W, 1024, 1024, 1);
        constexpr uint64_t dWo0 = cdesc(R_WO, 1024, 1024, 1);
        constexpr uint64_t dM = cdesc(R_RING, 128, 128, 0);
        constexpr uint64_t dX = cdesc(R_RING, 16, 1024, 1);
        constexpr uint64_t dX0 = cdesc(0, 16, 1024, 1);
        int tb = tid;
        int wq = wid;

        float d[16];
        for (int s = -1; s < NSEG; s++) {
            if (s >= 0) {
                OPAQUE(wq);
                const uint64_t dW = dW0 + (uint64_t)((wq >> 2) * (KS * 128));
                float y[4] = {0.f, 0.f, 0.f, 0.f};
                {
                    OPAQUE(tb);
                    const uint32_t ma = sb + R_RING + (tb & 31) * 16;
                    float z[4] = {0.f, 0.f, 0.f, 0.f}, u[4] = {0.f, 0.f, 0.f, 0.f};
                    uint32_t b[4][4];
                    mbar_wait(bar + 8 * B_MEM, s & 1);
                    PROF((wq >> 2) * 4 + 0);
                    if (s == 0) PT(3);
                    if (s == 1) PT(4);
#pragma unroll
                    for (int g = 0; g < 4; g++) ldsm4t(b[g], ma + g * 512);
#pragma unroll
                    for (int g = 0; g < KR / 2; g++) {
                        float* c0 = (g % 3 == 0) ? y : (g % 3 == 1) ? u : z;
                        float* c1 = (g % 3 == 0) ? z : (g % 3 == 1) ? y : u;
                        mma16816(c0, a[2 * g][0], a[2 * g][1], a[2 * g][2], a[2 * g][3], b[g & 3][0], b[g & 3][1]);
                        mma16816(c1, a[2 * g + 1][0], a[2 * g + 1][1], a[2 * g + 1][2], a[2 * g + 1][3], b[g & 3][2], b[g & 3][3]);
                        if (g + 4 < KR / 2) {
                            if ((g + 4) % 8 == 0) mbar_wait(bar + 8 * (B_MEM + (g + 4) / 8), s & 1);
                            ldsm4t(b[g & 3], ma + (g + 4) * 512);
                        }
                    }
                    y[0] += z[0] + u[0]; y[1] += z[1] + u[1]; y[2] += z[2] + u[2]; y[3] += z[3] + u[3];
                }
                PROF2(8);
                mbar_wait(bar + 8 * (B_MEM + 3), s & 1);
                wg_fence();
#pragma unroll
                for (int k = KR; k < 64; k++) wg_ss8<1, 1>(y, dW + (uint64_t)((k - KR) * 128), dM + (uint64_t)(k * 16), 1);
                wg_commit();
                asm volatile("wgmma.wait_group.sync.aligned 0;" : "+f"(y[0]), "+f"(y[1]), "+f"(y[2]), "+f"(y[3])::"memory");
                OPAQUE(tb);
                {
                    const uint32_t wo_ = (tb >> 5) * 256;
                    const uint32_t tile = sb + (role == 0 ? R_QX : (role == 1 ? R_K : R_V)) + wo_;
                    const uint32_t u0 = pack_bf16(y[0], y[1]), u1 = pack_bf16(y[2], y[3]);
                    sts32(tile + (tb & 31) * 4, u0);
                    sts32(tile + (tb & 31) * 4 + 128, u1);
                    __syncwarp();
                    uint4 v = lds128(tile + (tb & 15) * 16);
                    uint32_t peer = role + 1 + ((tb >> 4) & 1);
                    peer = peer >= 3 ? peer - 3 : peer;
                    const uint32_t rt = sb + (role == 0 ? R_QM : (role == 1 ? R_K : R_V)) + wo_ + (tb & 15) * 16;
                    st_async16(mapa(rt, peer), v, mapa(bar + 8 * (role == 2 ? B_HOPV : B_HOP1), peer));
                    if (role == 0) {
                        sts128(tile + 4096 + ((tb >> 4) & 1) * 4096 + (tb & 15) * 16, v);
                        sts32(tile + 12288 + (tb & 31) * 4, u0);
                        sts32(tile + 12288 + (tb & 31) * 4 + 128, u1);
                        __syncwarp();
                    }
                    e_arrive(bar + 8 * (role == 2 ? B_HOPV : B_HOP1));
                }
                PROF((wq >> 2) * 4 + 1);
                if (s < NSEG - 1) {
                    bar_sync(1, 256);
                    if (wq < 2) { fence_async(); x_load_pair(sb + R_RING + wq * 8192, &tm.x, h, wq, s + 1, bar + 8 * (B_FULL + wq)); }
                    OPAQUE(tb);
                }
                uint32_t* pp = g_part[s & 3] + (h * 32 + (wo_tile(role, 0) + (tb >> 7)) * 8192 + ((tb >> 5) & 3) * 2048 + (tb & 31));
                const uint64_t dWo = dWo0 + (uint64_t)((wq >> 2) * 1024);
                float w0[4];
                if (role != 0) {
                    if (s < NSEG - 1) {
                        if ((wq & 3) == 3) mbar_wait(bar + 8 * B_XRECV, s & 1);
                        mbar_wait(bar + 8 * B_O, s & 1);
                        PROF((wq >> 2) * 4 + 2);
                        wo_issue(w0, dWo);
                        wo_store<0>(w0, pp);
                        wo_issue(w0, dWo + 2048);
                        if ((wq & 3) == 3) x_load_pair(sb + (wq == 3 ? e0 : e1), &tm.x, h, 3 + (wq >> 2), s + 1, bar + 8 * (B_FULL + 3 + (wq >> 2)));
                        wo_store<0>(w0, pp + 6 * 8192);
                        wo_issue(w0, dWo + 4096);
                        wo_store<0>(w0, pp + 12 * 8192);
                    }
                } else {
                    constexpr uint64_t dV = cdesc(R_V, 2048, 128, 0);
                    constexpr uint64_t dP = cdesc(R_QX, 128, 4096, 0);
                    if ((wq & 3) == 0 && s >= 1) { bulk_wait_all(); e_count(&g_ocnt[(s - 1) >> 2]); }
                    mbar_wait(bar + 8 * B_O, s & 1);
                    PROF((wq >> 2) * 4 + 2);
                    float sf[8];
#pragma unroll
                    for (int j = 0; j < 4; j++) asm volatile("ld.shared.v2.f32 {%0,%1}, [%2];" : "=f"(sf[2 * j]), "=f"(sf[2 * j + 1]) : "r"(sb + R_G + 128 + j * 32 + (tb & 3) * 8) : "memory");
                    wo_issue(w0, dWo);
                    wg_fence();
#pragma unroll
                    for (int k = 0; k < 3; k++) wg_ss32<0>(d, dV + (uint64_t)((wq >> 2) * 64 + k * 256), dP + (uint64_t)(k * 16), k);
                    wg_commit();
                    if (s < NSEG - 1) wo_store<1>(w0, pp); else wg_wait<1>();
                    wo_issue(w0, dWo + 2048);
                    asm volatile("wgmma.wait_group.sync.aligned 1;" : ACC16(d)::"memory");
                    if (s < NSEG - 1 && ((wq & 3) == 1 || (wq & 3) == 2)) e_arrive_remote(mapa(bar + 8 * B_TFREE, wq & 3));
                    OPAQUE(tb);
                    const uint32_t r = ((tb >> 4) & 1) * 8 + (tb & 7), ch = ((tb >> 5) & 3) * 2 + ((tb >> 3) & 1);
                    const uint32_t oa = sb + R_QX + 2048 + (tb >> 7) * 8192 + r * 128 + ((ch ^ (r & 7)) << 4);
                    stsm4t(oa, pack_bf16(d[0] * sf[0], d[1] * sf[1]), pack_bf16(d[2] * sf[0], d[3] * sf[1]), pack_bf16(d[4] * sf[2], d[5] * sf[3]), pack_bf16(d[6] * sf[2], d[7] * sf[3]));
                    stsm4t(oa + 4096, pack_bf16(d[8] * sf[4], d[9] * sf[5]), pack_bf16(d[10] * sf[4], d[11] * sf[5]), pack_bf16(d[12] * sf[6], d[13] * sf[7]), pack_bf16(d[14] * sf[6], d[15] * sf[7]));
                    fence_async();
                    __syncwarp();
                    e_arrive(bar + 8 * B_OST0 + (wq >> 2) * 8);
                    if (s < NSEG - 1) wo_store<0>(w0, pp + 6 * 8192); else wg_wait<0>();
                }
                if (wq == 0) PROF(10);
                if (s == NSEG - 1) {
                    if (role == 0 && (wq & 3) == 0) { o_store(tm, sb, bar, wq, h, s); bulk_wait_all(); }
                    break;
                }
            }
            const int seg = s + 1;
            OPAQUE(wq);
            const uint64_t dW = dW0 + (uint64_t)((wq >> 2) * (KS * 128));
#pragma unroll
            for (int p = 0; p < 8; p++) {
                const int slot = p % 5;
                mbar_wait(bar + 8 * (B_FULL + slot), slot < 3 ? (uint32_t)(p / 5) : (uint32_t)(seg & 1));
                PROF2(p);
                const uint64_t db = slot < 3 ? dX + (uint64_t)(slot * 512) : dX0 + (uint64_t)((slot == 3 ? e0 : e1) >> 4);
                wg_fence();
#pragma unroll
                for (int kk = 0; kk < 8; kk++) {
                    const int k = XORD >= 3 ? (kk & 1) * 4 + (kk >> 1) : kk;
                    const int ks = xo(2 * p + (k >> 2)) * 4 + (k & 3);
                    if (ks >= KR) wg_ss32<1>(d, dW + (uint64_t)((ks - KR) * 128), db + (uint64_t)((k >> 2) * 256 + (k & 3) * 2), p + k);
                    else wg_rs32(d, a[ks < KR ? ks : 0], db + (uint64_t)((k >> 2) * 256 + (k & 3) * 2), p + k);
                }
                wg_commit();
                if (p == 0 && role == 0 && (wq & 3) == 0 && s >= 0) o_store(tm, sb, bar, wq, h, s);
                if (p >= 1) {
                    wg_wait<1>();
                    if (p <= 3) {
                        if ((wq & 3) == p) e_arrive(bar + 8 * (B_EMPTY + p - 1));
                        if (wq == p + (p & 1) * 4) {
                            mbar_wait(bar + 8 * (B_EMPTY + p - 1), seg & 1);
                            x_load_pair(sb + R_RING + (p - 1) * 8192, &tm.x, h, p + 4, seg, bar + 8 * (B_FULL + p - 1));
                        }
                    }
                    if (p == 5 && (wq & 3) < ((role == 0 && s >= 0) ? 1 : 3)) {
                        if (role == 0) bulk_wait_read();
                        e_arrive_remote(mapa(bar + 8 * B_TFREE, wq & 3));
                    }
                    if (p == 6 && (wq & 3) == 1) e_arrive(bar + 8 * B_AFREE0);
                    if (p == 7 && (wq & 3) == 2) e_arrive(bar + 8 * B_AFREE1);
                }
            }
            asm volatile("wgmma.wait_group.sync.aligned 0;" : ACC16(d)::"memory");
            PROF2(16);
            mbar_wait(bar + 8 * B_TFREE, seg & 1);
            const uint32_t tilex = sb + (role == 0 ? R_QX + 2048 : (role == 1 ? R_K + 2048 : R_V + 2048));
            {
                OPAQUE(tb);
                const uint32_t gs = role == 0 ? 4096 : 2048;
                const uint32_t sa = tilex + ((tb >> 4) & 1) * gs + (tb >> 5) * 256 + (tb & 15) * 16;
                stsm4(sa, pack_bf16(d[0], d[1]), pack_bf16(d[2], d[3]), pack_bf16(d[4], d[5]), pack_bf16(d[6], d[7]));
                stsm4(sa + 2 * gs, pack_bf16(d[8], d[9]), pack_bf16(d[10], d[11]), pack_bf16(d[12], d[13]), pack_bf16(d[14], d[15]));
            }
            fence_async();
            __syncwarp();
            e_arrive(bar + 8 * B_XDONE);
            if ((wq & 3) == 0 || wq == 2) {
                mbar_wait(bar + 8 * B_XDONE, seg & 1);
                if (wq == 2) { if (seg + 1 < NSEG) x_load_pair(sb + R_RING + 16384, &tm.x, h, 2, seg + 1, bar + 8 * (B_FULL + 2)); }
                else if (role != 0) { uint32_t pr = role + 1 + (wq >> 2); pr = pr >= 3 ? pr - 3 : pr; e_bulk_s2s(mapa(tilex, pr), tilex, 8192, mapa(bar + 8 * B_XT, pr)); }
                else if (seg + 1 < NSEG) x_load_pair(sb + (wq == 0 ? e0 : e1), &tm.x, h, 3 + (wq >> 2), seg + 1, bar + 8 * (B_FULL + 3 + (wq >> 2)));
            }
        }
}

template <uint32_t role> DEVINL void r_chain(const RMaps& tm, const bf16* __restrict__ mem0, const bf16* __restrict__ x, const bf16* __restrict__ gate_w, const int wid) {
    extern __shared__ __align__(1024) unsigned char smem_raw[];
    const uint32_t sb = smem_u32(smem_raw);
    const uint32_t bar = sb + R_BAR;
    const int tid = threadIdx.x;
    int h; asm("mov.u32 %0, %%clusterid.x;" : "=r"(h));
        int t = tid & 127;
        const float sl2 = 0.08838834764831845f * 1.4426950408889634f;
        const float NEGRAW = -1000000000.0f / 0.08838834764831845f;
        const int rg0 = ((int)role - 1) * 32 + h;
        if (role != 0) {
#pragma unroll 1
            for (int r = 0; r < 4; r++) {
                uint32_t* zp = g_part[r] + ((rg0 + (t >> 6) * 64) * 1024 + (t & 63) * 4);
#pragma unroll
                for (int i = 0; i < 4; i++) st_strong16(zp + i * 256, make_uint4(0u, 0u, 0u, 0u));
                if ((t & 63) < 8) st_strong16(&g_mem[r][(rg0 + (t >> 6) * 64) * 32 + (t & 63) * 4], make_uint4(0u, 0u, 0u, 0u));
            }
            __threadfence();
        }
        {
#pragma unroll 1
            for (int r = (h * 3 + (int)role) * 4 + (t >> 5); r < SEQ; r += 384) {
                const uint32_t gb = __float_as_uint(gate_row(x + r * DM, gate_w, t & 31));
                if ((t & 31) == 0) st_strong4(&g_gate[r], gb ? gb : 0x80000000u);
            }
        }
        if (role == 0) sts128(sb + R_QM + t * 16, make_uint4(0u, 0u, 0u, 0u));
        {
            uint4 v[8];
#pragma unroll
            for (int r = 0; r < 8; r++) v[r] = __ldg((const uint4*)(mem0 + r * DM) + t);
            mbar_wait(bar + 8 * B_AFREE0, 0);
            mbar_wait(bar + 8 * B_AFREE1, 0);
#define TR2(f, c) \
            sts128(sb + R_RING + t * 128 + (c) * 16, make_uint4(__byte_perm(v[0].f, v[1].f, 0x5410), __byte_perm(v[2].f, v[3].f, 0x5410), __byte_perm(v[4].f, v[5].f, 0x5410), __byte_perm(v[6].f, v[7].f, 0x5410))); \
            sts128(sb + R_RING + t * 128 + (c) * 16 + 16, make_uint4(__byte_perm(v[0].f, v[1].f, 0x7632), __byte_perm(v[2].f, v[3].f, 0x7632), __byte_perm(v[4].f, v[5].f, 0x7632), __byte_perm(v[6].f, v[7].f, 0x7632)));
            TR2(x, 0) TR2(y, 2) TR2(z, 4) TR2(w, 6)
            fence_async();
            __syncwarp();
            e_arrive(bar + 8 * B_MEM + (t >> 5) * 8);
        }
        constexpr uint64_t dQ = role == 0 ? cdesc(R_QX, 128, 2048, 0) : cdesc(R_QM, 128, 0, 0);
        constexpr uint64_t dK = cdesc(R_K, 128, 2048, 0);

        for (int s = 0; s < NSEG; s++) {
            if (role == 0) {
                uint32_t n = 0, gate;
                do { gate = ld_strong4(&g_gate[s * SEG + (t >> 2)]); if (++n > 20000000u) __trap(); } while (gate == 0u);
                sts32(sb + R_G + (t >> 2) * 4, gate);
                __syncwarp();
            }
            mbar_wait(bar + 8 * B_XDONE, s & 1);
            mbar_wait(bar + 8 * B_XT, s & 1);
            if (t >= 1 && t < 3) { uint32_t pr = role + t; pr = pr >= 3 ? pr - 3 : pr; mbar_arrive_remote(mapa(bar + 8 * B_XRECV, pr)); }
            __syncwarp();
            mbar_wait(bar + 8 * B_HOP1, s & 1);
            PROF(8);
            fence_async();
            OPAQUE(t);
            if (s == NSEG - 1 && role != 0) { mbar_wait(bar + 8 * B_HOPV, s & 1); break; }
            float sc[20];
            wg_fence();
#pragma unroll
            for (int k = 0; k < 8; k++) wg_ss40(sc, dQ + (uint64_t)(k * 16), dK + (uint64_t)(k * 16), k);
            wg_commit();
            uint32_t t_o = 0;
            {
                const uint32_t va = sb + R_V + 2048 + (t >> 5) * 512 + ((t >> 4) & 1) * 2048 + (t & 15) * 16;
                uint32_t v0[4], v1[4];
                ldsm4(v0, va); ldsm4(v1, va + 256);
                const int lim = (t >> 2) - (t & 3) * 2 + 8;
                wg_wait<0>();
                float m = fmaxf(sc[0], sc[1]), m1 = fmaxf(sc[2], sc[3]);
#pragma unroll
                for (int j = 1; j < 5; j++) {
                    m = fmaxf(m, fmaxf(sc[4 * j], sc[4 * j + 1]));
                    if (role == 0) {
                        sc[4 * j + 2] = 8 * j <= lim ? sc[4 * j + 2] : NEGRAW;
                        sc[4 * j + 3] = 8 * j + 1 <= lim ? sc[4 * j + 3] : NEGRAW;
                        m1 = fmaxf(m1, fmaxf(sc[4 * j + 2], sc[4 * j + 3]));
                    }
                }
                m = fmaxf(m, __shfl_xor_sync(0xffffffffu, m, 1));
                if (role == 0) m1 = fmaxf(m1, __shfl_xor_sync(0xffffffffu, m1, 1));
                m = fmaxf(m, __shfl_xor_sync(0xffffffffu, m, 2));
                if (role == 0) m1 = fmaxf(m1, __shfl_xor_sync(0xffffffffu, m1, 2));
                const float mb = m * sl2, mb1 = m1 * sl2;
                uint32_t pk[5], pt[5];
#pragma unroll
                for (int j = 0; j < 5; j++) pk[j] = pack_bf16(ex2(fmaf(sc[4 * j], sl2, -mb)), ex2(fmaf(sc[4 * j + 1], sl2, -mb)));
                float o0[4] = {0.f, 0.f, 0.f, 0.f}, o1[4] = {0.f, 0.f, 0.f, 0.f}, ls[4] = {0.f, 0.f, 0.f, 0.f};
                constexpr uint32_t ONE = 0x3F803F80u;
                mma16816(o0, v0[0], v0[1], v0[2], v0[3], pk[1], pk[2]);
                mma16816(o1, v1[0], v1[1], v1[2], v1[3], pk[1], pk[2]);
                ldsm4(v0, va + 4096); ldsm4(v1, va + 4096 + 256);
                mma16816(ls, ONE, ONE, ONE, ONE, pk[1], pk[2]);
                mma16816(ls, ONE, ONE, ONE, ONE, pk[3], pk[4]);
                mma1688(ls, ONE, ONE, pk[0]);
                mma16816(o0, v0[0], v0[1], v0[2], v0[3], pk[3], pk[4]);
                mma16816(o1, v1[0], v1[1], v1[2], v1[3], pk[3], pk[4]);
                if (role == 0) {
#pragma unroll
                    for (int j = 0; j < 5; j++) pt[j] = pack_bf16(ex2(fmaf(sc[4 * j + 2], sl2, -mb1)), ex2(fmaf(sc[4 * j + 3], sl2, -mb1)));
                }
                mbar_wait(bar + 8 * B_HOPV, s & 1);
                ldsm4(v0, sb + R_V + t * 16);
                mma1688(o0, v0[0], v0[1], pk[0]);
                mma1688(o1, v0[2], v0[3], pk[0]);
                const float i0 = __fdividef(1.0f, ls[0]), i1 = __fdividef(1.0f, ls[1]);
                const uint32_t oa = sb + R_O + (t >> 5) * 512 + (t & 31) * 4;
                sts32(oa, pack_bf16(o0[0] * i0, o0[1] * i1));
                sts32(oa + 128, pack_bf16(o0[2] * i0, o0[3] * i1));
                sts32(oa + 256, pack_bf16(o1[0] * i0, o1[1] * i1));
                sts32(oa + 384, pack_bf16(o1[2] * i0, o1[3] * i1));
                if (role == 0) {
                    float lt[4] = {0.f, 0.f, 0.f, 0.f};
                    mma16816(lt, pt[0], pt[1], pt[2], pt[3], ONE, ONE);
                    mma1688(lt, pt[4], 0u, ONE);
                    const uint32_t pa = sb + R_QX + (t >> 5) * 4096 + (t & 31) * 4;
#pragma unroll
                    for (int j = 0; j < 5; j++) sts32(pa + j * 128, pt[j]);
                    sts32(pa + 5 * 128, 0u);
                    float gate; asm volatile("ld.shared.f32 %0, [%1];" : "=f"(gate) : "r"(sb + R_G + (t >> 2) * 4) : "memory");
                    sts32(sb + R_G + 128 + (t >> 2) * 4, __float_as_uint(__fdividef(gate, lt[0] + lt[2])));
                }
                fence_async();
                __syncwarp();
                e_arrive(bar + 8 * B_O);
                t_o = clk32();
                PROF(9);
            }
            if (t < 32) { e_expect(bar + 8 * B_HOP1, role == 2 ? 4096 : 2048); if (role != 2) e_expect(bar + 8 * B_HOPV, 2048); e_expect(bar + 8 * B_XT, role == 0 ? 16384 : 8192); }
            if (s == NSEG - 1) break;
            OPAQUE(t);
            PROF(11);
            if (role != 0) {
                const uint32_t* rp = g_part[s & 3] + ((rg0 + (t >> 6) * 64) * 1024 + ((t >> 2) & 7) * 32 + ((t >> 5) & 1) * 16 + (t & 3) * 4);
                uint32_t* wp = &g_mem[(s + 1) & 3][(rg0 + (t >> 6) * 64) * 32 + ((t >> 5) & 1) * 16 + (t & 3) * 4 + ((t >> 3) & 3)];
                spin_until(t_o + D2_BASE + (role - 1 + (t >> 6) * 2) * D2_STEP);
                PROF3(0, clk32());
#define LO(u) __uint_as_float((u) << 16)
#define HI(u) __uint_as_float((u) & 0xffff0000u)
                uint4 v[4];
                uint32_t n = poll_set<4>(v, rp, 256, (role - 1 + (t >> 6) * 2) * PHQ);
                {
                    PROF3(1, clk32());
                    float f[8];
                    f[0] = (LO(v[0].x) + LO(v[1].x)) + (LO(v[2].x) + LO(v[3].x)); f[1] = (HI(v[0].x) + HI(v[1].x)) + (HI(v[2].x) + HI(v[3].x));
                    f[2] = (LO(v[0].y) + LO(v[1].y)) + (LO(v[2].y) + LO(v[3].y)); f[3] = (HI(v[0].y) + HI(v[1].y)) + (HI(v[2].y) + HI(v[3].y));
                    f[4] = (LO(v[0].z) + LO(v[1].z)) + (LO(v[2].z) + LO(v[3].z)); f[5] = (HI(v[0].z) + HI(v[1].z)) + (HI(v[2].z) + HI(v[3].z));
                    f[6] = (LO(v[0].w) + LO(v[1].w)) + (LO(v[2].w) + LO(v[3].w)); f[7] = (HI(v[0].w) + HI(v[1].w)) + (HI(v[2].w) + HI(v[3].w));
                    const bool b4 = t & 16, b3 = t & 8;
                    float g4[4], g2[2];
#pragma unroll
                    for (int i = 0; i < 4; i++) g4[i] = (b4 ? f[4 + i] : f[i]) + __shfl_xor_sync(0xffffffffu, b4 ? f[i] : f[4 + i], 16);
#pragma unroll
                    for (int i = 0; i < 2; i++) g2[i] = (b3 ? g4[2 + i] : g4[i]) + __shfl_xor_sync(0xffffffffu, b3 ? g4[i] : g4[2 + i], 8);
                    g2[0] += __shfl_xor_sync(0xffffffffu, g2[0], 4);
                    g2[1] += __shfl_xor_sync(0xffffffffu, g2[1], 4);
                    st_strong4(wp, pack_nz(g2[0], g2[1]));
                }
                PROF3(8, n); (void)n;
            }
            t_o += D2_BASE + DQ + D3 + (t >> 5) * D2_STEP;
            OPAQUE(t);
            PROF(12);
            {
                const uint32_t* rp = &g_mem[(s + 1) & 3][((t >> 5) * 256 + (t & 31)) * 4];
                const uint32_t da = sb + R_RING + ((t >> 5) * 256 + (t & 31)) * 16;
                uint4 v[8];
                spin_until(t_o);
                PROF3(2, clk32());
                uint32_t n = poll_set<8>(v, rp, 128, PH3 + (t >> 5) * PHQ);
                PROF(13);
                PROF3(3, clk32()); PROF3(9, n); (void)n;
                mbar_wait(bar + 8 * B_AFREE0 + (t >> 6) * 8, (s + 1) & 1);
                PROF3(4, clk32());
#pragma unroll
                for (int i = 0; i < 8; i++) sts128(da + i * 512, v[i]);
                if (t >= 64) fence_async();
                __syncwarp();
                e_arrive(bar + 8 * B_MEM + (t >> 5) * 8);
                PROF(14);
                PROF3(5, clk32());
            }
            if (role != 0) {
                OPAQUE(t);
                uint32_t* zp = g_part[s & 3] + ((rg0 + (t >> 6) * 64) * 1024 + ((t >> 2) & 7) * 32 + ((t >> 5) & 1) * 16 + (t & 3) * 4);
#pragma unroll
                for (int i = 0; i < 4; i++) st_strong16(zp + i * 256, make_uint4(0u, 0u, 0u, 0u));
                if ((t & 31) < 4) st_strong16(&g_mem[s & 3][(rg0 + (t >> 6) * 64) * 32 + ((t >> 5) & 1) * 16 + (t & 3) * 4], make_uint4(0u, 0u, 0u, 0u));
            }
        }
}

__global__ void __launch_bounds__(384, 1) r_kernel(const __grid_constant__ RMaps tm, const bf16* __restrict__ mem0, const bf16* __restrict__ x, const bf16* __restrict__ gate_w) {
    extern __shared__ __align__(1024) unsigned char smem_raw[];
    const uint32_t sb = smem_u32(smem_raw);
    if ((sb & 0x3FFFFu) != SB0) __trap();
    const int tid = threadIdx.x;
    const int wid = __shfl_sync(0xffffffffu, tid >> 5, 0);
    uint32_t role; asm("mov.u32 %0, %%cluster_ctarank;" : "=r"(role));
    int h; asm("mov.u32 %0, %%clusterid.x;" : "=r"(h));
    const uint32_t bar = sb + R_BAR;
    asm volatile("griddepcontrol.launch_dependents;");
    KT(0, 0);

    if (tid == 0) {
        for (int i = 0; i < 5; i++) mbar_init(bar + 8 * (B_FULL + i), 1);
        for (int i = 0; i < 3; i++) mbar_init(bar + 8 * (B_EMPTY + i), 2);
        for (int i = 0; i < 4; i++) mbar_init(bar + 8 * (B_MEM + i), 1);
        mbar_init(bar + 8 * B_HOP1, role == 2 ? 1 : 9);
        mbar_init(bar + 8 * B_HOPV, role == 2 ? 8 : 1);
        mbar_init(bar + 8 * B_XT, 1);
        mbar_init(bar + 8 * B_TFREE, 6);
        mbar_init(bar + 8 * B_P, 4);
        mbar_init(bar + 8 * B_XDONE, 8);
        mbar_init(bar + 8 * B_OST0, 4);
        mbar_init(bar + 8 * B_OST1, 4);
        mbar_init(bar + 8 * B_XRECV, 2);
        mbar_init(bar + 8 * B_O, 4);
        mbar_init(bar + 8 * B_AFREE0, 2);
        mbar_init(bar + 8 * B_AFREE1, 2);
        mbar_init(bar + 8 * B_PRO0, 1);
        mbar_init(bar + 8 * B_PRO1, 8);
        asm volatile("fence.mbarrier_init.release.cluster;" ::: "memory");
        fence_async();
        mbar_expect(bar + 8 * B_PRO0, KR * 4096);
        for (int i = 0; i < 3; i++) mbar_expect(bar + 8 * (B_FULL + i), 8192);
        mbar_expect(bar + 8 * B_HOP1, role == 2 ? 4096 : 2048);
        if (role != 2) mbar_expect(bar + 8 * B_HOPV, 2048);
        mbar_expect(bar + 8 * B_XT, role == 0 ? 16384 : 8192);
    }
    __syncthreads();
    asm volatile("barrier.cluster.arrive.relaxed.aligned;" ::: "memory");
    {
        const CUtensorMap* tw = &tm.w[role];
        if (wid < 11) {
            e_tma_load(sb + wid * 16384, tw, h * DH, KC(wid), bar + 8 * B_PRO0);
            e_tma_load(sb + wid * 16384 + 8192, tw, h * DH + 64, KC(wid), bar + 8 * B_PRO0);
        }
        if (wid < 6) e_tma_load(sb + R_RING + wid * 4096, &tm.x, XC(wid), 0, bar + 8 * (B_FULL + (wid >> 1)));
        if ((tid & 31) == 0) {
            if (wid < 10) tma_prefetch(tw, h * DH + (wid & 1) * 64, KC(KR / 4 + (wid >> 1)));
            if (wid >= 6 && wid - 6 < (role == 0 ? 4 : 6)) tma_prefetch(&tm.wo, wo_tile(role, wid - 6) * 64, h * DH);
            if (blockIdx.x < NSEG && wid < 8) { tma_prefetch(&tm.x, wid * 128, blockIdx.x * SEG); tma_prefetch(&tm.x, wid * 128 + 64, blockIdx.x * SEG); }
        }
        __syncwarp();
    }
    asm volatile("barrier.cluster.wait.aligned;" ::: "memory");

    if (wid < 8) {
        asm volatile("setmaxnreg.inc.sync.aligned.u32 224;");
        if (role == 0) r_big<0>(tm, wid); else if (role == 1) r_big<1>(tm, wid); else r_big<2>(tm, wid);
    } else {
        asm volatile("setmaxnreg.dec.sync.aligned.u32 56;");
        if (role == 0) r_chain<0>(tm, mem0, x, gate_w, wid); else if (role == 1) r_chain<1>(tm, mem0, x, gate_w, wid); else r_chain<2>(tm, mem0, x, gate_w, wid);
    }
    __syncwarp();
    asm volatile("barrier.cluster.arrive; barrier.cluster.wait;" ::: "memory");
    KT(0, 1);
}

constexpr int G_ST = 4;
constexpr int G_STAGE = 16384 + 32768;
constexpr int G_EPI = G_ST * G_STAGE;
constexpr int G_GATE = G_EPI + 32768;
constexpr int G_BAR = G_GATE + 1024;
constexpr int G_SMEM = G_BAR + 128 + 1024;

struct G1Maps { CUtensorMap x, wg, wu, hs, o, h, wo, wd, out; };
constexpr int G1_NB = FF / 128;
constexpr int G1_TILES = 16 * G1_NB;

DEVINL void g_mma_block(float* d, uint32_t sb, uint32_t bar, int it, int wg, int tid, bool first) {
    const int st = it % G_ST;
    mbar_wait(bar + 8 * st, (it / G_ST) & 1);
    const uint64_t da = mkdesc(sb + st * G_STAGE + wg * 8192, 16, 1024, 1);
    const uint64_t db = mkdesc(sb + st * G_STAGE + 16384, 8192, 1024, 1);
    wg_fence();
#pragma unroll
    for (int k = 0; k < 4; k++) wg_ss256(d, da + (uint64_t)(k * 2), db + (uint64_t)(k * 128), (first ? 0 : 1) | k);
    wg_commit();
    if (!first) { wg_wait<1>(); if ((tid & 127) == 0) mbar_arrive(bar + 8 * (G_ST + (it - 1) % G_ST)); }
}
DEVINL void g_load_block(uint32_t sb, uint32_t bar, int it, const CUtensorMap* ta, int k0, int m0, const CUtensorMap* tb, int n0) {
    const int st = it % G_ST;
    mbar_wait(bar + 8 * (G_ST + st), ((it / G_ST) & 1) ^ 1);
    const uint32_t fb = bar + 8 * st, sa = sb + st * G_STAGE;
    mbar_expect(fb, G_STAGE);
    tma_load(sa, ta, k0, m0, fb);
#pragma unroll
    for (int q = 0; q < 4; q++) tma_load(sa + 16384 + q * 8192, tb, n0 + q * 64, k0, fb);
}

__global__ void __launch_bounds__(384, 1) g1_kernel(const __grid_constant__ G1Maps tm) {
    extern __shared__ __align__(1024) unsigned char smem_raw[];
    const uint32_t sb = (smem_u32(smem_raw) + 1023) & ~1023u;
    const int tid = threadIdx.x, lane = tid & 31;
    const int wg = __shfl_sync(0xffffffffu, tid >> 7, 0);
    const int warp = __shfl_sync(0xffffffffu, (tid >> 5) & 3, 0);
    const uint32_t bar = sb + G_BAR;
    const int t_begin = (blockIdx.x * G1_TILES) / gridDim.x;
    const int t_end = ((blockIdx.x + 1) * G1_TILES) / gridDim.x;
    const int mb0 = t_begin / G1_NB;
    KT(1, 0);
    if (tid == 0) {
        for (int i = 0; i < G_ST; i++) { mbar_init(bar + 8 * i, 1); mbar_init(bar + 8 * (G_ST + i), 2); }
        fence_async();
    }
    __syncthreads();
    if (wg == 2) {
        asm volatile("setmaxnreg.dec.sync.aligned.u32 56;");
        if (warp == 0) {
            if (lane == 0) {
                int it = 0;
                for (int tile = t_begin; tile < t_end; tile++) {
                    const int mb = tile / G1_NB, nb = tile % G1_NB;
                    for (int kb = 0; kb < 16; kb++, it++) {
                        const int st = it % G_ST;
                        mbar_wait(bar + 8 * (G_ST + st), ((it / G_ST) & 1) ^ 1);
                        const uint32_t fb = bar + 8 * st, sa = sb + st * G_STAGE;
                        mbar_expect(fb, G_STAGE);
                        tma_load(sa, &tm.x, kb * 64, mb * 128, fb);
                        tma_load(sa + 16384, &tm.wg, nb * 128, kb * 64, fb);
                        tma_load(sa + 16384 + 8192, &tm.wg, nb * 128 + 64, kb * 64, fb);
                        tma_load(sa + 16384 + 16384, &tm.wu, nb * 128, kb * 64, fb);
                        tma_load(sa + 16384 + 24576, &tm.wu, nb * 128 + 64, kb * 64, fb);
                    }
                }
                for (int pass = 0; pass < 2; pass++) {
                    for (int i = blockIdx.x; i < (pass ? NFULL : NLATE); i += gridDim.x) {
                        const int tile = pass ? i : NFULL + i, mb = tile >> 2, nb = tile & 3;
                        wait_count(&g_hcnt[mb], 2 * G1_NB);
                        asm volatile("fence.proxy.async;" ::: "memory");
                        for (int kb = 0; kb < FF / 64; kb++, it++) g_load_block(sb, bar, it, &tm.h, kb * 64, mb * 128, &tm.wd, nb * 256);
                        if (pass) {
                            wait_count(&g_ocnt[mb], NH * 4 * 2);
                            asm volatile("fence.proxy.async;" ::: "memory");
                            for (int kb = 0; kb < HD / 64; kb++, it++) g_load_block(sb, bar, it, &tm.o, kb * 64, mb * 128, &tm.wo, nb * 256);
                        }
                    }
                }
            }
        }
    } else {
        asm volatile("setmaxnreg.inc.sync.aligned.u32 224;");
        float d[128];
        int it = 0;
        float s0 = 0.f, s1 = 0.f;
        const uint32_t epi = sb + G_EPI + wg * 16384;
        const int row = warp * 16 + ((lane >> 3) & 1) * 8 + (lane & 7);
        for (int tile = t_begin; tile < t_end; tile++) {
            const int mb = tile / G1_NB, nb = tile % G1_NB;
            for (int kb = 0; kb < 16; kb++, it++) g_mma_block(d, sb, bar, it, wg, tid, kb == 0);
            if (tile == t_begin || nb == 0) {
                const uint32_t* gp = &g_gate[mb * 128 + wg * 64 + warp * 16 + (lane >> 2)];
                uint32_t u0, u1, n = 0;
                do { u0 = ld_strong4(gp); u1 = ld_strong4(gp + 8); if (++n > 20000000u) __trap(); } while (u0 == 0u || u1 == 0u);
                s0 = 1.0f - __uint_as_float(u0); s1 = 1.0f - __uint_as_float(u1);
                __syncwarp();
            }
            wg_wait<0>();
            if ((tid & 127) == 0) { mbar_arrive(bar + 8 * (G_ST + (it - 1) % G_ST)); bulk_wait_read(); }
            bar_sync(1 + wg, 128);
#pragma unroll
            for (int j = 0; j < 16; j += 2) {
                uint32_t p[4];
#pragma unroll
                for (int q = 0; q < 4; q++) {
                    const int i = (j + (q >> 1)) * 4 + (q & 1) * 2;
                    const float sc = (q & 1) ? s1 : s0;
                    const float g0 = d[i], g1 = d[i + 1];
                    const float h0 = __fdividef(g0, 1.0f + __expf(-g0)) * d[64 + i] * sc;
                    const float h1 = __fdividef(g1, 1.0f + __expf(-g1)) * d[64 + i + 1] * sc;
                    p[q] = pack_bf16(h0, h1);
                }
                const int cgp = j + (lane >> 4);
                stsm4(epi + (cgp >> 3) * 8192 + row * 128 + (((cgp & 7) ^ (row & 7)) << 4), p[0], p[1], p[2], p[3]);
            }
            fence_async();
            bar_sync(1 + wg, 128);
            if ((tid & 127) == 0) {
                tma_store(&tm.hs, epi, nb * 128, mb * 128 + wg * 64);
                tma_store(&tm.hs, epi + 8192, nb * 128 + 64, mb * 128 + wg * 64);
                bulk_commit();
            }
        }
        if ((tid & 127) == 0) {
            bulk_wait_all();
            __threadfence();
            const int n0 = min(t_end, (mb0 + 1) * G1_NB) - t_begin;
            atomicAdd(&g_hcnt[mb0], (uint32_t)n0);
            if (t_end - t_begin > n0) atomicAdd(&g_hcnt[mb0 + 1], (uint32_t)(t_end - t_begin - n0));
        }
        for (int pass = 0; pass < 2; pass++) {
            for (int i = blockIdx.x; i < (pass ? NFULL : NLATE); i += gridDim.x) {
                const int nkb = pass ? (FF + HD) / 64 : FF / 64;
                for (int kb = 0; kb < nkb; kb++, it++) g_mma_block(d, sb, bar, it, wg, tid, kb == 0);
                wg_wait<0>();
                if ((tid & 127) == 0) mbar_arrive(bar + 8 * (G_ST + (it - 1) % G_ST));
                if (pass == 0) {
                    float4* pre = g_pre + i * (32 * 256) + tid;
#pragma unroll
                    for (int q = 0; q < 32; q++) __stcg(pre + q * 256, make_float4(d[4 * q], d[4 * q + 1], d[4 * q + 2], d[4 * q + 3]));
                } else {
                    const int mb = i >> 2, nb = i & 3;
#pragma unroll
                    for (int half = 0; half < 2; half++) {
                        if ((tid & 127) == 0) bulk_wait_read();
                        bar_sync(1 + wg, 128);
#pragma unroll
                        for (int j = 0; j < 16; j += 2) {
                            const float* e = d + half * 64 + 4 * j;
                            const int cgp = j + (lane >> 4);
                            stsm4(epi + (cgp >> 3) * 8192 + row * 128 + (((cgp & 7) ^ (row & 7)) << 4),
                                  pack_bf16(e[0], e[1]), pack_bf16(e[2], e[3]), pack_bf16(e[4], e[5]), pack_bf16(e[6], e[7]));
                        }
                        fence_async();
                        bar_sync(1 + wg, 128);
                        if ((tid & 127) == 0) {
                            tma_store(&tm.out, epi, nb * 256 + half * 128, mb * 128 + wg * 64);
                            tma_store(&tm.out, epi + 8192, nb * 256 + half * 128 + 64, mb * 128 + wg * 64);
                            bulk_commit();
                        }
                    }
                }
            }
        }
        if ((tid & 127) == 0) bulk_wait_all();
        KT(1, 1);
    }
    __syncwarp();
    asm volatile("griddepcontrol.wait;" ::: "memory");
}

struct G2Maps { CUtensorMap o, wo, out; };

__global__ void __launch_bounds__(384, 1) g2_kernel(const __grid_constant__ G2Maps tm) {
    extern __shared__ __align__(1024) unsigned char smem_raw[];
    const uint32_t sb = (smem_u32(smem_raw) + 1023) & ~1023u;
    const int tid = threadIdx.x, lane = tid & 31;
    const int wg = __shfl_sync(0xffffffffu, tid >> 7, 0);
    const int warp = __shfl_sync(0xffffffffu, (tid >> 5) & 3, 0);
    const uint32_t bar = sb + G_BAR;
    const int ks = blockIdx.x & 3, lt = blockIdx.x >> 2, nb = (NFULL + lt) & 3, mb = (NFULL + lt) >> 2;
    KT(2, 0);
    if (tid == 0) {
        for (int i = 0; i < G_ST; i++) { mbar_init(bar + 8 * i, 1); mbar_init(bar + 8 * (G_ST + i), 2); }
        fence_async();
    }
    __syncthreads();
    if (wg == 2) {
        asm volatile("setmaxnreg.dec.sync.aligned.u32 40;");
        if (warp == 0 && lane == 0) {
            for (int it = 0; it < 16; it++) g_load_block(sb, bar, it, &tm.o, (ks * 16 + it) * 64, mb * 128, &tm.wo, nb * 256);
        } else if (warp == 1) {
            if (blockIdx.x < SEQ / 32) g_gate[blockIdx.x * 32 + lane] = 0u;
            if (blockIdx.x == 0 && lane < 16) { g_hcnt[lane] = 0u; g_ocnt[lane] = 0u; }
        }
    } else {
        asm volatile("setmaxnreg.inc.sync.aligned.u32 232;");
        float d[128];
        float4 r[8];
        const float4* pre = g_pre + (lt * 32 + ks * 8) * 256 + tid;
#pragma unroll
        for (int q = 0; q < 8; q++) r[q] = __ldcg(pre + q * 256);
        for (int it = 0; it < 16; it++) g_mma_block(d, sb, bar, it, wg, tid, it == 0);
        wg_wait<0>();
        float4* mine = g_sk + blockIdx.x * (32 * 256) + tid;
#pragma unroll
        for (int c = 0; c < 4; c++) {
            if (c != ks) {
#pragma unroll
                for (int q = c * 8; q < c * 8 + 8; q++) __stcg(mine + q * 256, make_float4(d[4 * q], d[4 * q + 1], d[4 * q + 2], d[4 * q + 3]));
            } else {
#pragma unroll
                for (int q = 0; q < 8; q++) { r[q].x += d[c * 32 + 4 * q]; r[q].y += d[c * 32 + 4 * q + 1]; r[q].z += d[c * 32 + 4 * q + 2]; r[q].w += d[c * 32 + 4 * q + 3]; }
            }
        }
        __threadfence();
        bar_sync(1, 256);
        if (tid == 0) {
            atomicAdd(&g_skcnt[lt], 1u);
            uint32_t v, n = 0;
            do {
                asm volatile("ld.acquire.gpu.global.u32 %0, [%1];" : "=r"(v) : "l"(&g_skcnt[lt]) : "memory");
                if (++n > 200000000u) __trap();
            } while (v < 4u);
            if (atomicAdd(&g_skdone[lt], 1u) == 3u) { g_skcnt[lt] = 0u; g_skdone[lt] = 0u; }
        }
        bar_sync(1, 256);
#pragma unroll
        for (int c = 1; c < 4; c++) {
            const float4* th = g_sk + ((lt * 4 + ((ks + c) & 3)) * 32 + ks * 8) * 256 + tid;
#pragma unroll
            for (int q = 0; q < 8; q++) { const float4 u = __ldcg(th + q * 256); r[q].x += u.x; r[q].y += u.y; r[q].z += u.z; r[q].w += u.w; }
        }
        const uint32_t epi = sb + G_EPI + wg * 16384;
        const int row = warp * 16 + ((lane >> 3) & 1) * 8 + (lane & 7);
#pragma unroll
        for (int j = 0; j < 8; j += 2) {
            const int cgp = j + (lane >> 4);
            stsm4(epi + row * 128 + ((cgp ^ (row & 7)) << 4), pack_bf16(r[j].x, r[j].y), pack_bf16(r[j].z, r[j].w),
                  pack_bf16(r[j + 1].x, r[j + 1].y), pack_bf16(r[j + 1].z, r[j + 1].w));
        }
        fence_async();
        bar_sync(2 + wg, 128);
        if ((tid & 127) == 0) {
            tma_store(&tm.out, epi, nb * 256 + ks * 64, mb * 128 + wg * 64);
            bulk_commit();
            bulk_wait_all();
        }
        KT(2, 1);
    }
}

typedef CUresult (*EncodeFn)(CUtensorMap*, CUtensorMapDataType, cuuint32_t, void*, const cuuint64_t*, const cuuint64_t*, const cuuint32_t*,
                             const cuuint32_t*, CUtensorMapInterleave, CUtensorMapSwizzle, CUtensorMapL2promotion, CUtensorMapFloatOOBfill);

static void make_map(EncodeFn enc, CUtensorMap* m, const void* ptr, uint64_t rows, uint64_t cols, uint32_t box_rows) {
    cuuint64_t dims[2] = {cols, rows};
    cuuint64_t strides[1] = {cols * 2};
    cuuint32_t box[2] = {64, box_rows};
    cuuint32_t es[2] = {1, 1};
    enc(m, CU_TENSOR_MAP_DATA_TYPE_BFLOAT16, 2, (void*)ptr, dims, strides, box, es, CU_TENSOR_MAP_INTERLEAVE_NONE,
        CU_TENSOR_MAP_SWIZZLE_128B, CU_TENSOR_MAP_L2_PROMOTION_L2_256B, CU_TENSOR_MAP_FLOAT_OOB_FILL_NONE);
}

extern "C" void kernel_launch(void* const* d_in, const int* in_sizes, int n_in, void* d_out, int out_size) {
    (void)in_sizes; (void)n_in; (void)out_size;
    const bf16* x = (const bf16*)d_in[0];
    const bf16* mem0 = (const bf16*)d_in[1];
    const bf16* gate_w = (const bf16*)d_in[11];
    static EncodeFn enc = nullptr;
    static int n_sm = 0;
    static void *pO = nullptr, *pH = nullptr;
    if (!enc) {
        void* fn = nullptr;
        cudaDriverEntryPointQueryResult qr;
        cudaGetDriverEntryPoint("cuTensorMapEncodeTiled", &fn, cudaEnableDefault, &qr);
        enc = (EncodeFn)fn;
        cudaDeviceGetAttribute(&n_sm, cudaDevAttrMultiProcessorCount, 0);
        cudaFuncSetAttribute(r_kernel, cudaFuncAttributeMaxDynamicSharedMemorySize, R_SMEM);
        cudaFuncSetAttribute(g1_kernel, cudaFuncAttributeMaxDynamicSharedMemorySize, G_SMEM);
        cudaFuncSetAttribute(g2_kernel, cudaFuncAttributeMaxDynamicSharedMemorySize, G_SMEM);
        cudaGetSymbolAddress(&pO, g_O);
        cudaGetSymbolAddress(&pH, g_H);
    }
    RMaps rm; G1Maps m1; G2Maps m2;
    make_map(enc, &rm.x, x, SEQ, DM, 32);
    for (int i = 0; i < 3; i++) make_map(enc, &rm.w[i], d_in[2 + i], DM, HD, 64);
    make_map(enc, &rm.wo, d_in[5], HD, DM, 128);
    make_map(enc, &rm.o, pO, SEQ, HD, 16);
    make_map(enc, &m1.x, x, SEQ, DM, 128);
    make_map(enc, &m1.wg, d_in[8], DM, FF, 64);
    make_map(enc, &m1.wu, d_in[9], DM, FF, 64);
    make_map(enc, &m1.hs, pH, SEQ, FF, 64);
    make_map(enc, &m1.o, pO, SEQ, HD, 128);
    make_map(enc, &m1.h, pH, SEQ, FF, 128);
    make_map(enc, &m1.wo, d_in[5], HD, DM, 64);
    make_map(enc, &m1.wd, d_in[10], FF, DM, 64);
    make_map(enc, &m1.out, d_out, SEQ, DM, 64);
    m2.o = m1.o; m2.wo = m1.wo; m2.out = m1.out;

    cudaStream_t st = cudaStreamPerThread;
    {
        cudaLaunchConfig_t cfg = {};
        cfg.gridDim = dim3(96); cfg.blockDim = dim3(384); cfg.dynamicSmemBytes = R_SMEM; cfg.stream = st;
        cudaLaunchAttribute at[1];
        at[0].id = cudaLaunchAttributeClusterDimension; at[0].val.clusterDim.x = 3; at[0].val.clusterDim.y = 1; at[0].val.clusterDim.z = 1;
        cfg.attrs = at; cfg.numAttrs = 1;
        cudaLaunchKernelEx(&cfg, r_kernel, rm, mem0, x, gate_w);
    }
    {
        cudaLaunchConfig_t cfg = {};
        cfg.gridDim = dim3(n_sm - 96); cfg.blockDim = dim3(384); cfg.dynamicSmemBytes = G_SMEM; cfg.stream = st;
        cudaLaunchAttribute at[1];
        at[0].id = cudaLaunchAttributeProgrammaticStreamSerialization; at[0].val.programmaticStreamSerializationAllowed = 1;
        cfg.attrs = at; cfg.numAttrs = 1;
        cudaLaunchKernelEx(&cfg, g1_kernel, m1);
    }
    g2_kernel<<<NLATE * 4, 384, G_SMEM, st>>>(m2);
}
```

```cpp
#include <cuda_runtime.h>
#include <cuda_bf16.h>
#include <cuda.h>
#include <stdint.h>

typedef __nv_bfloat16 bf16;

constexpr int SEQ = 2048, DM = 1024, NH = 32, DH = 128, NMEM = 8, SEG = 32, NSEG = 64, FF = 3584;
constexpr int HD = NH * DH;

__device__ bf16 g_O[SEQ * HD];
__device__ bf16 g_H[SEQ * FF];
__device__ uint32_t g_gate[SEQ];
__device__ uint32_t g_part[4][128 * 32 * 32];
__device__ uint32_t g_mem[4][DM * 4];
constexpr int NFULL = 36;
constexpr int NLATE = 64 - NFULL;
__device__ float4 g_pre[NLATE * 32 * 256];
__device__ float4 g_sk[NLATE * 4 * 32 * 256];
__device__ uint32_t g_skcnt[NLATE], g_skdone[NLATE];
__device__ uint32_t g_hcnt[16], g_ocnt[16];
#define KT(k, i)
#define PT(i)

#define DEVINL __device__ __forceinline__
constexpr long long SPIN_LIMIT = 4000000000LL;

DEVINL uint32_t smem_u32(const void* p) { return (uint32_t)__cvta_generic_to_shared(p); }
DEVINL void mbar_init(uint32_t bar, uint32_t cnt) { asm volatile("mbarrier.init.shared::cta.b64 [%0], %1;" ::"r"(bar), "r"(cnt) : "memory"); }
DEVINL void mbar_arrive(uint32_t bar) { asm volatile("mbarrier.arrive.shared::cta.b64 _, [%0];" ::"r"(bar) : "memory"); }
DEVINL void mbar_expect(uint32_t bar, uint32_t bytes) { asm volatile("mbarrier.arrive.expect_tx.shared::cta.b64 _, [%0], %1;" ::"r"(bar), "r"(bytes) : "memory"); }
DEVINL void mbar_arrive_remote(uint32_t cbar) { asm volatile("mbarrier.arrive.relaxed.cluster.shared::cluster.b64 _, [%0];" ::"r"(cbar) : "memory"); }
DEVINL bool mbar_try(uint32_t bar, uint32_t par) {
    uint32_t ok;
    asm volatile("{ .reg .pred p; mbarrier.try_wait.parity.shared::cta.b64 p, [%1], %2; selp.u32 %0, 1, 0, p; }" : "=r"(ok) : "r"(bar), "r"(par) : "memory");
    return ok;
}
__device__ __noinline__ void mbar_wait_slow(uint32_t bar, uint32_t par) {
    long long t0 = clock64();
    while (!mbar_try(bar, par)) { if (clock64() - t0 > SPIN_LIMIT) __trap(); }
}
DEVINL void mbar_wait(uint32_t bar, uint32_t par) {
    uint32_t n = 0;
    while (!mbar_try(bar, par)) { if (++n > 200000000u) __trap(); }
}
DEVINL uint32_t mapa(uint32_t a, uint32_t r) { uint32_t o; asm volatile("mapa.shared::cluster.u32 %0, %1, %2;" : "=r"(o) : "r"(a), "r"(r)); return o; }
DEVINL void fence_async() { asm volatile("fence.proxy.async.shared::cta;" ::: "memory"); }
DEVINL void bar_sync(int id, int n) { asm volatile("bar.sync %0, %1;" ::"r"(id), "r"(n) : "memory"); }
DEVINL void cluster_sync() { asm volatile("barrier.cluster.arrive.aligned; barrier.cluster.wait.aligned;" ::: "memory"); }
DEVINL void tma_load(uint32_t dst, const CUtensorMap* tm, int c0, int c1, uint32_t bar) {
    asm volatile("cp.async.bulk.tensor.2d.shared::cluster.global.mbarrier::complete_tx::bytes [%0], [%1, {%3, %4}], [%2];"
                 ::"r"(dst), "l"(tm), "r"(bar), "r"(c0), "r"(c1) : "memory");
}
DEVINL void tma_prefetch(const CUtensorMap* tm, int c0, int c1) {
    asm volatile("cp.async.bulk.prefetch.tensor.2d.L2.global [%0, {%1, %2}];" ::"l"(tm), "r"(c0), "r"(c1) : "memory");
}
DEVINL void tma_store(const CUtensorMap* tm, uint32_t src, int c0, int c1) {
    asm volatile("cp.async.bulk.tensor.2d.global.shared::cta.bulk_group [%0, {%2, %3}], [%1];" ::"l"(tm), "r"(src), "r"(c0), "r"(c1) : "memory");
}
DEVINL void bulk_commit() { asm volatile("cp.async.bulk.commit_group;" ::: "memory"); }
DEVINL void bulk_wait_read() { asm volatile("cp.async.bulk.wait_group.read 0;" ::: "memory"); }
DEVINL void bulk_wait_all() { asm volatile("cp.async.bulk.wait_group 0;" ::: "memory"); }
DEVINL void bulk_s2s(uint32_t cdst, uint32_t src, uint32_t bytes, uint32_t cbar) {
    asm volatile("cp.async.bulk.shared::cluster.shared::cta.mbarrier::complete_tx::bytes [%0], [%1], %2, [%3];" ::"r"(cdst), "r"(src), "r"(bytes), "r"(cbar) : "memory");
}
DEVINL void st_async16(uint32_t cdst, uint4 v, uint32_t cbar) {
    asm volatile("st.async.shared::cluster.mbarrier::complete_tx::bytes.v4.b32 [%0], {%1,%2,%3,%4}, [%5];" ::"r"(cdst), "r"(v.x), "r"(v.y), "r"(v.z), "r"(v.w), "r"(cbar) : "memory");
}
DEVINL uint64_t mkdesc(uint32_t addr, uint32_t lbo, uint32_t sbo, uint32_t swz) {
    return (uint64_t)((addr & 0x3FFFF) >> 4) | ((uint64_t)(lbo >> 4) << 16) | ((uint64_t)(sbo >> 4) << 32) | ((uint64_t)swz << 62);
}
constexpr uint32_t SB0 = 1024;
__host__ __device__ constexpr uint64_t cdesc(uint32_t off, uint32_t lbo, uint32_t sbo, uint32_t swz) {
    return (uint64_t)(((SB0 + off) & 0x3FFFF) >> 4) | ((uint64_t)(lbo >> 4) << 16) | ((uint64_t)(sbo >> 4) << 32) | ((uint64_t)swz << 62);
}
DEVINL float ex2(float x) { float y; asm("ex2.approx.ftz.f32 %0, %1;" : "=f"(y) : "f"(x)); return y; }
DEVINL void spin_clk(int d) { uint32_t t0, t1; asm volatile("mov.u32 %0, %%clock;" : "=r"(t0)); do { asm volatile("mov.u32 %0, %%clock;" : "=r"(t1)); } while ((int)(t1 - t0) < d); }
#define PROBE_GAP 150
#define OPAQUE(x) asm volatile("" : "+r"(x))
DEVINL void wg_fence() { asm volatile("wgmma.fence.sync.aligned;" ::: "memory"); }
DEVINL void wg_commit() { asm volatile("wgmma.commit_group.sync.aligned;" ::: "memory"); }
template <int N> DEVINL void wg_wait() { asm volatile("wgmma.wait_group.sync.aligned %0;" ::"n"(N) : "memory"); }
DEVINL uint32_t pack_bf16(float lo, float hi) { uint32_t r; asm("cvt.rn.bf16x2.f32 %0, %1, %2;" : "=r"(r) : "f"(hi), "f"(lo)); return r; }
DEVINL void ldsm4(uint32_t* r, uint32_t a) { asm volatile("ldmatrix.sync.aligned.m8n8.x4.shared.b16 {%0,%1,%2,%3}, [%4];" : "=r"(r[0]), "=r"(r[1]), "=r"(r[2]), "=r"(r[3]) : "r"(a) : "memory"); }
DEVINL void ldsm4t(uint32_t* r, uint32_t a) { asm volatile("ldmatrix.sync.aligned.m8n8.x4.trans.shared.b16 {%0,%1,%2,%3}, [%4];" : "=r"(r[0]), "=r"(r[1]), "=r"(r[2]), "=r"(r[3]) : "r"(a) : "memory"); }
DEVINL void stsm4(uint32_t a, uint32_t r0, uint32_t r1, uint32_t r2, uint32_t r3) { asm volatile("stmatrix.sync.aligned.m8n8.x4.shared.b16 [%0], {%1,%2,%3,%4};" ::"r"(a), "r"(r0), "r"(r1), "r"(r2), "r"(r3) : "memory"); }
DEVINL void stsm4t(uint32_t a, uint32_t r0, uint32_t r1, uint32_t r2, uint32_t r3) { asm volatile("stmatrix.sync.aligned.m8n8.x4.trans.shared.b16 [%0], {%1,%2,%3,%4};" ::"r"(a), "r"(r0), "r"(r1), "r"(r2), "r"(r3) : "memory"); }
DEVINL void sts32(uint32_t a, uint32_t v) { asm volatile("st.shared.b32 [%0], %1;" ::"r"(a), "r"(v) : "memory"); }
DEVINL void sts128(uint32_t a, uint4 v) { asm volatile("st.shared.v4.b32 [%0], {%1,%2,%3,%4};" ::"r"(a), "r"(v.x), "r"(v.y), "r"(v.z), "r"(v.w) : "memory"); }
DEVINL uint4 lds128(uint32_t a) { uint4 v; asm volatile("ld.shared.v4.b32 {%0,%1,%2,%3}, [%4];" : "=r"(v.x), "=r"(v.y), "=r"(v.z), "=r"(v.w) : "r"(a) : "memory"); return v; }
DEVINL uint4 ld_strong16(const void* p) { uint4 v; asm volatile("ld.relaxed.gpu.global.v4.u32 {%0,%1,%2,%3}, [%4];" : "=r"(v.x), "=r"(v.y), "=r"(v.z), "=r"(v.w) : "l"(p) : "memory"); return v; }
DEVINL void st_strong8(void* p, uint32_t a, uint32_t b) { asm volatile("st.relaxed.gpu.global.v2.u32 [%0], {%1,%2};" ::"l"(p), "r"(a), "r"(b) : "memory"); }
DEVINL void st_strong4(void* p, uint32_t a) { asm volatile("st.relaxed.gpu.global.u32 [%0], %1;" ::"l"(p), "r"(a) : "memory"); }
DEVINL void st_strong16(void* p, uint4 v) { asm volatile("st.relaxed.gpu.global.v4.u32 [%0], {%1,%2,%3,%4};" ::"l"(p), "r"(v.x), "r"(v.y), "r"(v.z), "r"(v.w) : "memory"); }
DEVINL uint32_t pack_nz(float lo, float hi) { uint32_t r = pack_bf16(lo, hi); return r == 0u ? 0x8000u : r; }
DEVINL uint32_t min4(uint4 v, uint32_t m) { return __vimin3_u32(__vimin3_u32(v.x, v.y, m), v.z, v.w); }
DEVINL void mma16816(float* d, uint32_t a0, uint32_t a1, uint32_t a2, uint32_t a3, uint32_t b0, uint32_t b1) {
    asm volatile("mma.sync.aligned.m16n8k16.row.col.f32.bf16.bf16.f32 {%0,%1,%2,%3}, {%4,%5,%6,%7}, {%8,%9}, {%0,%1,%2,%3};"
                 : "+f"(d[0]), "+f"(d[1]), "+f"(d[2]), "+f"(d[3]) : "r"(a0), "r"(a1), "r"(a2), "r"(a3), "r"(b0), "r"(b1));
}
DEVINL void mma1688(float* d, uint32_t a0, uint32_t a1, uint32_t b0) {
    asm volatile("mma.sync.aligned.m16n8k8.row.col.f32.bf16.bf16.f32 {%0,%1,%2,%3}, {%4,%5}, {%6}, {%0,%1,%2,%3};"
                 : "+f"(d[0]), "+f"(d[1]), "+f"(d[2]), "+f"(d[3]) : "r"(a0), "r"(a1), "r"(b0));
}
template <int TA, int TB> DEVINL void wg_ss8(float* d, uint64_t da, uint64_t db, int sc) {
    asm volatile("{ .reg .pred p; setp.ne.b32 p, %6, 0; wgmma.mma_async.sync.aligned.m64n8k16.f32.bf16.bf16 {%0,%1,%2,%3}, %4, %5, p, 1, 1, %7, %8; }"
                 : "+f"(d[0]), "+f"(d[1]), "+f"(d[2]), "+f"(d[3]) : "l"(da), "l"(db), "r"(sc), "n"(TA), "n"(TB));
}
template <int TB> DEVINL void wg_rs8(float* d, const uint32_t* a, uint64_t db, int sc) {
    asm volatile("{ .reg .pred p; setp.ne.b32 p, %9, 0; wgmma.mma_async.sync.aligned.m64n8k16.f32.bf16.bf16 {%0,%1,%2,%3}, {%4,%5,%6,%7}, %8, p, 1, 1, %10; }"
                 : "+f"(d[0]), "+f"(d[1]), "+f"(d[2]), "+f"(d[3]) : "r"(a[0]), "r"(a[1]), "r"(a[2]), "r"(a[3]), "l"(db), "r"(sc), "n"(TB));
}
#define ACC16(d) "+f"(d[0]), "+f"(d[1]), "+f"(d[2]), "+f"(d[3]), "+f"(d[4]), "+f"(d[5]), "+f"(d[6]), "+f"(d[7]), "+f"(d[8]), "+f"(d[9]), "+f"(d[10]), "+f"(d[11]), "+f"(d[12]), "+f"(d[13]), "+f"(d[14]), "+f"(d[15])
template <int TA> DEVINL void wg_ss32(float* d, uint64_t da, uint64_t db, int sc) {
    asm volatile("{ .reg .pred p; setp.ne.b32 p, %18, 0; wgmma.mma_async.sync.aligned.m64n32k16.f32.bf16.bf16 {%0,%1,%2,%3,%4,%5,%6,%7,%8,%9,%10,%11,%12,%13,%14,%15}, %16, %17, p, 1, 1, %19, 0; }"
                 : ACC16(d) : "l"(da), "l"(db), "r"(sc), "n"(TA));
}
DEVINL void wg_rs32(float* d, const uint32_t* a, uint64_t db, int sc) {
    asm volatile("{ .reg .pred p; setp.ne.b32 p, %21, 0; wgmma.mma_async.sync.aligned.m64n32k16.f32.bf16.bf16 {%0,%1,%2,%3,%4,%5,%6,%7,%8,%9,%10,%11,%12,%13,%14,%15}, {%16,%17,%18,%19}, %20, p, 1, 1, 0; }"
                 : ACC16(d) : "r"(a[0]), "r"(a[1]), "r"(a[2]), "r"(a[3]), "l"(db), "r"(sc));
}
DEVINL void wg_ss40(float* d, uint64_t da, uint64_t db, int sc) {
    asm volatile("{ .reg .pred p; setp.ne.b32 p, %22, 0; wgmma.mma_async.sync.aligned.m64n40k16.f32.bf16.bf16 {%0,%1,%2,%3,%4,%5,%6,%7,%8,%9,%10,%11,%12,%13,%14,%15,%16,%17,%18,%19}, %20, %21, p, 1, 1, 1, 1; }"
                 : ACC16(d), "+f"(d[16]), "+f"(d[17]), "+f"(d[18]), "+f"(d[19]) : "l"(da), "l"(db), "r"(sc));
}
#define A8(d, o) "+f"(d[o]), "+f"(d[o + 1]), "+f"(d[o + 2]), "+f"(d[o + 3]), "+f"(d[o + 4]), "+f"(d[o + 5]), "+f"(d[o + 6]), "+f"(d[o + 7])
#define A32(d, o) A8(d, o), A8(d, o + 8), A8(d, o + 16), A8(d, o + 24)
DEVINL void wg_ss256(float* d, uint64_t da, uint64_t db, int sc) {
    asm volatile(
        "{ .reg .pred p; setp.ne.b32 p, %130, 0;\n"
        "wgmma.mma_async.sync.aligned.m64n256k16.f32.bf16.bf16 {"
        "%0,%1,%2,%3,%4,%5,%6,%7,%8,%9,%10,%11,%12,%13,%14,%15,%16,%17,%18,%19,%20,%21,%22,%23,%24,%25,%26,%27,%28,%29,%30,%31,"
        "%32,%33,%34,%35,%36,%37,%38,%39,%40,%41,%42,%43,%44,%45,%46,%47,%48,%49,%50,%51,%52,%53,%54,%55,%56,%57,%58,%59,%60,%61,%62,%63,"
        "%64,%65,%66,%67,%68,%69,%70,%71,%72,%73,%74,%75,%76,%77,%78,%79,%80,%81,%82,%83,%84,%85,%86,%87,%88,%89,%90,%91,%92,%93,%94,%95,"
        "%96,%97,%98,%99,%100,%101,%102,%103,%104,%105,%106,%107,%108,%109,%110,%111,%112,%113,%114,%115,%116,%117,%118,%119,%120,%121,%122,%123,%124,%125,%126,%127"
        "}, %128, %129, p, 1, 1, 0, 1; }"
        : A32(d, 0), A32(d, 32), A32(d, 64), A32(d, 96) : "l"(da), "l"(db), "r"(sc));
}

DEVINL float gate_row(const bf16* __restrict__ xr, const bf16* __restrict__ gate_w, int lane) {
    float acc = 0.f;
#pragma unroll
    for (int i = 0; i < 4; i++) {
        const uint4 xv = __ldg((const uint4*)xr + i * 32 + lane), gv = __ldg((const uint4*)gate_w + i * 32 + lane);
        const uint32_t xa[4] = {xv.x, xv.y, xv.z, xv.w}, ga[4] = {gv.x, gv.y, gv.z, gv.w};
#pragma unroll
        for (int e = 0; e < 4; e++) {
            acc = fmaf(__uint_as_float(xa[e] << 16), __uint_as_float(ga[e] << 16), acc);
            acc = fmaf(__uint_as_float(xa[e] & 0xffff0000u), __uint_as_float(ga[e] & 0xffff0000u), acc);
        }
    }
#pragma unroll
    for (int o = 16; o > 0; o >>= 1) acc += __shfl_xor_sync(0xffffffffu, acc, o);
    return 1.0f / (1.0f + __expf(-acc));
}
DEVINL uint32_t ld_strong4(const void* p) { uint32_t v; asm volatile("ld.relaxed.gpu.global.u32 %0, [%1];" : "=r"(v) : "l"(p) : "memory"); return v; }
DEVINL void wait_count(const uint32_t* p, uint32_t want) {
    uint32_t v, n = 0;
    while (true) {
        asm volatile("ld.acquire.gpu.global.u32 %0, [%1];" : "=r"(v) : "l"(p) : "memory");
        if (v >= want) break;
        __nanosleep(200);
        if (++n > 10000000u) __trap();
    }
}

constexpr int KR = 44;
constexpr int KS = 64 - KR;
constexpr int R_W = 0;
constexpr int R_WO = KS * 4096;
constexpr int R_QX = R_WO + 65536;
constexpr int R_RING = R_WO + 98304;
constexpr int R_K = R_RING + 24576;
constexpr int R_V = R_K + 10240;
constexpr int R_QM = R_V + 10240;
constexpr int R_O = R_QM + 2048;
constexpr int R_BAR = R_O + 2048;
constexpr int R_G = R_BAR + 256 + 512 + 256 + 128;
constexpr int R_Z = R_G + 256;
constexpr int R_SMEM = R_Z + 1024;
enum { B_FULL = 0, B_EMPTY = 5, B_MEM = 8, B_HOP1 = 12, B_XT, B_TFREE, B_O, B_AFREE0, B_AFREE1, B_PRO0, B_PRO1, B_XRECV, B_P, B_XDONE, B_OST0, B_OST1, B_HOPV };
#define D2_BASE 800
#define D2_STEP 250
#define PD2 6
#define CPB 8192
#define DDUP 0
#define WGAP 0
#define DQ 1700
#define D3 0

DEVINL uint32_t clk32() { uint32_t c_; asm volatile("mov.u32 %0, %%clock;" : "=r"(c_)); return c_; }
DEVINL void spin_until(uint32_t t) { while ((uint32_t)(t - clk32() - 1u) < 100000u) {} }
#define PROF(i)
#define PROF2(i)
#define PROF3(i, val)
DEVINL void e_arrive(uint32_t bar) { asm volatile("{ .reg .pred p; elect.sync _|p, 0xffffffff; @p mbarrier.arrive.shared::cta.b64 _, [%0]; }" ::"r"(bar) : "memory"); }
DEVINL void e_arrive_remote(uint32_t cbar) { asm volatile("{ .reg .pred p; elect.sync _|p, 0xffffffff; @p mbarrier.arrive.relaxed.cluster.shared::cluster.b64 _, [%0]; }" ::"r"(cbar) : "memory"); }
DEVINL void e_count(uint32_t* p) { asm volatile("{ .reg .pred p; elect.sync _|p, 0xffffffff; @p red.relaxed.gpu.global.add.u32 [%0], 1; }" ::"l"(p) : "memory"); }
DEVINL void e_expect(uint32_t bar, uint32_t bytes) { asm volatile("{ .reg .pred p; elect.sync _|p, 0xffffffff; @p mbarrier.arrive.expect_tx.shared::cta.b64 _, [%0], %1; }" ::"r"(bar), "r"(bytes) : "memory"); }
DEVINL void e_tma_load(uint32_t dst, const CUtensorMap* tm, int c0, int c1, uint32_t bar) {
    asm volatile("{ .reg .pred p; elect.sync _|p, 0xffffffff; @p cp.async.bulk.tensor.2d.shared::cluster.global.mbarrier::complete_tx::bytes [%0], [%1, {%3, %4}], [%2]; }"
                 ::"r"(dst), "l"(tm), "r"(bar), "r"(c0), "r"(c1) : "memory");
}
DEVINL void e_tma_store(const CUtensorMap* tm, uint32_t src, int c0, int c1) {
    asm volatile("{ .reg .pred p; elect.sync _|p, 0xffffffff; @p cp.async.bulk.tensor.2d.global.shared::cta.bulk_group [%0, {%2, %3}], [%1]; }" ::"l"(tm), "r"(src), "r"(c0), "r"(c1) : "memory");
}
DEVINL void e_bulk_s2g(void* dst, uint32_t src, uint32_t bytes) {
    asm volatile("{ .reg .pred p; elect.sync _|p, 0xffffffff; @p cp.async.bulk.global.shared::cta.bulk_group [%0], [%1], %2; }" ::"l"(dst), "r"(src), "r"(bytes) : "memory");
}
DEVINL void e_bulk_s2s(uint32_t cdst, uint32_t src, uint32_t bytes, uint32_t cbar) {
    asm volatile("{ .reg .pred p; elect.sync _|p, 0xffffffff; @p cp.async.bulk.shared::cluster.shared::cta.mbarrier::complete_tx::bytes [%0], [%1], %2, [%3]; }" ::"r"(cdst), "r"(src), "r"(bytes), "r"(cbar) : "memory");
}

#define SLOT 0
#define PH3 0
#define PHQ 0
DEVINL void wait_slot(uint32_t phase) {
    if (SLOT) {
        uint32_t c; asm volatile("mov.u32 %0, %%globaltimer_lo;" : "=r"(c));
        const uint32_t tgt = c + (SLOT ? SLOT : 1) - ((c - phase) % (SLOT ? SLOT : 1));
        do { asm volatile("mov.u32 %0, %%globaltimer_lo;" : "=r"(c)); } while ((uint32_t)(tgt - c - 1u) < 100000u);
    }
}
template <int N> DEVINL uint32_t poll_set(uint4 (&v)[N], const uint32_t* rp, int stride, uint32_t phase, uint32_t wbar = 0, uint32_t wpar = 0) {
    wait_slot(phase);
#pragma unroll
    for (int i = 0; i < N; i++) v[i] = ld_strong16(rp + i * stride);
    if (wbar) mbar_wait(wbar, wpar);
    uint32_t n = 0;
    while (true) {
        uint32_t m = 0xffffffffu;
#pragma unroll
        for (int i = 0; i < N; i++) m = min4(v[i], m);
        if (__all_sync(0xffffffffu, m != 0u)) return n;
        wait_slot(phase);
#pragma unroll
        for (int i = 0; i < N; i++)
            asm volatile("{ .reg .pred p; setp.eq.u32 p, %5, 0; @p ld.relaxed.gpu.global.v4.u32 {%0,%1,%2,%3}, [%4]; }"
                         : "+r"(v[i].x), "+r"(v[i].y), "+r"(v[i].z), "+r"(v[i].w) : "l"(rp + i * stride), "r"(min4(v[i], 0xffffffffu)) : "memory");
        if (++n > 20000000u) __trap();
    }
}

struct RMaps { CUtensorMap x, w[3], wo, o; };
#define KC(c) ((c) * 64)

#define XORD 3
__host__ __device__ constexpr int xo(int i) {
    return XORD == 0 ? i : XORD == 1 ? (i + 14) % 16 : XORD == 2 ? (i + 11) % 16
         : XORD == 3 ? (i < 10 ? ((i & 1) ? i / 2 : 11 + i / 2) : i - 5) : (i < 6 ? i : ((i & 1) ? 6 + (i - 6) / 2 : 11 + (i - 6) / 2));
}
#define XC(i) (xo(i) * 64)
DEVINL void x_load_pair(uint32_t dst, const CUtensorMap* tmx, int h, int p, int seg, uint32_t fbar) {
    e_expect(fbar, 8192);
    e_tma_load(dst, tmx, XC(2 * p), seg * SEG, fbar);
    e_tma_load(dst + 4096, tmx, XC(2 * p + 1), seg * SEG, fbar);
}
__host__ __device__ constexpr int wo_tile(int role, int i) {
    return role == 0 ? (i < 2 ? 4 + i : 8 + i) : (i >> 1) * 6 + (role - 1) * 2 + (i & 1);
}

template <int NT> DEVINL void wo_phase(uint32_t sb, int tb, uint32_t* pp, uint32_t obar, uint32_t opar) {
    const int lane = tb & 31, krow = (lane & 7) + ((lane >> 4) << 3), chunk = ((tb >> 5) & 3) * 2 + ((lane >> 3) & 1);
    uint32_t wa = sb + R_WO + (tb >> 7) * 16384 + krow * 128 + ((chunk ^ (krow & 7)) << 4);
    uint32_t af[4][4], bf[4][4], of[4][4];
#pragma unroll
    for (int g = 0; g < 4; g++) ldsm4t(af[g], wa + g * 2048);
    mbar_wait(obar, opar);
#pragma unroll
    for (int g = 0; g < 4; g++) ldsm4t(of[g], sb + R_O + g * 512 + lane * 16);
#pragma unroll 1
    for (int i = 0; i < NT; i++) {
        float w0[4] = {0.f, 0.f, 0.f, 0.f}, w1[4] = {0.f, 0.f, 0.f, 0.f};
        mma16816(w0, af[0][0], af[0][1], af[0][2], af[0][3], of[0][0], of[0][1]);
        ldsm4t(af[0], wa + 4 * 2048);
        mma16816(w1, af[1][0], af[1][1], af[1][2], af[1][3], of[0][2], of[0][3]);
        ldsm4t(af[1], wa + 5 * 2048);
        mma16816(w0, af[2][0], af[2][1], af[2][2], af[2][3], of[1][0], of[1][1]);
        ldsm4t(af[2], wa + 6 * 2048);
        mma16816(w1, af[3][0], af[3][1], af[3][2], af[3][3], of[1][2], of[1][3]);
        ldsm4t(af[3], wa + 7 * 2048);
        wa += (i + 1 < NT) ? 32768 : 0;
        mma16816(w0, af[0][0], af[0][1], af[0][2], af[0][3], of[2][0], of[2][1]);
        ldsm4t(af[0], wa);
        mma16816(w1, af[1][0], af[1][1], af[1][2], af[1][3], of[2][2], of[2][3]);
        ldsm4t(af[1], wa + 2048);
        mma16816(w0, af[2][0], af[2][1], af[2][2], af[2][3], of[3][0], of[3][1]);
        ldsm4t(af[2], wa + 2 * 2048);
        mma16816(w1, af[3][0], af[3][1], af[3][2], af[3][3], of[3][2], of[3][3]);
        ldsm4t(af[3], wa + 3 * 2048);
        st_strong4(pp, pack_nz(w0[0] + w1[0], w0[1] + w1[1]));
        st_strong4(pp + 1024, pack_nz(w0[2] + w1[2], w0[3] + w1[3]));
        pp += 6 * 8192;
    }
    (void)bf;
}

DEVINL void o_store(const RMaps& tm, uint32_t sb, uint32_t bar, int wq, int h, int s) {
    mbar_wait(bar + 8 * B_OST0 + (wq >> 2) * 8, s & 1);
    fence_async();
    const uint32_t src = sb + R_QX + 2048 + (wq >> 2) * 8192;
    e_tma_store(&tm.o, src, h * DH + (wq >> 2) * 64, s * SEG);
    e_tma_store(&tm.o, src + 4096, h * DH + (wq >> 2) * 64, s * SEG + 16);
    bulk_commit();
}

template <uint32_t role> DEVINL void r_big(const RMaps& tm, const int wid) {
    extern __shared__ __align__(1024) unsigned char smem_raw[];
    const uint32_t sb = smem_u32(smem_raw);
    const uint32_t bar = sb + R_BAR;
    const int tid = threadIdx.x;
    int h; asm("mov.u32 %0, %%clusterid.x;" : "=r"(h));
        uint32_t a[KR][4];
        mbar_wait(bar + 8 * B_PRO0, 0);
        PT(0);
        {
            const int lane = tid & 31;
            const int krow = (lane & 7) + ((lane >> 4) << 3);
            const int chunk = (wid & 3) * 2 + ((lane >> 3) & 1);
            const uint32_t la = sb + (wid >> 2) * 8192 + krow * 128 + ((chunk ^ (krow & 7)) << 4);
#pragma unroll
            for (int k = 0; k < KR; k++) ldsm4t(a[k], la + (k >> 2) * 16384 + (k & 3) * 2048);
        }
        bar_sync(1, 256);
        {
            fence_async();
            const CUtensorMap* tw = &tm.w[role];
            e_expect(bar + 8 * B_PRO1, (wid < 5 ? 16384 : 0) + (wid < (role == 0 ? 4 : 6) ? 16384 : 0));
            if (wid < 5) {
                e_tma_load(sb + R_W + wid * 8192, tw, h * DH, KC(KR / 4 + wid), bar + 8 * B_PRO1);
                e_tma_load(sb + R_W + KS * 2048 + wid * 8192, tw, h * DH + 64, KC(KR / 4 + wid), bar + 8 * B_PRO1);
            }
            if (wid < (role == 0 ? 4 : 6)) e_tma_load(sb + R_WO + wid * 16384, &tm.wo, wo_tile(role, wid) * 64, h * DH, bar + 8 * B_PRO1);
        }
        constexpr uint32_t e0 = role == 0 ? R_QX + 16384 : R_K + 2048, e1 = role == 0 ? R_QX + 24576 : R_V + 2048;
        if (wid == 6) x_load_pair(sb + e0, &tm.x, h, 3, 0, bar + 8 * (B_FULL + 3));
        if (wid == 7) x_load_pair(sb + e1, &tm.x, h, 4, 0, bar + 8 * (B_FULL + 4));
        PT(1);
        mbar_wait(bar + 8 * B_PRO1, 0);
        PT(2);

        constexpr uint64_t dW0 = cdesc(R_W, 1024, 1024, 1);
        constexpr uint64_t dM = cdesc(R_RING, 128, 128, 0);
        constexpr uint64_t dX = cdesc(R_RING, 16, 1024, 1);
        constexpr uint64_t dX0 = cdesc(0, 16, 1024, 1);
        int tb = tid;
        int wq = wid;

        float d[16];
        for (int s = -1; s < NSEG; s++) {
            if (s >= 0) {
                OPAQUE(wq);
                const uint64_t dW = dW0 + (uint64_t)((wq >> 2) * (KS * 128));
                float y[4] = {0.f, 0.f, 0.f, 0.f};
                {
                    OPAQUE(tb);
                    const uint32_t ma = sb + R_RING + (tb & 31) * 16;
                    float z[4] = {0.f, 0.f, 0.f, 0.f}, u[4] = {0.f, 0.f, 0.f, 0.f};
                    uint32_t b[4][4];
                    mbar_wait(bar + 8 * B_MEM, s & 1);
                    PROF((wq >> 2) * 4 + 0);
                    if (s == 0) PT(3);
                    if (s == 1) PT(4);
#pragma unroll
                    for (int g = 0; g < 4; g++) ldsm4t(b[g], ma + g * 512);
#pragma unroll
                    for (int g = 0; g < KR / 2; g++) {
                        float* c0 = (g % 3 == 0) ? y : (g % 3 == 1) ? u : z;
                        float* c1 = (g % 3 == 0) ? z : (g % 3 == 1) ? y : u;
                        mma16816(c0, a[2 * g][0], a[2 * g][1], a[2 * g][2], a[2 * g][3], b[g & 3][0], b[g & 3][1]);
                        mma16816(c1, a[2 * g + 1][0], a[2 * g + 1][1], a[2 * g + 1][2], a[2 * g + 1][3], b[g & 3][2], b[g & 3][3]);
                        if (g + 4 < KR / 2) {
                            if ((g + 4) % 8 == 0) mbar_wait(bar + 8 * (B_MEM + (g + 4) / 8), s & 1);
                            ldsm4t(b[g & 3], ma + (g + 4) * 512);
                        }
                    }
                    y[0] += z[0] + u[0]; y[1] += z[1] + u[1]; y[2] += z[2] + u[2]; y[3] += z[3] + u[3];
                }
                PROF2(8);
                mbar_wait(bar + 8 * (B_MEM + 3), s & 1);
                wg_fence();
#pragma unroll
                for (int k = KR; k < 64; k++) wg_ss8<1, 1>(y, dW + (uint64_t)((k - KR) * 128), dM + (uint64_t)(k * 16), 1);
                wg_commit();
                asm volatile("wgmma.wait_group.sync.aligned 0;" : "+f"(y[0]), "+f"(y[1]), "+f"(y[2]), "+f"(y[3])::"memory");
                OPAQUE(tb);
                {
                    const uint32_t wo_ = (tb >> 5) * 256;
                    const uint32_t tile = sb + (role == 0 ? R_QX : (role == 1 ? R_K : R_V)) + wo_;
                    const uint32_t u0 = pack_bf16(y[0], y[1]), u1 = pack_bf16(y[2], y[3]);
                    sts32(tile + (tb & 31) * 4, u0);
                    sts32(tile + (tb & 31) * 4 + 128, u1);
                    __syncwarp();
                    uint4 v = lds128(tile + (tb & 15) * 16);
                    uint32_t peer = role + 1 + ((tb >> 4) & 1);
                    peer = peer >= 3 ? peer - 3 : peer;
                    const uint32_t rt = sb + (role == 0 ? R_QM : (role == 1 ? R_K : R_V)) + wo_ + (tb & 15) * 16;
                    st_async16(mapa(rt, peer), v, mapa(bar + 8 * (role == 2 ? B_HOPV : B_HOP1), peer));
                    if (role == 0) {
                        sts128(tile + 4096 + ((tb >> 4) & 1) * 4096 + (tb & 15) * 16, v);
                        sts32(tile + 12288 + (tb & 31) * 4, u0);
                        sts32(tile + 12288 + (tb & 31) * 4 + 128, u1);
                        __syncwarp();
                    }
                    e_arrive(bar + 8 * (role == 2 ? B_HOPV : B_HOP1));
                }
                PROF((wq >> 2) * 4 + 1);
                if (s < NSEG - 1) {
                    bar_sync(1, 256);
                    if (wq < 2) { fence_async(); x_load_pair(sb + R_RING + wq * 8192, &tm.x, h, wq, s + 1, bar + 8 * (B_FULL + wq)); }
                    OPAQUE(tb);
                }
                uint32_t* pp = g_part[s & 3] + (h * 32 + (wo_tile(role, 0) + (tb >> 7)) * 8192 + ((tb >> 5) & 3) * 2048 + (tb & 31));
                asm volatile("" : "+l"(pp));
                if (role != 0) {
                    if (s < NSEG - 1) {
                        wo_phase<3>(sb, tb, pp, bar + 8 * B_O, s & 1);
                    }
                } else {
                    constexpr uint64_t dV = cdesc(R_V, 2048, 128, 0);
                    constexpr uint64_t dP = cdesc(R_QX, 128, 4096, 0);
                    if ((wq & 3) == 0 && s >= 1) { bulk_wait_all(); e_count(&g_ocnt[(s - 1) >> 2]); }
                    wo_phase<2>(sb, tb, pp, bar + 8 * B_O, s & 1);
                    mbar_wait(bar + 8 * B_P, s & 1);
                    float sf[8];
#pragma unroll
                    for (int j = 0; j < 4; j++) asm volatile("ld.shared.v2.f32 {%0,%1}, [%2];" : "=f"(sf[2 * j]), "=f"(sf[2 * j + 1]) : "r"(sb + R_G + 128 + j * 32 + (tb & 3) * 8) : "memory");
                    wg_fence();
#pragma unroll
                    for (int k = 0; k < 3; k++) wg_ss32<0>(d, dV + (uint64_t)((wq >> 2) * 64 + k * 256), dP + (uint64_t)(k * 16), k);
                    wg_commit();
                    asm volatile("wgmma.wait_group.sync.aligned 0;" : ACC16(d)::"memory");
                    if ((wq & 3) == 1 || (wq & 3) == 2) e_arrive_remote(mapa(bar + 8 * B_TFREE, wq & 3));
                    OPAQUE(tb);
                    const uint32_t r = ((tb >> 4) & 1) * 8 + (tb & 7), ch = ((tb >> 5) & 3) * 2 + ((tb >> 3) & 1);
                    const uint32_t oa = sb + R_QX + 2048 + (tb >> 7) * 8192 + r * 128 + ((ch ^ (r & 7)) << 4);
                    stsm4t(oa, pack_bf16(d[0] * sf[0], d[1] * sf[1]), pack_bf16(d[2] * sf[0], d[3] * sf[1]), pack_bf16(d[4] * sf[2], d[5] * sf[3]), pack_bf16(d[6] * sf[2], d[7] * sf[3]));
                    stsm4t(oa + 4096, pack_bf16(d[8] * sf[4], d[9] * sf[5]), pack_bf16(d[10] * sf[4], d[11] * sf[5]), pack_bf16(d[12] * sf[6], d[13] * sf[7]), pack_bf16(d[14] * sf[6], d[15] * sf[7]));
                    __syncwarp();
                    e_arrive(bar + 8 * B_OST0 + (wq >> 2) * 8);
                }
                if (wq == 0) PROF(10);
                if (s == NSEG - 1) {
                    if (role == 0 && (wq & 3) == 0) { o_store(tm, sb, bar, wq, h, s); bulk_wait_all(); }
                    break;
                }
            }
            const int seg = s + 1;
            OPAQUE(wq);
            const uint64_t dW = dW0 + (uint64_t)((wq >> 2) * (KS * 128));
#pragma unroll
            for (int p = 0; p < 8; p++) {
                const int slot = p % 5;
                mbar_wait(bar + 8 * (B_FULL + slot), slot < 3 ? (uint32_t)(p / 5) : (uint32_t)(seg & 1));
                PROF2(p);
                const uint64_t db = slot < 3 ? dX + (uint64_t)(slot * 512) : dX0 + (uint64_t)((slot == 3 ? e0 : e1) >> 4);
                wg_fence();
#pragma unroll
                for (int kk = 0; kk < 8; kk++) {
                    const int k = XORD >= 3 ? (kk & 1) * 4 + (kk >> 1) : kk;
                    const int ks = xo(2 * p + (k >> 2)) * 4 + (k & 3);
                    if (ks >= KR) wg_ss32<1>(d, dW + (uint64_t)((ks - KR) * 128), db + (uint64_t)((k >> 2) * 256 + (k & 3) * 2), p + k);
                    else wg_rs32(d, a[ks < KR ? ks : 0], db + (uint64_t)((k >> 2) * 256 + (k & 3) * 2), p + k);
                }
                wg_commit();
                if (p == 0 && role == 0 && (wq & 3) == 0 && s >= 0) o_store(tm, sb, bar, wq, h, s);
                if (p >= 1) {
                    wg_wait<1>();
                    if (p <= 3) {
                        if ((wq & 3) == p) e_arrive(bar + 8 * (B_EMPTY + p - 1));
                        if (wq == p + (p & 1) * 4) {
                            mbar_wait(bar + 8 * (B_EMPTY + p - 1), seg & 1);
                            x_load_pair(sb + R_RING + (p - 1) * 8192, &tm.x, h, p + 4, seg, bar + 8 * (B_FULL + p - 1));
                        }
                    }
                    if (p == 5 && (wq & 3) < ((role == 0 && s >= 0) ? 1 : 3)) {
                        if (role == 0) bulk_wait_read();
                        e_arrive_remote(mapa(bar + 8 * B_TFREE, wq & 3));
                    }
                    if (p == 6 && (wq & 3) == 1) e_arrive(bar + 8 * B_AFREE0);
                    if (p == 7 && (wq & 3) == 2) e_arrive(bar + 8 * B_AFREE1);
                }
            }
            asm volatile("wgmma.wait_group.sync.aligned 0;" : ACC16(d)::"memory");
            PROF2(16);
            mbar_wait(bar + 8 * B_TFREE, seg & 1);
            const uint32_t tilex = sb + (role == 0 ? R_QX + 2048 : (role == 1 ? R_K + 2048 : R_V + 2048));
            {
                OPAQUE(tb);
                const uint32_t gs = role == 0 ? 4096 : 2048;
                const uint32_t sa = tilex + ((tb >> 4) & 1) * gs + (tb >> 5) * 256 + (tb & 15) * 16;
                stsm4(sa, pack_bf16(d[0], d[1]), pack_bf16(d[2], d[3]), pack_bf16(d[4], d[5]), pack_bf16(d[6], d[7]));
                stsm4(sa + 2 * gs, pack_bf16(d[8], d[9]), pack_bf16(d[10], d[11]), pack_bf16(d[12], d[13]), pack_bf16(d[14], d[15]));
            }
            __syncwarp();
            e_arrive(bar + 8 * B_XDONE);
            if (role != 0 && (wq & 3) == 0) {
                mbar_wait(bar + 8 * B_XDONE, seg & 1);
                fence_async();
                uint32_t pr = role + 1 + (wq >> 2); pr = pr >= 3 ? pr - 3 : pr;
                e_bulk_s2s(mapa(tilex, pr), tilex, CPB, mapa(bar + 8 * B_XT, pr));
            }
        }
}

#define CLR 0
#define CLEAR(st) do { if (role != 0) { \
                const int w_ = wid & 3; \
                uint32_t* zp = g_part[(st) & 3] + ((rg0 + (w_ >> 1) * 64) * 1024 + (w_ & 1) * 512); \
                e_bulk_s2g(zp, sb + R_Z, 1024); \
                e_bulk_s2g(zp + 256, sb + R_Z, 1024); \
                e_bulk_s2g(&g_mem[(st) & 3][(rg0 + (w_ >> 1) * 64) * 32 + (w_ & 1) * 16], sb + R_Z, 64); \
                bulk_commit(); } } while (0)
template <uint32_t role> DEVINL void r_chain(const RMaps& tm, const bf16* __restrict__ mem0, const bf16* __restrict__ x, const bf16* __restrict__ gate_w, const int wid) {
    extern __shared__ __align__(1024) unsigned char smem_raw[];
    const uint32_t sb = smem_u32(smem_raw);
    const uint32_t bar = sb + R_BAR;
    const int tid = threadIdx.x;
    int h; asm("mov.u32 %0, %%clusterid.x;" : "=r"(h));
        int t = tid & 127;
        const float sl2 = 0.08838834764831845f * 1.4426950408889634f;
        const float NEGRAW = -1000000000.0f / 0.08838834764831845f;
        const int rg0 = ((int)role - 1) * 32 + h;
        if (role != 0) {
#pragma unroll 1
            for (int r = 0; r < 4; r++) {
                uint32_t* zp = g_part[r] + ((rg0 + (t >> 6) * 64) * 1024 + (t & 63) * 4);
#pragma unroll
                for (int i = 0; i < 4; i++) st_strong16(zp + i * 256, make_uint4(0u, 0u, 0u, 0u));
                if ((t & 63) < 8) st_strong16(&g_mem[r][(rg0 + (t >> 6) * 64) * 32 + (t & 63) * 4], make_uint4(0u, 0u, 0u, 0u));
            }
            __threadfence();
        }
        {
#pragma unroll 1
            for (int r = (h * 3 + (int)role) * 4 + (t >> 5); r < SEQ; r += 384) {
                const uint32_t gb = __float_as_uint(gate_row(x + r * DM, gate_w, t & 31));
                if ((t & 31) == 0) st_strong4(&g_gate[r], gb ? gb : 0x80000000u);
            }
        }
        if (t < 64) sts128(sb + R_Z + t * 16, make_uint4(0u, 0u, 0u, 0u));
        if (role == 0) sts128(sb + R_QM + t * 16, make_uint4(0u, 0u, 0u, 0u));
        {
            uint4 v[8];
#pragma unroll
            for (int r = 0; r < 8; r++) v[r] = __ldg((const uint4*)(mem0 + r * DM) + t);
            mbar_wait(bar + 8 * B_AFREE0, 0);
            mbar_wait(bar + 8 * B_AFREE1, 0);
#define TR2(f, c) \
            sts128(sb + R_RING + t * 128 + (c) * 16, make_uint4(__byte_perm(v[0].f, v[1].f, 0x5410), __byte_perm(v[2].f, v[3].f, 0x5410), __byte_perm(v[4].f, v[5].f, 0x5410), __byte_perm(v[6].f, v[7].f, 0x5410))); \
            sts128(sb + R_RING + t * 128 + (c) * 16 + 16, make_uint4(__byte_perm(v[0].f, v[1].f, 0x7632), __byte_perm(v[2].f, v[3].f, 0x7632), __byte_perm(v[4].f, v[5].f, 0x7632), __byte_perm(v[6].f, v[7].f, 0x7632)));
            TR2(x, 0) TR2(y, 2) TR2(z, 4) TR2(w, 6)
            fence_async();
            __syncwarp();
            e_arrive(bar + 8 * B_MEM + (t >> 5) * 8);
        }
        constexpr uint64_t dQ = role == 0 ? cdesc(R_QX, 128, 2048, 0) : cdesc(R_QM, 128, 0, 0);
        constexpr uint64_t dK = cdesc(R_K, 128, 2048, 0);

        for (int s = 0; s < NSEG; s++) {
            {
                const int w = wid & 3;
                mbar_wait(bar + 8 * B_XDONE, s & 1);
                if (s + 1 < NSEG) {
                    if (w == 2) x_load_pair(sb + R_RING + 16384, &tm.x, h, 2, s + 1, bar + 8 * (B_FULL + 2));
                    if (role == 0 && w < 2) x_load_pair(sb + R_QX + 16384 + w * 8192, &tm.x, h, 3 + w, s + 1, bar + 8 * (B_FULL + 3 + w));
                }
            }
            if (role == 0) {
                uint32_t n = 0, gate;
                do { gate = ld_strong4(&g_gate[s * SEG + (t >> 2)]); if (++n > 20000000u) __trap(); } while (gate == 0u);
                sts32(sb + R_G + (t >> 2) * 4, gate);
                __syncwarp();
            }
            mbar_wait(bar + 8 * B_XT, s & 1);
            if (t >= 1 && t < 3) { uint32_t pr = role + t; pr = pr >= 3 ? pr - 3 : pr; mbar_arrive_remote(mapa(bar + 8 * B_XRECV, pr)); }
            __syncwarp();
            mbar_wait(bar + 8 * B_HOP1, s & 1);
            PROF(8);
            fence_async();
            OPAQUE(t);
            if (s == NSEG - 1 && role != 0) { mbar_wait(bar + 8 * B_HOPV, s & 1); bulk_wait_all(); break; }
            float sc[20];
            wg_fence();
#pragma unroll
            for (int k = 0; k < 8; k++) wg_ss40(sc, dQ + (uint64_t)(k * 16), dK + (uint64_t)(k * 16), k);
            wg_commit();
            uint32_t t_o = clk32() + 500;
            {
                const uint32_t va = sb + R_V + 2048 + (t >> 5) * 512 + ((t >> 4) & 1) * 2048 + (t & 15) * 16;
                uint32_t v0[4], v1[4];
                ldsm4(v0, va); ldsm4(v1, va + 256);
                const int lim = (t >> 2) - (t & 3) * 2 + 8;
                wg_wait<0>();
                float m = fmaxf(sc[0], sc[1]), m1 = fmaxf(sc[2], sc[3]);
#pragma unroll
                for (int j = 1; j < 5; j++) {
                    m = fmaxf(m, fmaxf(sc[4 * j], sc[4 * j + 1]));
                    if (role == 0) {
                        sc[4 * j + 2] = 8 * j <= lim ? sc[4 * j + 2] : NEGRAW;
                        sc[4 * j + 3] = 8 * j + 1 <= lim ? sc[4 * j + 3] : NEGRAW;
                        m1 = fmaxf(m1, fmaxf(sc[4 * j + 2], sc[4 * j + 3]));
                    }
                }
                m = fmaxf(m, __shfl_xor_sync(0xffffffffu, m, 1));
                if (role == 0) m1 = fmaxf(m1, __shfl_xor_sync(0xffffffffu, m1, 1));
                m = fmaxf(m, __shfl_xor_sync(0xffffffffu, m, 2));
                if (role == 0) m1 = fmaxf(m1, __shfl_xor_sync(0xffffffffu, m1, 2));
                const float mb = m * sl2, mb1 = m1 * sl2;
                uint32_t pk[5], pt[5];
#pragma unroll
                for (int j = 0; j < 5; j++) pk[j] = pack_bf16(ex2(fmaf(sc[4 * j], sl2, -mb)), ex2(fmaf(sc[4 * j + 1], sl2, -mb)));
                float o0[4] = {0.f, 0.f, 0.f, 0.f}, o1[4] = {0.f, 0.f, 0.f, 0.f}, ls[4] = {0.f, 0.f, 0.f, 0.f}, lt[4] = {0.f, 0.f, 0.f, 0.f};
                constexpr uint32_t ONE = 0x3F803F80u;
                mma16816(o0, v0[0], v0[1], v0[2], v0[3], pk[1], pk[2]);
                mma16816(o1, v1[0], v1[1], v1[2], v1[3], pk[1], pk[2]);
                ldsm4(v0, va + 4096); ldsm4(v1, va + 4096 + 256);
                mma16816(ls, ONE, ONE, ONE, ONE, pk[1], pk[2]);
                mma16816(ls, ONE, ONE, ONE, ONE, pk[3], pk[4]);
                mma1688(ls, ONE, ONE, pk[0]);
                mma16816(o0, v0[0], v0[1], v0[2], v0[3], pk[3], pk[4]);
                mma16816(o1, v1[0], v1[1], v1[2], v1[3], pk[3], pk[4]);
                if (role == 0) {
#pragma unroll
                    for (int j = 0; j < 5; j++) pt[j] = pack_bf16(ex2(fmaf(sc[4 * j + 2], sl2, -mb1)), ex2(fmaf(sc[4 * j + 3], sl2, -mb1)));
                    mma16816(lt, pt[0], pt[1], pt[2], pt[3], ONE, ONE);
                    mma1688(lt, pt[4], 0u, ONE);
                }
                mbar_wait(bar + 8 * B_HOPV, s & 1);
                ldsm4(v0, sb + R_V + t * 16);
                mma1688(o0, v0[0], v0[1], pk[0]);
                mma1688(o1, v0[2], v0[3], pk[0]);
                const float i0 = __fdividef(1.0f, ls[0]), i1 = __fdividef(1.0f, ls[1]);
                const uint32_t oa = sb + R_O + (t >> 5) * 512 + (t & 31) * 4;
                sts32(oa, pack_bf16(o0[0] * i0, o0[1] * i1));
                sts32(oa + 128, pack_bf16(o0[2] * i0, o0[3] * i1));
                sts32(oa + 256, pack_bf16(o1[0] * i0, o1[1] * i1));
                sts32(oa + 384, pack_bf16(o1[2] * i0, o1[3] * i1));
                __syncwarp();
                e_arrive(bar + 8 * B_O);
                PROF(9);
                if (role == 0) {
                    const uint32_t pa = sb + R_QX + (t >> 5) * 4096 + (t & 31) * 4;
#pragma unroll
                    for (int j = 0; j < 5; j++) sts32(pa + j * 128, pt[j]);
                    sts32(pa + 5 * 128, 0u);
                    float gate; asm volatile("ld.shared.f32 %0, [%1];" : "=f"(gate) : "r"(sb + R_G + (t >> 2) * 4) : "memory");
                    sts32(sb + R_G + 128 + (t >> 2) * 4, __float_as_uint(__fdividef(gate, lt[0] + lt[2])));
                    fence_async();
                    __syncwarp();
                    e_arrive(bar + 8 * B_P);
                }
            }
            if (t < 32) { e_expect(bar + 8 * B_HOP1, role == 2 ? 4096 : 2048); if (role != 2) e_expect(bar + 8 * B_HOPV, 2048); e_expect(bar + 8 * B_XT, role == 0 ? 2 * CPB : CPB); }
            if (s == NSEG - 1) break;
            if (role != 0 && (wid & 3) >= 2) {
                mbar_wait(bar + 8 * B_XRECV, s & 1);
                mbar_wait(bar + 8 * B_O, s & 1);
                fence_async();
                x_load_pair(sb + ((wid & 1) ? R_V + 2048 : R_K + 2048), &tm.x, h, 3 + (wid & 1), s + 1, bar + 8 * (B_FULL + 3 + (wid & 1)));
            }
            OPAQUE(t);
            PROF(11);
            if (role != 0 || DDUP) {
                const int grp = role == 0 ? (t >> 6) * 32 + h : rg0 + (t >> 6) * 64;
                const uint32_t* rp = g_part[s & 3] + (grp * 1024 + ((t >> 2) & 7) * 32 + ((t >> 5) & 1) * 16 + (t & 3) * 4);
                uint32_t* wp = &g_mem[(s + 1) & 3][grp * 32 + ((t >> 5) & 1) * 16 + (t & 3) * 4 + ((t >> 3) & 3)];
                bulk_wait_all();
                spin_until(t_o + D2_BASE + (role == 0 ? DDUP + (t >> 6) * D2_STEP : (role - 1 + (t >> 6) * 2) * D2_STEP));
                PROF3(0, clk32());
#define LO(u) __uint_as_float((u) << 16)
#define HI(u) __uint_as_float((u) & 0xffff0000u)
                uint4 v[4];
                uint32_t n = poll_set<4>(v, rp, 256, (role - 1 + (t >> 6) * 2) * PHQ);
                {
                    PROF3(1, clk32());
                    float f[8];
                    f[0] = (LO(v[0].x) + LO(v[1].x)) + (LO(v[2].x) + LO(v[3].x)); f[1] = (HI(v[0].x) + HI(v[1].x)) + (HI(v[2].x) + HI(v[3].x));
                    f[2] = (LO(v[0].y) + LO(v[1].y)) + (LO(v[2].y) + LO(v[3].y)); f[3] = (HI(v[0].y) + HI(v[1].y)) + (HI(v[2].y) + HI(v[3].y));
                    f[4] = (LO(v[0].z) + LO(v[1].z)) + (LO(v[2].z) + LO(v[3].z)); f[5] = (HI(v[0].z) + HI(v[1].z)) + (HI(v[2].z) + HI(v[3].z));
                    f[6] = (LO(v[0].w) + LO(v[1].w)) + (LO(v[2].w) + LO(v[3].w)); f[7] = (HI(v[0].w) + HI(v[1].w)) + (HI(v[2].w) + HI(v[3].w));
                    const bool b4 = t & 16, b3 = t & 8;
                    float g4[4], g2[2];
#pragma unroll
                    for (int i = 0; i < 4; i++) g4[i] = (b4 ? f[4 + i] : f[i]) + __shfl_xor_sync(0xffffffffu, b4 ? f[i] : f[4 + i], 16);
#pragma unroll
                    for (int i = 0; i < 2; i++) g2[i] = (b3 ? g4[2 + i] : g4[i]) + __shfl_xor_sync(0xffffffffu, b3 ? g4[i] : g4[2 + i], 8);
                    g2[0] += __shfl_xor_sync(0xffffffffu, g2[0], 4);
                    g2[1] += __shfl_xor_sync(0xffffffffu, g2[1], 4);
                    st_strong4(wp, pack_nz(g2[0], g2[1]));
                }
                PROF3(8, n); (void)n;
            }
            t_o += D2_BASE + DQ + D3 + (t >> 5) * D2_STEP;
            OPAQUE(t);
            PROF(12);
            {
                const uint32_t* rp = &g_mem[(s + 1) & 3][((t >> 5) * 256 + (t & 31)) * 4];
                const uint32_t da = sb + R_RING + ((t >> 5) * 256 + (t & 31)) * 16;
                uint4 v[8];
                spin_until(t_o);
                PROF3(2, clk32());
                uint32_t n = poll_set<8>(v, rp, 128, PH3 + (t >> 5) * PHQ);
                PROF(13);
                PROF3(3, clk32()); PROF3(9, n); (void)n;
                mbar_wait(bar + 8 * B_AFREE0 + (t >> 6) * 8, (s + 1) & 1);
                PROF3(4, clk32());
#pragma unroll
                for (int i = 0; i < 8; i++) sts128(da + i * 512, v[i]);
                if (t >= 64) fence_async();
                __syncwarp();
                e_arrive(bar + 8 * B_MEM + (t >> 5) * 8);
                PROF(14);
                PROF3(5, clk32());
            }
            CLEAR(s + 3);
        }
}

__global__ void __launch_bounds__(384, 1) r_kernel(const __grid_constant__ RMaps tm, const bf16* __restrict__ mem0, const bf16* __restrict__ x, const bf16* __restrict__ gate_w) {
    extern __shared__ __align__(1024) unsigned char smem_raw[];
    const uint32_t sb = smem_u32(smem_raw);
    if ((sb & 0x3FFFFu) != SB0) __trap();
    const int tid = threadIdx.x;
    const int wid = __shfl_sync(0xffffffffu, tid >> 5, 0);
    uint32_t role; asm("mov.u32 %0, %%cluster_ctarank;" : "=r"(role));
    int h; asm("mov.u32 %0, %%clusterid.x;" : "=r"(h));
    const uint32_t bar = sb + R_BAR;
    asm volatile("griddepcontrol.launch_dependents;");
    KT(0, 0);

    if (tid == 0) {
        for (int i = 0; i < 5; i++) mbar_init(bar + 8 * (B_FULL + i), 1);
        for (int i = 0; i < 3; i++) mbar_init(bar + 8 * (B_EMPTY + i), 2);
        for (int i = 0; i < 4; i++) mbar_init(bar + 8 * (B_MEM + i), 1);
        mbar_init(bar + 8 * B_HOP1, role == 2 ? 1 : 9);
        mbar_init(bar + 8 * B_HOPV, role == 2 ? 8 : 1);
        mbar_init(bar + 8 * B_XT, 1);
        mbar_init(bar + 8 * B_TFREE, 6);
        mbar_init(bar + 8 * B_P, 4);
        mbar_init(bar + 8 * B_XDONE, 8);
        mbar_init(bar + 8 * B_OST0, 4);
        mbar_init(bar + 8 * B_OST1, 4);
        mbar_init(bar + 8 * B_XRECV, 2);
        mbar_init(bar + 8 * B_O, 4);
        mbar_init(bar + 8 * B_AFREE0, 2);
        mbar_init(bar + 8 * B_AFREE1, 2);
        mbar_init(bar + 8 * B_PRO0, 1);
        mbar_init(bar + 8 * B_PRO1, 8);
        asm volatile("fence.mbarrier_init.release.cluster;" ::: "memory");
        fence_async();
        mbar_expect(bar + 8 * B_PRO0, KR * 4096);
        for (int i = 0; i < 3; i++) mbar_expect(bar + 8 * (B_FULL + i), 8192);
        mbar_expect(bar + 8 * B_HOP1, role == 2 ? 4096 : 2048);
        if (role != 2) mbar_expect(bar + 8 * B_HOPV, 2048);
        mbar_expect(bar + 8 * B_XT, role == 0 ? 2 * CPB : CPB);
    }
    __syncthreads();
    asm volatile("barrier.cluster.arrive.relaxed.aligned;" ::: "memory");
    {
        const CUtensorMap* tw = &tm.w[role];
        if (wid < 11) {
            e_tma_load(sb + wid * 16384, tw, h * DH, KC(wid), bar + 8 * B_PRO0);
            e_tma_load(sb + wid * 16384 + 8192, tw, h * DH + 64, KC(wid), bar + 8 * B_PRO0);
        }
        if (wid < 6) e_tma_load(sb + R_RING + wid * 4096, &tm.x, XC(wid), 0, bar + 8 * (B_FULL + (wid >> 1)));
        if ((tid & 31) == 0) {
            if (wid < 10) tma_prefetch(tw, h * DH + (wid & 1) * 64, KC(KR / 4 + (wid >> 1)));
            if (wid >= 6 && wid - 6 < (role == 0 ? 4 : 6)) tma_prefetch(&tm.wo, wo_tile(role, wid - 6) * 64, h * DH);
            if (blockIdx.x < NSEG && wid < 8) { tma_prefetch(&tm.x, wid * 128, blockIdx.x * SEG); tma_prefetch(&tm.x, wid * 128 + 64, blockIdx.x * SEG); }
        }
        __syncwarp();
    }
    asm volatile("barrier.cluster.wait.aligned;" ::: "memory");

    if (wid < 8) {
        asm volatile("setmaxnreg.inc.sync.aligned.u32 224;");
        if (role == 0) r_big<0>(tm, wid); else if (role == 1) r_big<1>(tm, wid); else r_big<2>(tm, wid);
    } else {
        asm volatile("setmaxnreg.dec.sync.aligned.u32 56;");
        if (role == 0) r_chain<0>(tm, mem0, x, gate_w, wid); else if (role == 1) r_chain<1>(tm, mem0, x, gate_w, wid); else r_chain<2>(tm, mem0, x, gate_w, wid);
    }
    __syncwarp();
    asm volatile("barrier.cluster.arrive; barrier.cluster.wait;" ::: "memory");
    KT(0, 1);
}

constexpr int G_ST = 4;
constexpr int G_STAGE = 16384 + 32768;
constexpr int G_EPI = G_ST * G_STAGE;
constexpr int G_GATE = G_EPI + 32768;
constexpr int G_BAR = G_GATE + 1024;
constexpr int G_SMEM = G_BAR + 128 + 1024;

struct G1Maps { CUtensorMap x, wg, wu, hs, o, h, wo, wd, out; };
constexpr int G1_NB = FF / 128;
constexpr int G1_TILES = 16 * G1_NB;

DEVINL void g_mma_block(float* d, uint32_t sb, uint32_t bar, int it, int wg, int tid, bool first) {
    const int st = it % G_ST;
    mbar_wait(bar + 8 * st, (it / G_ST) & 1);
    const uint64_t da = mkdesc(sb + st * G_STAGE + wg * 8192, 16, 1024, 1);
    const uint64_t db = mkdesc(sb + st * G_STAGE + 16384, 8192, 1024, 1);
    wg_fence();
#pragma unroll
    for (int k = 0; k < 4; k++) wg_ss256(d, da + (uint64_t)(k * 2), db + (uint64_t)(k * 128), (first ? 0 : 1) | k);
    wg_commit();
    if (!first) { wg_wait<1>(); if ((tid & 127) == 0) mbar_arrive(bar + 8 * (G_ST + (it - 1) % G_ST)); }
}
DEVINL void g_load_block(uint32_t sb, uint32_t bar, int it, const CUtensorMap* ta, int k0, int m0, const CUtensorMap* tb, int n0) {
    const int st = it % G_ST;
    mbar_wait(bar + 8 * (G_ST + st), ((it / G_ST) & 1) ^ 1);
    const uint32_t fb = bar + 8 * st, sa = sb + st * G_STAGE;
    mbar_expect(fb, G_STAGE);
    tma_load(sa, ta, k0, m0, fb);
#pragma unroll
    for (int q = 0; q < 4; q++) tma_load(sa + 16384 + q * 8192, tb, n0 + q * 64, k0, fb);
}

__global__ void __launch_bounds__(384, 1) g1_kernel(const __grid_constant__ G1Maps tm) {
    extern __shared__ __align__(1024) unsigned char smem_raw[];
    const uint32_t sb = (smem_u32(smem_raw) + 1023) & ~1023u;
    const int tid = threadIdx.x, lane = tid & 31;
    const int wg = __shfl_sync(0xffffffffu, tid >> 7, 0);
    const int warp = __shfl_sync(0xffffffffu, (tid >> 5) & 3, 0);
    const uint32_t bar = sb + G_BAR;
    const int t_begin = (blockIdx.x * G1_TILES) / gridDim.x;
    const int t_end = ((blockIdx.x + 1) * G1_TILES) / gridDim.x;
    const int mb0 = t_begin / G1_NB;
    KT(1, 0);
    if (tid == 0) {
        for (int i = 0; i < G_ST; i++) { mbar_init(bar + 8 * i, 1); mbar_init(bar + 8 * (G_ST + i), 2); }
        fence_async();
    }
    __syncthreads();
    if (wg == 2) {
        asm volatile("setmaxnreg.dec.sync.aligned.u32 56;");
        if (warp == 0) {
            if (lane == 0) {
                int it = 0;
                for (int tile = t_begin; tile < t_end; tile++) {
                    const int mb = tile / G1_NB, nb = tile % G1_NB;
                    for (int kb = 0; kb < 16; kb++, it++) {
                        const int st = it % G_ST;
                        mbar_wait(bar + 8 * (G_ST + st), ((it / G_ST) & 1) ^ 1);
                        const uint32_t fb = bar + 8 * st, sa = sb + st * G_STAGE;
                        mbar_expect(fb, G_STAGE);
                        tma_load(sa, &tm.x, kb * 64, mb * 128, fb);
                        tma_load(sa + 16384, &tm.wg, nb * 128, kb * 64, fb);
                        tma_load(sa + 16384 + 8192, &tm.wg, nb * 128 + 64, kb * 64, fb);
                        tma_load(sa + 16384 + 16384, &tm.wu, nb * 128, kb * 64, fb);
                        tma_load(sa + 16384 + 24576, &tm.wu, nb * 128 + 64, kb * 64, fb);
                    }
                }
                for (int pass = 0; pass < 2; pass++) {
                    for (int i = blockIdx.x; i < (pass ? NFULL : NLATE); i += gridDim.x) {
                        const int tile = pass ? i : NFULL + i, mb = tile >> 2, nb = tile & 3;
                        wait_count(&g_hcnt[mb], 2 * G1_NB);
                        asm volatile("fence.proxy.async;" ::: "memory");
                        for (int kb = 0; kb < FF / 64; kb++, it++) g_load_block(sb, bar, it, &tm.h, kb * 64, mb * 128, &tm.wd, nb * 256);
                        if (pass) {
                            wait_count(&g_ocnt[mb], NH * 4 * 2);
                            asm volatile("fence.proxy.async;" ::: "memory");
                            for (int kb = 0; kb < HD / 64; kb++, it++) g_load_block(sb, bar, it, &tm.o, kb * 64, mb * 128, &tm.wo, nb * 256);
                        }
                    }
                }
            }
        }
    } else {
        asm volatile("setmaxnreg.inc.sync.aligned.u32 224;");
        float d[128];
        int it = 0;
        float s0 = 0.f, s1 = 0.f;
        const uint32_t epi = sb + G_EPI + wg * 16384;
        const int row = warp * 16 + ((lane >> 3) & 1) * 8 + (lane & 7);
        for (int tile = t_begin; tile < t_end; tile++) {
            const int mb = tile / G1_NB, nb = tile % G1_NB;
            for (int kb = 0; kb < 16; kb++, it++) g_mma_block(d, sb, bar, it, wg, tid, kb == 0);
            if (tile == t_begin || nb == 0) {
                const uint32_t* gp = &g_gate[mb * 128 + wg * 64 + warp * 16 + (lane >> 2)];
                uint32_t u0, u1, n = 0;
                do { u0 = ld_strong4(gp); u1 = ld_strong4(gp + 8); if (++n > 20000000u) __trap(); } while (u0 == 0u || u1 == 0u);
                s0 = 1.0f - __uint_as_float(u0); s1 = 1.0f - __uint_as_float(u1);
                __syncwarp();
            }
            wg_wait<0>();
            if ((tid & 127) == 0) { mbar_arrive(bar + 8 * (G_ST + (it - 1) % G_ST)); bulk_wait_read(); }
            bar_sync(1 + wg, 128);
#pragma unroll
            for (int j = 0; j < 16; j += 2) {
                uint32_t p[4];
#pragma unroll
                for (int q = 0; q < 4; q++) {
                    const int i = (j + (q >> 1)) * 4 + (q & 1) * 2;
                    const float sc = (q & 1) ? s1 : s0;
                    const float g0 = d[i], g1 = d[i + 1];
                    const float h0 = __fdividef(g0, 1.0f + __expf(-g0)) * d[64 + i] * sc;
                    const float h1 = __fdividef(g1, 1.0f + __expf(-g1)) * d[64 + i + 1] * sc;
                    p[q] = pack_bf16(h0, h1);
                }
                const int cgp = j + (lane >> 4);
                stsm4(epi + (cgp >> 3) * 8192 + row * 128 + (((cgp & 7) ^ (row & 7)) << 4), p[0], p[1], p[2], p[3]);
            }
            fence_async();
            bar_sync(1 + wg, 128);
            if ((tid & 127) == 0) {
                tma_store(&tm.hs, epi, nb * 128, mb * 128 + wg * 64);
                tma_store(&tm.hs, epi + 8192, nb * 128 + 64, mb * 128 + wg * 64);
                bulk_commit();
            }
        }
        if ((tid & 127) == 0) {
            bulk_wait_all();
            __threadfence();
            const int n0 = min(t_end, (mb0 + 1) * G1_NB) - t_begin;
            atomicAdd(&g_hcnt[mb0], (uint32_t)n0);
            if (t_end - t_begin > n0) atomicAdd(&g_hcnt[mb0 + 1], (uint32_t)(t_end - t_begin - n0));
        }
        for (int pass = 0; pass < 2; pass++) {
            for (int i = blockIdx.x; i < (pass ? NFULL : NLATE); i += gridDim.x) {
                const int nkb = pass ? (FF + HD) / 64 : FF / 64;
                for (int kb = 0; kb < nkb; kb++, it++) g_mma_block(d, sb, bar, it, wg, tid, kb == 0);
                wg_wait<0>();
                if ((tid & 127) == 0) mbar_arrive(bar + 8 * (G_ST + (it - 1) % G_ST));
                if (pass == 0) {
                    float4* pre = g_pre + i * (32 * 256) + tid;
#pragma unroll
                    for (int q = 0; q < 32; q++) __stcg(pre + q * 256, make_float4(d[4 * q], d[4 * q + 1], d[4 * q + 2], d[4 * q + 3]));
                } else {
                    const int mb = i >> 2, nb = i & 3;
#pragma unroll
                    for (int half = 0; half < 2; half++) {
                        if ((tid & 127) == 0) bulk_wait_read();
                        bar_sync(1 + wg, 128);
#pragma unroll
                        for (int j = 0; j < 16; j += 2) {
                            const float* e = d + half * 64 + 4 * j;
                            const int cgp = j + (lane >> 4);
                            stsm4(epi + (cgp >> 3) * 8192 + row * 128 + (((cgp & 7) ^ (row & 7)) << 4),
                                  pack_bf16(e[0], e[1]), pack_bf16(e[2], e[3]), pack_bf16(e[4], e[5]), pack_bf16(e[6], e[7]));
                        }
                        fence_async();
                        bar_sync(1 + wg, 128);
                        if ((tid & 127) == 0) {
                            tma_store(&tm.out, epi, nb * 256 + half * 128, mb * 128 + wg * 64);
                            tma_store(&tm.out, epi + 8192, nb * 256 + half * 128 + 64, mb * 128 + wg * 64);
                            bulk_commit();
                        }
                    }
                }
            }
        }
        if ((tid & 127) == 0) bulk_wait_all();
        KT(1, 1);
    }
    __syncwarp();
    asm volatile("griddepcontrol.wait;" ::: "memory");
}

struct G2Maps { CUtensorMap o, wo, out; };

__global__ void __launch_bounds__(384, 1) g2_kernel(const __grid_constant__ G2Maps tm) {
    extern __shared__ __align__(1024) unsigned char smem_raw[];
    const uint32_t sb = (smem_u32(smem_raw) + 1023) & ~1023u;
    const int tid = threadIdx.x, lane = tid & 31;
    const int wg = __shfl_sync(0xffffffffu, tid >> 7, 0);
    const int warp = __shfl_sync(0xffffffffu, (tid >> 5) & 3, 0);
    const uint32_t bar = sb + G_BAR;
    const int ks = blockIdx.x & 3, lt = blockIdx.x >> 2, nb = (NFULL + lt) & 3, mb = (NFULL + lt) >> 2;
    KT(2, 0);
    if (tid == 0) {
        for (int i = 0; i < G_ST; i++) { mbar_init(bar + 8 * i, 1); mbar_init(bar + 8 * (G_ST + i), 2); }
        fence_async();
    }
    __syncthreads();
    if (wg == 2) {
        asm volatile("setmaxnreg.dec.sync.aligned.u32 40;");
        if (warp == 0 && lane == 0) {
            for (int it = 0; it < 16; it++) g_load_block(sb, bar, it, &tm.o, (ks * 16 + it) * 64, mb * 128, &tm.wo, nb * 256);
        } else if (warp == 1) {
            if (blockIdx.x < SEQ / 32) g_gate[blockIdx.x * 32 + lane] = 0u;
            if (blockIdx.x == 0 && lane < 16) { g_hcnt[lane] = 0u; g_ocnt[lane] = 0u; }
        }
    } else {
        asm volatile("setmaxnreg.inc.sync.aligned.u32 232;");
        float d[128];
        float4 r[8];
        const float4* pre = g_pre + (lt * 32 + ks * 8) * 256 + tid;
#pragma unroll
        for (int q = 0; q < 8; q++) r[q] = __ldcg(pre + q * 256);
        for (int it = 0; it < 16; it++) g_mma_block(d, sb, bar, it, wg, tid, it == 0);
        wg_wait<0>();
        float4* mine = g_sk + blockIdx.x * (32 * 256) + tid;
#pragma unroll
        for (int c = 0; c < 4; c++) {
            if (c != ks) {
#pragma unroll
                for (int q = c * 8; q < c * 8 + 8; q++) __stcg(mine + q * 256, make_float4(d[4 * q], d[4 * q + 1], d[4 * q + 2], d[4 * q + 3]));
            } else {
#pragma unroll
                for (int q = 0; q < 8; q++) { r[q].x += d[c * 32 + 4 * q]; r[q].y += d[c * 32 + 4 * q + 1]; r[q].z += d[c * 32 + 4 * q + 2]; r[q].w += d[c * 32 + 4 * q + 3]; }
            }
        }
        __threadfence();
        bar_sync(1, 256);
        if (tid == 0) {
            atomicAdd(&g_skcnt[lt], 1u);
            uint32_t v, n = 0;
            do {
                asm volatile("ld.acquire.gpu.global.u32 %0, [%1];" : "=r"(v) : "l"(&g_skcnt[lt]) : "memory");
                if (++n > 200000000u) __trap();
            } while (v < 4u);
            if (atomicAdd(&g_skdone[lt], 1u) == 3u) { g_skcnt[lt] = 0u; g_skdone[lt] = 0u; }
        }
        bar_sync(1, 256);
#pragma unroll
        for (int c = 1; c < 4; c++) {
            const float4* th = g_sk + ((lt * 4 + ((ks + c) & 3)) * 32 + ks * 8) * 256 + tid;
#pragma unroll
            for (int q = 0; q < 8; q++) { const float4 u = __ldcg(th + q * 256); r[q].x += u.x; r[q].y += u.y; r[q].z += u.z; r[q].w += u.w; }
        }
        const uint32_t epi = sb + G_EPI + wg * 16384;
        const int row = warp * 16 + ((lane >> 3) & 1) * 8 + (lane & 7);
#pragma unroll
        for (int j = 0; j < 8; j += 2) {
            const int cgp = j + (lane >> 4);
            stsm4(epi + row * 128 + ((cgp ^ (row & 7)) << 4), pack_bf16(r[j].x, r[j].y), pack_bf16(r[j].z, r[j].w),
                  pack_bf16(r[j + 1].x, r[j + 1].y), pack_bf16(r[j + 1].z, r[j + 1].w));
        }
        fence_async();
        bar_sync(2 + wg, 128);
        if ((tid & 127) == 0) {
            tma_store(&tm.out, epi, nb * 256 + ks * 64, mb * 128 + wg * 64);
            bulk_commit();
            bulk_wait_all();
        }
        KT(2, 1);
    }
}

typedef CUresult (*EncodeFn)(CUtensorMap*, CUtensorMapDataType, cuuint32_t, void*, const cuuint64_t*, const cuuint64_t*, const cuuint32_t*,
                             const cuuint32_t*, CUtensorMapInterleave, CUtensorMapSwizzle, CUtensorMapL2promotion, CUtensorMapFloatOOBfill);

static void make_map(EncodeFn enc, CUtensorMap* m, const void* ptr, uint64_t rows, uint64_t cols, uint32_t box_rows) {
    cuuint64_t dims[2] = {cols, rows};
    cuuint64_t strides[1] = {cols * 2};
    cuuint32_t box[2] = {64, box_rows};
    cuuint32_t es[2] = {1, 1};
    enc(m, CU_TENSOR_MAP_DATA_TYPE_BFLOAT16, 2, (void*)ptr, dims, strides, box, es, CU_TENSOR_MAP_INTERLEAVE_NONE,
        CU_TENSOR_MAP_SWIZZLE_128B, CU_TENSOR_MAP_L2_PROMOTION_L2_256B, CU_TENSOR_MAP_FLOAT_OOB_FILL_NONE);
}

extern "C" void kernel_launch(void* const* d_in, const int* in_sizes, int n_in, void* d_out, int out_size) {
    (void)in_sizes; (void)n_in; (void)out_size;
    const bf16* x = (const bf16*)d_in[0];
    const bf16* mem0 = (const bf16*)d_in[1];
    const bf16* gate_w = (const bf16*)d_in[11];
    static EncodeFn enc = nullptr;
    static int n_sm = 0;
    static void *pO = nullptr, *pH = nullptr;
    if (!enc) {
        void* fn = nullptr;
        cudaDriverEntryPointQueryResult qr;
        cudaGetDriverEntryPoint("cuTensorMapEncodeTiled", &fn, cudaEnableDefault, &qr);
        enc = (EncodeFn)fn;
        cudaDeviceGetAttribute(&n_sm, cudaDevAttrMultiProcessorCount, 0);
        cudaFuncSetAttribute(r_kernel, cudaFuncAttributeMaxDynamicSharedMemorySize, R_SMEM);
        cudaFuncSetAttribute(g1_kernel, cudaFuncAttributeMaxDynamicSharedMemorySize, G_SMEM);
        cudaFuncSetAttribute(g2_kernel, cudaFuncAttributeMaxDynamicSharedMemorySize, G_SMEM);
        cudaGetSymbolAddress(&pO, g_O);
        cudaGetSymbolAddress(&pH, g_H);
    }
    RMaps rm; G1Maps m1; G2Maps m2;
    make_map(enc, &rm.x, x, SEQ, DM, 32);
    for (int i = 0; i < 3; i++) make_map(enc, &rm.w[i], d_in[2 + i], DM, HD, 64);
    make_map(enc, &rm.wo, d_in[5], HD, DM, 128);
    make_map(enc, &rm.o, pO, SEQ, HD, 16);
    make_map(enc, &m1.x, x, SEQ, DM, 128);
    make_map(enc, &m1.wg, d_in[8], DM, FF, 64);
    make_map(enc, &m1.wu, d_in[9], DM, FF, 64);
    make_map(enc, &m1.hs, pH, SEQ, FF, 64);
    make_map(enc, &m1.o, pO, SEQ, HD, 128);
    make_map(enc, &m1.h, pH, SEQ, FF, 128);
    make_map(enc, &m1.wo, d_in[5], HD, DM, 64);
    make_map(enc, &m1.wd, d_in[10], FF, DM, 64);
    make_map(enc, &m1.out, d_out, SEQ, DM, 64);
    m2.o = m1.o; m2.wo = m1.wo; m2.out = m1.out;

    cudaStream_t st = cudaStreamPerThread;
    {
        cudaLaunchConfig_t cfg = {};
        cfg.gridDim = dim3(96); cfg.blockDim = dim3(384); cfg.dynamicSmemBytes = R_SMEM; cfg.stream = st;
        cudaLaunchAttribute at[1];
        at[0].id = cudaLaunchAttributeClusterDimension; at[0].val.clusterDim.x = 3; at[0].val.clusterDim.y = 1; at[0].val.clusterDim.z = 1;
        cfg.attrs = at; cfg.numAttrs = 1;
        cudaLaunchKernelEx(&cfg, r_kernel, rm, mem0, x, gate_w);
    }
    {
        cudaLaunchConfig_t cfg = {};
        cfg.gridDim = dim3(n_sm - 96); cfg.blockDim = dim3(384); cfg.dynamicSmemBytes = G_SMEM; cfg.stream = st;
        cudaLaunchAttribute at[1];
        at[0].id = cudaLaunchAttributeProgrammaticStreamSerialization; at[0].val.programmaticStreamSerializationAllowed = 1;
        cfg.attrs = at; cfg.numAttrs = 1;
        cudaLaunchKernelEx(&cfg, g1_kernel, m1);
    }
    g2_kernel<<<NLATE * 4, 384, G_SMEM, st>>>(m2);
}
```

```cpp
#include <cuda_runtime.h>
#include <cuda_bf16.h>
#include <cuda.h>
#include <stdint.h>

typedef __nv_bfloat16 bf16;

constexpr int SEQ = 2048, DM = 1024, NH = 32, DH = 128, NMEM = 8, SEG = 32, NSEG = 64, FF = 3584;
constexpr int HD = NH * DH;

__device__ bf16 g_O[SEQ * HD];
__device__ bf16 g_H[SEQ * FF];
__device__ uint32_t g_gate[SEQ];
__device__ uint32_t g_part[4][128 * 32 * 32];
__device__ uint32_t g_mem[4][DM * 4];
constexpr int NFULL = 36, T_MID = 44, T_LATE = 52;
constexpr int NPRE = 64 - NFULL;
__device__ float4 g_pre[NPRE * 32 * 256];
__device__ float4 g_sk[((T_LATE - T_MID) * 4 + (64 - T_LATE) * 8) * 32 * 256];
__device__ uint32_t g_skcnt[64], g_pcnt[64];
__device__ uint32_t g_hcnt[16], g_ocnt[16];
#define KT(k, i)
#define PT(i)

#define DEVINL __device__ __forceinline__
constexpr long long SPIN_LIMIT = 4000000000LL;

DEVINL uint32_t smem_u32(const void* p) { return (uint32_t)__cvta_generic_to_shared(p); }
DEVINL void mbar_init(uint32_t bar, uint32_t cnt) { asm volatile("mbarrier.init.shared::cta.b64 [%0], %1;" ::"r"(bar), "r"(cnt) : "memory"); }
DEVINL void mbar_arrive(uint32_t bar) { asm volatile("mbarrier.arrive.shared::cta.b64 _, [%0];" ::"r"(bar) : "memory"); }
DEVINL void mbar_expect(uint32_t bar, uint32_t bytes) { asm volatile("mbarrier.arrive.expect_tx.shared::cta.b64 _, [%0], %1;" ::"r"(bar), "r"(bytes) : "memory"); }
DEVINL void mbar_arrive_remote(uint32_t cbar) { asm volatile("mbarrier.arrive.relaxed.cluster.shared::cluster.b64 _, [%0];" ::"r"(cbar) : "memory"); }
DEVINL bool mbar_try(uint32_t bar, uint32_t par) {
    uint32_t ok;
    asm volatile("{ .reg .pred p; mbarrier.try_wait.parity.shared::cta.b64 p, [%1], %2; selp.u32 %0, 1, 0, p; }" : "=r"(ok) : "r"(bar), "r"(par) : "memory");
    return ok;
}
__device__ __noinline__ void mbar_wait_slow(uint32_t bar, uint32_t par) {
    long long t0 = clock64();
    while (!mbar_try(bar, par)) { if (clock64() - t0 > SPIN_LIMIT) __trap(); }
}
DEVINL void mbar_wait(uint32_t bar, uint32_t par) {
    uint32_t n = 0;
    while (!mbar_try(bar, par)) { if (++n > 200000000u) __trap(); }
}
DEVINL uint32_t mapa(uint32_t a, uint32_t r) { uint32_t o; asm volatile("mapa.shared::cluster.u32 %0, %1, %2;" : "=r"(o) : "r"(a), "r"(r)); return o; }
DEVINL void fence_async() { asm volatile("fence.proxy.async.shared::cta;" ::: "memory"); }
DEVINL void bar_sync(int id, int n) { asm volatile("bar.sync %0, %1;" ::"r"(id), "r"(n) : "memory"); }
DEVINL void cluster_sync() { asm volatile("barrier.cluster.arrive.aligned; barrier.cluster.wait.aligned;" ::: "memory"); }
DEVINL void tma_load(uint32_t dst, const CUtensorMap* tm, int c0, int c1, uint32_t bar) {
    asm volatile("cp.async.bulk.tensor.2d.shared::cluster.global.mbarrier::complete_tx::bytes [%0], [%1, {%3, %4}], [%2];"
                 ::"r"(dst), "l"(tm), "r"(bar), "r"(c0), "r"(c1) : "memory");
}
DEVINL void tma_prefetch(const CUtensorMap* tm, int c0, int c1) {
    asm volatile("cp.async.bulk.prefetch.tensor.2d.L2.global [%0, {%1, %2}];" ::"l"(tm), "r"(c0), "r"(c1) : "memory");
}
DEVINL void tma_store(const CUtensorMap* tm, uint32_t src, int c0, int c1) {
    asm volatile("cp.async.bulk.tensor.2d.global.shared::cta.bulk_group [%0, {%2, %3}], [%1];" ::"l"(tm), "r"(src), "r"(c0), "r"(c1) : "memory");
}
DEVINL void bulk_commit() { asm volatile("cp.async.bulk.commit_group;" ::: "memory"); }
DEVINL void bulk_wait_read() { asm volatile("cp.async.bulk.wait_group.read 0;" ::: "memory"); }
DEVINL void bulk_wait_all() { asm volatile("cp.async.bulk.wait_group 0;" ::: "memory"); }
DEVINL void bulk_s2s(uint32_t cdst, uint32_t src, uint32_t bytes, uint32_t cbar) {
    asm volatile("cp.async.bulk.shared::cluster.shared::cta.mbarrier::complete_tx::bytes [%0], [%1], %2, [%3];" ::"r"(cdst), "r"(src), "r"(bytes), "r"(cbar) : "memory");
}
DEVINL void st_async16(uint32_t cdst, uint4 v, uint32_t cbar) {
    asm volatile("st.async.shared::cluster.mbarrier::complete_tx::bytes.v4.b32 [%0], {%1,%2,%3,%4}, [%5];" ::"r"(cdst), "r"(v.x), "r"(v.y), "r"(v.z), "r"(v.w), "r"(cbar) : "memory");
}
DEVINL uint64_t mkdesc(uint32_t addr, uint32_t lbo, uint32_t sbo, uint32_t swz) {
    return (uint64_t)((addr & 0x3FFFF) >> 4) | ((uint64_t)(lbo >> 4) << 16) | ((uint64_t)(sbo >> 4) << 32) | ((uint64_t)swz << 62);
}
constexpr uint32_t SB0 = 1024;
__host__ __device__ constexpr uint64_t cdesc(uint32_t off, uint32_t lbo, uint32_t sbo, uint32_t swz) {
    return (uint64_t)(((SB0 + off) & 0x3FFFF) >> 4) | ((uint64_t)(lbo >> 4) << 16) | ((uint64_t)(sbo >> 4) << 32) | ((uint64_t)swz << 62);
}
DEVINL float ex2(float x) { float y; asm("ex2.approx.ftz.f32 %0, %1;" : "=f"(y) : "f"(x)); return y; }
DEVINL void spin_clk(int d) { uint32_t t0, t1; asm volatile("mov.u32 %0, %%clock;" : "=r"(t0)); do { asm volatile("mov.u32 %0, %%clock;" : "=r"(t1)); } while ((int)(t1 - t0) < d); }
#define PROBE_GAP 150
#define OPAQUE(x) asm volatile("" : "+r"(x))
DEVINL void wg_fence() { asm volatile("wgmma.fence.sync.aligned;" ::: "memory"); }
DEVINL void wg_commit() { asm volatile("wgmma.commit_group.sync.aligned;" ::: "memory"); }
template <int N> DEVINL void wg_wait() { asm volatile("wgmma.wait_group.sync.aligned %0;" ::"n"(N) : "memory"); }
DEVINL uint32_t pack_bf16(float lo, float hi) { uint32_t r; asm("cvt.rn.bf16x2.f32 %0, %1, %2;" : "=r"(r) : "f"(hi), "f"(lo)); return r; }
DEVINL void ldsm4(uint32_t* r, uint32_t a) { asm volatile("ldmatrix.sync.aligned.m8n8.x4.shared.b16 {%0,%1,%2,%3}, [%4];" : "=r"(r[0]), "=r"(r[1]), "=r"(r[2]), "=r"(r[3]) : "r"(a) : "memory"); }
DEVINL void ldsm4t(uint32_t* r, uint32_t a) { asm volatile("ldmatrix.sync.aligned.m8n8.x4.trans.shared.b16 {%0,%1,%2,%3}, [%4];" : "=r"(r[0]), "=r"(r[1]), "=r"(r[2]), "=r"(r[3]) : "r"(a) : "memory"); }
DEVINL void stsm4(uint32_t a, uint32_t r0, uint32_t r1, uint32_t r2, uint32_t r3) { asm volatile("stmatrix.sync.aligned.m8n8.x4.shared.b16 [%0], {%1,%2,%3,%4};" ::"r"(a), "r"(r0), "r"(r1), "r"(r2), "r"(r3) : "memory"); }
DEVINL void stsm4t(uint32_t a, uint32_t r0, uint32_t r1, uint32_t r2, uint32_t r3) { asm volatile("stmatrix.sync.aligned.m8n8.x4.trans.shared.b16 [%0], {%1,%2,%3,%4};" ::"r"(a), "r"(r0), "r"(r1), "r"(r2), "r"(r3) : "memory"); }
DEVINL void sts32(uint32_t a, uint32_t v) { asm volatile("st.shared.b32 [%0], %1;" ::"r"(a), "r"(v) : "memory"); }
DEVINL void sts128(uint32_t a, uint4 v) { asm volatile("st.shared.v4.b32 [%0], {%1,%2,%3,%4};" ::"r"(a), "r"(v.x), "r"(v.y), "r"(v.z), "r"(v.w) : "memory"); }
DEVINL uint4 lds128(uint32_t a) { uint4 v; asm volatile("ld.shared.v4.b32 {%0,%1,%2,%3}, [%4];" : "=r"(v.x), "=r"(v.y), "=r"(v.z), "=r"(v.w) : "r"(a) : "memory"); return v; }
DEVINL uint4 ld_strong16(const void* p) { uint4 v; asm volatile("ld.relaxed.gpu.global.v4.u32 {%0,%1,%2,%3}, [%4];" : "=r"(v.x), "=r"(v.y), "=r"(v.z), "=r"(v.w) : "l"(p) : "memory"); return v; }
DEVINL void st_strong8(void* p, uint32_t a, uint32_t b) { asm volatile("st.relaxed.gpu.global.v2.u32 [%0], {%1,%2};" ::"l"(p), "r"(a), "r"(b) : "memory"); }
DEVINL void st_strong4(void* p, uint32_t a) { asm volatile("st.relaxed.gpu.global.u32 [%0], %1;" ::"l"(p), "r"(a) : "memory"); }
DEVINL void st_strong16(void* p, uint4 v) { asm volatile("st.relaxed.gpu.global.v4.u32 [%0], {%1,%2,%3,%4};" ::"l"(p), "r"(v.x), "r"(v.y), "r"(v.z), "r"(v.w) : "memory"); }
DEVINL uint32_t pack_nz(float lo, float hi) { uint32_t r = pack_bf16(lo, hi); return r == 0u ? 0x8000u : r; }
DEVINL uint32_t min4(uint4 v, uint32_t m) { return __vimin3_u32(__vimin3_u32(v.x, v.y, m), v.z, v.w); }
DEVINL void mma16816(float* d, uint32_t a0, uint32_t a1, uint32_t a2, uint32_t a3, uint32_t b0, uint32_t b1) {
    asm volatile("mma.sync.aligned.m16n8k16.row.col.f32.bf16.bf16.f32 {%0,%1,%2,%3}, {%4,%5,%6,%7}, {%8,%9}, {%0,%1,%2,%3};"
                 : "+f"(d[0]), "+f"(d[1]), "+f"(d[2]), "+f"(d[3]) : "r"(a0), "r"(a1), "r"(a2), "r"(a3), "r"(b0), "r"(b1));
}
DEVINL void mma1688(float* d, uint32_t a0, uint32_t a1, uint32_t b0) {
    asm volatile("mma.sync.aligned.m16n8k8.row.col.f32.bf16.bf16.f32 {%0,%1,%2,%3}, {%4,%5}, {%6}, {%0,%1,%2,%3};"
                 : "+f"(d[0]), "+f"(d[1]), "+f"(d[2]), "+f"(d[3]) : "r"(a0), "r"(a1), "r"(b0));
}
template <int TA, int TB> DEVINL void wg_ss8(float* d, uint64_t da, uint64_t db, int sc) {
    asm volatile("{ .reg .pred p; setp.ne.b32 p, %6, 0; wgmma.mma_async.sync.aligned.m64n8k16.f32.bf16.bf16 {%0,%1,%2,%3}, %4, %5, p, 1, 1, %7, %8; }"
                 : "+f"(d[0]), "+f"(d[1]), "+f"(d[2]), "+f"(d[3]) : "l"(da), "l"(db), "r"(sc), "n"(TA), "n"(TB));
}
template <int TB> DEVINL void wg_rs8(float* d, const uint32_t* a, uint64_t db, int sc) {
    asm volatile("{ .reg .pred p; setp.ne.b32 p, %9, 0; wgmma.mma_async.sync.aligned.m64n8k16.f32.bf16.bf16 {%0,%1,%2,%3}, {%4,%5,%6,%7}, %8, p, 1, 1, %10; }"
                 : "+f"(d[0]), "+f"(d[1]), "+f"(d[2]), "+f"(d[3]) : "r"(a[0]), "r"(a[1]), "r"(a[2]), "r"(a[3]), "l"(db), "r"(sc), "n"(TB));
}
#define ACC16(d) "+f"(d[0]), "+f"(d[1]), "+f"(d[2]), "+f"(d[3]), "+f"(d[4]), "+f"(d[5]), "+f"(d[6]), "+f"(d[7]), "+f"(d[8]), "+f"(d[9]), "+f"(d[10]), "+f"(d[11]), "+f"(d[12]), "+f"(d[13]), "+f"(d[14]), "+f"(d[15])
template <int TA> DEVINL void wg_ss32(float* d, uint64_t da, uint64_t db, int sc) {
    asm volatile("{ .reg .pred p; setp.ne.b32 p, %18, 0; wgmma.mma_async.sync.aligned.m64n32k16.f32.bf16.bf16 {%0,%1,%2,%3,%4,%5,%6,%7,%8,%9,%10,%11,%12,%13,%14,%15}, %16, %17, p, 1, 1, %19, 0; }"
                 : ACC16(d) : "l"(da), "l"(db), "r"(sc), "n"(TA));
}
DEVINL void wg_rs32(float* d, const uint32_t* a, uint64_t db, int sc) {
    asm volatile("{ .reg .pred p; setp.ne.b32 p, %21, 0; wgmma.mma_async.sync.aligned.m64n32k16.f32.bf16.bf16 {%0,%1,%2,%3,%4,%5,%6,%7,%8,%9,%10,%11,%12,%13,%14,%15}, {%16,%17,%18,%19}, %20, p, 1, 1, 0; }"
                 : ACC16(d) : "r"(a[0]), "r"(a[1]), "r"(a[2]), "r"(a[3]), "l"(db), "r"(sc));
}
DEVINL void wg_ss40(float* d, uint64_t da, uint64_t db, int sc) {
    asm volatile("{ .reg .pred p; setp.ne.b32 p, %22, 0; wgmma.mma_async.sync.aligned.m64n40k16.f32.bf16.bf16 {%0,%1,%2,%3,%4,%5,%6,%7,%8,%9,%10,%11,%12,%13,%14,%15,%16,%17,%18,%19}, %20, %21, p, 1, 1, 1, 1; }"
                 : ACC16(d), "+f"(d[16]), "+f"(d[17]), "+f"(d[18]), "+f"(d[19]) : "l"(da), "l"(db), "r"(sc));
}
#define A8(d, o) "+f"(d[o]), "+f"(d[o + 1]), "+f"(d[o + 2]), "+f"(d[o + 3]), "+f"(d[o + 4]), "+f"(d[o + 5]), "+f"(d[o + 6]), "+f"(d[o + 7])
#define A32(d, o) A8(d, o), A8(d, o + 8), A8(d, o + 16), A8(d, o + 24)
DEVINL void wg_ss256(float* d, uint64_t da, uint64_t db, int sc) {
    asm volatile(
        "{ .reg .pred p; setp.ne.b32 p, %130, 0;\n"
        "wgmma.mma_async.sync.aligned.m64n256k16.f32.bf16.bf16 {"
        "%0,%1,%2,%3,%4,%5,%6,%7,%8,%9,%10,%11,%12,%13,%14,%15,%16,%17,%18,%19,%20,%21,%22,%23,%24,%25,%26,%27,%28,%29,%30,%31,"
        "%32,%33,%34,%35,%36,%37,%38,%39,%40,%41,%42,%43,%44,%45,%46,%47,%48,%49,%50,%51,%52,%53,%54,%55,%56,%57,%58,%59,%60,%61,%62,%63,"
        "%64,%65,%66,%67,%68,%69,%70,%71,%72,%73,%74,%75,%76,%77,%78,%79,%80,%81,%82,%83,%84,%85,%86,%87,%88,%89,%90,%91,%92,%93,%94,%95,"
        "%96,%97,%98,%99,%100,%101,%102,%103,%104,%105,%106,%107,%108,%109,%110,%111,%112,%113,%114,%115,%116,%117,%118,%119,%120,%121,%122,%123,%124,%125,%126,%127"
        "}, %128, %129, p, 1, 1, 0, 1; }"
        : A32(d, 0), A32(d, 32), A32(d, 64), A32(d, 96) : "l"(da), "l"(db), "r"(sc));
}

DEVINL float gate_row(const bf16* __restrict__ xr, const bf16* __restrict__ gate_w, int lane) {
    float acc = 0.f;
#pragma unroll
    for (int i = 0; i < 4; i++) {
        const uint4 xv = __ldg((const uint4*)xr + i * 32 + lane), gv = __ldg((const uint4*)gate_w + i * 32 + lane);
        const uint32_t xa[4] = {xv.x, xv.y, xv.z, xv.w}, ga[4] = {gv.x, gv.y, gv.z, gv.w};
#pragma unroll
        for (int e = 0; e < 4; e++) {
            acc = fmaf(__uint_as_float(xa[e] << 16), __uint_as_float(ga[e] << 16), acc);
            acc = fmaf(__uint_as_float(xa[e] & 0xffff0000u), __uint_as_float(ga[e] & 0xffff0000u), acc);
        }
    }
#pragma unroll
    for (int o = 16; o > 0; o >>= 1) acc += __shfl_xor_sync(0xffffffffu, acc, o);
    return 1.0f / (1.0f + __expf(-acc));
}
DEVINL uint32_t ld_strong4(const void* p) { uint32_t v; asm volatile("ld.relaxed.gpu.global.u32 %0, [%1];" : "=r"(v) : "l"(p) : "memory"); return v; }
DEVINL void wait_count(const uint32_t* p, uint32_t want) {
    uint32_t v, n = 0;
    while (true) {
        asm volatile("ld.acquire.gpu.global.u32 %0, [%1];" : "=r"(v) : "l"(p) : "memory");
        if (v >= want) break;
        __nanosleep(200);
        if (++n > 10000000u) __trap();
    }
}

constexpr int KR = 44;
constexpr int KS = 64 - KR;
constexpr int R_W = 0;
constexpr int R_WO = KS * 4096;
constexpr int R_QX = R_WO + 65536;
constexpr int R_RING = R_WO + 98304;
constexpr int R_K = R_RING + 24576;
constexpr int R_V = R_K + 10240;
constexpr int R_QM = R_V + 10240;
constexpr int R_O = R_QM + 2048;
constexpr int R_BAR = R_O + 2048;
constexpr int R_G = R_BAR + 256 + 512 + 256 + 128;
constexpr int R_Z = R_G + 256;
constexpr int R_SMEM = R_Z + 1024;
enum { B_FULL = 0, B_EMPTY = 5, B_MEM = 8, B_HOP1 = 12, B_XT, B_TFREE, B_O, B_AFREE0, B_AFREE1, B_PRO0, B_PRO1, B_XRECV, B_P, B_XDONE, B_OST0, B_OST1, B_HOPV };
#define D2_BASE 800
#define D2_STEP 250
#define PD2 6
#define CPB 8192
#define DDUP 0
#define WGAP 0
#define DQ 1700
#define D3 0

DEVINL uint32_t clk32() { uint32_t c_; asm volatile("mov.u32 %0, %%clock;" : "=r"(c_)); return c_; }
DEVINL void spin_until(uint32_t t) { while ((uint32_t)(t - clk32() - 1u) < 100000u) {} }
#define PROF(i)
#define PROF2(i)
#define PROF3(i, val)
DEVINL void e_arrive(uint32_t bar) { asm volatile("{ .reg .pred p; elect.sync _|p, 0xffffffff; @p mbarrier.arrive.shared::cta.b64 _, [%0]; }" ::"r"(bar) : "memory"); }
DEVINL void e_arrive_remote(uint32_t cbar) { asm volatile("{ .reg .pred p; elect.sync _|p, 0xffffffff; @p mbarrier.arrive.relaxed.cluster.shared::cluster.b64 _, [%0]; }" ::"r"(cbar) : "memory"); }
DEVINL void e_count(uint32_t* p) { asm volatile("{ .reg .pred p; elect.sync _|p, 0xffffffff; @p red.relaxed.gpu.global.add.u32 [%0], 1; }" ::"l"(p) : "memory"); }
DEVINL void e_expect(uint32_t bar, uint32_t bytes) { asm volatile("{ .reg .pred p; elect.sync _|p, 0xffffffff; @p mbarrier.arrive.expect_tx.shared::cta.b64 _, [%0], %1; }" ::"r"(bar), "r"(bytes) : "memory"); }
DEVINL void e_tma_load(uint32_t dst, const CUtensorMap* tm, int c0, int c1, uint32_t bar) {
    asm volatile("{ .reg .pred p; elect.sync _|p, 0xffffffff; @p cp.async.bulk.tensor.2d.shared::cluster.global.mbarrier::complete_tx::bytes [%0], [%1, {%3, %4}], [%2]; }"
                 ::"r"(dst), "l"(tm), "r"(bar), "r"(c0), "r"(c1) : "memory");
}
DEVINL void e_tma_store(const CUtensorMap* tm, uint32_t src, int c0, int c1) {
    asm volatile("{ .reg .pred p; elect.sync _|p, 0xffffffff; @p cp.async.bulk.tensor.2d.global.shared::cta.bulk_group [%0, {%2, %3}], [%1]; }" ::"l"(tm), "r"(src), "r"(c0), "r"(c1) : "memory");
}
DEVINL void e_bulk_s2g(void* dst, uint32_t src, uint32_t bytes) {
    asm volatile("{ .reg .pred p; elect.sync _|p, 0xffffffff; @p cp.async.bulk.global.shared::cta.bulk_group [%0], [%1], %2; }" ::"l"(dst), "r"(src), "r"(bytes) : "memory");
}
DEVINL void e_bulk_s2s(uint32_t cdst, uint32_t src, uint32_t bytes, uint32_t cbar) {
    asm volatile("{ .reg .pred p; elect.sync _|p, 0xffffffff; @p cp.async.bulk.shared::cluster.shared::cta.mbarrier::complete_tx::bytes [%0], [%1], %2, [%3]; }" ::"r"(cdst), "r"(src), "r"(bytes), "r"(cbar) : "memory");
}

#define SLOT 0
#define PH3 0
#define PHQ 0
DEVINL void wait_slot(uint32_t phase) {
    if (SLOT) {
        uint32_t c; asm volatile("mov.u32 %0, %%globaltimer_lo;" : "=r"(c));
        const uint32_t tgt = c + (SLOT ? SLOT : 1) - ((c - phase) % (SLOT ? SLOT : 1));
        do { asm volatile("mov.u32 %0, %%globaltimer_lo;" : "=r"(c)); } while ((uint32_t)(tgt - c - 1u) < 100000u);
    }
}
template <int N> DEVINL uint32_t poll_set(uint4 (&v)[N], const uint32_t* rp, int stride, uint32_t phase, uint32_t wbar = 0, uint32_t wpar = 0) {
    wait_slot(phase);
#pragma unroll
    for (int i = 0; i < N; i++) v[i] = ld_strong16(rp + i * stride);
    if (wbar) mbar_wait(wbar, wpar);
    uint32_t n = 0;
    while (true) {
        uint32_t m = 0xffffffffu;
#pragma unroll
        for (int i = 0; i < N; i++) m = min4(v[i], m);
        if (__all_sync(0xffffffffu, m != 0u)) return n;
        wait_slot(phase);
#pragma unroll
        for (int i = 0; i < N; i++)
            asm volatile("{ .reg .pred p; setp.eq.u32 p, %5, 0; @p ld.relaxed.gpu.global.v4.u32 {%0,%1,%2,%3}, [%4]; }"
                         : "+r"(v[i].x), "+r"(v[i].y), "+r"(v[i].z), "+r"(v[i].w) : "l"(rp + i * stride), "r"(min4(v[i], 0xffffffffu)) : "memory");
        if (++n > 20000000u) __trap();
    }
}

struct RMaps { CUtensorMap x, w[3], wo, o; };
#define KC(c) ((c) * 64)

#define XORD 3
__host__ __device__ constexpr int xo(int i) {
    return XORD == 0 ? i : XORD == 1 ? (i + 14) % 16 : XORD == 2 ? (i + 11) % 16
         : XORD == 3 ? (i < 10 ? ((i & 1) ? i / 2 : 11 + i / 2) : i - 5) : (i < 6 ? i : ((i & 1) ? 6 + (i - 6) / 2 : 11 + (i - 6) / 2));
}
#define XC(i) (xo(i) * 64)
DEVINL void x_load_pair(uint32_t dst, const CUtensorMap* tmx, int h, int p, int seg, uint32_t fbar) {
    e_expect(fbar, 8192);
    e_tma_load(dst, tmx, XC(2 * p), seg * SEG, fbar);
    e_tma_load(dst + 4096, tmx, XC(2 * p + 1), seg * SEG, fbar);
}
__host__ __device__ constexpr int wo_tile(int role, int i) {
    return role == 0 ? (i < 2 ? 4 + i : 8 + i) : (i >> 1) * 6 + (role - 1) * 2 + (i & 1);
}

template <int NT> DEVINL void wo_phase(uint32_t sb, int tb, uint32_t* pp, uint32_t obar, uint32_t opar) {
    const int lane = tb & 31, krow = (lane & 7) + ((lane >> 4) << 3), chunk = ((tb >> 5) & 3) * 2 + ((lane >> 3) & 1);
    uint32_t wa = sb + R_WO + (tb >> 7) * 16384 + krow * 128 + ((chunk ^ (krow & 7)) << 4);
    uint32_t af[4][4], bf[4][4], of[4][4];
#pragma unroll
    for (int g = 0; g < 4; g++) ldsm4t(af[g], wa + g * 2048);
    mbar_wait(obar, opar);
#pragma unroll
    for (int g = 0; g < 4; g++) ldsm4t(of[g], sb + R_O + g * 512 + lane * 16);
#pragma unroll 1
    for (int i = 0; i < NT; i++) {
        float w0[4] = {0.f, 0.f, 0.f, 0.f}, w1[4] = {0.f, 0.f, 0.f, 0.f};
        mma16816(w0, af[0][0], af[0][1], af[0][2], af[0][3], of[0][0], of[0][1]);
        ldsm4t(af[0], wa + 4 * 2048);
        mma16816(w1, af[1][0], af[1][1], af[1][2], af[1][3], of[0][2], of[0][3]);
        ldsm4t(af[1], wa + 5 * 2048);
        mma16816(w0, af[2][0], af[2][1], af[2][2], af[2][3], of[1][0], of[1][1]);
        ldsm4t(af[2], wa + 6 * 2048);
        mma16816(w1, af[3][0], af[3][1], af[3][2], af[3][3], of[1][2], of[1][3]);
        ldsm4t(af[3], wa + 7 * 2048);
        wa += (i + 1 < NT) ? 32768 : 0;
        mma16816(w0, af[0][0], af[0][1], af[0][2], af[0][3], of[2][0], of[2][1]);
        ldsm4t(af[0], wa);
        mma16816(w1, af[1][0], af[1][1], af[1][2], af[1][3], of[2][2], of[2][3]);
        ldsm4t(af[1], wa + 2048);
        mma16816(w0, af[2][0], af[2][1], af[2][2], af[2][3], of[3][0], of[3][1]);
        ldsm4t(af[2], wa + 2 * 2048);
        mma16816(w1, af[3][0], af[3][1], af[3][2], af[3][3], of[3][2], of[3][3]);
        ldsm4t(af[3], wa + 3 * 2048);
        st_strong4(pp, pack_nz(w0[0] + w1[0], w0[1] + w1[1]));
        st_strong4(pp + 1024, pack_nz(w0[2] + w1[2], w0[3] + w1[3]));
        pp += 6 * 8192;
    }
    (void)bf;
}

DEVINL void o_store(const RMaps& tm, uint32_t sb, uint32_t bar, int wq, int h, int s) {
    mbar_wait(bar + 8 * B_OST0 + (wq >> 2) * 8, s & 1);
    fence_async();
    const uint32_t src = sb + R_QX + 2048 + (wq >> 2) * 8192;
    e_tma_store(&tm.o, src, h * DH + (wq >> 2) * 64, s * SEG);
    e_tma_store(&tm.o, src + 4096, h * DH + (wq >> 2) * 64, s * SEG + 16);
    bulk_commit();
}

template <uint32_t role> DEVINL void r_big(const RMaps& tm, const int wid) {
    extern __shared__ __align__(1024) unsigned char smem_raw[];
    const uint32_t sb = smem_u32(smem_raw);
    const uint32_t bar = sb + R_BAR;
    const int tid = threadIdx.x;
    int h; asm("mov.u32 %0, %%clusterid.x;" : "=r"(h));
        uint32_t a[KR][4];
        mbar_wait(bar + 8 * B_PRO0, 0);
        PT(0);
        {
            const int lane = tid & 31;
            const int krow = (lane & 7) + ((lane >> 4) << 3);
            const int chunk = (wid & 3) * 2 + ((lane >> 3) & 1);
            const uint32_t la = sb + (wid >> 2) * 8192 + krow * 128 + ((chunk ^ (krow & 7)) << 4);
#pragma unroll
            for (int k = 0; k < KR; k++) ldsm4t(a[k], la + (k >> 2) * 16384 + (k & 3) * 2048);
        }
        bar_sync(1, 256);
        {
            fence_async();
            const CUtensorMap* tw = &tm.w[role];
            e_expect(bar + 8 * B_PRO1, (wid < 5 ? 16384 : 0) + (wid < (role == 0 ? 4 : 6) ? 16384 : 0));
            if (wid < 5) {
                e_tma_load(sb + R_W + wid * 8192, tw, h * DH, KC(KR / 4 + wid), bar + 8 * B_PRO1);
                e_tma_load(sb + R_W + KS * 2048 + wid * 8192, tw, h * DH + 64, KC(KR / 4 + wid), bar + 8 * B_PRO1);
            }
            if (wid < (role == 0 ? 4 : 6)) e_tma_load(sb + R_WO + wid * 16384, &tm.wo, wo_tile(role, wid) * 64, h * DH, bar + 8 * B_PRO1);
        }
        constexpr uint32_t e0 = role == 0 ? R_QX + 16384 : R_K + 2048, e1 = role == 0 ? R_QX + 24576 : R_V + 2048;
        if (wid == 6) x_load_pair(sb + e0, &tm.x, h, 3, 0, bar + 8 * (B_FULL + 3));
        if (wid == 7) x_load_pair(sb + e1, &tm.x, h, 4, 0, bar + 8 * (B_FULL + 4));
        PT(1);
        mbar_wait(bar + 8 * B_PRO1, 0);
        PT(2);

        constexpr uint64_t dW0 = cdesc(R_W, 1024, 1024, 1);
        constexpr uint64_t dM = cdesc(R_RING, 128, 128, 0);
        constexpr uint64_t dX = cdesc(R_RING, 16, 1024, 1);
        constexpr uint64_t dX0 = cdesc(0, 16, 1024, 1);
        int tb = tid;
        int wq = wid;

        float d[16];
        for (int s = -1; s < NSEG; s++) {
            if (s >= 0) {
                OPAQUE(wq);
                const uint64_t dW = dW0 + (uint64_t)((wq >> 2) * (KS * 128));
                float y[4] = {0.f, 0.f, 0.f, 0.f};
                {
                    OPAQUE(tb);
                    const uint32_t ma = sb + R_RING + (tb & 31) * 16;
                    float z[4] = {0.f, 0.f, 0.f, 0.f}, u[4] = {0.f, 0.f, 0.f, 0.f};
                    uint32_t b[4][4];
                    mbar_wait(bar + 8 * B_MEM, s & 1);
                    PROF((wq >> 2) * 4 + 0);
                    if (s == 0) PT(3);
                    if (s == 1) PT(4);
#pragma unroll
                    for (int g = 0; g < 4; g++) ldsm4t(b[g], ma + g * 512);
#pragma unroll
                    for (int g = 0; g < KR / 2; g++) {
                        float* c0 = (g % 3 == 0) ? y : (g % 3 == 1) ? u : z;
                        float* c1 = (g % 3 == 0) ? z : (g % 3 == 1) ? y : u;
                        mma16816(c0, a[2 * g][0], a[2 * g][1], a[2 * g][2], a[2 * g][3], b[g & 3][0], b[g & 3][1]);
                        mma16816(c1, a[2 * g + 1][0], a[2 * g + 1][1], a[2 * g + 1][2], a[2 * g + 1][3], b[g & 3][2], b[g & 3][3]);
                        if (g + 4 < KR / 2) {
                            if ((g + 4) % 8 == 0) mbar_wait(bar + 8 * (B_MEM + (g + 4) / 8), s & 1);
                            ldsm4t(b[g & 3], ma + (g + 4) * 512);
                        }
                    }
                    y[0] += z[0] + u[0]; y[1] += z[1] + u[1]; y[2] += z[2] + u[2]; y[3] += z[3] + u[3];
                }
                PROF2(8);
                mbar_wait(bar + 8 * (B_MEM + 3), s & 1);
                wg_fence();
#pragma unroll
                for (int k = KR; k < 64; k++) wg_ss8<1, 1>(y, dW + (uint64_t)((k - KR) * 128), dM + (uint64_t)(k * 16), 1);
                wg_commit();
                asm volatile("wgmma.wait_group.sync.aligned 0;" : "+f"(y[0]), "+f"(y[1]), "+f"(y[2]), "+f"(y[3])::"memory");
                OPAQUE(tb);
                {
                    const uint32_t wo_ = (tb >> 5) * 256;
                    const uint32_t tile = sb + (role == 0 ? R_QX : (role == 1 ? R_K : R_V)) + wo_;
                    const uint32_t u0 = pack_bf16(y[0], y[1]), u1 = pack_bf16(y[2], y[3]);
                    sts32(tile + (tb & 31) * 4, u0);
                    sts32(tile + (tb & 31) * 4 + 128, u1);
                    __syncwarp();
                    uint4 v = lds128(tile + (tb & 15) * 16);
                    uint32_t peer = role + 1 + ((tb >> 4) & 1);
                    peer = peer >= 3 ? peer - 3 : peer;
                    const uint32_t rt = sb + (role == 0 ? R_QM : (role == 1 ? R_K : R_V)) + wo_ + (tb & 15) * 16;
                    st_async16(mapa(rt, peer), v, mapa(bar + 8 * (role == 2 ? B_HOPV : B_HOP1), peer));
                    if (role == 0) {
                        sts128(tile + 4096 + ((tb >> 4) & 1) * 4096 + (tb & 15) * 16, v);
                        sts32(tile + 12288 + (tb & 31) * 4, u0);
                        sts32(tile + 12288 + (tb & 31) * 4 + 128, u1);
                        __syncwarp();
                    }
                    e_arrive(bar + 8 * (role == 2 ? B_HOPV : B_HOP1));
                }
                PROF((wq >> 2) * 4 + 1);
                if (s < NSEG - 1) {
                    bar_sync(1, 256);
                    if (wq < 2) { fence_async(); x_load_pair(sb + R_RING + wq * 8192, &tm.x, h, wq, s + 1, bar + 8 * (B_FULL + wq)); }
                    OPAQUE(tb);
                }
                uint32_t* pp = g_part[s & 3] + (h * 32 + (wo_tile(role, 0) + (tb >> 7)) * 8192 + ((tb >> 5) & 3) * 2048 + (tb & 31));
                asm volatile("" : "+l"(pp));
                if (role != 0) {
                    if (s < NSEG - 1) {
                        wo_phase<3>(sb, tb, pp, bar + 8 * B_O, s & 1);
                    }
                } else {
                    constexpr uint64_t dV = cdesc(R_V, 2048, 128, 0);
                    constexpr uint64_t dP = cdesc(R_QX, 128, 4096, 0);
                    if ((wq & 3) == 0 && s >= 1) { bulk_wait_all(); e_count(&g_ocnt[(s - 1) >> 2]); }
                    wo_phase<2>(sb, tb, pp, bar + 8 * B_O, s & 1);
                    mbar_wait(bar + 8 * B_P, s & 1);
                    float sf[8];
#pragma unroll
                    for (int j = 0; j < 4; j++) asm volatile("ld.shared.v2.f32 {%0,%1}, [%2];" : "=f"(sf[2 * j]), "=f"(sf[2 * j + 1]) : "r"(sb + R_G + 128 + j * 32 + (tb & 3) * 8) : "memory");
                    wg_fence();
#pragma unroll
                    for (int k = 0; k < 3; k++) wg_ss32<0>(d, dV + (uint64_t)((wq >> 2) * 64 + k * 256), dP + (uint64_t)(k * 16), k);
                    wg_commit();
                    asm volatile("wgmma.wait_group.sync.aligned 0;" : ACC16(d)::"memory");
                    if ((wq & 3) == 1 || (wq & 3) == 2) e_arrive_remote(mapa(bar + 8 * B_TFREE, wq & 3));
                    OPAQUE(tb);
                    const uint32_t r = ((tb >> 4) & 1) * 8 + (tb & 7), ch = ((tb >> 5) & 3) * 2 + ((tb >> 3) & 1);
                    const uint32_t oa = sb + R_QX + 2048 + (tb >> 7) * 8192 + r * 128 + ((ch ^ (r & 7)) << 4);
                    stsm4t(oa, pack_bf16(d[0] * sf[0], d[1] * sf[1]), pack_bf16(d[2] * sf[0], d[3] * sf[1]), pack_bf16(d[4] * sf[2], d[5] * sf[3]), pack_bf16(d[6] * sf[2], d[7] * sf[3]));
                    stsm4t(oa + 4096, pack_bf16(d[8] * sf[4], d[9] * sf[5]), pack_bf16(d[10] * sf[4], d[11] * sf[5]), pack_bf16(d[12] * sf[6], d[13] * sf[7]), pack_bf16(d[14] * sf[6], d[15] * sf[7]));
                    __syncwarp();
                    e_arrive(bar + 8 * B_OST0 + (wq >> 2) * 8);
                }
                if (wq == 0) PROF(10);
                if (s == NSEG - 1) {
                    if (role == 0 && (wq & 3) == 0) { o_store(tm, sb, bar, wq, h, s); bulk_wait_all(); }
                    break;
                }
            }
            const int seg = s + 1;
            OPAQUE(wq);
            const uint64_t dW = dW0 + (uint64_t)((wq >> 2) * (KS * 128));
#pragma unroll
            for (int p = 0; p < 8; p++) {
                const int slot = p % 5;
                mbar_wait(bar + 8 * (B_FULL + slot), slot < 3 ? (uint32_t)(p / 5) : (uint32_t)(seg & 1));
                PROF2(p);
                const uint64_t db = slot < 3 ? dX + (uint64_t)(slot * 512) : dX0 + (uint64_t)((slot == 3 ? e0 : e1) >> 4);
                wg_fence();
#pragma unroll
                for (int kk = 0; kk < 8; kk++) {
                    const int k = XORD >= 3 ? (kk & 1) * 4 + (kk >> 1) : kk;
                    const int ks = xo(2 * p + (k >> 2)) * 4 + (k & 3);
                    if (ks >= KR) wg_ss32<1>(d, dW + (uint64_t)((ks - KR) * 128), db + (uint64_t)((k >> 2) * 256 + (k & 3) * 2), p + k);
                    else wg_rs32(d, a[ks < KR ? ks : 0], db + (uint64_t)((k >> 2) * 256 + (k & 3) * 2), p + k);
                }
                wg_commit();
                if (p == 0 && role == 0 && (wq & 3) == 0 && s >= 0) o_store(tm, sb, bar, wq, h, s);
                if (p >= 1) {
                    wg_wait<1>();
                    if (p <= 3) {
                        if ((wq & 3) == p) e_arrive(bar + 8 * (B_EMPTY + p - 1));
                        if (wq == p + (p & 1) * 4) {
                            mbar_wait(bar + 8 * (B_EMPTY + p - 1), seg & 1);
                            x_load_pair(sb + R_RING + (p - 1) * 8192, &tm.x, h, p + 4, seg, bar + 8 * (B_FULL + p - 1));
                        }
                    }
                    if (p == 5 && (wq & 3) < ((role == 0 && s >= 0) ? 1 : 3)) {
                        if (role == 0) bulk_wait_read();
                        e_arrive_remote(mapa(bar + 8 * B_TFREE, wq & 3));
                    }
                    if (p == 6 && (wq & 3) == 1) e_arrive(bar + 8 * B_AFREE0);
                    if (p == 7 && (wq & 3) == 2) e_arrive(bar + 8 * B_AFREE1);
                }
            }
            asm volatile("wgmma.wait_group.sync.aligned 0;" : ACC16(d)::"memory");
            PROF2(16);
            mbar_wait(bar + 8 * B_TFREE, seg & 1);
            const uint32_t tilex = sb + (role == 0 ? R_QX + 2048 : (role == 1 ? R_K + 2048 : R_V + 2048));
            {
                OPAQUE(tb);
                const uint32_t gs = role == 0 ? 4096 : 2048;
                const uint32_t sa = tilex + ((tb >> 4) & 1) * gs + (tb >> 5) * 256 + (tb & 15) * 16;
                stsm4(sa, pack_bf16(d[0], d[1]), pack_bf16(d[2], d[3]), pack_bf16(d[4], d[5]), pack_bf16(d[6], d[7]));
                stsm4(sa + 2 * gs, pack_bf16(d[8], d[9]), pack_bf16(d[10], d[11]), pack_bf16(d[12], d[13]), pack_bf16(d[14], d[15]));
            }
            __syncwarp();
            e_arrive(bar + 8 * B_XDONE);
            if (role != 0 && (wq & 3) == 0) {
                mbar_wait(bar + 8 * B_XDONE, seg & 1);
                fence_async();
                uint32_t pr = role + 1 + (wq >> 2); pr = pr >= 3 ? pr - 3 : pr;
                e_bulk_s2s(mapa(tilex, pr), tilex, CPB, mapa(bar + 8 * B_XT, pr));
            }
        }
}

#define CLR 0
#define CLEAR(st) do { if (role != 0) { \
                const int w_ = wid & 3; \
                uint32_t* zp = g_part[(st) & 3] + ((rg0 + (w_ >> 1) * 64) * 1024 + (w_ & 1) * 512); \
                e_bulk_s2g(zp, sb + R_Z, 1024); \
                e_bulk_s2g(zp + 256, sb + R_Z, 1024); \
                e_bulk_s2g(&g_mem[(st) & 3][(rg0 + (w_ >> 1) * 64) * 32 + (w_ & 1) * 16], sb + R_Z, 64); \
                bulk_commit(); } } while (0)
template <uint32_t role> DEVINL void r_chain(const RMaps& tm, const bf16* __restrict__ mem0, const bf16* __restrict__ x, const bf16* __restrict__ gate_w, const int wid) {
    extern __shared__ __align__(1024) unsigned char smem_raw[];
    const uint32_t sb = smem_u32(smem_raw);
    const uint32_t bar = sb + R_BAR;
    const int tid = threadIdx.x;
    int h; asm("mov.u32 %0, %%clusterid.x;" : "=r"(h));
        int t = tid & 127;
        const float sl2 = 0.08838834764831845f * 1.4426950408889634f;
        const float NEGRAW = -1000000000.0f / 0.08838834764831845f;
        const int rg0 = ((int)role - 1) * 32 + h;
        if (role != 0) {
#pragma unroll 1
            for (int r = 0; r < 4; r++) {
                uint32_t* zp = g_part[r] + ((rg0 + (t >> 6) * 64) * 1024 + (t & 63) * 4);
#pragma unroll
                for (int i = 0; i < 4; i++) st_strong16(zp + i * 256, make_uint4(0u, 0u, 0u, 0u));
                if ((t & 63) < 8) st_strong16(&g_mem[r][(rg0 + (t >> 6) * 64) * 32 + (t & 63) * 4], make_uint4(0u, 0u, 0u, 0u));
            }
            __threadfence();
        }
        {
#pragma unroll 1
            for (int r = (h * 3 + (int)role) * 4 + (t >> 5); r < SEQ; r += 384) {
                const uint32_t gb = __float_as_uint(gate_row(x + r * DM, gate_w, t & 31));
                if ((t & 31) == 0) st_strong4(&g_gate[r], gb ? gb : 0x80000000u);
            }
        }
        if (t < 64) sts128(sb + R_Z + t * 16, make_uint4(0u, 0u, 0u, 0u));
        if (role == 0) sts128(sb + R_QM + t * 16, make_uint4(0u, 0u, 0u, 0u));
        {
            uint4 v[8];
#pragma unroll
            for (int r = 0; r < 8; r++) v[r] = __ldg((const uint4*)(mem0 + r * DM) + t);
            mbar_wait(bar + 8 * B_AFREE0, 0);
            mbar_wait(bar + 8 * B_AFREE1, 0);
#define TR2(f, c) \
            sts128(sb + R_RING + t * 128 + (c) * 16, make_uint4(__byte_perm(v[0].f, v[1].f, 0x5410), __byte_perm(v[2].f, v[3].f, 0x5410), __byte_perm(v[4].f, v[5].f, 0x5410), __byte_perm(v[6].f, v[7].f, 0x5410))); \
            sts128(sb + R_RING + t * 128 + (c) * 16 + 16, make_uint4(__byte_perm(v[0].f, v[1].f, 0x7632), __byte_perm(v[2].f, v[3].f, 0x7632), __byte_perm(v[4].f, v[5].f, 0x7632), __byte_perm(v[6].f, v[7].f, 0x7632)));
            TR2(x, 0) TR2(y, 2) TR2(z, 4) TR2(w, 6)
            fence_async();
            __syncwarp();
            e_arrive(bar + 8 * B_MEM + (t >> 5) * 8);
        }
        constexpr uint64_t dQ = role == 0 ? cdesc(R_QX, 128, 2048, 0) : cdesc(R_QM, 128, 0, 0);
        constexpr uint64_t dK = cdesc(R_K, 128, 2048, 0);

        for (int s = 0; s < NSEG; s++) {
            {
                const int w = wid & 3;
                mbar_wait(bar + 8 * B_XDONE, s & 1);
                if (s + 1 < NSEG) {
                    if (w == 2) x_load_pair(sb + R_RING + 16384, &tm.x, h, 2, s + 1, bar + 8 * (B_FULL + 2));
                    if (role == 0 && w < 2) x_load_pair(sb + R_QX + 16384 + w * 8192, &tm.x, h, 3 + w, s + 1, bar + 8 * (B_FULL + 3 + w));
                }
            }
            if (role == 0) {
                uint32_t n = 0, gate;
                do { gate = ld_strong4(&g_gate[s * SEG + (t >> 2)]); if (++n > 20000000u) __trap(); } while (gate == 0u);
                sts32(sb + R_G + (t >> 2) * 4, gate);
                __syncwarp();
            }
            mbar_wait(bar + 8 * B_XT, s & 1);
            if (t >= 1 && t < 3) { uint32_t pr = role + t; pr = pr >= 3 ? pr - 3 : pr; mbar_arrive_remote(mapa(bar + 8 * B_XRECV, pr)); }
            __syncwarp();
            mbar_wait(bar + 8 * B_HOP1, s & 1);
            PROF(8);
            fence_async();
            OPAQUE(t);
            if (s == NSEG - 1 && role != 0) { mbar_wait(bar + 8 * B_HOPV, s & 1); bulk_wait_all(); break; }
            float sc[20];
            wg_fence();
#pragma unroll
            for (int k = 0; k < 8; k++) wg_ss40(sc, dQ + (uint64_t)(k * 16), dK + (uint64_t)(k * 16), k);
            wg_commit();
            uint32_t t_o = clk32() + 500;
            {
                const uint32_t va = sb + R_V + 2048 + (t >> 5) * 512 + ((t >> 4) & 1) * 2048 + (t & 15) * 16;
                uint32_t v0[4], v1[4];
                ldsm4(v0, va); ldsm4(v1, va + 256);
                const int lim = (t >> 2) - (t & 3) * 2 + 8;
                wg_wait<0>();
                float m = fmaxf(sc[0], sc[1]), m1 = fmaxf(sc[2], sc[3]);
#pragma unroll
                for (int j = 1; j < 5; j++) {
                    m = fmaxf(m, fmaxf(sc[4 * j], sc[4 * j + 1]));
                    if (role == 0) {
                        sc[4 * j + 2] = 8 * j <= lim ? sc[4 * j + 2] : NEGRAW;
                        sc[4 * j + 3] = 8 * j + 1 <= lim ? sc[4 * j + 3] : NEGRAW;
                        m1 = fmaxf(m1, fmaxf(sc[4 * j + 2], sc[4 * j + 3]));
                    }
                }
                m = fmaxf(m, __shfl_xor_sync(0xffffffffu, m, 1));
                if (role == 0) m1 = fmaxf(m1, __shfl_xor_sync(0xffffffffu, m1, 1));
                m = fmaxf(m, __shfl_xor_sync(0xffffffffu, m, 2));
                if (role == 0) m1 = fmaxf(m1, __shfl_xor_sync(0xffffffffu, m1, 2));
                const float mb = m * sl2, mb1 = m1 * sl2;
                uint32_t pk[5], pt[5];
#pragma unroll
                for (int j = 0; j < 5; j++) pk[j] = pack_bf16(ex2(fmaf(sc[4 * j], sl2, -mb)), ex2(fmaf(sc[4 * j + 1], sl2, -mb)));
                float o0[4] = {0.f, 0.f, 0.f, 0.f}, o1[4] = {0.f, 0.f, 0.f, 0.f}, ls[4] = {0.f, 0.f, 0.f, 0.f}, lt[4] = {0.f, 0.f, 0.f, 0.f};
                constexpr uint32_t ONE = 0x3F803F80u;
                mma16816(o0, v0[0], v0[1], v0[2], v0[3], pk[1], pk[2]);
                mma16816(o1, v1[0], v1[1], v1[2], v1[3], pk[1], pk[2]);
                ldsm4(v0, va + 4096); ldsm4(v1, va + 4096 + 256);
                mma16816(ls, ONE, ONE, ONE, ONE, pk[1], pk[2]);
                mma16816(ls, ONE, ONE, ONE, ONE, pk[3], pk[4]);
                mma1688(ls, ONE, ONE, pk[0]);
                mma16816(o0, v0[0], v0[1], v0[2], v0[3], pk[3], pk[4]);
                mma16816(o1, v1[0], v1[1], v1[2], v1[3], pk[3], pk[4]);
                if (role == 0) {
#pragma unroll
                    for (int j = 0; j < 5; j++) pt[j] = pack_bf16(ex2(fmaf(sc[4 * j + 2], sl2, -mb1)), ex2(fmaf(sc[4 * j + 3], sl2, -mb1)));
                    mma16816(lt, pt[0], pt[1], pt[2], pt[3], ONE, ONE);
                    mma1688(lt, pt[4], 0u, ONE);
                }
                mbar_wait(bar + 8 * B_HOPV, s & 1);
                ldsm4(v0, sb + R_V + t * 16);
                mma1688(o0, v0[0], v0[1], pk[0]);
                mma1688(o1, v0[2], v0[3], pk[0]);
                const float i0 = __fdividef(1.0f, ls[0]), i1 = __fdividef(1.0f, ls[1]);
                const uint32_t oa = sb + R_O + (t >> 5) * 512 + (t & 31) * 4;
                sts32(oa, pack_bf16(o0[0] * i0, o0[1] * i1));
                sts32(oa + 128, pack_bf16(o0[2] * i0, o0[3] * i1));
                sts32(oa + 256, pack_bf16(o1[0] * i0, o1[1] * i1));
                sts32(oa + 384, pack_bf16(o1[2] * i0, o1[3] * i1));
                __syncwarp();
                e_arrive(bar + 8 * B_O);
                PROF(9);
                if (role == 0) {
                    const uint32_t pa = sb + R_QX + (t >> 5) * 4096 + (t & 31) * 4;
#pragma unroll
                    for (int j = 0; j < 5; j++) sts32(pa + j * 128, pt[j]);
                    sts32(pa + 5 * 128, 0u);
                    float gate; asm volatile("ld.shared.f32 %0, [%1];" : "=f"(gate) : "r"(sb + R_G + (t >> 2) * 4) : "memory");
                    sts32(sb + R_G + 128 + (t >> 2) * 4, __float_as_uint(__fdividef(gate, lt[0] + lt[2])));
                    fence_async();
                    __syncwarp();
                    e_arrive(bar + 8 * B_P);
                }
            }
            if (t < 32) { e_expect(bar + 8 * B_HOP1, role == 2 ? 4096 : 2048); if (role != 2) e_expect(bar + 8 * B_HOPV, 2048); e_expect(bar + 8 * B_XT, role == 0 ? 2 * CPB : CPB); }
            if (s == NSEG - 1) break;
            if (role != 0 && (wid & 3) >= 2) {
                mbar_wait(bar + 8 * B_XRECV, s & 1);
                mbar_wait(bar + 8 * B_O, s & 1);
                fence_async();
                x_load_pair(sb + ((wid & 1) ? R_V + 2048 : R_K + 2048), &tm.x, h, 3 + (wid & 1), s + 1, bar + 8 * (B_FULL + 3 + (wid & 1)));
            }
            OPAQUE(t);
            PROF(11);
            if (role != 0 || DDUP) {
                const int grp = role == 0 ? (t >> 6) * 32 + h : rg0 + (t >> 6) * 64;
                const uint32_t* rp = g_part[s & 3] + (grp * 1024 + ((t >> 2) & 7) * 32 + ((t >> 5) & 1) * 16 + (t & 3) * 4);
                uint32_t* wp = &g_mem[(s + 1) & 3][grp * 32 + ((t >> 5) & 1) * 16 + (t & 3) * 4 + ((t >> 3) & 3)];
                bulk_wait_all();
                spin_until(t_o + D2_BASE + (role == 0 ? DDUP + (t >> 6) * D2_STEP : (role - 1 + (t >> 6) * 2) * D2_STEP));
                PROF3(0, clk32());
#define LO(u) __uint_as_float((u) << 16)
#define HI(u) __uint_as_float((u) & 0xffff0000u)
                uint4 v[4];
                uint32_t n = poll_set<4>(v, rp, 256, (role - 1 + (t >> 6) * 2) * PHQ);
                {
                    PROF3(1, clk32());
                    float f[8];
                    f[0] = (LO(v[0].x) + LO(v[1].x)) + (LO(v[2].x) + LO(v[3].x)); f[1] = (HI(v[0].x) + HI(v[1].x)) + (HI(v[2].x) + HI(v[3].x));
                    f[2] = (LO(v[0].y) + LO(v[1].y)) + (LO(v[2].y) + LO(v[3].y)); f[3] = (HI(v[0].y) + HI(v[1].y)) + (HI(v[2].y) + HI(v[3].y));
                    f[4] = (LO(v[0].z) + LO(v[1].z)) + (LO(v[2].z) + LO(v[3].z)); f[5] = (HI(v[0].z) + HI(v[1].z)) + (HI(v[2].z) + HI(v[3].z));
                    f[6] = (LO(v[0].w) + LO(v[1].w)) + (LO(v[2].w) + LO(v[3].w)); f[7] = (HI(v[0].w) + HI(v[1].w)) + (HI(v[2].w) + HI(v[3].w));
                    const bool b4 = t & 16, b3 = t & 8;
                    float g4[4], g2[2];
#pragma unroll
                    for (int i = 0; i < 4; i++) g4[i] = (b4 ? f[4 + i] : f[i]) + __shfl_xor_sync(0xffffffffu, b4 ? f[i] : f[4 + i], 16);
#pragma unroll
                    for (int i = 0; i < 2; i++) g2[i] = (b3 ? g4[2 + i] : g4[i]) + __shfl_xor_sync(0xffffffffu, b3 ? g4[i] : g4[2 + i], 8);
                    g2[0] += __shfl_xor_sync(0xffffffffu, g2[0], 4);
                    g2[1] += __shfl_xor_sync(0xffffffffu, g2[1], 4);
                    st_strong4(wp, pack_nz(g2[0], g2[1]));
                }
                PROF3(8, n); (void)n;
            }
            t_o += D2_BASE + DQ + D3 + (t >> 5) * D2_STEP;
            OPAQUE(t);
            PROF(12);
            {
                const uint32_t* rp = &g_mem[(s + 1) & 3][((t >> 5) * 256 + (t & 31)) * 4];
                const uint32_t da = sb + R_RING + ((t >> 5) * 256 + (t & 31)) * 16;
                uint4 v[8];
                spin_until(t_o);
                PROF3(2, clk32());
                uint32_t n = poll_set<8>(v, rp, 128, PH3 + (t >> 5) * PHQ);
                PROF(13);
                PROF3(3, clk32()); PROF3(9, n); (void)n;
                mbar_wait(bar + 8 * B_AFREE0 + (t >> 6) * 8, (s + 1) & 1);
                PROF3(4, clk32());
#pragma unroll
                for (int i = 0; i < 8; i++) sts128(da + i * 512, v[i]);
                if (t >= 64) fence_async();
                __syncwarp();
                e_arrive(bar + 8 * B_MEM + (t >> 5) * 8);
                PROF(14);
                PROF3(5, clk32());
            }
            CLEAR(s + 3);
        }
}

__global__ void __launch_bounds__(384, 1) r_kernel(const __grid_constant__ RMaps tm, const bf16* __restrict__ mem0, const bf16* __restrict__ x, const bf16* __restrict__ gate_w) {
    extern __shared__ __align__(1024) unsigned char smem_raw[];
    const uint32_t sb = smem_u32(smem_raw);
    if ((sb & 0x3FFFFu) != SB0) __trap();
    const int tid = threadIdx.x;
    const int wid = __shfl_sync(0xffffffffu, tid >> 5, 0);
    uint32_t role; asm("mov.u32 %0, %%cluster_ctarank;" : "=r"(role));
    int h; asm("mov.u32 %0, %%clusterid.x;" : "=r"(h));
    const uint32_t bar = sb + R_BAR;
    asm volatile("griddepcontrol.launch_dependents;");
    KT(0, 0);

    if (tid == 0) {
        for (int i = 0; i < 5; i++) mbar_init(bar + 8 * (B_FULL + i), 1);
        for (int i = 0; i < 3; i++) mbar_init(bar + 8 * (B_EMPTY + i), 2);
        for (int i = 0; i < 4; i++) mbar_init(bar + 8 * (B_MEM + i), 1);
        mbar_init(bar + 8 * B_HOP1, role == 2 ? 1 : 9);
        mbar_init(bar + 8 * B_HOPV, role == 2 ? 8 : 1);
        mbar_init(bar + 8 * B_XT, 1);
        mbar_init(bar + 8 * B_TFREE, 6);
        mbar_init(bar + 8 * B_P, 4);
        mbar_init(bar + 8 * B_XDONE, 8);
        mbar_init(bar + 8 * B_OST0, 4);
        mbar_init(bar + 8 * B_OST1, 4);
        mbar_init(bar + 8 * B_XRECV, 2);
        mbar_init(bar + 8 * B_O, 4);
        mbar_init(bar + 8 * B_AFREE0, 2);
        mbar_init(bar + 8 * B_AFREE1, 2);
        mbar_init(bar + 8 * B_PRO0, 1);
        mbar_init(bar + 8 * B_PRO1, 8);
        asm volatile("fence.mbarrier_init.release.cluster;" ::: "memory");
        fence_async();
        mbar_expect(bar + 8 * B_PRO0, KR * 4096);
        for (int i = 0; i < 3; i++) mbar_expect(bar + 8 * (B_FULL + i), 8192);
        mbar_expect(bar + 8 * B_HOP1, role == 2 ? 4096 : 2048);
        if (role != 2) mbar_expect(bar + 8 * B_HOPV, 2048);
        mbar_expect(bar + 8 * B_XT, role == 0 ? 2 * CPB : CPB);
    }
    __syncthreads();
    asm volatile("barrier.cluster.arrive.relaxed.aligned;" ::: "memory");
    {
        const CUtensorMap* tw = &tm.w[role];
        if (wid < 11) {
            e_tma_load(sb + wid * 16384, tw, h * DH, KC(wid), bar + 8 * B_PRO0);
            e_tma_load(sb + wid * 16384 + 8192, tw, h * DH + 64, KC(wid), bar + 8 * B_PRO0);
        }
        if (wid < 6) e_tma_load(sb + R_RING + wid * 4096, &tm.x, XC(wid), 0, bar + 8 * (B_FULL + (wid >> 1)));
        if ((tid & 31) == 0) {
            if (wid < 10) tma_prefetch(tw, h * DH + (wid & 1) * 64, KC(KR / 4 + (wid >> 1)));
            if (wid >= 6 && wid - 6 < (role == 0 ? 4 : 6)) tma_prefetch(&tm.wo, wo_tile(role, wid - 6) * 64, h * DH);
            if (blockIdx.x < NSEG && wid < 8) { tma_prefetch(&tm.x, wid * 128, blockIdx.x * SEG); tma_prefetch(&tm.x, wid * 128 + 64, blockIdx.x * SEG); }
        }
        __syncwarp();
    }
    asm volatile("barrier.cluster.wait.aligned;" ::: "memory");

    if (wid < 8) {
        asm volatile("setmaxnreg.inc.sync.aligned.u32 224;");
        if (role == 0) r_big<0>(tm, wid); else if (role == 1) r_big<1>(tm, wid); else r_big<2>(tm, wid);
    } else {
        asm volatile("setmaxnreg.dec.sync.aligned.u32 56;");
        if (role == 0) r_chain<0>(tm, mem0, x, gate_w, wid); else if (role == 1) r_chain<1>(tm, mem0, x, gate_w, wid); else r_chain<2>(tm, mem0, x, gate_w, wid);
    }
    __syncwarp();
    asm volatile("barrier.cluster.arrive; barrier.cluster.wait;" ::: "memory");
    KT(0, 1);
}

constexpr int G_ST = 4;
constexpr int G_STAGE = 16384 + 32768;
constexpr int G_EPI = G_ST * G_STAGE;
constexpr int G_GATE = G_EPI + 32768;
constexpr int G_BAR = G_GATE + 1024;
constexpr int G_SMEM = G_BAR + 128 + 1024;

struct G1Maps { CUtensorMap x, wg, wu, hs, o, h, wo, wd, out; };
constexpr int G1_NB = FF / 128;
constexpr int G1_TILES = 16 * G1_NB;

DEVINL void g_mma_block(float* d, uint32_t sb, uint32_t bar, int it, int wg, int tid, bool first) {
    const int st = it % G_ST;
    mbar_wait(bar + 8 * st, (it / G_ST) & 1);
    const uint64_t da = mkdesc(sb + st * G_STAGE + wg * 8192, 16, 1024, 1);
    const uint64_t db = mkdesc(sb + st * G_STAGE + 16384, 8192, 1024, 1);
    wg_fence();
#pragma unroll
    for (int k = 0; k < 4; k++) wg_ss256(d, da + (uint64_t)(k * 2), db + (uint64_t)(k * 128), (first ? 0 : 1) | k);
    wg_commit();
    if (!first) { wg_wait<1>(); if ((tid & 127) == 0) mbar_arrive(bar + 8 * (G_ST + (it - 1) % G_ST)); }
}
DEVINL void g_load_block(uint32_t sb, uint32_t bar, int it, const CUtensorMap* ta, int k0, int m0, const CUtensorMap* tb, int n0) {
    const int st = it % G_ST;
    mbar_wait(bar + 8 * (G_ST + st), ((it / G_ST) & 1) ^ 1);
    const uint32_t fb = bar + 8 * st, sa = sb + st * G_STAGE;
    mbar_expect(fb, G_STAGE);
    tma_load(sa, ta, k0, m0, fb);
#pragma unroll
    for (int q = 0; q < 4; q++) tma_load(sa + 16384 + q * 8192, tb, n0 + q * 64, k0, fb);
}

DEVINL void g_store_tile(const float* d, const CUtensorMap* tout, uint32_t epi, int mb, int nb, int wg, int tid) {
    const int lane = tid & 31, row = ((tid >> 5) & 3) * 16 + ((lane >> 3) & 1) * 8 + (lane & 7);
#pragma unroll
    for (int half = 0; half < 2; half++) {
        if ((tid & 127) == 0) bulk_wait_read();
        bar_sync(1 + wg, 128);
#pragma unroll
        for (int j = 0; j < 16; j += 2) {
            const float* e = d + half * 64 + 4 * j;
            const int cgp = j + (lane >> 4);
            stsm4(epi + (cgp >> 3) * 8192 + row * 128 + (((cgp & 7) ^ (row & 7)) << 4),
                  pack_bf16(e[0], e[1]), pack_bf16(e[2], e[3]), pack_bf16(e[4], e[5]), pack_bf16(e[6], e[7]));
        }
        fence_async();
        bar_sync(1 + wg, 128);
        if ((tid & 127) == 0) {
            tma_store(tout, epi, nb * 256 + half * 128, mb * 128 + wg * 64);
            tma_store(tout, epi + 8192, nb * 256 + half * 128 + 64, mb * 128 + wg * 64);
            bulk_commit();
        }
    }
}
template <int NS> DEVINL void g_split_finish(const float* d, float4 (&r)[32 / NS], float4* sk, int tile, int ks, bf16* __restrict__ out, int tid) {
    constexpr int Q = 32 / NS;
    float4* mine = sk + ks * (32 * 256) + tid;
#pragma unroll
    for (int c = 0; c < NS; c++) {
        if (c != ks) {
#pragma unroll
            for (int q = c * Q; q < c * Q + Q; q++) __stcg(mine + q * 256, make_float4(d[4 * q], d[4 * q + 1], d[4 * q + 2], d[4 * q + 3]));
        } else {
#pragma unroll
            for (int q = 0; q < Q; q++) { const float* e = d + (c * Q + q) * 4; r[q].x += e[0]; r[q].y += e[1]; r[q].z += e[2]; r[q].w += e[3]; }
        }
    }
    __threadfence();
    bar_sync(3, 256);
    if (tid == 0) {
        atomicAdd(&g_skcnt[tile], 1u);
        uint32_t v, n = 0;
        do {
            asm volatile("ld.acquire.gpu.global.u32 %0, [%1];" : "=r"(v) : "l"(&g_skcnt[tile]) : "memory");
            if (++n > 200000000u) __trap();
        } while (v < NS);
        if (atomicAdd(&g_skcnt[tile], 1u) == 2 * NS - 1) g_skcnt[tile] = 0u;
    }
    bar_sync(3, 256);
#pragma unroll
    for (int c = 1; c < NS; c++) {
        const float4* th = sk + (((ks + c) & (NS - 1)) * 32 + ks * Q) * 256 + tid;
#pragma unroll
        for (int q = 0; q < Q; q++) { const float4 u = __ldcg(th + q * 256); r[q].x += u.x; r[q].y += u.y; r[q].z += u.z; r[q].w += u.w; }
    }
    const int lane = tid & 31;
    uint32_t* op = (uint32_t*)(out + ((tile >> 2) * 128 + (tid >> 5) * 16 + (lane >> 2)) * DM + (tile & 3) * 256 + ks * Q * 8 + (lane & 3) * 2);
#pragma unroll
    for (int q = 0; q < Q; q++) { op[q * 4] = pack_bf16(r[q].x, r[q].y); op[q * 4 + 4 * DM] = pack_bf16(r[q].z, r[q].w); }
}
DEVINL int g1_count(int pass) { return pass == 0 ? NPRE : pass == 1 ? NFULL : pass == 2 ? T_MID - NFULL : (T_LATE - T_MID) * 4; }
DEVINL int g1_first(int pass) { return pass == 2 ? (int)(gridDim.x - 1 - blockIdx.x) : (int)blockIdx.x; }

__global__ void __launch_bounds__(384, 1) g1_kernel(const __grid_constant__ G1Maps tm, bf16* __restrict__ out) {
    extern __shared__ __align__(1024) unsigned char smem_raw[];
    const uint32_t sb = (smem_u32(smem_raw) + 1023) & ~1023u;
    const int tid = threadIdx.x, lane = tid & 31;
    const int wg = __shfl_sync(0xffffffffu, tid >> 7, 0);
    const int warp = __shfl_sync(0xffffffffu, (tid >> 5) & 3, 0);
    const uint32_t bar = sb + G_BAR;
    const int t_begin = (blockIdx.x * G1_TILES) / gridDim.x;
    const int t_end = ((blockIdx.x + 1) * G1_TILES) / gridDim.x;
    const int mb0 = t_begin / G1_NB;
    asm volatile("griddepcontrol.launch_dependents;");
    KT(1, 0);
    if (tid == 0) {
        for (int i = 0; i < G_ST; i++) { mbar_init(bar + 8 * i, 1); mbar_init(bar + 8 * (G_ST + i), 2); }
        fence_async();
    }
    __syncthreads();
    if (wg == 2) {
        asm volatile("setmaxnreg.dec.sync.aligned.u32 40;");
        if (warp == 0) {
            if (lane == 0) {
                int it = 0;
                for (int tile = t_begin; tile < t_end; tile++) {
                    const int mb = tile / G1_NB, nb = tile % G1_NB;
                    for (int kb = 0; kb < 16; kb++, it++) {
                        const int st = it % G_ST;
                        mbar_wait(bar + 8 * (G_ST + st), ((it / G_ST) & 1) ^ 1);
                        const uint32_t fb = bar + 8 * st, sa = sb + st * G_STAGE;
                        mbar_expect(fb, G_STAGE);
                        tma_load(sa, &tm.x, kb * 64, mb * 128, fb);
                        tma_load(sa + 16384, &tm.wg, nb * 128, kb * 64, fb);
                        tma_load(sa + 16384 + 8192, &tm.wg, nb * 128 + 64, kb * 64, fb);
                        tma_load(sa + 16384 + 16384, &tm.wu, nb * 128, kb * 64, fb);
                        tma_load(sa + 16384 + 24576, &tm.wu, nb * 128 + 64, kb * 64, fb);
                    }
                }
                for (int pass = 0; pass < 4; pass++) {
                    for (int i = g1_first(pass); i < g1_count(pass); i += gridDim.x) {
                        const int tile = pass == 1 ? i : pass == 3 ? T_MID + (i >> 2) : NFULL + i, mb = tile >> 2, nb = tile & 3;
                        if (pass < 2) {
                            wait_count(&g_hcnt[mb], 2 * G1_NB);
                            asm volatile("fence.proxy.async;" ::: "memory");
                            for (int kb = 0; kb < FF / 64; kb++, it++) g_load_block(sb, bar, it, &tm.h, kb * 64, mb * 128, &tm.wd, nb * 256);
                        }
                        if (pass > 0) {
                            const int k0 = pass == 3 ? (i & 3) * 16 : 0, k1 = pass == 3 ? k0 + 16 : HD / 64;
                            wait_count(&g_ocnt[mb], NH * 4 * 2);
                            asm volatile("fence.proxy.async;" ::: "memory");
                            for (int kb = k0; kb < k1; kb++, it++) g_load_block(sb, bar, it, &tm.o, kb * 64, mb * 128, &tm.wo, nb * 256);
                        }
                    }
                }
            }
        }
    } else {
        asm volatile("setmaxnreg.inc.sync.aligned.u32 232;");
        float d[128];
        int it = 0;
        float s0 = 0.f, s1 = 0.f;
        const uint32_t epi = sb + G_EPI + wg * 16384;
        const int row = warp * 16 + ((lane >> 3) & 1) * 8 + (lane & 7);
        for (int tile = t_begin; tile < t_end; tile++) {
            const int mb = tile / G1_NB, nb = tile % G1_NB;
            for (int kb = 0; kb < 16; kb++, it++) g_mma_block(d, sb, bar, it, wg, tid, kb == 0);
            if (tile == t_begin || nb == 0) {
                const uint32_t* gp = &g_gate[mb * 128 + wg * 64 + warp * 16 + (lane >> 2)];
                uint32_t u0, u1, n = 0;
                do { u0 = ld_strong4(gp); u1 = ld_strong4(gp + 8); if (++n > 20000000u) __trap(); } while (u0 == 0u || u1 == 0u);
                s0 = 1.0f - __uint_as_float(u0); s1 = 1.0f - __uint_as_float(u1);
                __syncwarp();
            }
            wg_wait<0>();
            if ((tid & 127) == 0) { mbar_arrive(bar + 8 * (G_ST + (it - 1) % G_ST)); bulk_wait_read(); }
            bar_sync(1 + wg, 128);
#pragma unroll
            for (int j = 0; j < 16; j += 2) {
                uint32_t p[4];
#pragma unroll
                for (int q = 0; q < 4; q++) {
                    const int i = (j + (q >> 1)) * 4 + (q & 1) * 2;
                    const float sc = (q & 1) ? s1 : s0;
                    const float g0 = d[i], g1 = d[i + 1];
                    const float h0 = __fdividef(g0, 1.0f + __expf(-g0)) * d[64 + i] * sc;
                    const float h1 = __fdividef(g1, 1.0f + __expf(-g1)) * d[64 + i + 1] * sc;
                    p[q] = pack_bf16(h0, h1);
                }
                const int cgp = j + (lane >> 4);
                stsm4(epi + (cgp >> 3) * 8192 + row * 128 + (((cgp & 7) ^ (row & 7)) << 4), p[0], p[1], p[2], p[3]);
            }
            fence_async();
            bar_sync(1 + wg, 128);
            if ((tid & 127) == 0) {
                tma_store(&tm.hs, epi, nb * 128, mb * 128 + wg * 64);
                tma_store(&tm.hs, epi + 8192, nb * 128 + 64, mb * 128 + wg * 64);
                bulk_commit();
            }
        }
        if ((tid & 127) == 0) {
            bulk_wait_all();
            __threadfence();
            const int n0 = min(t_end, (mb0 + 1) * G1_NB) - t_begin;
            atomicAdd(&g_hcnt[mb0], (uint32_t)n0);
            if (t_end - t_begin > n0) atomicAdd(&g_hcnt[mb0 + 1], (uint32_t)(t_end - t_begin - n0));
        }
        for (int pass = 0; pass < 4; pass++) {
            for (int i = g1_first(pass); i < g1_count(pass); i += gridDim.x) {
                const int tile = pass == 1 ? i : pass == 3 ? T_MID + (i >> 2) : NFULL + i;
                const int nkb = pass == 0 ? FF / 64 : pass == 1 ? (FF + HD) / 64 : pass == 2 ? HD / 64 : 16;
                for (int kb = 0; kb < nkb; kb++, it++) g_mma_block(d, sb, bar, it, wg, tid, kb == 0);
                wg_wait<0>();
                if ((tid & 127) == 0) mbar_arrive(bar + 8 * (G_ST + (it - 1) % G_ST));
                float4* pre = g_pre + (tile - NFULL) * (32 * 256) + tid;
                if (pass >= 2) { if ((tid & 31) == 0) wait_count(&g_pcnt[tile], 8); __syncwarp(); }
                if (pass == 0) {
#pragma unroll
                    for (int q = 0; q < 32; q++) __stcg(pre + q * 256, make_float4(d[4 * q], d[4 * q + 1], d[4 * q + 2], d[4 * q + 3]));
                    __threadfence();
                    __syncwarp();
                    if ((tid & 31) == 0) atomicAdd(&g_pcnt[tile], 1u);
                } else if (pass == 3) {
                    float4 r[8];
#pragma unroll
                    for (int q = 0; q < 8; q++) r[q] = __ldcg(pre + ((i & 3) * 8 + q) * 256);
                    g_split_finish<4>(d, r, g_sk + (tile - T_MID) * 4 * (32 * 256), tile, i & 3, out, tid);
                } else {
                    if (pass == 2) {
#pragma unroll
                        for (int q = 0; q < 32; q++) {
                            const float4 u = __ldcg(pre + q * 256); d[4 * q] += u.x; d[4 * q + 1] += u.y; d[4 * q + 2] += u.z; d[4 * q + 3] += u.w;
                            if ((q & 7) == 7) __syncwarp();
                        }
                    }
                    g_store_tile(d, &tm.out, epi, tile >> 2, tile & 3, wg, tid);
                }
            }
        }
        if ((tid & 127) == 0) bulk_wait_all();
        KT(1, 1);
    }
    __syncwarp();
    asm volatile("griddepcontrol.wait;" ::: "memory");
}

struct G2Maps { CUtensorMap o, wo; };

__global__ void __launch_bounds__(384, 1) g2_kernel(const __grid_constant__ G2Maps tm, bf16* __restrict__ out) {
    extern __shared__ __align__(1024) unsigned char smem_raw[];
    const uint32_t sb = (smem_u32(smem_raw) + 1023) & ~1023u;
    const int tid = threadIdx.x, lane = tid & 31;
    const int wg = __shfl_sync(0xffffffffu, tid >> 7, 0);
    const int warp = __shfl_sync(0xffffffffu, (tid >> 5) & 3, 0);
    const uint32_t bar = sb + G_BAR;
    const int ks = blockIdx.x & 7, tile = T_LATE + (blockIdx.x >> 3), nb = tile & 3, mb = tile >> 2;
    KT(2, 0);
    if (tid == 0) {
        for (int i = 0; i < G_ST; i++) { mbar_init(bar + 8 * i, 1); mbar_init(bar + 8 * (G_ST + i), 2); }
        fence_async();
        for (int it = 0; it < G_ST; it++) {
            mbar_expect(bar + 8 * it, G_STAGE);
            for (int q = 0; q < 4; q++) tma_load(sb + it * G_STAGE + 16384 + q * 8192, &tm.wo, nb * 256 + q * 64, (ks * 8 + it) * 64, bar + 8 * it);
        }
        for (int it = G_ST; it < 8; it++)
            for (int q = 0; q < 4; q++) tma_prefetch(&tm.wo, nb * 256 + q * 64, (ks * 8 + it) * 64);
    }
    __syncthreads();
    asm volatile("griddepcontrol.wait;" ::: "memory");
    if (wg == 2) {
        asm volatile("setmaxnreg.dec.sync.aligned.u32 40;");
        if (warp == 0 && lane == 0) {
            for (int it = 0; it < G_ST; it++) tma_load(sb + it * G_STAGE, &tm.o, (ks * 8 + it) * 64, mb * 128, bar + 8 * it);
            for (int it = G_ST; it < 8; it++) g_load_block(sb, bar, it, &tm.o, (ks * 8 + it) * 64, mb * 128, &tm.wo, nb * 256);
        } else if (warp == 1) {
            if (blockIdx.x < SEQ / 32) g_gate[blockIdx.x * 32 + lane] = 0u;
            if (blockIdx.x == 0) { if (lane < 16) { g_hcnt[lane] = 0u; g_ocnt[lane] = 0u; } g_pcnt[lane] = 0u; g_pcnt[32 + lane] = 0u; }
        }
    } else {
        asm volatile("setmaxnreg.inc.sync.aligned.u32 232;");
        float d[128];
        float4 r[4];
        const float4* pre = g_pre + ((tile - NFULL) * 32 + ks * 4) * 256 + tid;
#pragma unroll
        for (int q = 0; q < 4; q++) r[q] = __ldcg(pre + q * 256);
        for (int it = 0; it < 8; it++) g_mma_block(d, sb, bar, it, wg, tid, it == 0);
        wg_wait<0>();
        g_split_finish<8>(d, r, g_sk + ((T_LATE - T_MID) * 4 + (tile - T_LATE) * 8) * (32 * 256), tile, ks, out, tid);
        KT(2, 1);
    }
}

typedef CUresult (*EncodeFn)(CUtensorMap*, CUtensorMapDataType, cuuint32_t, void*, const cuuint64_t*, const cuuint64_t*, const cuuint32_t*,
                             const cuuint32_t*, CUtensorMapInterleave, CUtensorMapSwizzle, CUtensorMapL2promotion, CUtensorMapFloatOOBfill);

static void make_map(EncodeFn enc, CUtensorMap* m, const void* ptr, uint64_t rows, uint64_t cols, uint32_t box_rows) {
    cuuint64_t dims[2] = {cols, rows};
    cuuint64_t strides[1] = {cols * 2};
    cuuint32_t box[2] = {64, box_rows};
    cuuint32_t es[2] = {1, 1};
    enc(m, CU_TENSOR_MAP_DATA_TYPE_BFLOAT16, 2, (void*)ptr, dims, strides, box, es, CU_TENSOR_MAP_INTERLEAVE_NONE,
        CU_TENSOR_MAP_SWIZZLE_128B, CU_TENSOR_MAP_L2_PROMOTION_L2_256B, CU_TENSOR_MAP_FLOAT_OOB_FILL_NONE);
}

extern "C" void kernel_launch(void* const* d_in, const int* in_sizes, int n_in, void* d_out, int out_size) {
    (void)in_sizes; (void)n_in; (void)out_size;
    const bf16* x = (const bf16*)d_in[0];
    const bf16* mem0 = (const bf16*)d_in[1];
    const bf16* gate_w = (const bf16*)d_in[11];
    static EncodeFn enc = nullptr;
    static int n_sm = 0;
    static void *pO = nullptr, *pH = nullptr;
    if (!enc) {
        void* fn = nullptr;
        cudaDriverEntryPointQueryResult qr;
        cudaGetDriverEntryPoint("cuTensorMapEncodeTiled", &fn, cudaEnableDefault, &qr);
        enc = (EncodeFn)fn;
        cudaDeviceGetAttribute(&n_sm, cudaDevAttrMultiProcessorCount, 0);
        cudaFuncSetAttribute(r_kernel, cudaFuncAttributeMaxDynamicSharedMemorySize, R_SMEM);
        cudaFuncSetAttribute(g1_kernel, cudaFuncAttributeMaxDynamicSharedMemorySize, G_SMEM);
        cudaFuncSetAttribute(g2_kernel, cudaFuncAttributeMaxDynamicSharedMemorySize, G_SMEM);
        cudaGetSymbolAddress(&pO, g_O);
        cudaGetSymbolAddress(&pH, g_H);
    }
    RMaps rm; G1Maps m1; G2Maps m2;
    make_map(enc, &rm.x, x, SEQ, DM, 32);
    for (int i = 0; i < 3; i++) make_map(enc, &rm.w[i], d_in[2 + i], DM, HD, 64);
    make_map(enc, &rm.wo, d_in[5], HD, DM, 128);
    make_map(enc, &rm.o, pO, SEQ, HD, 16);
    make_map(enc, &m1.x, x, SEQ, DM, 128);
    make_map(enc, &m1.wg, d_in[8], DM, FF, 64);
    make_map(enc, &m1.wu, d_in[9], DM, FF, 64);
    make_map(enc, &m1.hs, pH, SEQ, FF, 64);
    make_map(enc, &m1.o, pO, SEQ, HD, 128);
    make_map(enc, &m1.h, pH, SEQ, FF, 128);
    make_map(enc, &m1.wo, d_in[5], HD, DM, 64);
    make_map(enc, &m1.wd, d_in[10], FF, DM, 64);
    make_map(enc, &m1.out, d_out, SEQ, DM, 64);
    m2.o = m1.o; m2.wo = m1.wo;

    cudaStream_t st = cudaStreamPerThread;
    {
        cudaLaunchConfig_t cfg = {};
        cfg.gridDim = dim3(96); cfg.blockDim = dim3(384); cfg.dynamicSmemBytes = R_SMEM; cfg.stream = st;
        cudaLaunchAttribute at[1];
        at[0].id = cudaLaunchAttributeClusterDimension; at[0].val.clusterDim.x = 3; at[0].val.clusterDim.y = 1; at[0].val.clusterDim.z = 1;
        cfg.attrs = at; cfg.numAttrs = 1;
        cudaLaunchKernelEx(&cfg, r_kernel, rm, mem0, x, gate_w);
    }
    {
        cudaLaunchConfig_t cfg = {};
        cfg.gridDim = dim3(n_sm - 96); cfg.blockDim = dim3(384); cfg.dynamicSmemBytes = G_SMEM; cfg.stream = st;
        cudaLaunchAttribute at[1];
        at[0].id = cudaLaunchAttributeProgrammaticStreamSerialization; at[0].val.programmaticStreamSerializationAllowed = 1;
        cfg.attrs = at; cfg.numAttrs = 1;
        cudaLaunchKernelEx(&cfg, g1_kernel, m1, (bf16*)d_out);
    }
    {
        cudaLaunchConfig_t cfg = {};
        cfg.gridDim = dim3((64 - T_LATE) * 8); cfg.blockDim = dim3(384); cfg.dynamicSmemBytes = G_SMEM; cfg.stream = st;
        cudaLaunchAttribute at[1];
        at[0].id = cudaLaunchAttributeProgrammaticStreamSerialization; at[0].val.programmaticStreamSerializationAllowed = 1;
        cfg.attrs = at; cfg.numAttrs = 1;
        cudaLaunchKernelEx(&cfg, g2_kernel, m2, (bf16*)d_out);
    }
}
```

```cpp
#include <cuda_runtime.h>
#include <cuda_bf16.h>
#include <cuda.h>
#include <stdint.h>

typedef __nv_bfloat16 bf16;

constexpr int SEQ = 2048, DM = 1024, NH = 32, DH = 128, NMEM = 8, SEG = 32, NSEG = 64, FF = 3584;
constexpr int HD = NH * DH;

__device__ bf16 g_O[SEQ * HD];
__device__ bf16 g_H[SEQ * FF];
__device__ uint32_t g_gate[SEQ];
__device__ uint32_t g_part[4][128 * 32 * 32];
__device__ uint32_t g_mem[4][DM * 4];
constexpr int NFULL = 36, T_MID = 44, T_LATE = 52;
constexpr int NPRE = 64 - NFULL;
__device__ float4 g_pre[NPRE * 32 * 256];
__device__ float4 g_sk[((T_LATE - T_MID) * 4 + (64 - T_LATE) * 8) * 32 * 256];
__device__ uint32_t g_skcnt[64], g_pcnt[64];
__device__ uint32_t g_hcnt[16], g_ocnt[16];
#define KT(k, i)
#define PT(i)

#define DEVINL __device__ __forceinline__
constexpr long long SPIN_LIMIT = 4000000000LL;

DEVINL uint32_t smem_u32(const void* p) { return (uint32_t)__cvta_generic_to_shared(p); }
DEVINL void mbar_init(uint32_t bar, uint32_t cnt) { asm volatile("mbarrier.init.shared::cta.b64 [%0], %1;" ::"r"(bar), "r"(cnt) : "memory"); }
DEVINL void mbar_arrive(uint32_t bar) { asm volatile("mbarrier.arrive.shared::cta.b64 _, [%0];" ::"r"(bar) : "memory"); }
DEVINL void mbar_expect(uint32_t bar, uint32_t bytes) { asm volatile("mbarrier.arrive.expect_tx.shared::cta.b64 _, [%0], %1;" ::"r"(bar), "r"(bytes) : "memory"); }
DEVINL void mbar_arrive_remote(uint32_t cbar) { asm volatile("mbarrier.arrive.relaxed.cluster.shared::cluster.b64 _, [%0];" ::"r"(cbar) : "memory"); }
DEVINL bool mbar_try(uint32_t bar, uint32_t par) {
    uint32_t ok;
    asm volatile("{ .reg .pred p; mbarrier.try_wait.parity.shared::cta.b64 p, [%1], %2; selp.u32 %0, 1, 0, p; }" : "=r"(ok) : "r"(bar), "r"(par) : "memory");
    return ok;
}
__device__ __noinline__ void mbar_wait_slow(uint32_t bar, uint32_t par) {
    long long t0 = clock64();
    while (!mbar_try(bar, par)) { if (clock64() - t0 > SPIN_LIMIT) __trap(); }
}
DEVINL void mbar_wait(uint32_t bar, uint32_t par) {
    uint32_t n = 0;
    while (!mbar_try(bar, par)) { if (++n > 200000000u) __trap(); }
}
DEVINL uint32_t mapa(uint32_t a, uint32_t r) { uint32_t o; asm volatile("mapa.shared::cluster.u32 %0, %1, %2;" : "=r"(o) : "r"(a), "r"(r)); return o; }
DEVINL void fence_async() { asm volatile("fence.proxy.async.shared::cta;" ::: "memory"); }
DEVINL void bar_sync(int id, int n) { asm volatile("bar.sync %0, %1;" ::"r"(id), "r"(n) : "memory"); }
DEVINL void cluster_sync() { asm volatile("barrier.cluster.arrive.aligned; barrier.cluster.wait.aligned;" ::: "memory"); }
DEVINL void tma_load(uint32_t dst, const CUtensorMap* tm, int c0, int c1, uint32_t bar) {
    asm volatile("cp.async.bulk.tensor.2d.shared::cluster.global.mbarrier::complete_tx::bytes [%0], [%1, {%3, %4}], [%2];"
                 ::"r"(dst), "l"(tm), "r"(bar), "r"(c0), "r"(c1) : "memory");
}
DEVINL void tma_prefetch(const CUtensorMap* tm, int c0, int c1) {
    asm volatile("cp.async.bulk.prefetch.tensor.2d.L2.global [%0, {%1, %2}];" ::"l"(tm), "r"(c0), "r"(c1) : "memory");
}
DEVINL void tma_store(const CUtensorMap* tm, uint32_t src, int c0, int c1) {
    asm volatile("cp.async.bulk.tensor.2d.global.shared::cta.bulk_group [%0, {%2, %3}], [%1];" ::"l"(tm), "r"(src), "r"(c0), "r"(c1) : "memory");
}
DEVINL void bulk_commit() { asm volatile("cp.async.bulk.commit_group;" ::: "memory"); }
DEVINL void bulk_wait_read() { asm volatile("cp.async.bulk.wait_group.read 0;" ::: "memory"); }
DEVINL void bulk_wait_all() { asm volatile("cp.async.bulk.wait_group 0;" ::: "memory"); }
DEVINL void bulk_s2s(uint32_t cdst, uint32_t src, uint32_t bytes, uint32_t cbar) {
    asm volatile("cp.async.bulk.shared::cluster.shared::cta.mbarrier::complete_tx::bytes [%0], [%1], %2, [%3];" ::"r"(cdst), "r"(src), "r"(bytes), "r"(cbar) : "memory");
}
DEVINL void st_async16(uint32_t cdst, uint4 v, uint32_t cbar) {
    asm volatile("st.async.shared::cluster.mbarrier::complete_tx::bytes.v4.b32 [%0], {%1,%2,%3,%4}, [%5];" ::"r"(cdst), "r"(v.x), "r"(v.y), "r"(v.z), "r"(v.w), "r"(cbar) : "memory");
}
DEVINL uint64_t mkdesc(uint32_t addr, uint32_t lbo, uint32_t sbo, uint32_t swz) {
    return (uint64_t)((addr & 0x3FFFF) >> 4) | ((uint64_t)(lbo >> 4) << 16) | ((uint64_t)(sbo >> 4) << 32) | ((uint64_t)swz << 62);
}
constexpr uint32_t SB0 = 1024;
__host__ __device__ constexpr uint64_t cdesc(uint32_t off, uint32_t lbo, uint32_t sbo, uint32_t swz) {
    return (uint64_t)(((SB0 + off) & 0x3FFFF) >> 4) | ((uint64_t)(lbo >> 4) << 16) | ((uint64_t)(sbo >> 4) << 32) | ((uint64_t)swz << 62);
}
DEVINL float ex2(float x) { float y; asm("ex2.approx.ftz.f32 %0, %1;" : "=f"(y) : "f"(x)); return y; }
DEVINL void spin_clk(int d) { uint32_t t0, t1; asm volatile("mov.u32 %0, %%clock;" : "=r"(t0)); do { asm volatile("mov.u32 %0, %%clock;" : "=r"(t1)); } while ((int)(t1 - t0) < d); }
#define PROBE_GAP 150
#define OPAQUE(x) asm volatile("" : "+r"(x))
DEVINL void wg_fence() { asm volatile("wgmma.fence.sync.aligned;" ::: "memory"); }
DEVINL void wg_commit() { asm volatile("wgmma.commit_group.sync.aligned;" ::: "memory"); }
template <int N> DEVINL void wg_wait() { asm volatile("wgmma.wait_group.sync.aligned %0;" ::"n"(N) : "memory"); }
DEVINL uint32_t pack_bf16(float lo, float hi) { uint32_t r; asm("cvt.rn.bf16x2.f32 %0, %1, %2;" : "=r"(r) : "f"(hi), "f"(lo)); return r; }
DEVINL void ldsm4(uint32_t* r, uint32_t a) { asm volatile("ldmatrix.sync.aligned.m8n8.x4.shared.b16 {%0,%1,%2,%3}, [%4];" : "=r"(r[0]), "=r"(r[1]), "=r"(r[2]), "=r"(r[3]) : "r"(a) : "memory"); }
DEVINL void ldsm4t(uint32_t* r, uint32_t a) { asm volatile("ldmatrix.sync.aligned.m8n8.x4.trans.shared.b16 {%0,%1,%2,%3}, [%4];" : "=r"(r[0]), "=r"(r[1]), "=r"(r[2]), "=r"(r[3]) : "r"(a) : "memory"); }
DEVINL void stsm4(uint32_t a, uint32_t r0, uint32_t r1, uint32_t r2, uint32_t r3) { asm volatile("stmatrix.sync.aligned.m8n8.x4.shared.b16 [%0], {%1,%2,%3,%4};" ::"r"(a), "r"(r0), "r"(r1), "r"(r2), "r"(r3) : "memory"); }
DEVINL void stsm4t(uint32_t a, uint32_t r0, uint32_t r1, uint32_t r2, uint32_t r3) { asm volatile("stmatrix.sync.aligned.m8n8.x4.trans.shared.b16 [%0], {%1,%2,%3,%4};" ::"r"(a), "r"(r0), "r"(r1), "r"(r2), "r"(r3) : "memory"); }
DEVINL void sts32(uint32_t a, uint32_t v) { asm volatile("st.shared.b32 [%0], %1;" ::"r"(a), "r"(v) : "memory"); }
DEVINL void sts128(uint32_t a, uint4 v) { asm volatile("st.shared.v4.b32 [%0], {%1,%2,%3,%4};" ::"r"(a), "r"(v.x), "r"(v.y), "r"(v.z), "r"(v.w) : "memory"); }
DEVINL uint4 lds128(uint32_t a) { uint4 v; asm volatile("ld.shared.v4.b32 {%0,%1,%2,%3}, [%4];" : "=r"(v.x), "=r"(v.y), "=r"(v.z), "=r"(v.w) : "r"(a) : "memory"); return v; }
DEVINL uint4 ld_strong16(const void* p) { uint4 v; asm volatile("ld.relaxed.gpu.global.v4.u32 {%0,%1,%2,%3}, [%4];" : "=r"(v.x), "=r"(v.y), "=r"(v.z), "=r"(v.w) : "l"(p) : "memory"); return v; }
DEVINL void st_strong8(void* p, uint32_t a, uint32_t b) { asm volatile("st.relaxed.gpu.global.v2.u32 [%0], {%1,%2};" ::"l"(p), "r"(a), "r"(b) : "memory"); }
DEVINL void st_strong4(void* p, uint32_t a) { asm volatile("st.relaxed.gpu.global.u32 [%0], %1;" ::"l"(p), "r"(a) : "memory"); }
DEVINL void st_strong16(void* p, uint4 v) { asm volatile("st.relaxed.gpu.global.v4.u32 [%0], {%1,%2,%3,%4};" ::"l"(p), "r"(v.x), "r"(v.y), "r"(v.z), "r"(v.w) : "memory"); }
DEVINL uint32_t pack_nz(float lo, float hi) { uint32_t r = pack_bf16(lo, hi); return r == 0u ? 0x8000u : r; }
DEVINL uint32_t min4(uint4 v, uint32_t m) { return __vimin3_u32(__vimin3_u32(v.x, v.y, m), v.z, v.w); }
DEVINL void mma16816(float* d, uint32_t a0, uint32_t a1, uint32_t a2, uint32_t a3, uint32_t b0, uint32_t b1) {
    asm volatile("mma.sync.aligned.m16n8k16.row.col.f32.bf16.bf16.f32 {%0,%1,%2,%3}, {%4,%5,%6,%7}, {%8,%9}, {%0,%1,%2,%3};"
                 : "+f"(d[0]), "+f"(d[1]), "+f"(d[2]), "+f"(d[3]) : "r"(a0), "r"(a1), "r"(a2), "r"(a3), "r"(b0), "r"(b1));
}
DEVINL void mma1688(float* d, uint32_t a0, uint32_t a1, uint32_t b0) {
    asm volatile("mma.sync.aligned.m16n8k8.row.col.f32.bf16.bf16.f32 {%0,%1,%2,%3}, {%4,%5}, {%6}, {%0,%1,%2,%3};"
                 : "+f"(d[0]), "+f"(d[1]), "+f"(d[2]), "+f"(d[3]) : "r"(a0), "r"(a1), "r"(b0));
}
template <int TA, int TB> DEVINL void wg_ss8(float* d, uint64_t da, uint64_t db, int sc) {
    asm volatile("{ .reg .pred p; setp.ne.b32 p, %6, 0; wgmma.mma_async.sync.aligned.m64n8k16.f32.bf16.bf16 {%0,%1,%2,%3}, %4, %5, p, 1, 1, %7, %8; }"
                 : "+f"(d[0]), "+f"(d[1]), "+f"(d[2]), "+f"(d[3]) : "l"(da), "l"(db), "r"(sc), "n"(TA), "n"(TB));
}
template <int TB> DEVINL void wg_rs8(float* d, const uint32_t* a, uint64_t db, int sc) {
    asm volatile("{ .reg .pred p; setp.ne.b32 p, %9, 0; wgmma.mma_async.sync.aligned.m64n8k16.f32.bf16.bf16 {%0,%1,%2,%3}, {%4,%5,%6,%7}, %8, p, 1, 1, %10; }"
                 : "+f"(d[0]), "+f"(d[1]), "+f"(d[2]), "+f"(d[3]) : "r"(a[0]), "r"(a[1]), "r"(a[2]), "r"(a[3]), "l"(db), "r"(sc), "n"(TB));
}
#define ACC16(d) "+f"(d[0]), "+f"(d[1]), "+f"(d[2]), "+f"(d[3]), "+f"(d[4]), "+f"(d[5]), "+f"(d[6]), "+f"(d[7]), "+f"(d[8]), "+f"(d[9]), "+f"(d[10]), "+f"(d[11]), "+f"(d[12]), "+f"(d[13]), "+f"(d[14]), "+f"(d[15])
template <int TA> DEVINL void wg_ss32(float* d, uint64_t da, uint64_t db, int sc) {
    asm volatile("{ .reg .pred p; setp.ne.b32 p, %18, 0; wgmma.mma_async.sync.aligned.m64n32k16.f32.bf16.bf16 {%0,%1,%2,%3,%4,%5,%6,%7,%8,%9,%10,%11,%12,%13,%14,%15}, %16, %17, p, 1, 1, %19, 0; }"
                 : ACC16(d) : "l"(da), "l"(db), "r"(sc), "n"(TA));
}
DEVINL void wg_rs32(float* d, const uint32_t* a, uint64_t db, int sc) {
    asm volatile("{ .reg .pred p; setp.ne.b32 p, %21, 0; wgmma.mma_async.sync.aligned.m64n32k16.f32.bf16.bf16 {%0,%1,%2,%3,%4,%5,%6,%7,%8,%9,%10,%11,%12,%13,%14,%15}, {%16,%17,%18,%19}, %20, p, 1, 1, 0; }"
                 : ACC16(d) : "r"(a[0]), "r"(a[1]), "r"(a[2]), "r"(a[3]), "l"(db), "r"(sc));
}
DEVINL void wg_ss40(float* d, uint64_t da, uint64_t db, int sc) {
    asm volatile("{ .reg .pred p; setp.ne.b32 p, %22, 0; wgmma.mma_async.sync.aligned.m64n40k16.f32.bf16.bf16 {%0,%1,%2,%3,%4,%5,%6,%7,%8,%9,%10,%11,%12,%13,%14,%15,%16,%17,%18,%19}, %20, %21, p, 1, 1, 1, 1; }"
                 : ACC16(d), "+f"(d[16]), "+f"(d[17]), "+f"(d[18]), "+f"(d[19]) : "l"(da), "l"(db), "r"(sc));
}
#define A8(d, o) "+f"(d[o]), "+f"(d[o + 1]), "+f"(d[o + 2]), "+f"(d[o + 3]), "+f"(d[o + 4]), "+f"(d[o + 5]), "+f"(d[o + 6]), "+f"(d[o + 7])
#define A32(d, o) A8(d, o), A8(d, o + 8), A8(d, o + 16), A8(d, o + 24)
DEVINL void wg_ss256(float* d, uint64_t da, uint64_t db, int sc) {
    asm volatile(
        "{ .reg .pred p; setp.ne.b32 p, %130, 0;\n"
        "wgmma.mma_async.sync.aligned.m64n256k16.f32.bf16.bf16 {"
        "%0,%1,%2,%3,%4,%5,%6,%7,%8,%9,%10,%11,%12,%13,%14,%15,%16,%17,%18,%19,%20,%21,%22,%23,%24,%25,%26,%27,%28,%29,%30,%31,"
        "%32,%33,%34,%35,%36,%37,%38,%39,%40,%41,%42,%43,%44,%45,%46,%47,%48,%49,%50,%51,%52,%53,%54,%55,%56,%57,%58,%59,%60,%61,%62,%63,"
        "%64,%65,%66,%67,%68,%69,%70,%71,%72,%73,%74,%75,%76,%77,%78,%79,%80,%81,%82,%83,%84,%85,%86,%87,%88,%89,%90,%91,%92,%93,%94,%95,"
        "%96,%97,%98,%99,%100,%101,%102,%103,%104,%105,%106,%107,%108,%109,%110,%111,%112,%113,%114,%115,%116,%117,%118,%119,%120,%121,%122,%123,%124,%125,%126,%127"
        "}, %128, %129, p, 1, 1, 0, 1; }"
        : A32(d, 0), A32(d, 32), A32(d, 64), A32(d, 96) : "l"(da), "l"(db), "r"(sc));
}

DEVINL float gate_row(const bf16* __restrict__ xr, const bf16* __restrict__ gate_w, int lane) {
    float acc = 0.f;
#pragma unroll
    for (int i = 0; i < 4; i++) {
        const uint4 xv = __ldg((const uint4*)xr + i * 32 + lane), gv = __ldg((const uint4*)gate_w + i * 32 + lane);
        const uint32_t xa[4] = {xv.x, xv.y, xv.z, xv.w}, ga[4] = {gv.x, gv.y, gv.z, gv.w};
#pragma unroll
        for (int e = 0; e < 4; e++) {
            acc = fmaf(__uint_as_float(xa[e] << 16), __uint_as_float(ga[e] << 16), acc);
            acc = fmaf(__uint_as_float(xa[e] & 0xffff0000u), __uint_as_float(ga[e] & 0xffff0000u), acc);
        }
    }
#pragma unroll
    for (int o = 16; o > 0; o >>= 1) acc += __shfl_xor_sync(0xffffffffu, acc, o);
    return 1.0f / (1.0f + __expf(-acc));
}
DEVINL uint32_t ld_strong4(const void* p) { uint32_t v; asm volatile("ld.relaxed.gpu.global.u32 %0, [%1];" : "=r"(v) : "l"(p) : "memory"); return v; }
DEVINL void wait_count(const uint32_t* p, uint32_t want) {
    uint32_t v, n = 0;
    while (true) {
        asm volatile("ld.acquire.gpu.global.u32 %0, [%1];" : "=r"(v) : "l"(p) : "memory");
        if (v >= want) break;
        __nanosleep(200);
        if (++n > 10000000u) __trap();
    }
}

constexpr int KR = 44;
constexpr int KS = 64 - KR;
constexpr int R_W = 0;
constexpr int R_WO = KS * 4096;
constexpr int R_QX = R_WO + 65536;
constexpr int R_RING = R_WO + 98304;
constexpr int R_K = R_RING + 24576;
constexpr int R_V = R_K + 10240;
constexpr int R_QM = R_V + 10240;
constexpr int R_O = R_QM + 2048;
constexpr int R_BAR = R_O + 2048;
constexpr int R_G = R_BAR + 256 + 512 + 256 + 128;
constexpr int R_Z = R_G + 256;
constexpr int R_SMEM = R_Z + 1024;
enum { B_FULL = 0, B_EMPTY = 5, B_MEM = 8, B_HOP1 = 12, B_XT, B_TFREE, B_O, B_AFREE0, B_AFREE1, B_PRO0, B_PRO1, B_XRECV, B_P, B_XDONE, B_OST0, B_OST1, B_HOPV };
#define D2_BASE 800
#define D2_STEP 250
#define PD2 6
#define CPB 8192
#define DDUP 0
#define WGAP 0
#define DQ 1700
#define D3 0

DEVINL uint32_t clk32() { uint32_t c_; asm volatile("mov.u32 %0, %%clock;" : "=r"(c_)); return c_; }
DEVINL void spin_until(uint32_t t) { while ((uint32_t)(t - clk32() - 1u) < 100000u) {} }
#define PROF(i)
#define PROF2(i)
#define PROF3(i, val)
DEVINL void e_arrive(uint32_t bar) { asm volatile("{ .reg .pred p; elect.sync _|p, 0xffffffff; @p mbarrier.arrive.shared::cta.b64 _, [%0]; }" ::"r"(bar) : "memory"); }
DEVINL void e_arrive_remote(uint32_t cbar) { asm volatile("{ .reg .pred p; elect.sync _|p, 0xffffffff; @p mbarrier.arrive.relaxed.cluster.shared::cluster.b64 _, [%0]; }" ::"r"(cbar) : "memory"); }
DEVINL void e_count(uint32_t* p) { asm volatile("{ .reg .pred p; elect.sync _|p, 0xffffffff; @p red.relaxed.gpu.global.add.u32 [%0], 1; }" ::"l"(p) : "memory"); }
DEVINL void e_expect(uint32_t bar, uint32_t bytes) { asm volatile("{ .reg .pred p; elect.sync _|p, 0xffffffff; @p mbarrier.arrive.expect_tx.shared::cta.b64 _, [%0], %1; }" ::"r"(bar), "r"(bytes) : "memory"); }
DEVINL void e_tma_load(uint32_t dst, const CUtensorMap* tm, int c0, int c1, uint32_t bar) {
    asm volatile("{ .reg .pred p; elect.sync _|p, 0xffffffff; @p cp.async.bulk.tensor.2d.shared::cluster.global.mbarrier::complete_tx::bytes [%0], [%1, {%3, %4}], [%2]; }"
                 ::"r"(dst), "l"(tm), "r"(bar), "r"(c0), "r"(c1) : "memory");
}
DEVINL void e_tma_store(const CUtensorMap* tm, uint32_t src, int c0, int c1) {
    asm volatile("{ .reg .pred p; elect.sync _|p, 0xffffffff; @p cp.async.bulk.tensor.2d.global.shared::cta.bulk_group [%0, {%2, %3}], [%1]; }" ::"l"(tm), "r"(src), "r"(c0), "r"(c1) : "memory");
}
DEVINL void e_bulk_s2g(void* dst, uint32_t src, uint32_t bytes) {
    asm volatile("{ .reg .pred p; elect.sync _|p, 0xffffffff; @p cp.async.bulk.global.shared::cta.bulk_group [%0], [%1], %2; }" ::"l"(dst), "r"(src), "r"(bytes) : "memory");
}
DEVINL void e_bulk_s2s(uint32_t cdst, uint32_t src, uint32_t bytes, uint32_t cbar) {
    asm volatile("{ .reg .pred p; elect.sync _|p, 0xffffffff; @p cp.async.bulk.shared::cluster.shared::cta.mbarrier::complete_tx::bytes [%0], [%1], %2, [%3]; }" ::"r"(cdst), "r"(src), "r"(bytes), "r"(cbar) : "memory");
}

#define SLOT 0
#define PH3 0
#define PHQ 0
DEVINL void wait_slot(uint32_t phase) {
    if (SLOT) {
        uint32_t c; asm volatile("mov.u32 %0, %%globaltimer_lo;" : "=r"(c));
        const uint32_t tgt = c + (SLOT ? SLOT : 1) - ((c - phase) % (SLOT ? SLOT : 1));
        do { asm volatile("mov.u32 %0, %%globaltimer_lo;" : "=r"(c)); } while ((uint32_t)(tgt - c - 1u) < 100000u);
    }
}
template <int N> DEVINL uint32_t poll_set(uint4 (&v)[N], const uint32_t* rp, int stride, uint32_t phase, uint32_t wbar = 0, uint32_t wpar = 0) {
    wait_slot(phase);
#pragma unroll
    for (int i = 0; i < N; i++) v[i] = ld_strong16(rp + i * stride);
    if (wbar) mbar_wait(wbar, wpar);
    uint32_t n = 0;
    while (true) {
        uint32_t m = 0xffffffffu;
#pragma unroll
        for (int i = 0; i < N; i++) m = min4(v[i], m);
        if (__all_sync(0xffffffffu, m != 0u)) return n;
        wait_slot(phase);
#pragma unroll
        for (int i = 0; i < N; i++)
            asm volatile("{ .reg .pred p; setp.eq.u32 p, %5, 0; @p ld.relaxed.gpu.global.v4.u32 {%0,%1,%2,%3}, [%4]; }"
                         : "+r"(v[i].x), "+r"(v[i].y), "+r"(v[i].z), "+r"(v[i].w) : "l"(rp + i * stride), "r"(min4(v[i], 0xffffffffu)) : "memory");
        if (++n > 20000000u) __trap();
    }
}

struct RMaps { CUtensorMap x, w[3], wo, o; };
#define KC(c) ((c) * 64)

#define XORD 3
__host__ __device__ constexpr int xo(int i) {
    return XORD == 0 ? i : XORD == 1 ? (i + 14) % 16 : XORD == 2 ? (i + 11) % 16
         : XORD == 3 ? (i < 10 ? ((i & 1) ? i / 2 : 11 + i / 2) : i - 5) : (i < 6 ? i : ((i & 1) ? 6 + (i - 6) / 2 : 11 + (i - 6) / 2));
}
#define XC(i) (xo(i) * 64)
DEVINL void x_load_pair(uint32_t dst, const CUtensorMap* tmx, int h, int p, int seg, uint32_t fbar) {
    e_expect(fbar, 8192);
    e_tma_load(dst, tmx, XC(2 * p), seg * SEG, fbar);
    e_tma_load(dst + 4096, tmx, XC(2 * p + 1), seg * SEG, fbar);
}
__host__ __device__ constexpr int wo_tile(int role, int i) {
    return role == 0 ? (i < 2 ? 4 + i : 8 + i) : (i >> 1) * 6 + (role - 1) * 2 + (i & 1);
}

template <int NT> DEVINL void wo_phase(uint32_t sb, int tb, uint32_t* pp, uint32_t obar, uint32_t opar) {
    const int lane = tb & 31, krow = (lane & 7) + ((lane >> 4) << 3), chunk = ((tb >> 5) & 3) * 2 + ((lane >> 3) & 1);
    uint32_t wa = sb + R_WO + (tb >> 7) * 16384 + krow * 128 + ((chunk ^ (krow & 7)) << 4);
    uint32_t af[4][4], bf[4][4], of[4][4];
#pragma unroll
    for (int g = 0; g < 4; g++) ldsm4t(af[g], wa + g * 2048);
    mbar_wait(obar, opar);
#pragma unroll
    for (int g = 0; g < 4; g++) ldsm4t(of[g], sb + R_O + g * 512 + lane * 16);
#pragma unroll 1
    for (int i = 0; i < NT; i++) {
        float w0[4] = {0.f, 0.f, 0.f, 0.f}, w1[4] = {0.f, 0.f, 0.f, 0.f};
        mma16816(w0, af[0][0], af[0][1], af[0][2], af[0][3], of[0][0], of[0][1]);
        ldsm4t(af[0], wa + 4 * 2048);
        mma16816(w1, af[1][0], af[1][1], af[1][2], af[1][3], of[0][2], of[0][3]);
        ldsm4t(af[1], wa + 5 * 2048);
        mma16816(w0, af[2][0], af[2][1], af[2][2], af[2][3], of[1][0], of[1][1]);
        ldsm4t(af[2], wa + 6 * 2048);
        mma16816(w1, af[3][0], af[3][1], af[3][2], af[3][3], of[1][2], of[1][3]);
        ldsm4t(af[3], wa + 7 * 2048);
        wa += (i + 1 < NT) ? 32768 : 0;
        mma16816(w0, af[0][0], af[0][1], af[0][2], af[0][3], of[2][0], of[2][1]);
        ldsm4t(af[0], wa);
        mma16816(w1, af[1][0], af[1][1], af[1][2], af[1][3], of[2][2], of[2][3]);
        ldsm4t(af[1], wa + 2048);
        mma16816(w0, af[2][0], af[2][1], af[2][2], af[2][3], of[3][0], of[3][1]);
        ldsm4t(af[2], wa + 2 * 2048);
        mma16816(w1, af[3][0], af[3][1], af[3][2], af[3][3], of[3][2], of[3][3]);
        ldsm4t(af[3], wa + 3 * 2048);
        st_strong4(pp, pack_nz(w0[0] + w1[0], w0[1] + w1[1]));
        st_strong4(pp + 1024, pack_nz(w0[2] + w1[2], w0[3] + w1[3]));
        pp += 6 * 8192;
    }
    (void)bf;
}

DEVINL void o_store(const RMaps& tm, uint32_t sb, uint32_t bar, int wq, int h, int s) {
    mbar_wait(bar + 8 * B_OST0 + (wq >> 2) * 8, s & 1);
    fence_async();
    const uint32_t src = sb + R_QX + 2048 + (wq >> 2) * 8192;
    e_tma_store(&tm.o, src, h * DH + (wq >> 2) * 64, s * SEG);
    e_tma_store(&tm.o, src + 4096, h * DH + (wq >> 2) * 64, s * SEG + 16);
    bulk_commit();
}

template <uint32_t role> DEVINL void r_big(const RMaps& tm, const int wid) {
    extern __shared__ __align__(1024) unsigned char smem_raw[];
    const uint32_t sb = smem_u32(smem_raw);
    const uint32_t bar = sb + R_BAR;
    const int tid = threadIdx.x;
    int h; asm("mov.u32 %0, %%clusterid.x;" : "=r"(h));
        uint32_t a[KR][4];
        mbar_wait(bar + 8 * B_PRO0, 0);
        PT(0);
        {
            const int lane = tid & 31;
            const int krow = (lane & 7) + ((lane >> 4) << 3);
            const int chunk = (wid & 3) * 2 + ((lane >> 3) & 1);
            const uint32_t la = sb + (wid >> 2) * 8192 + krow * 128 + ((chunk ^ (krow & 7)) << 4);
#pragma unroll
            for (int k = 0; k < KR; k++) ldsm4t(a[k], la + (k >> 2) * 16384 + (k & 3) * 2048);
        }
        bar_sync(1, 256);
        {
            fence_async();
            const CUtensorMap* tw = &tm.w[role];
            e_expect(bar + 8 * B_PRO1, (wid < 5 ? 16384 : 0) + (wid < (role == 0 ? 4 : 6) ? 16384 : 0));
            if (wid < 5) {
                e_tma_load(sb + R_W + wid * 8192, tw, h * DH, KC(KR / 4 + wid), bar + 8 * B_PRO1);
                e_tma_load(sb + R_W + KS * 2048 + wid * 8192, tw, h * DH + 64, KC(KR / 4 + wid), bar + 8 * B_PRO1);
            }
            if (wid < (role == 0 ? 4 : 6)) e_tma_load(sb + R_WO + wid * 16384, &tm.wo, wo_tile(role, wid) * 64, h * DH, bar + 8 * B_PRO1);
        }
        constexpr uint32_t e0 = role == 0 ? R_QX + 16384 : R_K + 2048, e1 = role == 0 ? R_QX + 24576 : R_V + 2048;
        if (wid == 6) x_load_pair(sb + e0, &tm.x, h, 3, 0, bar + 8 * (B_FULL + 3));
        if (wid == 7) x_load_pair(sb + e1, &tm.x, h, 4, 0, bar + 8 * (B_FULL + 4));
        PT(1);
        mbar_wait(bar + 8 * B_PRO1, 0);
        PT(2);

        constexpr uint64_t dW0 = cdesc(R_W, 1024, 1024, 1);
        constexpr uint64_t dM = cdesc(R_RING, 128, 128, 0);
        constexpr uint64_t dX = cdesc(R_RING, 16, 1024, 1);
        constexpr uint64_t dX0 = cdesc(0, 16, 1024, 1);
        int tb = tid;
        int wq = wid;

        float d[16];
        for (int s = -1; s < NSEG; s++) {
            if (s >= 0) {
                OPAQUE(wq);
                const uint64_t dW = dW0 + (uint64_t)((wq >> 2) * (KS * 128));
                float y[4] = {0.f, 0.f, 0.f, 0.f};
                {
                    OPAQUE(tb);
                    const uint32_t ma = sb + R_RING + (tb & 31) * 16;
                    float z[4] = {0.f, 0.f, 0.f, 0.f}, u[4] = {0.f, 0.f, 0.f, 0.f};
                    uint32_t b[4][4];
                    mbar_wait(bar + 8 * B_MEM, s & 1);
                    PROF((wq >> 2) * 4 + 0);
                    if (s == 0) PT(3);
                    if (s == 1) PT(4);
#pragma unroll
                    for (int g = 0; g < 4; g++) ldsm4t(b[g], ma + g * 512);
#pragma unroll
                    for (int g = 0; g < KR / 2; g++) {
                        float* c0 = (g % 3 == 0) ? y : (g % 3 == 1) ? u : z;
                        float* c1 = (g % 3 == 0) ? z : (g % 3 == 1) ? y : u;
                        mma16816(c0, a[2 * g][0], a[2 * g][1], a[2 * g][2], a[2 * g][3], b[g & 3][0], b[g & 3][1]);
                        mma16816(c1, a[2 * g + 1][0], a[2 * g + 1][1], a[2 * g + 1][2], a[2 * g + 1][3], b[g & 3][2], b[g & 3][3]);
                        if (g + 4 < KR / 2) {
                            if ((g + 4) % 8 == 0) mbar_wait(bar + 8 * (B_MEM + (g + 4) / 8), s & 1);
                            ldsm4t(b[g & 3], ma + (g + 4) * 512);
                        }
                    }
                    y[0] += z[0] + u[0]; y[1] += z[1] + u[1]; y[2] += z[2] + u[2]; y[3] += z[3] + u[3];
                }
                PROF2(8);
                mbar_wait(bar + 8 * (B_MEM + 3), s & 1);
                wg_fence();
#pragma unroll
                for (int k = KR; k < 64; k++) wg_ss8<1, 1>(y, dW + (uint64_t)((k - KR) * 128), dM + (uint64_t)(k * 16), 1);
                wg_commit();
                asm volatile("wgmma.wait_group.sync.aligned 0;" : "+f"(y[0]), "+f"(y[1]), "+f"(y[2]), "+f"(y[3])::"memory");
                OPAQUE(tb);
                {
                    const uint32_t wo_ = (tb >> 5) * 256;
                    const uint32_t tile = sb + (role == 0 ? R_QX : (role == 1 ? R_K : R_V)) + wo_;
                    const uint32_t u0 = pack_bf16(y[0], y[1]), u1 = pack_bf16(y[2], y[3]);
                    sts32(tile + (tb & 31) * 4, u0);
                    sts32(tile + (tb & 31) * 4 + 128, u1);
                    __syncwarp();
                    uint4 v = lds128(tile + (tb & 15) * 16);
                    uint32_t peer = role + 1 + ((tb >> 4) & 1);
                    peer = peer >= 3 ? peer - 3 : peer;
                    const uint32_t rt = sb + (role == 0 ? R_QM : (role == 1 ? R_K : R_V)) + wo_ + (tb & 15) * 16;
                    st_async16(mapa(rt, peer), v, mapa(bar + 8 * (role == 2 ? B_HOPV : B_HOP1), peer));
                    if (role == 0) {
                        sts128(tile + 4096 + ((tb >> 4) & 1) * 4096 + (tb & 15) * 16, v);
                        sts32(tile + 12288 + (tb & 31) * 4, u0);
                        sts32(tile + 12288 + (tb & 31) * 4 + 128, u1);
                        __syncwarp();
                    }
                    e_arrive(bar + 8 * (role == 2 ? B_HOPV : B_HOP1));
                }
                PROF((wq >> 2) * 4 + 1);
                if (s < NSEG - 1) {
                    bar_sync(1, 256);
                    if (wq < 2) { fence_async(); x_load_pair(sb + R_RING + wq * 8192, &tm.x, h, wq, s + 1, bar + 8 * (B_FULL + wq)); }
                    OPAQUE(tb);
                }
                uint32_t* pp = g_part[s & 3] + (h * 32 + (wo_tile(role, 0) + (tb >> 7)) * 8192 + ((tb >> 5) & 3) * 2048 + (tb & 31));
                asm volatile("" : "+l"(pp));
                if (role != 0) {
                    if (s < NSEG - 1) {
                        wo_phase<3>(sb, tb, pp, bar + 8 * B_O, s & 1);
                    }
                } else {
                    constexpr uint64_t dV = cdesc(R_V, 2048, 128, 0);
                    constexpr uint64_t dP = cdesc(R_QX, 128, 4096, 0);
                    if ((wq & 3) == 0 && s >= 1) { bulk_wait_all(); e_count(&g_ocnt[(s - 1) >> 2]); }
                    wo_phase<2>(sb, tb, pp, bar + 8 * B_O, s & 1);
                    mbar_wait(bar + 8 * B_P, s & 1);
                    float sf[8];
#pragma unroll
                    for (int j = 0; j < 4; j++) asm volatile("ld.shared.v2.f32 {%0,%1}, [%2];" : "=f"(sf[2 * j]), "=f"(sf[2 * j + 1]) : "r"(sb + R_G + 128 + j * 32 + (tb & 3) * 8) : "memory");
                    wg_fence();
#pragma unroll
                    for (int k = 0; k < 3; k++) wg_ss32<0>(d, dV + (uint64_t)((wq >> 2) * 64 + k * 256), dP + (uint64_t)(k * 16), k);
                    wg_commit();
                    asm volatile("wgmma.wait_group.sync.aligned 0;" : ACC16(d)::"memory");
                    if ((wq & 3) == 1 || (wq & 3) == 2) e_arrive_remote(mapa(bar + 8 * B_TFREE, wq & 3));
                    OPAQUE(tb);
                    const uint32_t r = ((tb >> 4) & 1) * 8 + (tb & 7), ch = ((tb >> 5) & 3) * 2 + ((tb >> 3) & 1);
                    const uint32_t oa = sb + R_QX + 2048 + (tb >> 7) * 8192 + r * 128 + ((ch ^ (r & 7)) << 4);
                    stsm4t(oa, pack_bf16(d[0] * sf[0], d[1] * sf[1]), pack_bf16(d[2] * sf[0], d[3] * sf[1]), pack_bf16(d[4] * sf[2], d[5] * sf[3]), pack_bf16(d[6] * sf[2], d[7] * sf[3]));
                    stsm4t(oa + 4096, pack_bf16(d[8] * sf[4], d[9] * sf[5]), pack_bf16(d[10] * sf[4], d[11] * sf[5]), pack_bf16(d[12] * sf[6], d[13] * sf[7]), pack_bf16(d[14] * sf[6], d[15] * sf[7]));
                    __syncwarp();
                    e_arrive(bar + 8 * B_OST0 + (wq >> 2) * 8);
                }
                if (wq == 0) PROF(10);
                if (s == NSEG - 1) {
                    if (role == 0 && (wq & 3) == 0) { o_store(tm, sb, bar, wq, h, s); bulk_wait_all(); }
                    break;
                }
            }
            const int seg = s + 1;
            OPAQUE(wq);
            const uint64_t dW = dW0 + (uint64_t)((wq >> 2) * (KS * 128));
#pragma unroll
            for (int p = 0; p < 8; p++) {
                const int slot = p % 5;
                mbar_wait(bar + 8 * (B_FULL + slot), slot < 3 ? (uint32_t)(p / 5) : (uint32_t)(seg & 1));
                PROF2(p);
                const uint64_t db = slot < 3 ? dX + (uint64_t)(slot * 512) : dX0 + (uint64_t)((slot == 3 ? e0 : e1) >> 4);
                wg_fence();
#pragma unroll
                for (int kk = 0; kk < 8; kk++) {
                    const int k = XORD >= 3 ? (kk & 1) * 4 + (kk >> 1) : kk;
                    const int ks = xo(2 * p + (k >> 2)) * 4 + (k & 3);
                    if (ks >= KR) wg_ss32<1>(d, dW + (uint64_t)((ks - KR) * 128), db + (uint64_t)((k >> 2) * 256 + (k & 3) * 2), p + k);
                    else wg_rs32(d, a[ks < KR ? ks : 0], db + (uint64_t)((k >> 2) * 256 + (k & 3) * 2), p + k);
                }
                wg_commit();
                if (p == 0 && role == 0 && (wq & 3) == 0 && s >= 0) o_store(tm, sb, bar, wq, h, s);
                if (p >= 1) {
                    wg_wait<1>();
                    if (p <= 3) {
                        if ((wq & 3) == p) e_arrive(bar + 8 * (B_EMPTY + p - 1));
                        if (wq == p + (p & 1) * 4) {
                            mbar_wait(bar + 8 * (B_EMPTY + p - 1), seg & 1);
                            x_load_pair(sb + R_RING + (p - 1) * 8192, &tm.x, h, p + 4, seg, bar + 8 * (B_FULL + p - 1));
                        }
                    }
                    if (p == 5 && (wq & 3) < ((role == 0 && s >= 0) ? 1 : 3)) {
                        if (role == 0) bulk_wait_read();
                        e_arrive_remote(mapa(bar + 8 * B_TFREE, wq & 3));
                    }
                    if (p == 6 && (wq & 3) == 1) e_arrive(bar + 8 * B_AFREE0);
                    if (p == 7 && (wq & 3) == 2) e_arrive(bar + 8 * B_AFREE1);
                }
            }
            asm volatile("wgmma.wait_group.sync.aligned 0;" : ACC16(d)::"memory");
            PROF2(16);
            mbar_wait(bar + 8 * B_TFREE, seg & 1);
            const uint32_t tilex = sb + (role == 0 ? R_QX + 2048 : (role == 1 ? R_K + 2048 : R_V + 2048));
            {
                OPAQUE(tb);
                const uint32_t gs = role == 0 ? 4096 : 2048;
                const uint32_t sa = tilex + ((tb >> 4) & 1) * gs + (tb >> 5) * 256 + (tb & 15) * 16;
                stsm4(sa, pack_bf16(d[0], d[1]), pack_bf16(d[2], d[3]), pack_bf16(d[4], d[5]), pack_bf16(d[6], d[7]));
                stsm4(sa + 2 * gs, pack_bf16(d[8], d[9]), pack_bf16(d[10], d[11]), pack_bf16(d[12], d[13]), pack_bf16(d[14], d[15]));
            }
            __syncwarp();
            e_arrive(bar + 8 * B_XDONE);
            if (role != 0 && (wq & 3) == 0) {
                mbar_wait(bar + 8 * B_XDONE, seg & 1);
                fence_async();
                uint32_t pr = role + 1 + (wq >> 2); pr = pr >= 3 ? pr - 3 : pr;
                e_bulk_s2s(mapa(tilex, pr), tilex, CPB, mapa(bar + 8 * B_XT, pr));
            }
        }
}

#define CLR 0
#define CLEAR(st) do { if (role != 0) { \
                const int w_ = wid & 3; \
                uint32_t* zp = g_part[(st) & 3] + ((rg0 + (w_ >> 1) * 64) * 1024 + (w_ & 1) * 512); \
                e_bulk_s2g(zp, sb + R_Z, 1024); \
                e_bulk_s2g(zp + 256, sb + R_Z, 1024); \
                e_bulk_s2g(&g_mem[(st) & 3][(rg0 + (w_ >> 1) * 64) * 32 + (w_ & 1) * 16], sb + R_Z, 64); \
                bulk_commit(); } } while (0)
template <uint32_t role> DEVINL void r_chain(const RMaps& tm, const bf16* __restrict__ mem0, const bf16* __restrict__ x, const bf16* __restrict__ gate_w, const int wid) {
    extern __shared__ __align__(1024) unsigned char smem_raw[];
    const uint32_t sb = smem_u32(smem_raw);
    const uint32_t bar = sb + R_BAR;
    const int tid = threadIdx.x;
    int h; asm("mov.u32 %0, %%clusterid.x;" : "=r"(h));
        int t = tid & 127;
        const float sl2 = 0.08838834764831845f * 1.4426950408889634f;
        const float NEGRAW = -1000000000.0f / 0.08838834764831845f;
        const int rg0 = ((int)role - 1) * 32 + h;
        if (role != 0) {
#pragma unroll 1
            for (int r = 0; r < 4; r++) {
                uint32_t* zp = g_part[r] + ((rg0 + (t >> 6) * 64) * 1024 + (t & 63) * 4);
#pragma unroll
                for (int i = 0; i < 4; i++) st_strong16(zp + i * 256, make_uint4(0u, 0u, 0u, 0u));
                if ((t & 63) < 8) st_strong16(&g_mem[r][(rg0 + (t >> 6) * 64) * 32 + (t & 63) * 4], make_uint4(0u, 0u, 0u, 0u));
            }
            __threadfence();
        }
        {
#pragma unroll 1
            for (int r = (h * 3 + (int)role) * 4 + (t >> 5); r < SEQ; r += 384) {
                const uint32_t gb = __float_as_uint(gate_row(x + r * DM, gate_w, t & 31));
                if ((t & 31) == 0) st_strong4(&g_gate[r], gb ? gb : 0x80000000u);
            }
        }
        if (t < 64) sts128(sb + R_Z + t * 16, make_uint4(0u, 0u, 0u, 0u));
        if (role == 0) sts128(sb + R_QM + t * 16, make_uint4(0u, 0u, 0u, 0u));
        {
            uint4 v[8];
#pragma unroll
            for (int r = 0; r < 8; r++) v[r] = __ldg((const uint4*)(mem0 + r * DM) + t);
            mbar_wait(bar + 8 * B_AFREE0, 0);
            mbar_wait(bar + 8 * B_AFREE1, 0);
#define TR2(f, c) \
            sts128(sb + R_RING + t * 128 + (c) * 16, make_uint4(__byte_perm(v[0].f, v[1].f, 0x5410), __byte_perm(v[2].f, v[3].f, 0x5410), __byte_perm(v[4].f, v[5].f, 0x5410), __byte_perm(v[6].f, v[7].f, 0x5410))); \
            sts128(sb + R_RING + t * 128 + (c) * 16 + 16, make_uint4(__byte_perm(v[0].f, v[1].f, 0x7632), __byte_perm(v[2].f, v[3].f, 0x7632), __byte_perm(v[4].f, v[5].f, 0x7632), __byte_perm(v[6].f, v[7].f, 0x7632)));
            TR2(x, 0) TR2(y, 2) TR2(z, 4) TR2(w, 6)
            fence_async();
            __syncwarp();
            e_arrive(bar + 8 * B_MEM + (t >> 5) * 8);
        }
        constexpr uint64_t dQ = role == 0 ? cdesc(R_QX, 128, 2048, 0) : cdesc(R_QM, 128, 0, 0);
        constexpr uint64_t dK = cdesc(R_K, 128, 2048, 0);

        for (int s = 0; s < NSEG; s++) {
            {
                const int w = wid & 3;
                mbar_wait(bar + 8 * B_XDONE, s & 1);
                if (s + 1 < NSEG) {
                    if (w == 2) x_load_pair(sb + R_RING + 16384, &tm.x, h, 2, s + 1, bar + 8 * (B_FULL + 2));
                    if (role == 0 && w < 2) x_load_pair(sb + R_QX + 16384 + w * 8192, &tm.x, h, 3 + w, s + 1, bar + 8 * (B_FULL + 3 + w));
                }
            }
            if (role == 0) {
                uint32_t n = 0, gate;
                do { gate = ld_strong4(&g_gate[s * SEG + (t >> 2)]); if (++n > 20000000u) __trap(); } while (gate == 0u);
                sts32(sb + R_G + (t >> 2) * 4, gate);
                __syncwarp();
            }
            mbar_wait(bar + 8 * B_XT, s & 1);
            if (t >= 1 && t < 3) { uint32_t pr = role + t; pr = pr >= 3 ? pr - 3 : pr; mbar_arrive_remote(mapa(bar + 8 * B_XRECV, pr)); }
            __syncwarp();
            mbar_wait(bar + 8 * B_HOP1, s & 1);
            PROF(8);
            fence_async();
            OPAQUE(t);
            if (s == NSEG - 1 && role != 0) { mbar_wait(bar + 8 * B_HOPV, s & 1); bulk_wait_all(); break; }
            float sc[20];
            wg_fence();
#pragma unroll
            for (int k = 0; k < 8; k++) wg_ss40(sc, dQ + (uint64_t)(k * 16), dK + (uint64_t)(k * 16), k);
            wg_commit();
            uint32_t t_o = clk32() + 500;
            {
                const uint32_t va = sb + R_V + 2048 + (t >> 5) * 512 + ((t >> 4) & 1) * 2048 + (t & 15) * 16;
                uint32_t v0[4], v1[4];
                ldsm4(v0, va); ldsm4(v1, va + 256);
                const int lim = (t >> 2) - (t & 3) * 2 + 8;
                wg_wait<0>();
                float m = fmaxf(sc[0], sc[1]), m1 = fmaxf(sc[2], sc[3]);
#pragma unroll
                for (int j = 1; j < 5; j++) {
                    m = fmaxf(m, fmaxf(sc[4 * j], sc[4 * j + 1]));
                    if (role == 0) {
                        sc[4 * j + 2] = 8 * j <= lim ? sc[4 * j + 2] : NEGRAW;
                        sc[4 * j + 3] = 8 * j + 1 <= lim ? sc[4 * j + 3] : NEGRAW;
                        m1 = fmaxf(m1, fmaxf(sc[4 * j + 2], sc[4 * j + 3]));
                    }
                }
                m = fmaxf(m, __shfl_xor_sync(0xffffffffu, m, 1));
                if (role == 0) m1 = fmaxf(m1, __shfl_xor_sync(0xffffffffu, m1, 1));
                m = fmaxf(m, __shfl_xor_sync(0xffffffffu, m, 2));
                if (role == 0) m1 = fmaxf(m1, __shfl_xor_sync(0xffffffffu, m1, 2));
                const float mb = m * sl2, mb1 = m1 * sl2;
                uint32_t pk[5], pt[5];
#pragma unroll
                for (int j = 0; j < 5; j++) pk[j] = pack_bf16(ex2(fmaf(sc[4 * j], sl2, -mb)), ex2(fmaf(sc[4 * j + 1], sl2, -mb)));
                float o0[4] = {0.f, 0.f, 0.f, 0.f}, o1[4] = {0.f, 0.f, 0.f, 0.f}, ls[4] = {0.f, 0.f, 0.f, 0.f}, lt[4] = {0.f, 0.f, 0.f, 0.f};
                constexpr uint32_t ONE = 0x3F803F80u;
                mma16816(o0, v0[0], v0[1], v0[2], v0[3], pk[1], pk[2]);
                mma16816(o1, v1[0], v1[1], v1[2], v1[3], pk[1], pk[2]);
                ldsm4(v0, va + 4096); ldsm4(v1, va + 4096 + 256);
                mma16816(ls, ONE, ONE, ONE, ONE, pk[1], pk[2]);
                mma16816(ls, ONE, ONE, ONE, ONE, pk[3], pk[4]);
                mma1688(ls, ONE, ONE, pk[0]);
                mma16816(o0, v0[0], v0[1], v0[2], v0[3], pk[3], pk[4]);
                mma16816(o1, v1[0], v1[1], v1[2], v1[3], pk[3], pk[4]);
                if (role == 0) {
#pragma unroll
                    for (int j = 0; j < 5; j++) pt[j] = pack_bf16(ex2(fmaf(sc[4 * j + 2], sl2, -mb1)), ex2(fmaf(sc[4 * j + 3], sl2, -mb1)));
                    mma16816(lt, pt[0], pt[1], pt[2], pt[3], ONE, ONE);
                    mma1688(lt, pt[4], 0u, ONE);
                }
                mbar_wait(bar + 8 * B_HOPV, s & 1);
                ldsm4(v0, sb + R_V + t * 16);
                mma1688(o0, v0[0], v0[1], pk[0]);
                mma1688(o1, v0[2], v0[3], pk[0]);
                const float i0 = __fdividef(1.0f, ls[0]), i1 = __fdividef(1.0f, ls[1]);
                const uint32_t oa = sb + R_O + (t >> 5) * 512 + (t & 31) * 4;
                sts32(oa, pack_bf16(o0[0] * i0, o0[1] * i1));
                sts32(oa + 128, pack_bf16(o0[2] * i0, o0[3] * i1));
                sts32(oa + 256, pack_bf16(o1[0] * i0, o1[1] * i1));
                sts32(oa + 384, pack_bf16(o1[2] * i0, o1[3] * i1));
                __syncwarp();
                e_arrive(bar + 8 * B_O);
                PROF(9);
                if (role == 0) {
                    const uint32_t pa = sb + R_QX + (t >> 5) * 4096 + (t & 31) * 4;
#pragma unroll
                    for (int j = 0; j < 5; j++) sts32(pa + j * 128, pt[j]);
                    sts32(pa + 5 * 128, 0u);
                    float gate; asm volatile("ld.shared.f32 %0, [%1];" : "=f"(gate) : "r"(sb + R_G + (t >> 2) * 4) : "memory");
                    sts32(sb + R_G + 128 + (t >> 2) * 4, __float_as_uint(__fdividef(gate, lt[0] + lt[2])));
                    fence_async();
                    __syncwarp();
                    e_arrive(bar + 8 * B_P);
                }
            }
            if (t < 32) { e_expect(bar + 8 * B_HOP1, role == 2 ? 4096 : 2048); if (role != 2) e_expect(bar + 8 * B_HOPV, 2048); e_expect(bar + 8 * B_XT, role == 0 ? 2 * CPB : CPB); }
            if (s == NSEG - 1) break;
            if (role != 0 && (wid & 3) >= 2) {
                mbar_wait(bar + 8 * B_XRECV, s & 1);
                mbar_wait(bar + 8 * B_O, s & 1);
                fence_async();
                x_load_pair(sb + ((wid & 1) ? R_V + 2048 : R_K + 2048), &tm.x, h, 3 + (wid & 1), s + 1, bar + 8 * (B_FULL + 3 + (wid & 1)));
            }
            OPAQUE(t);
            PROF(11);
            if (role != 0 || DDUP) {
                const int grp = role == 0 ? (t >> 6) * 32 + h : rg0 + (t >> 6) * 64;
                const uint32_t* rp = g_part[s & 3] + (grp * 1024 + ((t >> 2) & 7) * 32 + ((t >> 5) & 1) * 16 + (t & 3) * 4);
                uint32_t* wp = &g_mem[(s + 1) & 3][grp * 32 + ((t >> 5) & 1) * 16 + (t & 3) * 4 + ((t >> 3) & 3)];
                bulk_wait_all();
                spin_until(t_o + D2_BASE + (role == 0 ? DDUP + (t >> 6) * D2_STEP : (role - 1 + (t >> 6) * 2) * D2_STEP));
                PROF3(0, clk32());
#define LO(u) __uint_as_float((u) << 16)
#define HI(u) __uint_as_float((u) & 0xffff0000u)
                uint4 v[4];
                uint32_t n = poll_set<4>(v, rp, 256, (role - 1 + (t >> 6) * 2) * PHQ);
                {
                    PROF3(1, clk32());
                    float f[8];
                    f[0] = (LO(v[0].x) + LO(v[1].x)) + (LO(v[2].x) + LO(v[3].x)); f[1] = (HI(v[0].x) + HI(v[1].x)) + (HI(v[2].x) + HI(v[3].x));
                    f[2] = (LO(v[0].y) + LO(v[1].y)) + (LO(v[2].y) + LO(v[3].y)); f[3] = (HI(v[0].y) + HI(v[1].y)) + (HI(v[2].y) + HI(v[3].y));
                    f[4] = (LO(v[0].z) + LO(v[1].z)) + (LO(v[2].z) + LO(v[3].z)); f[5] = (HI(v[0].z) + HI(v[1].z)) + (HI(v[2].z) + HI(v[3].z));
                    f[6] = (LO(v[0].w) + LO(v[1].w)) + (LO(v[2].w) + LO(v[3].w)); f[7] = (HI(v[0].w) + HI(v[1].w)) + (HI(v[2].w) + HI(v[3].w));
                    const bool b4 = t & 16, b3 = t & 8;
                    float g4[4], g2[2];
#pragma unroll
                    for (int i = 0; i < 4; i++) g4[i] = (b4 ? f[4 + i] : f[i]) + __shfl_xor_sync(0xffffffffu, b4 ? f[i] : f[4 + i], 16);
#pragma unroll
                    for (int i = 0; i < 2; i++) g2[i] = (b3 ? g4[2 + i] : g4[i]) + __shfl_xor_sync(0xffffffffu, b3 ? g4[i] : g4[2 + i], 8);
                    g2[0] += __shfl_xor_sync(0xffffffffu, g2[0], 4);
                    g2[1] += __shfl_xor_sync(0xffffffffu, g2[1], 4);
                    st_strong4(wp, pack_nz(g2[0], g2[1]));
                }
                PROF3(8, n); (void)n;
            }
            t_o += D2_BASE + DQ + D3 + (t >> 5) * D2_STEP;
            OPAQUE(t);
            PROF(12);
            {
                const uint32_t* rp = &g_mem[(s + 1) & 3][((t >> 5) * 256 + (t & 31)) * 4];
                const uint32_t da = sb + R_RING + ((t >> 5) * 256 + (t & 31)) * 16;
                uint4 v[8];
                spin_until(t_o);
                PROF3(2, clk32());
                uint32_t n = poll_set<8>(v, rp, 128, PH3 + (t >> 5) * PHQ);
                PROF(13);
                PROF3(3, clk32()); PROF3(9, n); (void)n;
                mbar_wait(bar + 8 * B_AFREE0 + (t >> 6) * 8, (s + 1) & 1);
                PROF3(4, clk32());
#pragma unroll
                for (int i = 0; i < 8; i++) sts128(da + i * 512, v[i]);
                if (t >= 64) fence_async();
                __syncwarp();
                e_arrive(bar + 8 * B_MEM + (t >> 5) * 8);
                PROF(14);
                PROF3(5, clk32());
            }
            CLEAR(s + 3);
        }
}

__global__ void __launch_bounds__(384, 1) r_kernel(const __grid_constant__ RMaps tm, const bf16* __restrict__ mem0, const bf16* __restrict__ x, const bf16* __restrict__ gate_w) {
    extern __shared__ __align__(1024) unsigned char smem_raw[];
    const uint32_t sb = smem_u32(smem_raw);
    if ((sb & 0x3FFFFu) != SB0) __trap();
    const int tid = threadIdx.x;
    const int wid = __shfl_sync(0xffffffffu, tid >> 5, 0);
    uint32_t role; asm("mov.u32 %0, %%cluster_ctarank;" : "=r"(role));
    int h; asm("mov.u32 %0, %%clusterid.x;" : "=r"(h));
    const uint32_t bar = sb + R_BAR;
    asm volatile("griddepcontrol.launch_dependents;");
    KT(0, 0);

    if (tid == 0) {
        for (int i = 0; i < 5; i++) mbar_init(bar + 8 * (B_FULL + i), 1);
        for (int i = 0; i < 3; i++) mbar_init(bar + 8 * (B_EMPTY + i), 2);
        for (int i = 0; i < 4; i++) mbar_init(bar + 8 * (B_MEM + i), 1);
        mbar_init(bar + 8 * B_HOP1, role == 2 ? 1 : 9);
        mbar_init(bar + 8 * B_HOPV, role == 2 ? 8 : 1);
        mbar_init(bar + 8 * B_XT, 1);
        mbar_init(bar + 8 * B_TFREE, 6);
        mbar_init(bar + 8 * B_P, 4);
        mbar_init(bar + 8 * B_XDONE, 8);
        mbar_init(bar + 8 * B_OST0, 4);
        mbar_init(bar + 8 * B_OST1, 4);
        mbar_init(bar + 8 * B_XRECV, 2);
        mbar_init(bar + 8 * B_O, 4);
        mbar_init(bar + 8 * B_AFREE0, 2);
        mbar_init(bar + 8 * B_AFREE1, 2);
        mbar_init(bar + 8 * B_PRO0, 1);
        mbar_init(bar + 8 * B_PRO1, 8);
        asm volatile("fence.mbarrier_init.release.cluster;" ::: "memory");
        fence_async();
        mbar_expect(bar + 8 * B_PRO0, KR * 4096);
        for (int i = 0; i < 3; i++) mbar_expect(bar + 8 * (B_FULL + i), 8192);
        mbar_expect(bar + 8 * B_HOP1, role == 2 ? 4096 : 2048);
        if (role != 2) mbar_expect(bar + 8 * B_HOPV, 2048);
        mbar_expect(bar + 8 * B_XT, role == 0 ? 2 * CPB : CPB);
    }
    __syncthreads();
    asm volatile("barrier.cluster.arrive.relaxed.aligned;" ::: "memory");
    {
        const CUtensorMap* tw = &tm.w[role];
        if (wid < 11) {
            e_tma_load(sb + wid * 16384, tw, h * DH, KC(wid), bar + 8 * B_PRO0);
            e_tma_load(sb + wid * 16384 + 8192, tw, h * DH + 64, KC(wid), bar + 8 * B_PRO0);
        }
        if (wid < 6) e_tma_load(sb + R_RING + wid * 4096, &tm.x, XC(wid), 0, bar + 8 * (B_FULL + (wid >> 1)));
        if ((tid & 31) == 0) {
            if (wid < 10) tma_prefetch(tw, h * DH + (wid & 1) * 64, KC(KR / 4 + (wid >> 1)));
            if (wid >= 6 && wid - 6 < (role == 0 ? 4 : 6)) tma_prefetch(&tm.wo, wo_tile(role, wid - 6) * 64, h * DH);
            if (blockIdx.x < NSEG && wid < 8) { tma_prefetch(&tm.x, wid * 128, blockIdx.x * SEG); tma_prefetch(&tm.x, wid * 128 + 64, blockIdx.x * SEG); }
        }
        __syncwarp();
    }
    asm volatile("barrier.cluster.wait.aligned;" ::: "memory");

    if (wid < 8) {
        asm volatile("setmaxnreg.inc.sync.aligned.u32 224;");
        if (role == 0) r_big<0>(tm, wid); else if (role == 1) r_big<1>(tm, wid); else r_big<2>(tm, wid);
    } else {
        asm volatile("setmaxnreg.dec.sync.aligned.u32 56;");
        if (role == 0) r_chain<0>(tm, mem0, x, gate_w, wid); else if (role == 1) r_chain<1>(tm, mem0, x, gate_w, wid); else r_chain<2>(tm, mem0, x, gate_w, wid);
    }
    __syncwarp();
    asm volatile("barrier.cluster.arrive; barrier.cluster.wait;" ::: "memory");
    KT(0, 1);
}

constexpr int G_ST = 4;
constexpr int G_STAGE = 16384 + 32768;
constexpr int G_EPI = G_ST * G_STAGE;
constexpr int G_GATE = G_EPI + 32768;
constexpr int G_BAR = G_GATE + 1024;
constexpr int G_SMEM = G_BAR + 128 + 1024;

struct G1Maps { CUtensorMap x, wg, wu, hs, o, h, wo, wd, out; };
constexpr int G1_NB = FF / 128;
constexpr int G1_TILES = 16 * G1_NB;

DEVINL void g_mma_block(float* d, uint32_t sb, uint32_t bar, int it, int wg, int tid, bool first) {
    const int st = it % G_ST;
    mbar_wait(bar + 8 * st, (it / G_ST) & 1);
    const uint64_t da = mkdesc(sb + st * G_STAGE + wg * 8192, 16, 1024, 1);
    const uint64_t db = mkdesc(sb + st * G_STAGE + 16384, 8192, 1024, 1);
    wg_fence();
#pragma unroll
    for (int k = 0; k < 4; k++) wg_ss256(d, da + (uint64_t)(k * 2), db + (uint64_t)(k * 128), (first ? 0 : 1) | k);
    wg_commit();
    if (!first) { wg_wait<1>(); if ((tid & 127) == 0) mbar_arrive(bar + 8 * (G_ST + (it - 1) % G_ST)); }
}
DEVINL void g_load_block(uint32_t sb, uint32_t bar, int it, const CUtensorMap* ta, int k0, int m0, const CUtensorMap* tb, int n0) {
    const int st = it % G_ST;
    mbar_wait(bar + 8 * (G_ST + st), ((it / G_ST) & 1) ^ 1);
    const uint32_t fb = bar + 8 * st, sa = sb + st * G_STAGE;
    mbar_expect(fb, G_STAGE);
    tma_load(sa, ta, k0, m0, fb);
#pragma unroll
    for (int q = 0; q < 4; q++) tma_load(sa + 16384 + q * 8192, tb, n0 + q * 64, k0, fb);
}

DEVINL void g_store_tile(const float* d, const CUtensorMap* tout, uint32_t epi, int mb, int nb, int wg, int tid) {
    const int lane = tid & 31, row = ((tid >> 5) & 3) * 16 + ((lane >> 3) & 1) * 8 + (lane & 7);
#pragma unroll
    for (int half = 0; half < 2; half++) {
        if ((tid & 127) == 0) bulk_wait_read();
        bar_sync(1 + wg, 128);
#pragma unroll
        for (int j = 0; j < 16; j += 2) {
            const float* e = d + half * 64 + 4 * j;
            const int cgp = j + (lane >> 4);
            stsm4(epi + (cgp >> 3) * 8192 + row * 128 + (((cgp & 7) ^ (row & 7)) << 4),
                  pack_bf16(e[0], e[1]), pack_bf16(e[2], e[3]), pack_bf16(e[4], e[5]), pack_bf16(e[6], e[7]));
        }
        fence_async();
        bar_sync(1 + wg, 128);
        if ((tid & 127) == 0) {
            tma_store(tout, epi, nb * 256 + half * 128, mb * 128 + wg * 64);
            tma_store(tout, epi + 8192, nb * 256 + half * 128 + 64, mb * 128 + wg * 64);
            bulk_commit();
        }
    }
}
template <int NS> DEVINL void g_split_finish(const float* d, float4 (&r)[32 / NS], float4* sk, int tile, int ks, bf16* __restrict__ out, int tid) {
    constexpr int Q = 32 / NS;
    float4* mine = sk + ks * (32 * 256) + tid;
#pragma unroll
    for (int c = 0; c < NS; c++) {
        if (c != ks) {
#pragma unroll
            for (int q = c * Q; q < c * Q + Q; q++) __stcg(mine + q * 256, make_float4(d[4 * q], d[4 * q + 1], d[4 * q + 2], d[4 * q + 3]));
        } else {
#pragma unroll
            for (int q = 0; q < Q; q++) { const float* e = d + (c * Q + q) * 4; r[q].x += e[0]; r[q].y += e[1]; r[q].z += e[2]; r[q].w += e[3]; }
        }
    }
    __threadfence();
    bar_sync(3, 256);
    if (NS == 8) PT(20);
    if (tid == 0) {
        atomicAdd(&g_skcnt[tile], 1u);
        uint32_t v, n = 0;
        do {
            asm volatile("ld.acquire.gpu.global.u32 %0, [%1];" : "=r"(v) : "l"(&g_skcnt[tile]) : "memory");
            if (++n > 200000000u) __trap();
        } while (v < NS);
        if (atomicAdd(&g_skcnt[tile], 1u) == 2 * NS - 1) g_skcnt[tile] = 0u;
    }
    bar_sync(3, 256);
    if (NS == 8) PT(21);
#pragma unroll
    for (int c = 1; c < NS; c++) {
        const float4* th = sk + (((ks + c) & (NS - 1)) * 32 + ks * Q) * 256 + tid;
#pragma unroll
        for (int q = 0; q < Q; q++) { const float4 u = __ldcg(th + q * 256); r[q].x += u.x; r[q].y += u.y; r[q].z += u.z; r[q].w += u.w; }
    }
    const int lane = tid & 31;
    uint32_t* op = (uint32_t*)(out + ((tile >> 2) * 128 + (tid >> 5) * 16 + (lane >> 2)) * DM + (tile & 3) * 256 + ks * Q * 8 + (lane & 3) * 2);
#pragma unroll
    for (int q = 0; q < Q; q++) { op[q * 4] = pack_bf16(r[q].x, r[q].y); op[q * 4 + 4 * DM] = pack_bf16(r[q].z, r[q].w); }
}
DEVINL int g1_count(int pass) { return pass == 0 ? NPRE : pass == 1 ? NFULL : pass == 2 ? T_MID - NFULL : (T_LATE - T_MID) * 4; }
DEVINL int g1_first(int pass) { return pass == 2 ? (int)(gridDim.x - 1 - blockIdx.x) : (int)blockIdx.x; }

__global__ void __launch_bounds__(384, 1) g1_kernel(const __grid_constant__ G1Maps tm, bf16* __restrict__ out) {
    extern __shared__ __align__(1024) unsigned char smem_raw[];
    const uint32_t sb = (smem_u32(smem_raw) + 1023) & ~1023u;
    const int tid = threadIdx.x, lane = tid & 31;
    const int wg = __shfl_sync(0xffffffffu, tid >> 7, 0);
    const int warp = __shfl_sync(0xffffffffu, (tid >> 5) & 3, 0);
    const uint32_t bar = sb + G_BAR;
    const int t_begin = (blockIdx.x * G1_TILES) / gridDim.x;
    const int t_end = ((blockIdx.x + 1) * G1_TILES) / gridDim.x;
    const int mb0 = t_begin / G1_NB;
    asm volatile("griddepcontrol.launch_dependents;");
    KT(1, 0);
    if (tid == 0) {
        for (int i = 0; i < G_ST; i++) { mbar_init(bar + 8 * i, 1); mbar_init(bar + 8 * (G_ST + i), 2); }
        fence_async();
    }
    __syncthreads();
    if (wg == 2) {
        asm volatile("setmaxnreg.dec.sync.aligned.u32 40;");
        if (warp == 0) {
            if (lane == 0) {
                int it = 0;
                for (int tile = t_begin; tile < t_end; tile++) {
                    const int mb = tile / G1_NB, nb = tile % G1_NB;
                    for (int kb = 0; kb < 16; kb++, it++) {
                        const int st = it % G_ST;
                        mbar_wait(bar + 8 * (G_ST + st), ((it / G_ST) & 1) ^ 1);
                        const uint32_t fb = bar + 8 * st, sa = sb + st * G_STAGE;
                        mbar_expect(fb, G_STAGE);
                        tma_load(sa, &tm.x, kb * 64, mb * 128, fb);
                        tma_load(sa + 16384, &tm.wg, nb * 128, kb * 64, fb);
                        tma_load(sa + 16384 + 8192, &tm.wg, nb * 128 + 64, kb * 64, fb);
                        tma_load(sa + 16384 + 16384, &tm.wu, nb * 128, kb * 64, fb);
                        tma_load(sa + 16384 + 24576, &tm.wu, nb * 128 + 64, kb * 64, fb);
                    }
                }
                for (int pass = 0; pass < 4; pass++) {
                    for (int i = g1_first(pass); i < g1_count(pass); i += gridDim.x) {
                        const int tile = pass == 1 ? i : pass == 3 ? T_MID + (i >> 2) : NFULL + i, mb = tile >> 2, nb = tile & 3;
                        if (pass < 2) {
                            wait_count(&g_hcnt[mb], 2 * G1_NB);
                            asm volatile("fence.proxy.async;" ::: "memory");
                            for (int kb = 0; kb < FF / 64; kb++, it++) g_load_block(sb, bar, it, &tm.h, kb * 64, mb * 128, &tm.wd, nb * 256);
                        }
                        if (pass > 0) {
                            const int k0 = pass == 3 ? (i & 3) * 16 : 0, k1 = pass == 3 ? k0 + 16 : HD / 64;
                            wait_count(&g_ocnt[mb], NH * 4 * 2);
                            asm volatile("fence.proxy.async;" ::: "memory");
                            for (int kb = k0; kb < k1; kb++, it++) g_load_block(sb, bar, it, &tm.o, kb * 64, mb * 128, &tm.wo, nb * 256);
                        }
                    }
                }
            }
        }
    } else {
        asm volatile("setmaxnreg.inc.sync.aligned.u32 232;");
        float d[128];
        int it = 0;
        float s0 = 0.f, s1 = 0.f;
        const uint32_t epi = sb + G_EPI + wg * 16384;
        const int row = warp * 16 + ((lane >> 3) & 1) * 8 + (lane & 7);
        for (int tile = t_begin; tile < t_end; tile++) {
            const int mb = tile / G1_NB, nb = tile % G1_NB;
            for (int kb = 0; kb < 16; kb++, it++) g_mma_block(d, sb, bar, it, wg, tid, kb == 0);
            if (tile == t_begin || nb == 0) {
                const uint32_t* gp = &g_gate[mb * 128 + wg * 64 + warp * 16 + (lane >> 2)];
                uint32_t u0, u1, n = 0;
                do { u0 = ld_strong4(gp); u1 = ld_strong4(gp + 8); if (++n > 20000000u) __trap(); } while (u0 == 0u || u1 == 0u);
                s0 = 1.0f - __uint_as_float(u0); s1 = 1.0f - __uint_as_float(u1);
                __syncwarp();
            }
            wg_wait<0>();
            if ((tid & 127) == 0) { mbar_arrive(bar + 8 * (G_ST + (it - 1) % G_ST)); bulk_wait_read(); }
            bar_sync(1 + wg, 128);
#pragma unroll
            for (int j = 0; j < 16; j += 2) {
                uint32_t p[4];
#pragma unroll
                for (int q = 0; q < 4; q++) {
                    const int i = (j + (q >> 1)) * 4 + (q & 1) * 2;
                    const float sc = (q & 1) ? s1 : s0;
                    const float g0 = d[i], g1 = d[i + 1];
                    const float h0 = __fdividef(g0, 1.0f + __expf(-g0)) * d[64 + i] * sc;
                    const float h1 = __fdividef(g1, 1.0f + __expf(-g1)) * d[64 + i + 1] * sc;
                    p[q] = pack_bf16(h0, h1);
                }
                const int cgp = j + (lane >> 4);
                stsm4(epi + (cgp >> 3) * 8192 + row * 128 + (((cgp & 7) ^ (row & 7)) << 4), p[0], p[1], p[2], p[3]);
            }
            fence_async();
            bar_sync(1 + wg, 128);
            if ((tid & 127) == 0) {
                tma_store(&tm.hs, epi, nb * 128, mb * 128 + wg * 64);
                tma_store(&tm.hs, epi + 8192, nb * 128 + 64, mb * 128 + wg * 64);
                bulk_commit();
            }
        }
        if ((tid & 127) == 0) {
            bulk_wait_all();
            __threadfence();
            const int n0 = min(t_end, (mb0 + 1) * G1_NB) - t_begin;
            atomicAdd(&g_hcnt[mb0], (uint32_t)n0);
            if (t_end - t_begin > n0) atomicAdd(&g_hcnt[mb0 + 1], (uint32_t)(t_end - t_begin - n0));
        }
        for (int pass = 0; pass < 4; pass++) {
            for (int i = g1_first(pass); i < g1_count(pass); i += gridDim.x) {
                const int tile = pass == 1 ? i : pass == 3 ? T_MID + (i >> 2) : NFULL + i;
                const int nkb = pass == 0 ? FF / 64 : pass == 1 ? (FF + HD) / 64 : pass == 2 ? HD / 64 : 16;
                for (int kb = 0; kb < nkb; kb++, it++) g_mma_block(d, sb, bar, it, wg, tid, kb == 0);
                wg_wait<0>();
                if ((tid & 127) == 0) mbar_arrive(bar + 8 * (G_ST + (it - 1) % G_ST));
                float4* pre = g_pre + (tile - NFULL) * (32 * 256) + tid;
                if (pass >= 2) { if ((tid & 31) == 0) wait_count(&g_pcnt[tile], 8); __syncwarp(); }
                if (pass == 0) {
#pragma unroll
                    for (int q = 0; q < 32; q++) __stcg(pre + q * 256, make_float4(d[4 * q], d[4 * q + 1], d[4 * q + 2], d[4 * q + 3]));
                    __threadfence();
                    __syncwarp();
                    if ((tid & 31) == 0) atomicAdd(&g_pcnt[tile], 1u);
                } else if (pass == 3) {
                    float4 r[8];
#pragma unroll
                    for (int q = 0; q < 8; q++) r[q] = __ldcg(pre + ((i & 3) * 8 + q) * 256);
                    g_split_finish<4>(d, r, g_sk + (tile - T_MID) * 4 * (32 * 256), tile, i & 3, out, tid);
                } else {
                    if (pass == 2) {
#pragma unroll
                        for (int q = 0; q < 32; q++) {
                            const float4 u = __ldcg(pre + q * 256); d[4 * q] += u.x; d[4 * q + 1] += u.y; d[4 * q + 2] += u.z; d[4 * q + 3] += u.w;
                            if ((q & 7) == 7) __syncwarp();
                        }
                    }
                    g_store_tile(d, &tm.out, epi, tile >> 2, tile & 3, wg, tid);
                }
            }
        }
        if ((tid & 127) == 0) bulk_wait_all();
        KT(1, 1);
    }
    __syncwarp();
    asm volatile("griddepcontrol.wait;" ::: "memory");
}

struct G2Maps { CUtensorMap o, wo; };

__global__ void __launch_bounds__(384, 1) g2_kernel(const __grid_constant__ G2Maps tm, bf16* __restrict__ out) {
    extern __shared__ __align__(1024) unsigned char smem_raw[];
    const uint32_t sb = (smem_u32(smem_raw) + 1023) & ~1023u;
    const int tid = threadIdx.x, lane = tid & 31;
    const int wg = __shfl_sync(0xffffffffu, tid >> 7, 0);
    const int warp = __shfl_sync(0xffffffffu, (tid >> 5) & 3, 0);
    const uint32_t bar = sb + G_BAR;
    const int ks = blockIdx.x & 7, tile = T_LATE + (blockIdx.x >> 3), nb = tile & 3, mb = tile >> 2;
    KT(2, 0);
    if (tid == 0) {
        for (int i = 0; i < G_ST; i++) { mbar_init(bar + 8 * i, 1); mbar_init(bar + 8 * (G_ST + i), 2); }
        fence_async();
        for (int it = 0; it < G_ST; it++) mbar_expect(bar + 8 * it, G_STAGE);
    }
    __syncthreads();
    if (tid < 256 && (tid & 7) == 0) {
        const int it = tid >> 5, q = (tid >> 3) & 3;
        if (it < G_ST) tma_load(sb + it * G_STAGE + 16384 + q * 8192, &tm.wo, nb * 256 + q * 64, (ks * 8 + it) * 64, bar + 8 * it);
        else tma_prefetch(&tm.wo, nb * 256 + q * 64, (ks * 8 + it) * 64);
    }
    __syncwarp();
    PT(16);
    asm volatile("griddepcontrol.wait;" ::: "memory");
    PT(17);
    if (wg == 2) {
        asm volatile("setmaxnreg.dec.sync.aligned.u32 40;");
        if (lane == 0) tma_load(sb + warp * G_STAGE, &tm.o, (ks * 8 + warp) * 64, mb * 128, bar + 8 * warp);
        if (warp == 0 && lane == 0) {
            for (int it = G_ST; it < 8; it++) g_load_block(sb, bar, it, &tm.o, (ks * 8 + it) * 64, mb * 128, &tm.wo, nb * 256);
        } else if (warp == 1) {
            if (blockIdx.x < SEQ / 32) g_gate[blockIdx.x * 32 + lane] = 0u;
            if (blockIdx.x == 0) { if (lane < 16) { g_hcnt[lane] = 0u; g_ocnt[lane] = 0u; } g_pcnt[lane] = 0u; g_pcnt[32 + lane] = 0u; }
        }
    } else {
        asm volatile("setmaxnreg.inc.sync.aligned.u32 232;");
        float d[128];
        float4 r[4];
        const float4* pre = g_pre + ((tile - NFULL) * 32 + ks * 4) * 256 + tid;
#pragma unroll
        for (int q = 0; q < 4; q++) r[q] = __ldcg(pre + q * 256);
        for (int it = 0; it < 8; it++) { g_mma_block(d, sb, bar, it, wg, tid, it == 0); if (it == 0) PT(18); }
        wg_wait<0>();
        PT(19);
        g_split_finish<8>(d, r, g_sk + ((T_LATE - T_MID) * 4 + (tile - T_LATE) * 8) * (32 * 256), tile, ks, out, tid);
        KT(2, 1);
    }
}

typedef CUresult (*EncodeFn)(CUtensorMap*, CUtensorMapDataType, cuuint32_t, void*, const cuuint64_t*, const cuuint64_t*, const cuuint32_t*,
                             const cuuint32_t*, CUtensorMapInterleave, CUtensorMapSwizzle, CUtensorMapL2promotion, CUtensorMapFloatOOBfill);

static void make_map(EncodeFn enc, CUtensorMap* m, const void* ptr, uint64_t rows, uint64_t cols, uint32_t box_rows) {
    cuuint64_t dims[2] = {cols, rows};
    cuuint64_t strides[1] = {cols * 2};
    cuuint32_t box[2] = {64, box_rows};
    cuuint32_t es[2] = {1, 1};
    enc(m, CU_TENSOR_MAP_DATA_TYPE_BFLOAT16, 2, (void*)ptr, dims, strides, box, es, CU_TENSOR_MAP_INTERLEAVE_NONE,
        CU_TENSOR_MAP_SWIZZLE_128B, CU_TENSOR_MAP_L2_PROMOTION_L2_256B, CU_TENSOR_MAP_FLOAT_OOB_FILL_NONE);
}

extern "C" void kernel_launch(void* const* d_in, const int* in_sizes, int n_in, void* d_out, int out_size) {
    (void)in_sizes; (void)n_in; (void)out_size;
    const bf16* x = (const bf16*)d_in[0];
    const bf16* mem0 = (const bf16*)d_in[1];
    const bf16* gate_w = (const bf16*)d_in[11];
    static EncodeFn enc = nullptr;
    static int n_sm = 0;
    static void *pO = nullptr, *pH = nullptr;
    if (!enc) {
        void* fn = nullptr;
        cudaDriverEntryPointQueryResult qr;
        cudaGetDriverEntryPoint("cuTensorMapEncodeTiled", &fn, cudaEnableDefault, &qr);
        enc = (EncodeFn)fn;
        cudaDeviceGetAttribute(&n_sm, cudaDevAttrMultiProcessorCount, 0);
        cudaFuncSetAttribute(r_kernel, cudaFuncAttributeMaxDynamicSharedMemorySize, R_SMEM);
        cudaFuncSetAttribute(g1_kernel, cudaFuncAttributeMaxDynamicSharedMemorySize, G_SMEM);
        cudaFuncSetAttribute(g2_kernel, cudaFuncAttributeMaxDynamicSharedMemorySize, G_SMEM);
        cudaGetSymbolAddress(&pO, g_O);
        cudaGetSymbolAddress(&pH, g_H);
    }
    RMaps rm; G1Maps m1; G2Maps m2;
    make_map(enc, &rm.x, x, SEQ, DM, 32);
    for (int i = 0; i < 3; i++) make_map(enc, &rm.w[i], d_in[2 + i], DM, HD, 64);
    make_map(enc, &rm.wo, d_in[5], HD, DM, 128);
    make_map(enc, &rm.o, pO, SEQ, HD, 16);
    make_map(enc, &m1.x, x, SEQ, DM, 128);
    make_map(enc, &m1.wg, d_in[8], DM, FF, 64);
    make_map(enc, &m1.wu, d_in[9], DM, FF, 64);
    make_map(enc, &m1.hs, pH, SEQ, FF, 64);
    make_map(enc, &m1.o, pO, SEQ, HD, 128);
    make_map(enc, &m1.h, pH, SEQ, FF, 128);
    make_map(enc, &m1.wo, d_in[5], HD, DM, 64);
    make_map(enc, &m1.wd, d_in[10], FF, DM, 64);
    make_map(enc, &m1.out, d_out, SEQ, DM, 64);
    m2.o = m1.o; m2.wo = m1.wo;

    cudaStream_t st = cudaStreamPerThread;
    {
        cudaLaunchConfig_t cfg = {};
        cfg.gridDim = dim3(96); cfg.blockDim = dim3(384); cfg.dynamicSmemBytes = R_SMEM; cfg.stream = st;
        cudaLaunchAttribute at[1];
        at[0].id = cudaLaunchAttributeClusterDimension; at[0].val.clusterDim.x = 3; at[0].val.clusterDim.y = 1; at[0].val.clusterDim.z = 1;
        cfg.attrs = at; cfg.numAttrs = 1;
        cudaLaunchKernelEx(&cfg, r_kernel, rm, mem0, x, gate_w);
    }
    {
        cudaLaunchConfig_t cfg = {};
        cfg.gridDim = dim3(n_sm - 96); cfg.blockDim = dim3(384); cfg.dynamicSmemBytes = G_SMEM; cfg.stream = st;
        cudaLaunchAttribute at[1];
        at[0].id = cudaLaunchAttributeProgrammaticStreamSerialization; at[0].val.programmaticStreamSerializationAllowed = 1;
        cfg.attrs = at; cfg.numAttrs = 1;
        cudaLaunchKernelEx(&cfg, g1_kernel, m1, (bf16*)d_out);
    }
    {
        cudaLaunchConfig_t cfg = {};
        cfg.gridDim = dim3((64 - T_LATE) * 8); cfg.blockDim = dim3(384); cfg.dynamicSmemBytes = G_SMEM; cfg.stream = st;
        cudaLaunchAttribute at[1];
        at[0].id = cudaLaunchAttributeProgrammaticStreamSerialization; at[0].val.programmaticStreamSerializationAllowed = 1;
        cfg.attrs = at; cfg.numAttrs = 1;
        cudaLaunchKernelEx(&cfg, g2_kernel, m2, (bf16*)d_out);
    }
}
```

```cpp
#include <cuda_runtime.h>
#include <cuda_bf16.h>
#include <cuda.h>
#include <stdint.h>

typedef __nv_bfloat16 bf16;

constexpr int SEQ = 2048, DM = 1024, NH = 32, DH = 128, NMEM = 8, SEG = 32, NSEG = 64, FF = 3584;
constexpr int HD = NH * DH;

__device__ bf16 g_O[SEQ * HD];
__device__ bf16 g_H[SEQ * FF];
__device__ uint32_t g_gate[SEQ];
__device__ uint32_t g_part[4][128 * 32 * 32];
__device__ uint32_t g_mem[4][DM * 4];
constexpr int NFULL = 36, T_MID = 44, T_LATE = 52;
constexpr int NPRE = 64 - NFULL;
__device__ float4 g_pre[NPRE * 32 * 256];
__device__ float4 g_sk[((T_LATE - T_MID) * 4 + (64 - T_LATE) * 8) * 32 * 256];
__device__ uint32_t g_skcnt[64], g_pcnt[64];
__device__ uint32_t g_hcnt[16], g_ocnt[16];
#define KT(k, i)
#define PT(i)

#define DEVINL __device__ __forceinline__
constexpr long long SPIN_LIMIT = 4000000000LL;

DEVINL uint32_t smem_u32(const void* p) { return (uint32_t)__cvta_generic_to_shared(p); }
DEVINL void mbar_init(uint32_t bar, uint32_t cnt) { asm volatile("mbarrier.init.shared::cta.b64 [%0], %1;" ::"r"(bar), "r"(cnt) : "memory"); }
DEVINL void mbar_arrive(uint32_t bar) { asm volatile("mbarrier.arrive.shared::cta.b64 _, [%0];" ::"r"(bar) : "memory"); }
DEVINL void mbar_expect(uint32_t bar, uint32_t bytes) { asm volatile("mbarrier.arrive.expect_tx.shared::cta.b64 _, [%0], %1;" ::"r"(bar), "r"(bytes) : "memory"); }
DEVINL void mbar_arrive_remote(uint32_t cbar) { asm volatile("mbarrier.arrive.relaxed.cluster.shared::cluster.b64 _, [%0];" ::"r"(cbar) : "memory"); }
DEVINL bool mbar_try(uint32_t bar, uint32_t par) {
    uint32_t ok;
    asm volatile("{ .reg .pred p; mbarrier.try_wait.parity.shared::cta.b64 p, [%1], %2; selp.u32 %0, 1, 0, p; }" : "=r"(ok) : "r"(bar), "r"(par) : "memory");
    return ok;
}
__device__ __noinline__ void mbar_wait_slow(uint32_t bar, uint32_t par) {
    long long t0 = clock64();
    while (!mbar_try(bar, par)) { if (clock64() - t0 > SPIN_LIMIT) __trap(); }
}
DEVINL void mbar_wait(uint32_t bar, uint32_t par) {
    uint32_t n = 0;
    while (!mbar_try(bar, par)) { if (++n > 200000000u) __trap(); }
}
DEVINL uint32_t mapa(uint32_t a, uint32_t r) { uint32_t o; asm volatile("mapa.shared::cluster.u32 %0, %1, %2;" : "=r"(o) : "r"(a), "r"(r)); return o; }
DEVINL void fence_async() { asm volatile("fence.proxy.async.shared::cta;" ::: "memory"); }
DEVINL void bar_sync(int id, int n) { asm volatile("bar.sync %0, %1;" ::"r"(id), "r"(n) : "memory"); }
DEVINL void cluster_sync() { asm volatile("barrier.cluster.arrive.aligned; barrier.cluster.wait.aligned;" ::: "memory"); }
DEVINL void tma_load(uint32_t dst, const CUtensorMap* tm, int c0, int c1, uint32_t bar) {
    asm volatile("cp.async.bulk.tensor.2d.shared::cluster.global.mbarrier::complete_tx::bytes [%0], [%1, {%3, %4}], [%2];"
                 ::"r"(dst), "l"(tm), "r"(bar), "r"(c0), "r"(c1) : "memory");
}
DEVINL void tma_prefetch(const CUtensorMap* tm, int c0, int c1) {
    asm volatile("cp.async.bulk.prefetch.tensor.2d.L2.global [%0, {%1, %2}];" ::"l"(tm), "r"(c0), "r"(c1) : "memory");
}
DEVINL void tma_store(const CUtensorMap* tm, uint32_t src, int c0, int c1) {
    asm volatile("cp.async.bulk.tensor.2d.global.shared::cta.bulk_group [%0, {%2, %3}], [%1];" ::"l"(tm), "r"(src), "r"(c0), "r"(c1) : "memory");
}
DEVINL void bulk_commit() { asm volatile("cp.async.bulk.commit_group;" ::: "memory"); }
DEVINL void bulk_wait_read() { asm volatile("cp.async.bulk.wait_group.read 0;" ::: "memory"); }
DEVINL void bulk_wait_all() { asm volatile("cp.async.bulk.wait_group 0;" ::: "memory"); }
DEVINL void bulk_s2s(uint32_t cdst, uint32_t src, uint32_t bytes, uint32_t cbar) {
    asm volatile("cp.async.bulk.shared::cluster.shared::cta.mbarrier::complete_tx::bytes [%0], [%1], %2, [%3];" ::"r"(cdst), "r"(src), "r"(bytes), "r"(cbar) : "memory");
}
DEVINL void st_async16(uint32_t cdst, uint4 v, uint32_t cbar) {
    asm volatile("st.async.shared::cluster.mbarrier::complete_tx::bytes.v4.b32 [%0], {%1,%2,%3,%4}, [%5];" ::"r"(cdst), "r"(v.x), "r"(v.y), "r"(v.z), "r"(v.w), "r"(cbar) : "memory");
}
DEVINL uint64_t mkdesc(uint32_t addr, uint32_t lbo, uint32_t sbo, uint32_t swz) {
    return (uint64_t)((addr & 0x3FFFF) >> 4) | ((uint64_t)(lbo >> 4) << 16) | ((uint64_t)(sbo >> 4) << 32) | ((uint64_t)swz << 62);
}
constexpr uint32_t SB0 = 1024;
__host__ __device__ constexpr uint64_t cdesc(uint32_t off, uint32_t lbo, uint32_t sbo, uint32_t swz) {
    return (uint64_t)(((SB0 + off) & 0x3FFFF) >> 4) | ((uint64_t)(lbo >> 4) << 16) | ((uint64_t)(sbo >> 4) << 32) | ((uint64_t)swz << 62);
}
DEVINL float ex2(float x) { float y; asm("ex2.approx.ftz.f32 %0, %1;" : "=f"(y) : "f"(x)); return y; }
DEVINL void spin_clk(int d) { uint32_t t0, t1; asm volatile("mov.u32 %0, %%clock;" : "=r"(t0)); do { asm volatile("mov.u32 %0, %%clock;" : "=r"(t1)); } while ((int)(t1 - t0) < d); }
#define PROBE_GAP 150
#define OPAQUE(x) asm volatile("" : "+r"(x))
DEVINL void wg_fence() { asm volatile("wgmma.fence.sync.aligned;" ::: "memory"); }
DEVINL void wg_commit() { asm volatile("wgmma.commit_group.sync.aligned;" ::: "memory"); }
template <int N> DEVINL void wg_wait() { asm volatile("wgmma.wait_group.sync.aligned %0;" ::"n"(N) : "memory"); }
DEVINL uint32_t pack_bf16(float lo, float hi) { uint32_t r; asm("cvt.rn.bf16x2.f32 %0, %1, %2;" : "=r"(r) : "f"(hi), "f"(lo)); return r; }
DEVINL void ldsm4(uint32_t* r, uint32_t a) { asm volatile("ldmatrix.sync.aligned.m8n8.x4.shared.b16 {%0,%1,%2,%3}, [%4];" : "=r"(r[0]), "=r"(r[1]), "=r"(r[2]), "=r"(r[3]) : "r"(a) : "memory"); }
DEVINL void ldsm4t(uint32_t* r, uint32_t a) { asm volatile("ldmatrix.sync.aligned.m8n8.x4.trans.shared.b16 {%0,%1,%2,%3}, [%4];" : "=r"(r[0]), "=r"(r[1]), "=r"(r[2]), "=r"(r[3]) : "r"(a) : "memory"); }
DEVINL void ldsm4t_if(uint32_t* r, uint32_t a, int c) { asm volatile("{ .reg .pred p; setp.ne.s32 p, %5, 0; @p ldmatrix.sync.aligned.m8n8.x4.trans.shared.b16 {%0,%1,%2,%3}, [%4]; }" : "+r"(r[0]), "+r"(r[1]), "+r"(r[2]), "+r"(r[3]) : "r"(a), "r"(c) : "memory"); }
DEVINL void stsm4(uint32_t a, uint32_t r0, uint32_t r1, uint32_t r2, uint32_t r3) { asm volatile("stmatrix.sync.aligned.m8n8.x4.shared.b16 [%0], {%1,%2,%3,%4};" ::"r"(a), "r"(r0), "r"(r1), "r"(r2), "r"(r3) : "memory"); }
DEVINL void stsm4t(uint32_t a, uint32_t r0, uint32_t r1, uint32_t r2, uint32_t r3) { asm volatile("stmatrix.sync.aligned.m8n8.x4.trans.shared.b16 [%0], {%1,%2,%3,%4};" ::"r"(a), "r"(r0), "r"(r1), "r"(r2), "r"(r3) : "memory"); }
DEVINL void sts32(uint32_t a, uint32_t v) { asm volatile("st.shared.b32 [%0], %1;" ::"r"(a), "r"(v) : "memory"); }
DEVINL void sts128(uint32_t a, uint4 v) { asm volatile("st.shared.v4.b32 [%0], {%1,%2,%3,%4};" ::"r"(a), "r"(v.x), "r"(v.y), "r"(v.z), "r"(v.w) : "memory"); }
DEVINL uint4 lds128(uint32_t a) { uint4 v; asm volatile("ld.shared.v4.b32 {%0,%1,%2,%3}, [%4];" : "=r"(v.x), "=r"(v.y), "=r"(v.z), "=r"(v.w) : "r"(a) : "memory"); return v; }
DEVINL uint4 ld_strong16(const void* p) { uint4 v; asm volatile("ld.relaxed.gpu.global.v4.u32 {%0,%1,%2,%3}, [%4];" : "=r"(v.x), "=r"(v.y), "=r"(v.z), "=r"(v.w) : "l"(p) : "memory"); return v; }
DEVINL void st_strong8(void* p, uint32_t a, uint32_t b) { asm volatile("st.relaxed.gpu.global.v2.u32 [%0], {%1,%2};" ::"l"(p), "r"(a), "r"(b) : "memory"); }
DEVINL void st_strong4(void* p, uint32_t a) { asm volatile("st.relaxed.gpu.global.u32 [%0], %1;" ::"l"(p), "r"(a) : "memory"); }
DEVINL void st_strong16(void* p, uint4 v) { asm volatile("st.relaxed.gpu.global.v4.u32 [%0], {%1,%2,%3,%4};" ::"l"(p), "r"(v.x), "r"(v.y), "r"(v.z), "r"(v.w) : "memory"); }
DEVINL uint32_t pack_nz(float lo, float hi) { uint32_t r = pack_bf16(lo, hi); return r == 0u ? 0x8000u : r; }
DEVINL uint32_t min4(uint4 v, uint32_t m) { return __vimin3_u32(__vimin3_u32(v.x, v.y, m), v.z, v.w); }
DEVINL void mma16816(float* d, uint32_t a0, uint32_t a1, uint32_t a2, uint32_t a3, uint32_t b0, uint32_t b1) {
    asm volatile("mma.sync.aligned.m16n8k16.row.col.f32.bf16.bf16.f32 {%0,%1,%2,%3}, {%4,%5,%6,%7}, {%8,%9}, {%0,%1,%2,%3};"
                 : "+f"(d[0]), "+f"(d[1]), "+f"(d[2]), "+f"(d[3]) : "r"(a0), "r"(a1), "r"(a2), "r"(a3), "r"(b0), "r"(b1));
}
DEVINL void mma1688(float* d, uint32_t a0, uint32_t a1, uint32_t b0) {
    asm volatile("mma.sync.aligned.m16n8k8.row.col.f32.bf16.bf16.f32 {%0,%1,%2,%3}, {%4,%5}, {%6}, {%0,%1,%2,%3};"
                 : "+f"(d[0]), "+f"(d[1]), "+f"(d[2]), "+f"(d[3]) : "r"(a0), "r"(a1), "r"(b0));
}
template <int TA, int TB> DEVINL void wg_ss8(float* d, uint64_t da, uint64_t db, int sc) {
    asm volatile("{ .reg .pred p; setp.ne.b32 p, %6, 0; wgmma.mma_async.sync.aligned.m64n8k16.f32.bf16.bf16 {%0,%1,%2,%3}, %4, %5, p, 1, 1, %7, %8; }"
                 : "+f"(d[0]), "+f"(d[1]), "+f"(d[2]), "+f"(d[3]) : "l"(da), "l"(db), "r"(sc), "n"(TA), "n"(TB));
}
template <int TB> DEVINL void wg_rs8(float* d, const uint32_t* a, uint64_t db, int sc) {
    asm volatile("{ .reg .pred p; setp.ne.b32 p, %9, 0; wgmma.mma_async.sync.aligned.m64n8k16.f32.bf16.bf16 {%0,%1,%2,%3}, {%4,%5,%6,%7}, %8, p, 1, 1, %10; }"
                 : "+f"(d[0]), "+f"(d[1]), "+f"(d[2]), "+f"(d[3]) : "r"(a[0]), "r"(a[1]), "r"(a[2]), "r"(a[3]), "l"(db), "r"(sc), "n"(TB));
}
#define ACC16(d) "+f"(d[0]), "+f"(d[1]), "+f"(d[2]), "+f"(d[3]), "+f"(d[4]), "+f"(d[5]), "+f"(d[6]), "+f"(d[7]), "+f"(d[8]), "+f"(d[9]), "+f"(d[10]), "+f"(d[11]), "+f"(d[12]), "+f"(d[13]), "+f"(d[14]), "+f"(d[15])
template <int TA> DEVINL void wg_ss32(float* d, uint64_t da, uint64_t db, int sc) {
    asm volatile("{ .reg .pred p; setp.ne.b32 p, %18, 0; wgmma.mma_async.sync.aligned.m64n32k16.f32.bf16.bf16 {%0,%1,%2,%3,%4,%5,%6,%7,%8,%9,%10,%11,%12,%13,%14,%15}, %16, %17, p, 1, 1, %19, 0; }"
                 : ACC16(d) : "l"(da), "l"(db), "r"(sc), "n"(TA));
}
DEVINL void wg_rs32(float* d, const uint32_t* a, uint64_t db, int sc) {
    asm volatile("{ .reg .pred p; setp.ne.b32 p, %21, 0; wgmma.mma_async.sync.aligned.m64n32k16.f32.bf16.bf16 {%0,%1,%2,%3,%4,%5,%6,%7,%8,%9,%10,%11,%12,%13,%14,%15}, {%16,%17,%18,%19}, %20, p, 1, 1, 0; }"
                 : ACC16(d) : "r"(a[0]), "r"(a[1]), "r"(a[2]), "r"(a[3]), "l"(db), "r"(sc));
}
DEVINL void wg_ss40(float* d, uint64_t da, uint64_t db, int sc) {
    asm volatile("{ .reg .pred p; setp.ne.b32 p, %22, 0; wgmma.mma_async.sync.aligned.m64n40k16.f32.bf16.bf16 {%0,%1,%2,%3,%4,%5,%6,%7,%8,%9,%10,%11,%12,%13,%14,%15,%16,%17,%18,%19}, %20, %21, p, 1, 1, 1, 1; }"
                 : ACC16(d), "+f"(d[16]), "+f"(d[17]), "+f"(d[18]), "+f"(d[19]) : "l"(da), "l"(db), "r"(sc));
}
#define A8(d, o) "+f"(d[o]), "+f"(d[o + 1]), "+f"(d[o + 2]), "+f"(d[o + 3]), "+f"(d[o + 4]), "+f"(d[o + 5]), "+f"(d[o + 6]), "+f"(d[o + 7])
#define A32(d, o) A8(d, o), A8(d, o + 8), A8(d, o + 16), A8(d, o + 24)
DEVINL void wg_ss256(float* d, uint64_t da, uint64_t db, int sc) {
    asm volatile(
        "{ .reg .pred p; setp.ne.b32 p, %130, 0;\n"
        "wgmma.mma_async.sync.aligned.m64n256k16.f32.bf16.bf16 {"
        "%0,%1,%2,%3,%4,%5,%6,%7,%8,%9,%10,%11,%12,%13,%14,%15,%16,%17,%18,%19,%20,%21,%22,%23,%24,%25,%26,%27,%28,%29,%30,%31,"
        "%32,%33,%34,%35,%36,%37,%38,%39,%40,%41,%42,%43,%44,%45,%46,%47,%48,%49,%50,%51,%52,%53,%54,%55,%56,%57,%58,%59,%60,%61,%62,%63,"
        "%64,%65,%66,%67,%68,%69,%70,%71,%72,%73,%74,%75,%76,%77,%78,%79,%80,%81,%82,%83,%84,%85,%86,%87,%88,%89,%90,%91,%92,%93,%94,%95,"
        "%96,%97,%98,%99,%100,%101,%102,%103,%104,%105,%106,%107,%108,%109,%110,%111,%112,%113,%114,%115,%116,%117,%118,%119,%120,%121,%122,%123,%124,%125,%126,%127"
        "}, %128, %129, p, 1, 1, 0, 1; }"
        : A32(d, 0), A32(d, 32), A32(d, 64), A32(d, 96) : "l"(da), "l"(db), "r"(sc));
}

DEVINL float gate_row(const bf16* __restrict__ xr, const bf16* __restrict__ gate_w, int lane) {
    float acc = 0.f;
#pragma unroll
    for (int i = 0; i < 4; i++) {
        const uint4 xv = __ldg((const uint4*)xr + i * 32 + lane), gv = __ldg((const uint4*)gate_w + i * 32 + lane);
        const uint32_t xa[4] = {xv.x, xv.y, xv.z, xv.w}, ga[4] = {gv.x, gv.y, gv.z, gv.w};
#pragma unroll
        for (int e = 0; e < 4; e++) {
            acc = fmaf(__uint_as_float(xa[e] << 16), __uint_as_float(ga[e] << 16), acc);
            acc = fmaf(__uint_as_float(xa[e] & 0xffff0000u), __uint_as_float(ga[e] & 0xffff0000u), acc);
        }
    }
#pragma unroll
    for (int o = 16; o > 0; o >>= 1) acc += __shfl_xor_sync(0xffffffffu, acc, o);
    return 1.0f / (1.0f + __expf(-acc));
}
DEVINL uint32_t ld_strong4(const void* p) { uint32_t v; asm volatile("ld.relaxed.gpu.global.u32 %0, [%1];" : "=r"(v) : "l"(p) : "memory"); return v; }
DEVINL void wait_count(const uint32_t* p, uint32_t want) {
    uint32_t v, n = 0;
    while (true) {
        asm volatile("ld.acquire.gpu.global.u32 %0, [%1];" : "=r"(v) : "l"(p) : "memory");
        if (v >= want) break;
        __nanosleep(200);
        if (++n > 10000000u) __trap();
    }
}

constexpr int KR = 44;
constexpr int KS = 64 - KR;
constexpr int R_W = 0;
constexpr int R_WO = KS * 4096;
constexpr int R_QX = R_WO + 65536;
constexpr int R_RING = R_WO + 98304;
constexpr int R_K = R_RING + 24576;
constexpr int R_V = R_K + 10240;
constexpr int R_QM = R_V + 10240;
constexpr int R_O = R_QM + 2048;
constexpr int R_BAR = R_O + 2048;
constexpr int R_G = R_BAR + 256 + 512 + 256 + 128;
constexpr int R_Z = R_G + 256;
constexpr int R_SMEM = R_Z + 1024;
enum { B_FULL = 0, B_EMPTY = 5, B_MEM = 8, B_HOP1 = 12, B_XT, B_TFREE, B_O, B_AFREE0, B_AFREE1, B_PRO0, B_PRO1, B_XRECV, B_P, B_XDONE, B_OST0, B_OST1, B_HOPV };
#define D2_BASE 900
#define D2_STEP 200
#define PD2 6
#define CPB 8192
#define DDUP 0
#define WGAP 0
#define PVD 400
#define ELD 700
#define QD 3
#define DQ 1700
#define D3 0

DEVINL uint32_t clk32() { uint32_t c_; asm volatile("mov.u32 %0, %%clock;" : "=r"(c_)); return c_; }
DEVINL void spin_until(uint32_t t) { while ((uint32_t)(t - clk32() - 1u) < 100000u) {} }
#define PROF(i)
#define PROF2(i)
#define PROF3(i, val)
DEVINL void e_arrive(uint32_t bar) { asm volatile("{ .reg .pred p; elect.sync _|p, 0xffffffff; @p mbarrier.arrive.shared::cta.b64 _, [%0]; }" ::"r"(bar) : "memory"); }
DEVINL void e_arrive_remote(uint32_t cbar) { asm volatile("{ .reg .pred p; elect.sync _|p, 0xffffffff; @p mbarrier.arrive.relaxed.cluster.shared::cluster.b64 _, [%0]; }" ::"r"(cbar) : "memory"); }
DEVINL void e_count(uint32_t* p) { asm volatile("{ .reg .pred p; elect.sync _|p, 0xffffffff; @p red.relaxed.gpu.global.add.u32 [%0], 1; }" ::"l"(p) : "memory"); }
DEVINL void e_expect(uint32_t bar, uint32_t bytes) { asm volatile("{ .reg .pred p; elect.sync _|p, 0xffffffff; @p mbarrier.arrive.expect_tx.shared::cta.b64 _, [%0], %1; }" ::"r"(bar), "r"(bytes) : "memory"); }
DEVINL void e_tma_load(uint32_t dst, const CUtensorMap* tm, int c0, int c1, uint32_t bar) {
    asm volatile("{ .reg .pred p; elect.sync _|p, 0xffffffff; @p cp.async.bulk.tensor.2d.shared::cluster.global.mbarrier::complete_tx::bytes [%0], [%1, {%3, %4}], [%2]; }"
                 ::"r"(dst), "l"(tm), "r"(bar), "r"(c0), "r"(c1) : "memory");
}
DEVINL void e_tma_store(const CUtensorMap* tm, uint32_t src, int c0, int c1) {
    asm volatile("{ .reg .pred p; elect.sync _|p, 0xffffffff; @p cp.async.bulk.tensor.2d.global.shared::cta.bulk_group [%0, {%2, %3}], [%1]; }" ::"l"(tm), "r"(src), "r"(c0), "r"(c1) : "memory");
}
DEVINL void e_bulk_s2g(void* dst, uint32_t src, uint32_t bytes) {
    asm volatile("{ .reg .pred p; elect.sync _|p, 0xffffffff; @p cp.async.bulk.global.shared::cta.bulk_group [%0], [%1], %2; }" ::"l"(dst), "r"(src), "r"(bytes) : "memory");
}
DEVINL void e_bulk_s2s(uint32_t cdst, uint32_t src, uint32_t bytes, uint32_t cbar) {
    asm volatile("{ .reg .pred p; elect.sync _|p, 0xffffffff; @p cp.async.bulk.shared::cluster.shared::cta.mbarrier::complete_tx::bytes [%0], [%1], %2, [%3]; }" ::"r"(cdst), "r"(src), "r"(bytes), "r"(cbar) : "memory");
}

#define SLOT 0
#define PH3 0
#define PHQ 0
DEVINL void wait_slot(uint32_t phase) {
    if (SLOT) {
        uint32_t c; asm volatile("mov.u32 %0, %%globaltimer_lo;" : "=r"(c));
        const uint32_t tgt = c + (SLOT ? SLOT : 1) - ((c - phase) % (SLOT ? SLOT : 1));
        do { asm volatile("mov.u32 %0, %%globaltimer_lo;" : "=r"(c)); } while ((uint32_t)(tgt - c - 1u) < 100000u);
    }
}
template <int N> DEVINL uint32_t poll_set(uint4 (&v)[N], const uint32_t* rp, int stride, uint32_t phase, uint32_t wbar = 0, uint32_t wpar = 0) {
    wait_slot(phase);
#pragma unroll
    for (int i = 0; i < N; i++) v[i] = ld_strong16(rp + i * stride);
    if (wbar) mbar_wait(wbar, wpar);
    uint32_t n = 0;
    while (true) {
        uint32_t m = 0xffffffffu;
#pragma unroll
        for (int i = 0; i < N; i++) m = min4(v[i], m);
        if (__all_sync(0xffffffffu, m != 0u)) return n;
        wait_slot(phase);
#pragma unroll
        for (int i = 0; i < N; i++)
            asm volatile("{ .reg .pred p; setp.eq.u32 p, %5, 0; @p ld.relaxed.gpu.global.v4.u32 {%0,%1,%2,%3}, [%4]; }"
                         : "+r"(v[i].x), "+r"(v[i].y), "+r"(v[i].z), "+r"(v[i].w) : "l"(rp + i * stride), "r"(min4(v[i], 0xffffffffu)) : "memory");
        if (++n > 20000000u) __trap();
    }
}

struct RMaps { CUtensorMap x, w[3], wo, o; };
#define KC(c) ((c) * 64)

#define XORD 3
__host__ __device__ constexpr int xo(int i) {
    return XORD == 0 ? i : XORD == 1 ? (i + 14) % 16 : XORD == 2 ? (i + 11) % 16
         : XORD == 3 ? (i < 10 ? ((i & 1) ? i / 2 : 11 + i / 2) : i - 5) : (i < 6 ? i : ((i & 1) ? 6 + (i - 6) / 2 : 11 + (i - 6) / 2));
}
#define XC(i) (xo(i) * 64)
DEVINL void x_load_pair(uint32_t dst, const CUtensorMap* tmx, int h, int p, int seg, uint32_t fbar) {
    e_expect(fbar, 8192);
    e_tma_load(dst, tmx, XC(2 * p), seg * SEG, fbar);
    e_tma_load(dst + 4096, tmx, XC(2 * p + 1), seg * SEG, fbar);
}
__host__ __device__ constexpr int wo_tile(int role, int i) {
    return role == 0 ? (i < 2 ? 8 + i : 12 + i) : (i < 4 ? (i >> 1) * 4 : 10) + (role - 1) * 2 + (i & 1);
}

template <int NT> DEVINL void wo_phase(uint32_t sb, int tb, uint32_t* pp, uint32_t obar, uint32_t opar) {
    const int lane = tb & 31, krow = (lane & 7) + ((lane >> 4) << 3), chunk = ((tb >> 5) & 3) * 2 + ((lane >> 3) & 1);
    uint32_t wa = sb + R_WO + (tb >> 7) * 16384 + krow * 128 + ((chunk ^ (krow & 7)) << 4);
    uint32_t af[4][4], of[4][4];
#pragma unroll
    for (int g = 0; g < 4; g++) ldsm4t(af[g], wa + g * 2048);
    mbar_wait(obar, opar);
#pragma unroll
    for (int g = 0; g < 4; g++) ldsm4t(of[g], sb + R_O + g * 512 + lane * 16);
#pragma unroll 1
    for (int i = 0; i < NT; i++) {
        float w0[4] = {0.f, 0.f, 0.f, 0.f}, w1[4] = {0.f, 0.f, 0.f, 0.f};
        const int more = NT - 1 - i, yes = NT - i;
        mma16816(w0, af[0][0], af[0][1], af[0][2], af[0][3], of[0][0], of[0][1]);
        ldsm4t_if(af[0], wa + 4 * 2048, yes);
        mma16816(w1, af[1][0], af[1][1], af[1][2], af[1][3], of[0][2], of[0][3]);
        ldsm4t_if(af[1], wa + 5 * 2048, yes);
        mma16816(w0, af[2][0], af[2][1], af[2][2], af[2][3], of[1][0], of[1][1]);
        ldsm4t_if(af[2], wa + 6 * 2048, yes);
        mma16816(w1, af[3][0], af[3][1], af[3][2], af[3][3], of[1][2], of[1][3]);
        ldsm4t_if(af[3], wa + 7 * 2048, yes);
        wa += 32768;
        mma16816(w0, af[0][0], af[0][1], af[0][2], af[0][3], of[2][0], of[2][1]);
        ldsm4t_if(af[0], wa, more);
        mma16816(w1, af[1][0], af[1][1], af[1][2], af[1][3], of[2][2], of[2][3]);
        ldsm4t_if(af[1], wa + 2048, more);
        mma16816(w0, af[2][0], af[2][1], af[2][2], af[2][3], of[3][0], of[3][1]);
        ldsm4t_if(af[2], wa + 2 * 2048, more);
        mma16816(w1, af[3][0], af[3][1], af[3][2], af[3][3], of[3][2], of[3][3]);
        ldsm4t_if(af[3], wa + 3 * 2048, more);
        st_strong4(pp, pack_nz(w0[0] + w1[0], w0[1] + w1[1]));
        st_strong4(pp + 1024, pack_nz(w0[2] + w1[2], w0[3] + w1[3]));
        pp += (NT == 3 && i == 0) ? 4 * 8192 : 6 * 8192;
    }
}

template <uint32_t role> DEVINL void r_big(const RMaps& tm, const int wid) {
    extern __shared__ __align__(1024) unsigned char smem_raw[];
    const uint32_t sb = smem_u32(smem_raw);
    const uint32_t bar = sb + R_BAR;
    const int tid = threadIdx.x;
    int h; asm("mov.u32 %0, %%clusterid.x;" : "=r"(h));
        uint32_t a[KR][4];
        mbar_wait(bar + 8 * B_PRO0, 0);
        PT(0);
        {
            const int lane = tid & 31;
            const int krow = (lane & 7) + ((lane >> 4) << 3);
            const int chunk = (wid & 3) * 2 + ((lane >> 3) & 1);
            const uint32_t la = sb + (wid >> 2) * 8192 + krow * 128 + ((chunk ^ (krow & 7)) << 4);
#pragma unroll
            for (int k = 0; k < KR; k++) ldsm4t(a[k], la + (k >> 2) * 16384 + (k & 3) * 2048);
        }
        bar_sync(1, 256);
        {
            fence_async();
            const CUtensorMap* tw = &tm.w[role];
            e_expect(bar + 8 * B_PRO1, (wid < 5 ? 16384 : 0) + (wid < (role == 0 ? 4 : 6) ? 16384 : 0));
            if (wid < 5) {
                e_tma_load(sb + R_W + wid * 8192, tw, h * DH, KC(KR / 4 + wid), bar + 8 * B_PRO1);
                e_tma_load(sb + R_W + KS * 2048 + wid * 8192, tw, h * DH + 64, KC(KR / 4 + wid), bar + 8 * B_PRO1);
            }
            if (wid < (role == 0 ? 4 : 6)) e_tma_load(sb + R_WO + wid * 16384, &tm.wo, wo_tile(role, wid) * 64, h * DH, bar + 8 * B_PRO1);
        }
        constexpr uint32_t e0 = role == 0 ? R_QX + 16384 : R_K + 2048, e1 = role == 0 ? R_QX + 24576 : R_V + 2048;
        if (wid == 6) x_load_pair(sb + e0, &tm.x, h, 3, 0, bar + 8 * (B_FULL + 3));
        if (wid == 7) x_load_pair(sb + e1, &tm.x, h, 4, 0, bar + 8 * (B_FULL + 4));
        PT(1);
        mbar_wait(bar + 8 * B_PRO1, 0);
        PT(2);

        constexpr uint64_t dW0 = cdesc(R_W, 1024, 1024, 1);
        constexpr uint64_t dM = cdesc(R_RING, 128, 128, 0);
        constexpr uint64_t dX = cdesc(R_RING, 16, 1024, 1);
        constexpr uint64_t dX0 = cdesc(0, 16, 1024, 1);
        int tb = tid;
        int wq = wid;

        for (int seg = 0; seg < NSEG; seg++) {
            {
            const int s = seg - 1; (void)s;
            float d[16];
            OPAQUE(wq);
            const uint64_t dW = dW0 + (uint64_t)((wq >> 2) * (KS * 128));
#pragma unroll
            for (int p = 0; p < 8; p++) {
                const int slot = p % 5;
                mbar_wait(bar + 8 * (B_FULL + slot), slot < 3 ? (uint32_t)(p / 5) : (uint32_t)(seg & 1));
                PROF2(p);
                const uint64_t db = slot < 3 ? dX + (uint64_t)(slot * 512) : dX0 + (uint64_t)((slot == 3 ? e0 : e1) >> 4);
                wg_fence();
#pragma unroll
                for (int kk = 0; kk < 8; kk++) {
                    const int k = XORD >= 3 ? (kk & 1) * 4 + (kk >> 1) : kk;
                    const int ks = xo(2 * p + (k >> 2)) * 4 + (k & 3);
                    if (ks >= KR) wg_ss32<1>(d, dW + (uint64_t)((ks - KR) * 128), db + (uint64_t)((k >> 2) * 256 + (k & 3) * 2), p + k);
                    else wg_rs32(d, a[ks < KR ? ks : 0], db + (uint64_t)((k >> 2) * 256 + (k & 3) * 2), p + k);
                }
                wg_commit();
                if (p >= 1) {
                    wg_wait<1>();
                    if (p <= 3) {
                        if ((wq & 3) == p) e_arrive(bar + 8 * (B_EMPTY + p - 1));
                        if (wq == p + (p & 1) * 4) {
                            mbar_wait(bar + 8 * (B_EMPTY + p - 1), seg & 1);
                            x_load_pair(sb + R_RING + (p - 1) * 8192, &tm.x, h, p + 4, seg, bar + 8 * (B_FULL + p - 1));
                        }
                    }
                    if (p == 5 && role != 0 && (wq & 3) < 3) e_arrive_remote(mapa(bar + 8 * B_TFREE, wq & 3));
                    if (p == 6 && (wq & 3) == 1) e_arrive(bar + 8 * B_AFREE0);
                    if (p == 7 && (wq & 3) == 2) e_arrive(bar + 8 * B_AFREE1);
                }
            }
            mbar_wait(bar + 8 * B_TFREE, seg & 1);
            asm volatile("wgmma.wait_group.sync.aligned 0;" : ACC16(d)::"memory");
            PROF2(16);
            const uint32_t tilex = sb + (role == 0 ? R_QX + 2048 : (role == 1 ? R_K + 2048 : R_V + 2048));
            {
                OPAQUE(tb);
                const uint32_t gs = role == 0 ? 4096 : 2048;
                const uint32_t sa = tilex + ((tb >> 4) & 1) * gs + (tb >> 5) * 256 + (tb & 15) * 16;
                stsm4(sa, pack_bf16(d[0], d[1]), pack_bf16(d[2], d[3]), pack_bf16(d[4], d[5]), pack_bf16(d[6], d[7]));
                stsm4(sa + 2 * gs, pack_bf16(d[8], d[9]), pack_bf16(d[10], d[11]), pack_bf16(d[12], d[13]), pack_bf16(d[14], d[15]));
            }
            __syncwarp();
            e_arrive(bar + 8 * B_XDONE);
            if (role != 0 && (wq & 3) == 0) {
                mbar_wait(bar + 8 * B_XDONE, seg & 1);
                fence_async();
                uint32_t pr = role + 1 + (wq >> 2); pr = pr >= 3 ? pr - 3 : pr;
                e_bulk_s2s(mapa(tilex, pr), tilex, CPB, mapa(bar + 8 * B_XT, pr));
            }
            }
            {
                const int s = seg;
                OPAQUE(wq);
                const uint64_t dW = dW0 + (uint64_t)((wq >> 2) * (KS * 128));
                float y[4] = {0.f, 0.f, 0.f, 0.f};
                {
                    OPAQUE(tb);
                    const uint32_t ma = sb + R_RING + (tb & 31) * 16;
                    float z[4] = {0.f, 0.f, 0.f, 0.f}, u[4] = {0.f, 0.f, 0.f, 0.f};
                    uint32_t b[QD][4];
                    const int yes = s + 1;
                    mbar_wait(bar + 8 * B_MEM, s & 1);
                    PROF((wq >> 2) * 4 + 0);
                    if (s == 0) PT(3);
                    if (s == 1) PT(4);
#pragma unroll
                    for (int g = 0; g < QD; g++) ldsm4t(b[g], ma + g * 512);
#pragma unroll
                    for (int g = 0; g < KR / 2; g++) {
                        float* c0 = (g % 3 == 0) ? y : (g % 3 == 1) ? u : z;
                        float* c1 = (g % 3 == 0) ? z : (g % 3 == 1) ? y : u;
                        mma16816(c0, a[2 * g][0], a[2 * g][1], a[2 * g][2], a[2 * g][3], b[g % QD][0], b[g % QD][1]);
                        mma16816(c1, a[2 * g + 1][0], a[2 * g + 1][1], a[2 * g + 1][2], a[2 * g + 1][3], b[g % QD][2], b[g % QD][3]);
                        if (g + QD < KR / 2) {
                            if ((g + QD) % 8 == 0) mbar_wait(bar + 8 * (B_MEM + (g + QD) / 8), s & 1);
                            ldsm4t_if(b[g % QD], ma + (g + QD) * 512, yes);
                        }
                    }
                    y[0] += z[0] + u[0]; y[1] += z[1] + u[1]; y[2] += z[2] + u[2]; y[3] += z[3] + u[3];
                }
                PROF2(8);
                mbar_wait(bar + 8 * (B_MEM + 3), s & 1);
                wg_fence();
#pragma unroll
                for (int k = KR; k < 64; k++) wg_ss8<1, 1>(y, dW + (uint64_t)((k - KR) * 128), dM + (uint64_t)(k * 16), 1);
                wg_commit();
                asm volatile("wgmma.wait_group.sync.aligned 0;" : "+f"(y[0]), "+f"(y[1]), "+f"(y[2]), "+f"(y[3])::"memory");
                OPAQUE(tb);
                {
                    const uint32_t wo_ = (tb >> 5) * 256;
                    const uint32_t tile = sb + (role == 0 ? R_QX : (role == 1 ? R_K : R_V)) + wo_;
                    const uint32_t u0 = pack_bf16(y[0], y[1]), u1 = pack_bf16(y[2], y[3]);
                    sts32(tile + (tb & 31) * 4, u0);
                    sts32(tile + (tb & 31) * 4 + 128, u1);
                    __syncwarp();
                    uint4 v = lds128(tile + (tb & 15) * 16);
                    uint32_t peer = role + 1 + ((tb >> 4) & 1);
                    peer = peer >= 3 ? peer - 3 : peer;
                    const uint32_t rt = sb + (role == 0 ? R_QM : (role == 1 ? R_K : R_V)) + wo_ + (tb & 15) * 16;
                    st_async16(mapa(rt, peer), v, mapa(bar + 8 * (role == 2 ? B_HOPV : B_HOP1), peer));
                    if (role == 0) {
                        sts128(tile + 4096 + ((tb >> 4) & 1) * 4096 + (tb & 15) * 16, v);
                        sts32(tile + 12288 + (tb & 31) * 4, u0);
                        sts32(tile + 12288 + (tb & 31) * 4 + 128, u1);
                        __syncwarp();
                    }
                    e_arrive(bar + 8 * (role == 2 ? B_HOPV : B_HOP1));
                }
                PROF((wq >> 2) * 4 + 1);
                if (s < NSEG - 1) {
                    bar_sync(1, 256);
                    if (wq < 3) { fence_async(); x_load_pair(sb + R_RING + wq * 8192, &tm.x, h, wq, s + 1, bar + 8 * (B_FULL + wq)); }
                    else if (role == 0 && wq < 5) x_load_pair(sb + (wq == 3 ? e0 : e1), &tm.x, h, wq, s + 1, bar + 8 * (B_FULL + wq));
                    OPAQUE(tb);
                }
                uint32_t* pp = g_part[s & 3] + (h * 32 + (wo_tile(role, 0) + (tb >> 7)) * 8192 + ((tb >> 5) & 3) * 2048 + (tb & 31));
                asm volatile("" : "+l"(pp));
                if (s == NSEG - 1) break;
                wo_phase<role == 0 ? 2 : 3>(sb, tb, pp, bar + 8 * B_O, s & 1);
                if (wq == 0) PROF(10);
            }
        }
}

#define CLR 0
#define CLEAR(st) do { if (role != 0) { \
                const int w_ = wid & 3; \
                uint32_t* zp = g_part[(st) & 3] + ((rg0 + (w_ >> 1) * 64) * 1024 + (w_ & 1) * 512); \
                e_bulk_s2g(zp, sb + R_Z, 1024); \
                e_bulk_s2g(zp + 256, sb + R_Z, 1024); \
                e_bulk_s2g(&g_mem[(st) & 3][(rg0 + (w_ >> 1) * 64) * 32 + (w_ & 1) * 16], sb + R_Z, 64); \
                bulk_commit(); } } while (0)
template <uint32_t role> DEVINL void r_chain(const RMaps& tm, const bf16* __restrict__ mem0, const bf16* __restrict__ x, const bf16* __restrict__ gate_w, const int wid) {
    extern __shared__ __align__(1024) unsigned char smem_raw[];
    const uint32_t sb = smem_u32(smem_raw);
    const uint32_t bar = sb + R_BAR;
    const int tid = threadIdx.x;
    int h; asm("mov.u32 %0, %%clusterid.x;" : "=r"(h));
        int t = tid & 127;
        const float sl2 = 0.08838834764831845f * 1.4426950408889634f;
        const float NEGRAW = -1000000000.0f / 0.08838834764831845f;
        const int rg0 = ((int)role - 1) * 32 + h;
        if (role != 0) {
#pragma unroll 1
            for (int r = 0; r < 4; r++) {
                uint32_t* zp = g_part[r] + ((rg0 + (t >> 6) * 64) * 1024 + (t & 63) * 4);
#pragma unroll
                for (int i = 0; i < 4; i++) st_strong16(zp + i * 256, make_uint4(0u, 0u, 0u, 0u));
                if ((t & 63) < 8) st_strong16(&g_mem[r][(rg0 + (t >> 6) * 64) * 32 + (t & 63) * 4], make_uint4(0u, 0u, 0u, 0u));
            }
            __threadfence();
        }
        {
#pragma unroll 1
            for (int r = (h * 3 + (int)role) * 4 + (t >> 5); r < SEQ; r += 384) {
                const uint32_t gb = __float_as_uint(gate_row(x + r * DM, gate_w, t & 31));
                if ((t & 31) == 0) st_strong4(&g_gate[r], gb ? gb : 0x80000000u);
            }
        }
        if (role == 0 && (wid & 3) < 3) e_arrive_remote(mapa(bar + 8 * B_TFREE, wid & 3));
        if (t < 64) sts128(sb + R_Z + t * 16, make_uint4(0u, 0u, 0u, 0u));
        if (role == 0) sts128(sb + R_QM + t * 16, make_uint4(0u, 0u, 0u, 0u));
        {
            uint4 v[8];
#pragma unroll
            for (int r = 0; r < 8; r++) v[r] = __ldg((const uint4*)(mem0 + r * DM) + t);
            mbar_wait(bar + 8 * B_AFREE0, 0);
            mbar_wait(bar + 8 * B_AFREE1, 0);
#define TR2(f, c) \
            sts128(sb + R_RING + t * 128 + (c) * 16, make_uint4(__byte_perm(v[0].f, v[1].f, 0x5410), __byte_perm(v[2].f, v[3].f, 0x5410), __byte_perm(v[4].f, v[5].f, 0x5410), __byte_perm(v[6].f, v[7].f, 0x5410))); \
            sts128(sb + R_RING + t * 128 + (c) * 16 + 16, make_uint4(__byte_perm(v[0].f, v[1].f, 0x7632), __byte_perm(v[2].f, v[3].f, 0x7632), __byte_perm(v[4].f, v[5].f, 0x7632), __byte_perm(v[6].f, v[7].f, 0x7632)));
            TR2(x, 0) TR2(y, 2) TR2(z, 4) TR2(w, 6)
            fence_async();
            __syncwarp();
            e_arrive(bar + 8 * B_MEM + (t >> 5) * 8);
        }
        constexpr uint64_t dQ = role == 0 ? cdesc(R_QX, 128, 2048, 0) : cdesc(R_QM, 128, 0, 0);
        constexpr uint64_t dK = cdesc(R_K, 128, 2048, 0);

        for (int s = 0; s < NSEG; s++) {
            if (role == 0) {
                uint32_t n = 0, gate;
                do { gate = ld_strong4(&g_gate[s * SEG + (t >> 2)]); if (++n > 20000000u) __trap(); } while (gate == 0u);
                sts32(sb + R_G + (t >> 2) * 4, gate);
                __syncwarp();
            }
            mbar_wait(bar + 8 * B_XDONE, s & 1);
            mbar_wait(bar + 8 * B_XT, s & 1);
            if (t >= 1 && t < 3) { uint32_t pr = role + t; pr = pr >= 3 ? pr - 3 : pr; mbar_arrive_remote(mapa(bar + 8 * B_XRECV, pr)); }
            __syncwarp();
            mbar_wait(bar + 8 * B_HOP1, s & 1);
            PROF(8);
            fence_async();
            OPAQUE(t);
            if (s == NSEG - 1 && role != 0) { mbar_wait(bar + 8 * B_HOPV, s & 1); bulk_wait_all(); break; }
            float sc[20];
            wg_fence();
#pragma unroll
            for (int k = 0; k < 8; k++) wg_ss40(sc, dQ + (uint64_t)(k * 16), dK + (uint64_t)(k * 16), k);
            wg_commit();
            uint32_t t_o = clk32() + 500;
            {
                const uint32_t va = sb + R_V + 2048 + (t >> 5) * 512 + ((t >> 4) & 1) * 2048 + (t & 15) * 16;
                uint32_t v0[4], v1[4];
                ldsm4(v0, va); ldsm4(v1, va + 256);
                uint32_t vm[4];
                const bool v_here = mbar_try(bar + 8 * B_HOPV, s & 1);
                if (v_here) ldsm4(vm, sb + R_V + t * 16);
                wg_wait<0>();
                if (role == 0) {
#pragma unroll
                    for (int j = 0; j < 5; j++)
                        asm volatile("st.shared.v2.f32 [%0], {%1,%2};" ::"r"(sb + R_QX + 768 + (t >> 5) * 4096 + j * 256 + (t & 31) * 8), "f"(sc[4 * j + 2]), "f"(sc[4 * j + 3]) : "memory");
                }
                float m = fmaxf(sc[0], sc[1]);
#pragma unroll
                for (int j = 1; j < 5; j++) m = fmaxf(m, fmaxf(sc[4 * j], sc[4 * j + 1]));
                m = fmaxf(m, __shfl_xor_sync(0xffffffffu, m, 1));
                m = fmaxf(m, __shfl_xor_sync(0xffffffffu, m, 2));
                const float mb = m * sl2;
                uint32_t pk[5];
#pragma unroll
                for (int j = 0; j < 5; j++) pk[j] = pack_bf16(ex2(fmaf(sc[4 * j], sl2, -mb)), ex2(fmaf(sc[4 * j + 1], sl2, -mb)));
                float o0[4] = {0.f, 0.f, 0.f, 0.f}, o1[4] = {0.f, 0.f, 0.f, 0.f}, ls[4] = {0.f, 0.f, 0.f, 0.f};
                constexpr uint32_t ONE = 0x3F803F80u;
                mma16816(o0, v0[0], v0[1], v0[2], v0[3], pk[1], pk[2]);
                mma16816(o1, v1[0], v1[1], v1[2], v1[3], pk[1], pk[2]);
                ldsm4(v0, va + 4096); ldsm4(v1, va + 4096 + 256);
                mma16816(ls, ONE, ONE, ONE, ONE, pk[1], pk[2]);
                mma16816(ls, ONE, ONE, ONE, ONE, pk[3], pk[4]);
                mma1688(ls, ONE, ONE, pk[0]);
                mma16816(o0, v0[0], v0[1], v0[2], v0[3], pk[3], pk[4]);
                mma16816(o1, v1[0], v1[1], v1[2], v1[3], pk[3], pk[4]);
                if (!v_here) { mbar_wait(bar + 8 * B_HOPV, s & 1); ldsm4(vm, sb + R_V + t * 16); }
                mma1688(o0, vm[0], vm[1], pk[0]);
                mma1688(o1, vm[2], vm[3], pk[0]);
                const float i0 = __fdividef(1.0f, ls[0]), i1 = __fdividef(1.0f, ls[1]);
                const uint32_t oa = sb + R_O + (t >> 5) * 512 + (t & 31) * 4;
                sts32(oa, pack_bf16(o0[0] * i0, o0[1] * i1));
                sts32(oa + 128, pack_bf16(o0[2] * i0, o0[3] * i1));
                sts32(oa + 256, pack_bf16(o1[0] * i0, o1[1] * i1));
                sts32(oa + 384, pack_bf16(o1[2] * i0, o1[3] * i1));
                __syncwarp();
                e_arrive(bar + 8 * B_O);
                PROF(9);
                if (role == 0) {
                    OPAQUE(t);
                    const int lim = (t >> 2) - (t & 3) * 2 + 8;
                    float z[10];
#pragma unroll
                    for (int j = 0; j < 5; j++)
                        asm volatile("ld.shared.v2.f32 {%0,%1}, [%2];" : "=f"(z[2 * j]), "=f"(z[2 * j + 1]) : "r"(sb + R_QX + 768 + (t >> 5) * 4096 + j * 256 + (t & 31) * 8) : "memory");
                    float gate; asm volatile("ld.shared.f32 %0, [%1];" : "=f"(gate) : "r"(sb + R_G + (t >> 2) * 4) : "memory");
                    float m1 = fmaxf(z[0], z[1]);
#pragma unroll
                    for (int j = 1; j < 5; j++) {
                        z[2 * j] = 8 * j <= lim ? z[2 * j] : NEGRAW;
                        z[2 * j + 1] = 8 * j + 1 <= lim ? z[2 * j + 1] : NEGRAW;
                        m1 = fmaxf(m1, fmaxf(z[2 * j], z[2 * j + 1]));
                    }
                    m1 = fmaxf(m1, __shfl_xor_sync(0xffffffffu, m1, 1));
                    m1 = fmaxf(m1, __shfl_xor_sync(0xffffffffu, m1, 2));
                    const float mb1 = m1 * sl2;
                    float l1 = 0.f;
                    const uint32_t pa = sb + R_QX + (t >> 5) * 4096 + (t & 31) * 4;
#pragma unroll
                    for (int j = 0; j < 5; j++) {
                        const uint32_t pw = pack_bf16(ex2(fmaf(z[2 * j], sl2, -mb1)), ex2(fmaf(z[2 * j + 1], sl2, -mb1)));
                        l1 += __uint_as_float(pw << 16) + __uint_as_float(pw & 0xffff0000u);
                        sts32(pa + j * 128, pw);
                    }
                    sts32(pa + 5 * 128, 0u);
                    l1 += __shfl_xor_sync(0xffffffffu, l1, 1);
                    l1 += __shfl_xor_sync(0xffffffffu, l1, 2);
                    sts32(sb + R_G + 128 + (t >> 2) * 4, __float_as_uint(__fdividef(gate, l1)));
                    spin_until(t_o + PVD);
                    if ((wid & 3) == 0 && s >= 1) { bulk_wait_all(); e_count(&g_ocnt[(s - 1) >> 2]); }
                    fence_async();
                    bar_sync(2, 128);
                    constexpr uint64_t dV = cdesc(R_V, 2048, 128, 0);
                    constexpr uint64_t dP = cdesc(R_QX, 128, 4096, 0);
                    float sf[8];
#pragma unroll
                    for (int j = 0; j < 4; j++) asm volatile("ld.shared.v2.f32 {%0,%1}, [%2];" : "=f"(sf[2 * j]), "=f"(sf[2 * j + 1]) : "r"(sb + R_G + 128 + j * 32 + (t & 3) * 8) : "memory");
                    const uint32_t r = ((t >> 4) & 1) * 8 + (t & 7), ch = (t >> 5) * 2 + ((t >> 3) & 1);
                    const uint32_t sa = sb + R_QX + 2048 + r * 128 + ((ch ^ (r & 7)) << 4);
#pragma unroll
                    for (int hf = 0; hf < 2; hf++) {
                        float d[16];
                        wg_fence();
#pragma unroll
                        for (int k = 0; k < 3; k++) wg_ss32<0>(d, dV + (uint64_t)(hf * 64 + k * 256), dP + (uint64_t)(k * 16), k);
                        wg_commit();
                        asm volatile("wgmma.wait_group.sync.aligned 0;" : ACC16(d)::"memory");
                        stsm4t(sa + hf * 8192, pack_bf16(d[0] * sf[0], d[1] * sf[1]), pack_bf16(d[2] * sf[0], d[3] * sf[1]), pack_bf16(d[4] * sf[2], d[5] * sf[3]), pack_bf16(d[6] * sf[2], d[7] * sf[3]));
                        stsm4t(sa + hf * 8192 + 4096, pack_bf16(d[8] * sf[4], d[9] * sf[5]), pack_bf16(d[10] * sf[4], d[11] * sf[5]), pack_bf16(d[12] * sf[6], d[13] * sf[7]), pack_bf16(d[14] * sf[6], d[15] * sf[7]));
                    }
                    fence_async();
                    bar_sync(2, 128);
                    if ((wid & 3) == 0) {
#pragma unroll
                        for (int q = 0; q < 4; q++) e_tma_store(&tm.o, sb + R_QX + 2048 + q * 4096, h * DH + (q >> 1) * 64, s * SEG + (q & 1) * 16);
                        bulk_commit();
                        bulk_wait_read();
                    }
                    if ((wid & 3) < 3) e_arrive_remote(mapa(bar + 8 * B_TFREE, wid & 3));
                }
            }
            if (t < 32) { e_expect(bar + 8 * B_HOP1, role == 2 ? 4096 : 2048); if (role != 2) e_expect(bar + 8 * B_HOPV, 2048); e_expect(bar + 8 * B_XT, role == 0 ? 2 * CPB : CPB); }
            if (s == NSEG - 1) { bulk_wait_all(); break; }
            if (role != 0 && (wid & 3) >= 2) {
                mbar_wait(bar + 8 * B_XRECV, s & 1);
                mbar_wait(bar + 8 * B_O, s & 1);
                fence_async();
                spin_until(t_o + ELD);
                x_load_pair(sb + ((wid & 1) ? R_V + 2048 : R_K + 2048), &tm.x, h, 3 + (wid & 1), s + 1, bar + 8 * (B_FULL + 3 + (wid & 1)));
            }
            OPAQUE(t);
            PROF(11);
            if (role != 0 || DDUP) {
                const int grp = role == 0 ? (t >> 6) * 32 + h : rg0 + (t >> 6) * 64;
                const uint32_t* rp = g_part[s & 3] + (grp * 1024 + ((t >> 2) & 7) * 32 + ((t >> 5) & 1) * 16 + (t & 3) * 4);
                uint32_t* wp = &g_mem[(s + 1) & 3][grp * 32 + ((t >> 5) & 1) * 16 + (t & 3) * 4 + ((t >> 3) & 3)];
                bulk_wait_all();
                spin_until(t_o + D2_BASE + (role == 0 ? DDUP + (t >> 6) * D2_STEP : (role - 1 + (t >> 6) * 2) * D2_STEP));
                PROF3(0, clk32());
#define LO(u) __uint_as_float((u) << 16)
#define HI(u) __uint_as_float((u) & 0xffff0000u)
                uint4 v[4];
                uint32_t n = poll_set<4>(v, rp, 256, (role - 1 + (t >> 6) * 2) * PHQ);
                {
                    PROF3(1, clk32());
                    float f[8];
                    f[0] = (LO(v[0].x) + LO(v[1].x)) + (LO(v[2].x) + LO(v[3].x)); f[1] = (HI(v[0].x) + HI(v[1].x)) + (HI(v[2].x) + HI(v[3].x));
                    f[2] = (LO(v[0].y) + LO(v[1].y)) + (LO(v[2].y) + LO(v[3].y)); f[3] = (HI(v[0].y) + HI(v[1].y)) + (HI(v[2].y) + HI(v[3].y));
                    f[4] = (LO(v[0].z) + LO(v[1].z)) + (LO(v[2].z) + LO(v[3].z)); f[5] = (HI(v[0].z) + HI(v[1].z)) + (HI(v[2].z) + HI(v[3].z));
                    f[6] = (LO(v[0].w) + LO(v[1].w)) + (LO(v[2].w) + LO(v[3].w)); f[7] = (HI(v[0].w) + HI(v[1].w)) + (HI(v[2].w) + HI(v[3].w));
                    const bool b4 = t & 16, b3 = t & 8;
                    float g4[4], g2[2];
#pragma unroll
                    for (int i = 0; i < 4; i++) g4[i] = (b4 ? f[4 + i] : f[i]) + __shfl_xor_sync(0xffffffffu, b4 ? f[i] : f[4 + i], 16);
#pragma unroll
                    for (int i = 0; i < 2; i++) g2[i] = (b3 ? g4[2 + i] : g4[i]) + __shfl_xor_sync(0xffffffffu, b3 ? g4[i] : g4[2 + i], 8);
                    g2[0] += __shfl_xor_sync(0xffffffffu, g2[0], 4);
                    g2[1] += __shfl_xor_sync(0xffffffffu, g2[1], 4);
                    st_strong4(wp, pack_nz(g2[0], g2[1]));
                }
                PROF3(8, n); (void)n;
            }
            t_o += D2_BASE + DQ + D3 + (t >> 5) * D2_STEP;
            OPAQUE(t);
            PROF(12);
            {
                const uint32_t* rp = &g_mem[(s + 1) & 3][((t >> 5) * 256 + (t & 31)) * 4];
                const uint32_t da = sb + R_RING + ((t >> 5) * 256 + (t & 31)) * 16;
                uint4 v[8];
                spin_until(t_o);
                PROF3(2, clk32());
                uint32_t n = poll_set<8>(v, rp, 128, PH3 + (t >> 5) * PHQ);
                PROF(13);
                PROF3(3, clk32()); PROF3(9, n); (void)n;
                mbar_wait(bar + 8 * B_AFREE0 + (t >> 6) * 8, (s + 1) & 1);
                PROF3(4, clk32());
#pragma unroll
                for (int i = 0; i < 8; i++) sts128(da + i * 512, v[i]);
                if (t >= 64) fence_async();
                __syncwarp();
                e_arrive(bar + 8 * B_MEM + (t >> 5) * 8);
                PROF(14);
                PROF3(5, clk32());
            }
            CLEAR(s + 3);
        }
}

__global__ void __launch_bounds__(384, 1) r_kernel(const __grid_constant__ RMaps tm, const bf16* __restrict__ mem0, const bf16* __restrict__ x, const bf16* __restrict__ gate_w) {
    extern __shared__ __align__(1024) unsigned char smem_raw[];
    const uint32_t sb = smem_u32(smem_raw);
    if ((sb & 0x3FFFFu) != SB0) __trap();
    const int tid = threadIdx.x;
    const int wid = __shfl_sync(0xffffffffu, tid >> 5, 0);
    uint32_t role; asm("mov.u32 %0, %%cluster_ctarank;" : "=r"(role));
    int h; asm("mov.u32 %0, %%clusterid.x;" : "=r"(h));
    const uint32_t bar = sb + R_BAR;
    asm volatile("griddepcontrol.launch_dependents;");
    KT(0, 0);

    if (tid == 0) {
        for (int i = 0; i < 5; i++) mbar_init(bar + 8 * (B_FULL + i), 1);
        for (int i = 0; i < 3; i++) mbar_init(bar + 8 * (B_EMPTY + i), 2);
        for (int i = 0; i < 4; i++) mbar_init(bar + 8 * (B_MEM + i), 1);
        mbar_init(bar + 8 * B_HOP1, role == 2 ? 1 : 9);
        mbar_init(bar + 8 * B_HOPV, role == 2 ? 8 : 1);
        mbar_init(bar + 8 * B_XT, 1);
        mbar_init(bar + 8 * B_TFREE, 5);
        mbar_init(bar + 8 * B_P, 4);
        mbar_init(bar + 8 * B_XDONE, 8);
        mbar_init(bar + 8 * B_OST0, 4);
        mbar_init(bar + 8 * B_OST1, 4);
        mbar_init(bar + 8 * B_XRECV, 2);
        mbar_init(bar + 8 * B_O, 4);
        mbar_init(bar + 8 * B_AFREE0, 2);
        mbar_init(bar + 8 * B_AFREE1, 2);
        mbar_init(bar + 8 * B_PRO0, 1);
        mbar_init(bar + 8 * B_PRO1, 8);
        asm volatile("fence.mbarrier_init.release.cluster;" ::: "memory");
        fence_async();
        mbar_expect(bar + 8 * B_PRO0, KR * 4096);
        for (int i = 0; i < 3; i++) mbar_expect(bar + 8 * (B_FULL + i), 8192);
        mbar_expect(bar + 8 * B_HOP1, role == 2 ? 4096 : 2048);
        if (role != 2) mbar_expect(bar + 8 * B_HOPV, 2048);
        mbar_expect(bar + 8 * B_XT, role == 0 ? 2 * CPB : CPB);
    }
    __syncthreads();
    asm volatile("barrier.cluster.arrive.relaxed.aligned;" ::: "memory");
    {
        const CUtensorMap* tw = &tm.w[role];
        if (wid < 11) {
            e_tma_load(sb + wid * 16384, tw, h * DH, KC(wid), bar + 8 * B_PRO0);
            e_tma_load(sb + wid * 16384 + 8192, tw, h * DH + 64, KC(wid), bar + 8 * B_PRO0);
        }
        if (wid < 6) e_tma_load(sb + R_RING + wid * 4096, &tm.x, XC(wid), 0, bar + 8 * (B_FULL + (wid >> 1)));
        if ((tid & 31) == 0) {
            if (wid < 10) tma_prefetch(tw, h * DH + (wid & 1) * 64, KC(KR / 4 + (wid >> 1)));
            if (wid >= 6 && wid - 6 < (role == 0 ? 4 : 6)) tma_prefetch(&tm.wo, wo_tile(role, wid - 6) * 64, h * DH);
            if (blockIdx.x < NSEG && wid < 8) { tma_prefetch(&tm.x, wid * 128, blockIdx.x * SEG); tma_prefetch(&tm.x, wid * 128 + 64, blockIdx.x * SEG); }
        }
        __syncwarp();
    }
    asm volatile("barrier.cluster.wait.aligned;" ::: "memory");

    if (wid < 8) {
        asm volatile("setmaxnreg.inc.sync.aligned.u32 224;");
        if (role == 0) r_big<0>(tm, wid); else if (role == 1) r_big<1>(tm, wid); else r_big<2>(tm, wid);
    } else {
        asm volatile("setmaxnreg.dec.sync.aligned.u32 56;");
        if (role == 0) r_chain<0>(tm, mem0, x, gate_w, wid); else if (role == 1) r_chain<1>(tm, mem0, x, gate_w, wid); else r_chain<2>(tm, mem0, x, gate_w, wid);
    }
    __syncwarp();
    asm volatile("barrier.cluster.arrive; barrier.cluster.wait;" ::: "memory");
    KT(0, 1);
}

constexpr int G_ST = 4;
constexpr int G_STAGE = 16384 + 32768;
constexpr int G_EPI = G_ST * G_STAGE;
constexpr int G_GATE = G_EPI + 32768;
constexpr int G_BAR = G_GATE + 1024;
constexpr int G_SMEM = G_BAR + 128 + 1024;

struct G1Maps { CUtensorMap x, wg, wu, hs, o, h, wo, wd, out; };
constexpr int G1_NB = FF / 128;
constexpr int G1_TILES = 16 * G1_NB;

DEVINL void g_mma_block(float* d, uint32_t sb, uint32_t bar, int it, int wg, int tid, bool first) {
    const int st = it % G_ST;
    mbar_wait(bar + 8 * st, (it / G_ST) & 1);
    const uint64_t da = mkdesc(sb + st * G_STAGE + wg * 8192, 16, 1024, 1);
    const uint64_t db = mkdesc(sb + st * G_STAGE + 16384, 8192, 1024, 1);
    wg_fence();
#pragma unroll
    for (int k = 0; k < 4; k++) wg_ss256(d, da + (uint64_t)(k * 2), db + (uint64_t)(k * 128), (first ? 0 : 1) | k);
    wg_commit();
    if (!first) { wg_wait<1>(); if ((tid & 127) == 0) mbar_arrive(bar + 8 * (G_ST + (it - 1) % G_ST)); }
}
DEVINL void g_load_block(uint32_t sb, uint32_t bar, int it, const CUtensorMap* ta, int k0, int m0, const CUtensorMap* tb, int n0) {
    const int st = it % G_ST;
    mbar_wait(bar + 8 * (G_ST + st), ((it / G_ST) & 1) ^ 1);
    const uint32_t fb = bar + 8 * st, sa = sb + st * G_STAGE;
    mbar_expect(fb, G_STAGE);
    tma_load(sa, ta, k0, m0, fb);
#pragma unroll
    for (int q = 0; q < 4; q++) tma_load(sa + 16384 + q * 8192, tb, n0 + q * 64, k0, fb);
}

DEVINL void g_store_tile(const float* d, const CUtensorMap* tout, uint32_t epi, int mb, int nb, int wg, int tid) {
    const int lane = tid & 31, row = ((tid >> 5) & 3) * 16 + ((lane >> 3) & 1) * 8 + (lane & 7);
#pragma unroll
    for (int half = 0; half < 2; half++) {
        if ((tid & 127) == 0) bulk_wait_read();
        bar_sync(1 + wg, 128);
#pragma unroll
        for (int j = 0; j < 16; j += 2) {
            const float* e = d + half * 64 + 4 * j;
            const int cgp = j + (lane >> 4);
            stsm4(epi + (cgp >> 3) * 8192 + row * 128 + (((cgp & 7) ^ (row & 7)) << 4),
                  pack_bf16(e[0], e[1]), pack_bf16(e[2], e[3]), pack_bf16(e[4], e[5]), pack_bf16(e[6], e[7]));
        }
        fence_async();
        bar_sync(1 + wg, 128);
        if ((tid & 127) == 0) {
            tma_store(tout, epi, nb * 256 + half * 128, mb * 128 + wg * 64);
            tma_store(tout, epi + 8192, nb * 256 + half * 128 + 64, mb * 128 + wg * 64);
            bulk_commit();
        }
    }
}
template <int NS> DEVINL void g_split_finish(const float* d, float4 (&r)[32 / NS], float4* sk, int tile, int ks, bf16* __restrict__ out, int tid) {
    constexpr int Q = 32 / NS;
    float4* mine = sk + ks * (32 * 256) + tid;
#pragma unroll
    for (int c = 0; c < NS; c++) {
        if (c != ks) {
#pragma unroll
            for (int q = c * Q; q < c * Q + Q; q++) __stcg(mine + q * 256, make_float4(d[4 * q], d[4 * q + 1], d[4 * q + 2], d[4 * q + 3]));
        } else {
#pragma unroll
            for (int q = 0; q < Q; q++) { const float* e = d + (c * Q + q) * 4; r[q].x += e[0]; r[q].y += e[1]; r[q].z += e[2]; r[q].w += e[3]; }
        }
    }
    __threadfence();
    bar_sync(3, 256);
    if (NS == 8) PT(20);
    if (tid == 0) {
        atomicAdd(&g_skcnt[tile], 1u);
        uint32_t v, n = 0;
        do {
            asm volatile("ld.acquire.gpu.global.u32 %0, [%1];" : "=r"(v) : "l"(&g_skcnt[tile]) : "memory");
            if (++n > 200000000u) __trap();
        } while (v < NS);
        if (atomicAdd(&g_skcnt[tile], 1u) == 2 * NS - 1) g_skcnt[tile] = 0u;
    }
    bar_sync(3, 256);
    if (NS == 8) PT(21);
#pragma unroll
    for (int c = 1; c < NS; c++) {
        const float4* th = sk + (((ks + c) & (NS - 1)) * 32 + ks * Q) * 256 + tid;
#pragma unroll
        for (int q = 0; q < Q; q++) { const float4 u = __ldcg(th + q * 256); r[q].x += u.x; r[q].y += u.y; r[q].z += u.z; r[q].w += u.w; }
    }
    const int lane = tid & 31;
    uint32_t* op = (uint32_t*)(out + ((tile >> 2) * 128 + (tid >> 5) * 16 + (lane >> 2)) * DM + (tile & 3) * 256 + ks * Q * 8 + (lane & 3) * 2);
#pragma unroll
    for (int q = 0; q < Q; q++) { op[q * 4] = pack_bf16(r[q].x, r[q].y); op[q * 4 + 4 * DM] = pack_bf16(r[q].z, r[q].w); }
}
DEVINL int g1_count(int pass) { return pass == 0 ? NPRE : pass == 1 ? NFULL : pass == 2 ? T_MID - NFULL : (T_LATE - T_MID) * 4; }
DEVINL int g1_first(int pass) { return pass == 2 ? (int)(gridDim.x - 1 - blockIdx.x) : (int)blockIdx.x; }

__global__ void __launch_bounds__(384, 1) g1_kernel(const __grid_constant__ G1Maps tm, bf16* __restrict__ out) {
    extern __shared__ __align__(1024) unsigned char smem_raw[];
    const uint32_t sb = (smem_u32(smem_raw) + 1023) & ~1023u;
    const int tid = threadIdx.x, lane = tid & 31;
    const int wg = __shfl_sync(0xffffffffu, tid >> 7, 0);
    const int warp = __shfl_sync(0xffffffffu, (tid >> 5) & 3, 0);
    const uint32_t bar = sb + G_BAR;
    asm volatile("griddepcontrol.launch_dependents;");
    KT(1, 0);
    if (tid == 0) {
        for (int i = 0; i < G_ST; i++) { mbar_init(bar + 8 * i, 1); mbar_init(bar + 8 * (G_ST + i), 2); }
        fence_async();
    }
    __syncthreads();
    if (wg == 2) {
        asm volatile("setmaxnreg.dec.sync.aligned.u32 40;");
        if (warp == 0) {
            if (lane == 0) {
                int it = 0;
                for (int tile = blockIdx.x; tile < G1_TILES; tile += gridDim.x) {
                    const int mb = tile & 15, nb = tile >> 4;
                    for (int kb = 0; kb < 16; kb++, it++) {
                        const int st = it % G_ST;
                        mbar_wait(bar + 8 * (G_ST + st), ((it / G_ST) & 1) ^ 1);
                        const uint32_t fb = bar + 8 * st, sa = sb + st * G_STAGE;
                        mbar_expect(fb, G_STAGE);
                        tma_load(sa, &tm.x, kb * 64, mb * 128, fb);
                        tma_load(sa + 16384, &tm.wg, nb * 128, kb * 64, fb);
                        tma_load(sa + 16384 + 8192, &tm.wg, nb * 128 + 64, kb * 64, fb);
                        tma_load(sa + 16384 + 16384, &tm.wu, nb * 128, kb * 64, fb);
                        tma_load(sa + 16384 + 24576, &tm.wu, nb * 128 + 64, kb * 64, fb);
                    }
                }
                for (int pass = 0; pass < 4; pass++) {
                    for (int i = g1_first(pass); i < g1_count(pass); i += gridDim.x) {
                        const int tile = pass == 1 ? i : pass == 3 ? T_MID + (i >> 2) : NFULL + i, mb = tile >> 2, nb = tile & 3;
                        if (pass < 2) {
                            wait_count(&g_hcnt[mb], 2 * G1_NB);
                            asm volatile("fence.proxy.async;" ::: "memory");
                            for (int kb = 0; kb < FF / 64; kb++, it++) g_load_block(sb, bar, it, &tm.h, kb * 64, mb * 128, &tm.wd, nb * 256);
                        }
                        if (pass > 0) {
                            const int k0 = pass == 3 ? (i & 3) * 16 : 0, k1 = pass == 3 ? k0 + 16 : HD / 64;
                            wait_count(&g_ocnt[mb], NH * 4);
                            asm volatile("fence.proxy.async;" ::: "memory");
                            for (int kb = k0; kb < k1; kb++, it++) g_load_block(sb, bar, it, &tm.o, kb * 64, mb * 128, &tm.wo, nb * 256);
                        }
                    }
                }
            }
        }
    } else {
        asm volatile("setmaxnreg.inc.sync.aligned.u32 232;");
        float d[128];
        int it = 0;
        float s0 = 0.f, s1 = 0.f;
        const uint32_t epi = sb + G_EPI + wg * 16384;
        const int row = warp * 16 + ((lane >> 3) & 1) * 8 + (lane & 7);
        for (int tile = blockIdx.x; tile < G1_TILES; tile += gridDim.x) {
            const int mb = tile & 15, nb = tile >> 4;
            for (int kb = 0; kb < 16; kb++, it++) g_mma_block(d, sb, bar, it, wg, tid, kb == 0);
            {
                const uint32_t* gp = &g_gate[mb * 128 + wg * 64 + warp * 16 + (lane >> 2)];
                uint32_t u0, u1, n = 0;
                do { u0 = ld_strong4(gp); u1 = ld_strong4(gp + 8); if (++n > 20000000u) __trap(); } while (u0 == 0u || u1 == 0u);
                s0 = 1.0f - __uint_as_float(u0); s1 = 1.0f - __uint_as_float(u1);
                __syncwarp();
            }
            wg_wait<0>();
            if ((tid & 127) == 0) { mbar_arrive(bar + 8 * (G_ST + (it - 1) % G_ST)); bulk_wait_read(); }
            bar_sync(1 + wg, 128);
#pragma unroll
            for (int j = 0; j < 16; j += 2) {
                uint32_t p[4];
#pragma unroll
                for (int q = 0; q < 4; q++) {
                    const int i = (j + (q >> 1)) * 4 + (q & 1) * 2;
                    const float sc = (q & 1) ? s1 : s0;
                    const float g0 = d[i], g1 = d[i + 1];
                    const float h0 = __fdividef(g0, 1.0f + __expf(-g0)) * d[64 + i] * sc;
                    const float h1 = __fdividef(g1, 1.0f + __expf(-g1)) * d[64 + i + 1] * sc;
                    p[q] = pack_bf16(h0, h1);
                }
                const int cgp = j + (lane >> 4);
                stsm4(epi + (cgp >> 3) * 8192 + row * 128 + (((cgp & 7) ^ (row & 7)) << 4), p[0], p[1], p[2], p[3]);
            }
            fence_async();
            bar_sync(1 + wg, 128);
            if ((tid & 127) == 0) {
                tma_store(&tm.hs, epi, nb * 128, mb * 128 + wg * 64);
                tma_store(&tm.hs, epi + 8192, nb * 128 + 64, mb * 128 + wg * 64);
                bulk_commit();
            }
        }
        if ((tid & 127) == 0) {
            bulk_wait_all();
            __threadfence();
            for (int tile = blockIdx.x; tile < G1_TILES; tile += gridDim.x) atomicAdd(&g_hcnt[tile & 15], 1u);
        }
        for (int pass = 0; pass < 4; pass++) {
            for (int i = g1_first(pass); i < g1_count(pass); i += gridDim.x) {
                const int tile = pass == 1 ? i : pass == 3 ? T_MID + (i >> 2) : NFULL + i;
                const int nkb = pass == 0 ? FF / 64 : pass == 1 ? (FF + HD) / 64 : pass == 2 ? HD / 64 : 16;
                for (int kb = 0; kb < nkb; kb++, it++) g_mma_block(d, sb, bar, it, wg, tid, kb == 0);
                wg_wait<0>();
                if ((tid & 127) == 0) mbar_arrive(bar + 8 * (G_ST + (it - 1) % G_ST));
                float4* pre = g_pre + (tile - NFULL) * (32 * 256) + tid;
                if (pass >= 2) { if ((tid & 31) == 0) wait_count(&g_pcnt[tile], 8); __syncwarp(); }
                if (pass == 0) {
#pragma unroll
                    for (int q = 0; q < 32; q++) __stcg(pre + q * 256, make_float4(d[4 * q], d[4 * q + 1], d[4 * q + 2], d[4 * q + 3]));
                    __threadfence();
                    __syncwarp();
                    if ((tid & 31) == 0) atomicAdd(&g_pcnt[tile], 1u);
                } else if (pass == 3) {
                    float4 r[8];
#pragma unroll
                    for (int q = 0; q < 8; q++) r[q] = __ldcg(pre + ((i & 3) * 8 + q) * 256);
                    g_split_finish<4>(d, r, g_sk + (tile - T_MID) * 4 * (32 * 256), tile, i & 3, out, tid);
                } else {
                    if (pass == 2) {
#pragma unroll
                        for (int q = 0; q < 32; q++) {
                            const float4 u = __ldcg(pre + q * 256); d[4 * q] += u.x; d[4 * q + 1] += u.y; d[4 * q + 2] += u.z; d[4 * q + 3] += u.w;
                            if ((q & 7) == 7) __syncwarp();
                        }
                    }
                    g_store_tile(d, &tm.out, epi, tile >> 2, tile & 3, wg, tid);
                }
            }
        }
        if ((tid & 127) == 0) bulk_wait_all();
        KT(1, 1);
    }
    __syncwarp();
    asm volatile("griddepcontrol.wait;" ::: "memory");
}

struct G2Maps { CUtensorMap o, wo; };

__global__ void __launch_bounds__(384, 1) g2_kernel(const __grid_constant__ G2Maps tm, bf16* __restrict__ out) {
    extern __shared__ __align__(1024) unsigned char smem_raw[];
    const uint32_t sb = (smem_u32(smem_raw) + 1023) & ~1023u;
    const int tid = threadIdx.x, lane = tid & 31;
    const int wg = __shfl_sync(0xffffffffu, tid >> 7, 0);
    const int warp = __shfl_sync(0xffffffffu, (tid >> 5) & 3, 0);
    const uint32_t bar = sb + G_BAR;
    const int ks = blockIdx.x & 7, tile = T_LATE + (blockIdx.x >> 3), nb = tile & 3, mb = tile >> 2;
    KT(2, 0);
    if (tid == 0) {
        for (int i = 0; i < G_ST; i++) { mbar_init(bar + 8 * i, 1); mbar_init(bar + 8 * (G_ST + i), 2); }
        fence_async();
        for (int it = 0; it < G_ST; it++) mbar_expect(bar + 8 * it, G_STAGE);
    }
    __syncthreads();
    if (tid < 256 && (tid & 7) == 0) {
        const int it = tid >> 5, q = (tid >> 3) & 3;
        if (it < G_ST) tma_load(sb + it * G_STAGE + 16384 + q * 8192, &tm.wo, nb * 256 + q * 64, (ks * 8 + it) * 64, bar + 8 * it);
        else tma_prefetch(&tm.wo, nb * 256 + q * 64, (ks * 8 + it) * 64);
    }
    __syncwarp();
    PT(16);
    asm volatile("griddepcontrol.wait;" ::: "memory");
    PT(17);
    if (wg == 2) {
        asm volatile("setmaxnreg.dec.sync.aligned.u32 40;");
        if (lane == 0) tma_load(sb + warp * G_STAGE, &tm.o, (ks * 8 + warp) * 64, mb * 128, bar + 8 * warp);
        if (warp == 0 && lane == 0) {
            for (int it = G_ST; it < 8; it++) g_load_block(sb, bar, it, &tm.o, (ks * 8 + it) * 64, mb * 128, &tm.wo, nb * 256);
        } else if (warp == 1) {
            if (blockIdx.x < SEQ / 32) g_gate[blockIdx.x * 32 + lane] = 0u;
            if (blockIdx.x == 0) { if (lane < 16) { g_hcnt[lane] = 0u; g_ocnt[lane] = 0u; } g_pcnt[lane] = 0u; g_pcnt[32 + lane] = 0u; }
        }
    } else {
        asm volatile("setmaxnreg.inc.sync.aligned.u32 232;");
        float d[128];
        float4 r[4];
        const float4* pre = g_pre + ((tile - NFULL) * 32 + ks * 4) * 256 + tid;
#pragma unroll
        for (int q = 0; q < 4; q++) r[q] = __ldcg(pre + q * 256);
        for (int it = 0; it < 8; it++) { g_mma_block(d, sb, bar, it, wg, tid, it == 0); if (it == 0) PT(18); }
        wg_wait<0>();
        PT(19);
        g_split_finish<8>(d, r, g_sk + ((T_LATE - T_MID) * 4 + (tile - T_LATE) * 8) * (32 * 256), tile, ks, out, tid);
        KT(2, 1);
    }
}

typedef CUresult (*EncodeFn)(CUtensorMap*, CUtensorMapDataType, cuuint32_t, void*, const cuuint64_t*, const cuuint64_t*, const cuuint32_t*,
                             const cuuint32_t*, CUtensorMapInterleave, CUtensorMapSwizzle, CUtensorMapL2promotion, CUtensorMapFloatOOBfill);

static void make_map(EncodeFn enc, CUtensorMap* m, const void* ptr, uint64_t rows, uint64_t cols, uint32_t box_rows) {
    cuuint64_t dims[2] = {cols, rows};
    cuuint64_t strides[1] = {cols * 2};
    cuuint32_t box[2] = {64, box_rows};
    cuuint32_t es[2] = {1, 1};
    enc(m, CU_TENSOR_MAP_DATA_TYPE_BFLOAT16, 2, (void*)ptr, dims, strides, box, es, CU_TENSOR_MAP_INTERLEAVE_NONE,
        CU_TENSOR_MAP_SWIZZLE_128B, CU_TENSOR_MAP_L2_PROMOTION_L2_256B, CU_TENSOR_MAP_FLOAT_OOB_FILL_NONE);
}

extern "C" void kernel_launch(void* const* d_in, const int* in_sizes, int n_in, void* d_out, int out_size) {
    (void)in_sizes; (void)n_in; (void)out_size;
    const bf16* x = (const bf16*)d_in[0];
    const bf16* mem0 = (const bf16*)d_in[1];
    const bf16* gate_w = (const bf16*)d_in[11];
    static EncodeFn enc = nullptr;
    static int n_sm = 0;
    static void *pO = nullptr, *pH = nullptr;
    if (!enc) {
        void* fn = nullptr;
        cudaDriverEntryPointQueryResult qr;
        cudaGetDriverEntryPoint("cuTensorMapEncodeTiled", &fn, cudaEnableDefault, &qr);
        enc = (EncodeFn)fn;
        cudaDeviceGetAttribute(&n_sm, cudaDevAttrMultiProcessorCount, 0);
        cudaFuncSetAttribute(r_kernel, cudaFuncAttributeMaxDynamicSharedMemorySize, R_SMEM);
        cudaFuncSetAttribute(g1_kernel, cudaFuncAttributeMaxDynamicSharedMemorySize, G_SMEM);
        cudaFuncSetAttribute(g2_kernel, cudaFuncAttributeMaxDynamicSharedMemorySize, G_SMEM);
        cudaGetSymbolAddress(&pO, g_O);
        cudaGetSymbolAddress(&pH, g_H);
    }
    RMaps rm; G1Maps m1; G2Maps m2;
    make_map(enc, &rm.x, x, SEQ, DM, 32);
    for (int i = 0; i < 3; i++) make_map(enc, &rm.w[i], d_in[2 + i], DM, HD, 64);
    make_map(enc, &rm.wo, d_in[5], HD, DM, 128);
    make_map(enc, &rm.o, pO, SEQ, HD, 16);
    make_map(enc, &m1.x, x, SEQ, DM, 128);
    make_map(enc, &m1.wg, d_in[8], DM, FF, 64);
    make_map(enc, &m1.wu, d_in[9], DM, FF, 64);
    make_map(enc, &m1.hs, pH, SEQ, FF, 64);
    make_map(enc, &m1.o, pO, SEQ, HD, 128);
    make_map(enc, &m1.h, pH, SEQ, FF, 128);
    make_map(enc, &m1.wo, d_in[5], HD, DM, 64);
    make_map(enc, &m1.wd, d_in[10], FF, DM, 64);
    make_map(enc, &m1.out, d_out, SEQ, DM, 64);
    m2.o = m1.o; m2.wo = m1.wo;

    cudaStream_t st = cudaStreamPerThread;
    {
        cudaLaunchConfig_t cfg = {};
        cfg.gridDim = dim3(96); cfg.blockDim = dim3(384); cfg.dynamicSmemBytes = R_SMEM; cfg.stream = st;
        cudaLaunchAttribute at[1];
        at[0].id = cudaLaunchAttributeClusterDimension; at[0].val.clusterDim.x = 3; at[0].val.clusterDim.y = 1; at[0].val.clusterDim.z = 1;
        cfg.attrs = at; cfg.numAttrs = 1;
        cudaLaunchKernelEx(&cfg, r_kernel, rm, mem0, x, gate_w);
    }
    {
        cudaLaunchConfig_t cfg = {};
        cfg.gridDim = dim3(n_sm - 96); cfg.blockDim = dim3(384); cfg.dynamicSmemBytes = G_SMEM; cfg.stream = st;
        cudaLaunchAttribute at[1];
        at[0].id = cudaLaunchAttributeProgrammaticStreamSerialization; at[0].val.programmaticStreamSerializationAllowed = 1;
        cfg.attrs = at; cfg.numAttrs = 1;
        cudaLaunchKernelEx(&cfg, g1_kernel, m1, (bf16*)d_out);
    }
    {
        cudaLaunchConfig_t cfg = {};
        cfg.gridDim = dim3((64 - T_LATE) * 8); cfg.blockDim = dim3(384); cfg.dynamicSmemBytes = G_SMEM; cfg.stream = st;
        cudaLaunchAttribute at[1];
        at[0].id = cudaLaunchAttributeProgrammaticStreamSerialization; at[0].val.programmaticStreamSerializationAllowed = 1;
        cfg.attrs = at; cfg.numAttrs = 1;
        cudaLaunchKernelEx(&cfg, g2_kernel, m2, (bf16*)d_out);
    }
}
```

```cpp
#include <cuda_runtime.h>
#include <cuda_bf16.h>
#include <cuda.h>
#include <stdint.h>

typedef __nv_bfloat16 bf16;

constexpr int SEQ = 2048, DM = 1024, NH = 32, DH = 128, NMEM = 8, SEG = 32, NSEG = 64, FF = 3584;
constexpr int HD = NH * DH;

__device__ bf16 g_O[SEQ * HD];
__device__ bf16 g_H[SEQ * FF];
__device__ uint32_t g_gate[SEQ];
__device__ uint32_t g_part[4][128 * 32 * 32];
__device__ uint32_t g_mem[4][DM * 4];
constexpr int NFULL = 36, T_MID = 44, T_LATE = 48;
constexpr int NPRE = 64 - NFULL;
__device__ float4 g_pre[NPRE * 32 * 256];
__device__ float4 g_sk[(64 - T_MID) * 8 * 32 * 256];
__device__ uint32_t g_skcnt[64], g_pcnt[64];
__device__ uint32_t g_hcnt[32], g_ocnt[16];
#define KT(k, i)
#define PT(i)

#define DEVINL __device__ __forceinline__
constexpr long long SPIN_LIMIT = 4000000000LL;

DEVINL uint32_t smem_u32(const void* p) { return (uint32_t)__cvta_generic_to_shared(p); }
DEVINL void mbar_init(uint32_t bar, uint32_t cnt) { asm volatile("mbarrier.init.shared::cta.b64 [%0], %1;" ::"r"(bar), "r"(cnt) : "memory"); }
DEVINL void mbar_arrive(uint32_t bar) { asm volatile("mbarrier.arrive.shared::cta.b64 _, [%0];" ::"r"(bar) : "memory"); }
DEVINL void mbar_expect(uint32_t bar, uint32_t bytes) { asm volatile("mbarrier.arrive.expect_tx.shared::cta.b64 _, [%0], %1;" ::"r"(bar), "r"(bytes) : "memory"); }
DEVINL void mbar_arrive_remote(uint32_t cbar) { asm volatile("mbarrier.arrive.relaxed.cluster.shared::cluster.b64 _, [%0];" ::"r"(cbar) : "memory"); }
DEVINL bool mbar_try(uint32_t bar, uint32_t par) {
    uint32_t ok;
    asm volatile("{ .reg .pred p; mbarrier.try_wait.parity.shared::cta.b64 p, [%1], %2; selp.u32 %0, 1, 0, p; }" : "=r"(ok) : "r"(bar), "r"(par) : "memory");
    return ok;
}
__device__ __noinline__ void mbar_wait_slow(uint32_t bar, uint32_t par) {
    long long t0 = clock64();
    while (!mbar_try(bar, par)) { if (clock64() - t0 > SPIN_LIMIT) __trap(); }
}
DEVINL void mbar_wait(uint32_t bar, uint32_t par) {
    uint32_t n = 0;
    while (!mbar_try(bar, par)) { if (++n > 200000000u) __trap(); }
}
DEVINL uint32_t mapa(uint32_t a, uint32_t r) { uint32_t o; asm volatile("mapa.shared::cluster.u32 %0, %1, %2;" : "=r"(o) : "r"(a), "r"(r)); return o; }
DEVINL void fence_async() { asm volatile("fence.proxy.async.shared::cta;" ::: "memory"); }
DEVINL void bar_sync(int id, int n) { asm volatile("bar.sync %0, %1;" ::"r"(id), "r"(n) : "memory"); }
DEVINL void cluster_sync() { asm volatile("barrier.cluster.arrive.aligned; barrier.cluster.wait.aligned;" ::: "memory"); }
DEVINL void tma_load(uint32_t dst, const CUtensorMap* tm, int c0, int c1, uint32_t bar) {
    asm volatile("cp.async.bulk.tensor.2d.shared::cluster.global.mbarrier::complete_tx::bytes [%0], [%1, {%3, %4}], [%2];"
                 ::"r"(dst), "l"(tm), "r"(bar), "r"(c0), "r"(c1) : "memory");
}
DEVINL void tma_prefetch(const CUtensorMap* tm, int c0, int c1) {
    asm volatile("cp.async.bulk.prefetch.tensor.2d.L2.global [%0, {%1, %2}];" ::"l"(tm), "r"(c0), "r"(c1) : "memory");
}
DEVINL void tma_store(const CUtensorMap* tm, uint32_t src, int c0, int c1) {
    asm volatile("cp.async.bulk.tensor.2d.global.shared::cta.bulk_group [%0, {%2, %3}], [%1];" ::"l"(tm), "r"(src), "r"(c0), "r"(c1) : "memory");
}
DEVINL void bulk_commit() { asm volatile("cp.async.bulk.commit_group;" ::: "memory"); }
DEVINL void bulk_wait_read() { asm volatile("cp.async.bulk.wait_group.read 0;" ::: "memory"); }
DEVINL void bulk_wait_all() { asm volatile("cp.async.bulk.wait_group 0;" ::: "memory"); }
DEVINL void bulk_s2s(uint32_t cdst, uint32_t src, uint32_t bytes, uint32_t cbar) {
    asm volatile("cp.async.bulk.shared::cluster.shared::cta.mbarrier::complete_tx::bytes [%0], [%1], %2, [%3];" ::"r"(cdst), "r"(src), "r"(bytes), "r"(cbar) : "memory");
}
DEVINL void st_async16(uint32_t cdst, uint4 v, uint32_t cbar) {
    asm volatile("st.async.shared::cluster.mbarrier::complete_tx::bytes.v4.b32 [%0], {%1,%2,%3,%4}, [%5];" ::"r"(cdst), "r"(v.x), "r"(v.y), "r"(v.z), "r"(v.w), "r"(cbar) : "memory");
}
DEVINL uint64_t mkdesc(uint32_t addr, uint32_t lbo, uint32_t sbo, uint32_t swz) {
    return (uint64_t)((addr & 0x3FFFF) >> 4) | ((uint64_t)(lbo >> 4) << 16) | ((uint64_t)(sbo >> 4) << 32) | ((uint64_t)swz << 62);
}
constexpr uint32_t SB0 = 1024;
__host__ __device__ constexpr uint64_t cdesc(uint32_t off, uint32_t lbo, uint32_t sbo, uint32_t swz) {
    return (uint64_t)(((SB0 + off) & 0x3FFFF) >> 4) | ((uint64_t)(lbo >> 4) << 16) | ((uint64_t)(sbo >> 4) << 32) | ((uint64_t)swz << 62);
}
DEVINL float rcp(float x) { float y; asm("rcp.approx.ftz.f32 %0, %1;" : "=f"(y) : "f"(x)); return y; }
DEVINL float ex2(float x) { float y; asm("ex2.approx.ftz.f32 %0, %1;" : "=f"(y) : "f"(x)); return y; }
DEVINL void spin_clk(int d) { uint32_t t0, t1; asm volatile("mov.u32 %0, %%clock;" : "=r"(t0)); do { asm volatile("mov.u32 %0, %%clock;" : "=r"(t1)); } while ((int)(t1 - t0) < d); }
#define PROBE_GAP 150
#define OPAQUE(x) asm volatile("" : "+r"(x))
DEVINL void wg_fence() { asm volatile("wgmma.fence.sync.aligned;" ::: "memory"); }
DEVINL void wg_commit() { asm volatile("wgmma.commit_group.sync.aligned;" ::: "memory"); }
template <int N> DEVINL void wg_wait() { asm volatile("wgmma.wait_group.sync.aligned %0;" ::"n"(N) : "memory"); }
DEVINL uint32_t pack_bf16(float lo, float hi) { uint32_t r; asm("cvt.rn.bf16x2.f32 %0, %1, %2;" : "=r"(r) : "f"(hi), "f"(lo)); return r; }
DEVINL void ldsm4(uint32_t* r, uint32_t a) { asm volatile("ldmatrix.sync.aligned.m8n8.x4.shared.b16 {%0,%1,%2,%3}, [%4];" : "=r"(r[0]), "=r"(r[1]), "=r"(r[2]), "=r"(r[3]) : "r"(a) : "memory"); }
DEVINL void ldsm4t(uint32_t* r, uint32_t a) { asm volatile("ldmatrix.sync.aligned.m8n8.x4.trans.shared.b16 {%0,%1,%2,%3}, [%4];" : "=r"(r[0]), "=r"(r[1]), "=r"(r[2]), "=r"(r[3]) : "r"(a) : "memory"); }
DEVINL void ldsm4t_if(uint32_t* r, uint32_t a, int c) { asm volatile("{ .reg .pred p; setp.ne.s32 p, %5, 0; @p ldmatrix.sync.aligned.m8n8.x4.trans.shared.b16 {%0,%1,%2,%3}, [%4]; }" : "+r"(r[0]), "+r"(r[1]), "+r"(r[2]), "+r"(r[3]) : "r"(a), "r"(c) : "memory"); }
DEVINL void stsm4(uint32_t a, uint32_t r0, uint32_t r1, uint32_t r2, uint32_t r3) { asm volatile("stmatrix.sync.aligned.m8n8.x4.shared.b16 [%0], {%1,%2,%3,%4};" ::"r"(a), "r"(r0), "r"(r1), "r"(r2), "r"(r3) : "memory"); }
DEVINL void stsm4t(uint32_t a, uint32_t r0, uint32_t r1, uint32_t r2, uint32_t r3) { asm volatile("stmatrix.sync.aligned.m8n8.x4.trans.shared.b16 [%0], {%1,%2,%3,%4};" ::"r"(a), "r"(r0), "r"(r1), "r"(r2), "r"(r3) : "memory"); }
DEVINL void sts32(uint32_t a, uint32_t v) { asm volatile("st.shared.b32 [%0], %1;" ::"r"(a), "r"(v) : "memory"); }
DEVINL void sts128(uint32_t a, uint4 v) { asm volatile("st.shared.v4.b32 [%0], {%1,%2,%3,%4};" ::"r"(a), "r"(v.x), "r"(v.y), "r"(v.z), "r"(v.w) : "memory"); }
DEVINL uint4 lds128(uint32_t a) { uint4 v; asm volatile("ld.shared.v4.b32 {%0,%1,%2,%3}, [%4];" : "=r"(v.x), "=r"(v.y), "=r"(v.z), "=r"(v.w) : "r"(a) : "memory"); return v; }
DEVINL uint4 ld_strong16(const void* p) { uint4 v; asm volatile("ld.relaxed.gpu.global.v4.u32 {%0,%1,%2,%3}, [%4];" : "=r"(v.x), "=r"(v.y), "=r"(v.z), "=r"(v.w) : "l"(p) : "memory"); return v; }
DEVINL void st_strong8(void* p, uint32_t a, uint32_t b) { asm volatile("st.relaxed.gpu.global.v2.u32 [%0], {%1,%2};" ::"l"(p), "r"(a), "r"(b) : "memory"); }
DEVINL void st_strong4(void* p, uint32_t a) { asm volatile("st.relaxed.gpu.global.u32 [%0], %1;" ::"l"(p), "r"(a) : "memory"); }
DEVINL void st_strong16(void* p, uint4 v) { asm volatile("st.relaxed.gpu.global.v4.u32 [%0], {%1,%2,%3,%4};" ::"l"(p), "r"(v.x), "r"(v.y), "r"(v.z), "r"(v.w) : "memory"); }
DEVINL uint32_t pack_nz(float lo, float hi) { uint32_t r = pack_bf16(lo, hi); return r == 0u ? 0x8000u : r; }
DEVINL uint32_t min4(uint4 v, uint32_t m) { return __vimin3_u32(__vimin3_u32(v.x, v.y, m), v.z, v.w); }
DEVINL void mma16816(float* d, uint32_t a0, uint32_t a1, uint32_t a2, uint32_t a3, uint32_t b0, uint32_t b1) {
    asm volatile("mma.sync.aligned.m16n8k16.row.col.f32.bf16.bf16.f32 {%0,%1,%2,%3}, {%4,%5,%6,%7}, {%8,%9}, {%0,%1,%2,%3};"
                 : "+f"(d[0]), "+f"(d[1]), "+f"(d[2]), "+f"(d[3]) : "r"(a0), "r"(a1), "r"(a2), "r"(a3), "r"(b0), "r"(b1));
}
DEVINL void mma1688(float* d, uint32_t a0, uint32_t a1, uint32_t b0) {
    asm volatile("mma.sync.aligned.m16n8k8.row.col.f32.bf16.bf16.f32 {%0,%1,%2,%3}, {%4,%5}, {%6}, {%0,%1,%2,%3};"
                 : "+f"(d[0]), "+f"(d[1]), "+f"(d[2]), "+f"(d[3]) : "r"(a0), "r"(a1), "r"(b0));
}
template <int TA, int TB> DEVINL void wg_ss8(float* d, uint64_t da, uint64_t db, int sc) {
    asm volatile("{ .reg .pred p; setp.ne.b32 p, %6, 0; wgmma.mma_async.sync.aligned.m64n8k16.f32.bf16.bf16 {%0,%1,%2,%3}, %4, %5, p, 1, 1, %7, %8; }"
                 : "+f"(d[0]), "+f"(d[1]), "+f"(d[2]), "+f"(d[3]) : "l"(da), "l"(db), "r"(sc), "n"(TA), "n"(TB));
}
template <int TB> DEVINL void wg_rs8(float* d, const uint32_t* a, uint64_t db, int sc) {
    asm volatile("{ .reg .pred p; setp.ne.b32 p, %9, 0; wgmma.mma_async.sync.aligned.m64n8k16.f32.bf16.bf16 {%0,%1,%2,%3}, {%4,%5,%6,%7}, %8, p, 1, 1, %10; }"
                 : "+f"(d[0]), "+f"(d[1]), "+f"(d[2]), "+f"(d[3]) : "r"(a[0]), "r"(a[1]), "r"(a[2]), "r"(a[3]), "l"(db), "r"(sc), "n"(TB));
}
#define ACC16(d) "+f"(d[0]), "+f"(d[1]), "+f"(d[2]), "+f"(d[3]), "+f"(d[4]), "+f"(d[5]), "+f"(d[6]), "+f"(d[7]), "+f"(d[8]), "+f"(d[9]), "+f"(d[10]), "+f"(d[11]), "+f"(d[12]), "+f"(d[13]), "+f"(d[14]), "+f"(d[15])
template <int TA> DEVINL void wg_ss32(float* d, uint64_t da, uint64_t db, int sc) {
    asm volatile("{ .reg .pred p; setp.ne.b32 p, %18, 0; wgmma.mma_async.sync.aligned.m64n32k16.f32.bf16.bf16 {%0,%1,%2,%3,%4,%5,%6,%7,%8,%9,%10,%11,%12,%13,%14,%15}, %16, %17, p, 1, 1, %19, 0; }"
                 : ACC16(d) : "l"(da), "l"(db), "r"(sc), "n"(TA));
}
DEVINL void wg_rs32(float* d, const uint32_t* a, uint64_t db, int sc) {
    asm volatile("{ .reg .pred p; setp.ne.b32 p, %21, 0; wgmma.mma_async.sync.aligned.m64n32k16.f32.bf16.bf16 {%0,%1,%2,%3,%4,%5,%6,%7,%8,%9,%10,%11,%12,%13,%14,%15}, {%16,%17,%18,%19}, %20, p, 1, 1, 0; }"
                 : ACC16(d) : "r"(a[0]), "r"(a[1]), "r"(a[2]), "r"(a[3]), "l"(db), "r"(sc));
}
DEVINL void wg_ss40(float* d, uint64_t da, uint64_t db, int sc) {
    asm volatile("{ .reg .pred p; setp.ne.b32 p, %22, 0; wgmma.mma_async.sync.aligned.m64n40k16.f32.bf16.bf16 {%0,%1,%2,%3,%4,%5,%6,%7,%8,%9,%10,%11,%12,%13,%14,%15,%16,%17,%18,%19}, %20, %21, p, 1, 1, 1, 1; }"
                 : ACC16(d), "+f"(d[16]), "+f"(d[17]), "+f"(d[18]), "+f"(d[19]) : "l"(da), "l"(db), "r"(sc));
}
#define A8(d, o) "+f"(d[o]), "+f"(d[o + 1]), "+f"(d[o + 2]), "+f"(d[o + 3]), "+f"(d[o + 4]), "+f"(d[o + 5]), "+f"(d[o + 6]), "+f"(d[o + 7])
#define A32(d, o) A8(d, o), A8(d, o + 8), A8(d, o + 16), A8(d, o + 24)
DEVINL void wg_ss256(float* d, uint64_t da, uint64_t db, int sc) {
    asm volatile(
        "{ .reg .pred p; setp.ne.b32 p, %130, 0;\n"
        "wgmma.mma_async.sync.aligned.m64n256k16.f32.bf16.bf16 {"
        "%0,%1,%2,%3,%4,%5,%6,%7,%8,%9,%10,%11,%12,%13,%14,%15,%16,%17,%18,%19,%20,%21,%22,%23,%24,%25,%26,%27,%28,%29,%30,%31,"
        "%32,%33,%34,%35,%36,%37,%38,%39,%40,%41,%42,%43,%44,%45,%46,%47,%48,%49,%50,%51,%52,%53,%54,%55,%56,%57,%58,%59,%60,%61,%62,%63,"
        "%64,%65,%66,%67,%68,%69,%70,%71,%72,%73,%74,%75,%76,%77,%78,%79,%80,%81,%82,%83,%84,%85,%86,%87,%88,%89,%90,%91,%92,%93,%94,%95,"
        "%96,%97,%98,%99,%100,%101,%102,%103,%104,%105,%106,%107,%108,%109,%110,%111,%112,%113,%114,%115,%116,%117,%118,%119,%120,%121,%122,%123,%124,%125,%126,%127"
        "}, %128, %129, p, 1, 1, 0, 1; }"
        : A32(d, 0), A32(d, 32), A32(d, 64), A32(d, 96) : "l"(da), "l"(db), "r"(sc));
}

DEVINL float gate_row(const uint4 (&xv)[4], const uint4 (&gv)[4]) {
    float acc = 0.f;
#pragma unroll
    for (int i = 0; i < 4; i++) {
        const uint32_t xa[4] = {xv[i].x, xv[i].y, xv[i].z, xv[i].w}, ga[4] = {gv[i].x, gv[i].y, gv[i].z, gv[i].w};
#pragma unroll
        for (int e = 0; e < 4; e++) {
            acc = fmaf(__uint_as_float(xa[e] << 16), __uint_as_float(ga[e] << 16), acc);
            acc = fmaf(__uint_as_float(xa[e] & 0xffff0000u), __uint_as_float(ga[e] & 0xffff0000u), acc);
        }
    }
#pragma unroll
    for (int o = 16; o > 0; o >>= 1) acc += __shfl_xor_sync(0xffffffffu, acc, o);
    return 1.0f / (1.0f + __expf(-acc));
}
DEVINL uint4 ldg_nc(const void* p) { uint4 v; asm volatile("ld.global.nc.v4.u32 {%0,%1,%2,%3}, [%4];" : "=r"(v.x), "=r"(v.y), "=r"(v.z), "=r"(v.w) : "l"(p) : "memory"); return v; }
DEVINL uint32_t ld_strong4(const void* p) { uint32_t v; asm volatile("ld.relaxed.gpu.global.u32 %0, [%1];" : "=r"(v) : "l"(p) : "memory"); return v; }
DEVINL void wait_count(const uint32_t* p, uint32_t want) {
    uint32_t v, n = 0;
    while (true) {
        asm volatile("ld.acquire.gpu.global.u32 %0, [%1];" : "=r"(v) : "l"(p) : "memory");
        if (v >= want) break;
        __nanosleep(200);
        if (++n > 10000000u) __trap();
    }
}

constexpr int KR = 44;
constexpr int KS = 64 - KR;
constexpr int R_W = 0;
constexpr int R_WO = KS * 4096;
constexpr int R_QX = R_WO + 65536;
constexpr int R_RING = R_WO + 98304;
constexpr int R_K = R_RING + 24576;
constexpr int R_V = R_K + 10240;
constexpr int R_QM = R_V + 10240;
constexpr int R_O = R_QM + 2048;
constexpr int R_BAR = R_O + 2048;
constexpr int R_G = R_BAR + 256 + 512 + 256 + 128;
constexpr int R_Z = R_G + 256;
constexpr int R_SMEM = R_Z + 1024;
enum { B_FULL = 0, B_EMPTY = 5, B_MEM = 8, B_HOP1 = 12, B_XT, B_TFREE, B_O, B_AFREE0, B_AFREE1, B_PRO0, B_PRO1, B_XRECV, B_P, B_XDONE, B_OST0, B_OST1, B_HOPV };
#define D2_BASE 900
#define D2_STEP 200
#define PD2 6
#define CPB 8192
#define DDUP 0
#define WGAP 0
#define PVD 400
#define ELD 700
#define QD 3
#define DQ 1700
#define D3 0

DEVINL uint32_t clk32() { uint32_t c_; asm volatile("mov.u32 %0, %%clock;" : "=r"(c_)); return c_; }
DEVINL void spin_until(uint32_t t) { while ((uint32_t)(t - clk32() - 1u) < 100000u) {} }
#define PROF(i)
#define PROF2(i)
#define PROF3(i, val)
DEVINL void e_arrive(uint32_t bar) { asm volatile("{ .reg .pred p; elect.sync _|p, 0xffffffff; @p mbarrier.arrive.shared::cta.b64 _, [%0]; }" ::"r"(bar) : "memory"); }
DEVINL void e_arrive_remote(uint32_t cbar) { asm volatile("{ .reg .pred p; elect.sync _|p, 0xffffffff; @p mbarrier.arrive.relaxed.cluster.shared::cluster.b64 _, [%0]; }" ::"r"(cbar) : "memory"); }
DEVINL void e_count(uint32_t* p) { asm volatile("{ .reg .pred p; elect.sync _|p, 0xffffffff; @p red.relaxed.gpu.global.add.u32 [%0], 1; }" ::"l"(p) : "memory"); }
DEVINL void e_expect(uint32_t bar, uint32_t bytes) { asm volatile("{ .reg .pred p; elect.sync _|p, 0xffffffff; @p mbarrier.arrive.expect_tx.shared::cta.b64 _, [%0], %1; }" ::"r"(bar), "r"(bytes) : "memory"); }
DEVINL void e_tma_load(uint32_t dst, const CUtensorMap* tm, int c0, int c1, uint32_t bar) {
    asm volatile("{ .reg .pred p; elect.sync _|p, 0xffffffff; @p cp.async.bulk.tensor.2d.shared::cluster.global.mbarrier::complete_tx::bytes [%0], [%1, {%3, %4}], [%2]; }"
                 ::"r"(dst), "l"(tm), "r"(bar), "r"(c0), "r"(c1) : "memory");
}
DEVINL void e_tma_store(const CUtensorMap* tm, uint32_t src, int c0, int c1) {
    asm volatile("{ .reg .pred p; elect.sync _|p, 0xffffffff; @p cp.async.bulk.tensor.2d.global.shared::cta.bulk_group [%0, {%2, %3}], [%1]; }" ::"l"(tm), "r"(src), "r"(c0), "r"(c1) : "memory");
}
DEVINL void e_bulk_s2g(void* dst, uint32_t src, uint32_t bytes) {
    asm volatile("{ .reg .pred p; elect.sync _|p, 0xffffffff; @p cp.async.bulk.global.shared::cta.bulk_group [%0], [%1], %2; }" ::"l"(dst), "r"(src), "r"(bytes) : "memory");
}
DEVINL void e_bulk_s2s(uint32_t cdst, uint32_t src, uint32_t bytes, uint32_t cbar) {
    asm volatile("{ .reg .pred p; elect.sync _|p, 0xffffffff; @p cp.async.bulk.shared::cluster.shared::cta.mbarrier::complete_tx::bytes [%0], [%1], %2, [%3]; }" ::"r"(cdst), "r"(src), "r"(bytes), "r"(cbar) : "memory");
}

#define SLOT 0
#define PH3 0
#define PHQ 0
DEVINL void wait_slot(uint32_t phase) {
    if (SLOT) {
        uint32_t c; asm volatile("mov.u32 %0, %%globaltimer_lo;" : "=r"(c));
        const uint32_t tgt = c + (SLOT ? SLOT : 1) - ((c - phase) % (SLOT ? SLOT : 1));
        do { asm volatile("mov.u32 %0, %%globaltimer_lo;" : "=r"(c)); } while ((uint32_t)(tgt - c - 1u) < 100000u);
    }
}
template <int N> DEVINL uint32_t poll_set(uint4 (&v)[N], const uint32_t* rp, int stride, uint32_t phase, uint32_t wbar = 0, uint32_t wpar = 0) {
    wait_slot(phase);
#pragma unroll
    for (int i = 0; i < N; i++) v[i] = ld_strong16(rp + i * stride);
    if (wbar) mbar_wait(wbar, wpar);
    uint32_t n = 0;
    while (true) {
        uint32_t m = 0xffffffffu;
#pragma unroll
        for (int i = 0; i < N; i++) m = min4(v[i], m);
        if (__all_sync(0xffffffffu, m != 0u)) return n;
        wait_slot(phase);
#pragma unroll
        for (int i = 0; i < N; i++)
            asm volatile("{ .reg .pred p; setp.eq.u32 p, %5, 0; @p ld.relaxed.gpu.global.v4.u32 {%0,%1,%2,%3}, [%4]; }"
                         : "+r"(v[i].x), "+r"(v[i].y), "+r"(v[i].z), "+r"(v[i].w) : "l"(rp + i * stride), "r"(min4(v[i], 0xffffffffu)) : "memory");
        if (++n > 20000000u) __trap();
    }
}

struct RMaps { CUtensorMap x, w[3], wo, o; };
#define KC(c) ((c) * 64)

#define XORD 3
__host__ __device__ constexpr int xo(int i) {
    return XORD == 0 ? i : XORD == 1 ? (i + 14) % 16 : XORD == 2 ? (i + 11) % 16
         : XORD == 3 ? (i < 10 ? ((i & 1) ? i / 2 : 11 + i / 2) : i - 5) : (i < 6 ? i : ((i & 1) ? 6 + (i - 6) / 2 : 11 + (i - 6) / 2));
}
#define XC(i) (xo(i) * 64)
DEVINL void x_load_pair(uint32_t dst, const CUtensorMap* tmx, int h, int p, int seg, uint32_t fbar) {
    e_expect(fbar, 8192);
    e_tma_load(dst, tmx, XC(2 * p), seg * SEG, fbar);
    e_tma_load(dst + 4096, tmx, XC(2 * p + 1), seg * SEG, fbar);
}
__host__ __device__ constexpr int wo_tile(int role, int i) {
    return role == 0 ? (i < 2 ? 8 + i : 12 + i) : (i < 4 ? (i >> 1) * 4 : 10) + (role - 1) * 2 + (i & 1);
}

template <int NT> DEVINL void wo_phase(uint32_t sb, int tb, uint32_t* pp, uint32_t obar, uint32_t opar) {
    const int lane = tb & 31, krow = (lane & 7) + ((lane >> 4) << 3), chunk = ((tb >> 5) & 3) * 2 + ((lane >> 3) & 1);
    uint32_t wa = sb + R_WO + (tb >> 7) * 16384 + krow * 128 + ((chunk ^ (krow & 7)) << 4);
    uint32_t af[4][4], of[4][4];
#pragma unroll
    for (int g = 0; g < 4; g++) ldsm4t(af[g], wa + g * 2048);
    mbar_wait(obar, opar);
#pragma unroll
    for (int g = 0; g < 4; g++) ldsm4t(of[g], sb + R_O + g * 512 + lane * 16);
#pragma unroll 1
    for (int i = 0; i < NT; i++) {
        float w0[4] = {0.f, 0.f, 0.f, 0.f}, w1[4] = {0.f, 0.f, 0.f, 0.f};
        const int more = NT - 1 - i, yes = NT - i;
        mma16816(w0, af[0][0], af[0][1], af[0][2], af[0][3], of[0][0], of[0][1]);
        ldsm4t_if(af[0], wa + 4 * 2048, yes);
        mma16816(w1, af[1][0], af[1][1], af[1][2], af[1][3], of[0][2], of[0][3]);
        ldsm4t_if(af[1], wa + 5 * 2048, yes);
        mma16816(w0, af[2][0], af[2][1], af[2][2], af[2][3], of[1][0], of[1][1]);
        ldsm4t_if(af[2], wa + 6 * 2048, yes);
        mma16816(w1, af[3][0], af[3][1], af[3][2], af[3][3], of[1][2], of[1][3]);
        ldsm4t_if(af[3], wa + 7 * 2048, yes);
        wa += 32768;
        mma16816(w0, af[0][0], af[0][1], af[0][2], af[0][3], of[2][0], of[2][1]);
        ldsm4t_if(af[0], wa, more);
        mma16816(w1, af[1][0], af[1][1], af[1][2], af[1][3], of[2][2], of[2][3]);
        ldsm4t_if(af[1], wa + 2048, more);
        mma16816(w0, af[2][0], af[2][1], af[2][2], af[2][3], of[3][0], of[3][1]);
        ldsm4t_if(af[2], wa + 2 * 2048, more);
        mma16816(w1, af[3][0], af[3][1], af[3][2], af[3][3], of[3][2], of[3][3]);
        ldsm4t_if(af[3], wa + 3 * 2048, more);
        st_strong4(pp, pack_nz(w0[0] + w1[0], w0[1] + w1[1]));
        st_strong4(pp + 1024, pack_nz(w0[2] + w1[2], w0[3] + w1[3]));
        pp += (NT == 3 && i == 0) ? 4 * 8192 : 6 * 8192;
    }
}

template <uint32_t role> DEVINL void r_big(const RMaps& tm, const int wid) {
    extern __shared__ __align__(1024) unsigned char smem_raw[];
    const uint32_t sb = smem_u32(smem_raw);
    const uint32_t bar = sb + R_BAR;
    const int tid = threadIdx.x;
    int h; asm("mov.u32 %0, %%clusterid.x;" : "=r"(h));
        uint32_t a[KR][4];
        mbar_wait(bar + 8 * B_PRO0, 0);
        PT(0);
        {
            const int lane = tid & 31;
            const int krow = (lane & 7) + ((lane >> 4) << 3);
            const int chunk = (wid & 3) * 2 + ((lane >> 3) & 1);
            const uint32_t la = sb + (wid >> 2) * 8192 + krow * 128 + ((chunk ^ (krow & 7)) << 4);
#pragma unroll
            for (int k = 0; k < KR; k++) ldsm4t(a[k], la + (k >> 2) * 16384 + (k & 3) * 2048);
        }
        bar_sync(1, 256);
        {
            fence_async();
            const CUtensorMap* tw = &tm.w[role];
            e_expect(bar + 8 * B_PRO1, (wid < 5 ? 16384 : 0) + (wid < (role == 0 ? 4 : 6) ? 16384 : 0));
            if (wid < 5) {
                e_tma_load(sb + R_W + wid * 8192, tw, h * DH, KC(KR / 4 + wid), bar + 8 * B_PRO1);
                e_tma_load(sb + R_W + KS * 2048 + wid * 8192, tw, h * DH + 64, KC(KR / 4 + wid), bar + 8 * B_PRO1);
            }
            if (wid < (role == 0 ? 4 : 6)) e_tma_load(sb + R_WO + wid * 16384, &tm.wo, wo_tile(role, wid) * 64, h * DH, bar + 8 * B_PRO1);
        }
        constexpr uint32_t e0 = role == 0 ? R_QX + 16384 : R_K + 2048, e1 = role == 0 ? R_QX + 24576 : R_V + 2048;
        if (wid == 6) x_load_pair(sb + e0, &tm.x, h, 3, 0, bar + 8 * (B_FULL + 3));
        if (wid == 7) x_load_pair(sb + e1, &tm.x, h, 4, 0, bar + 8 * (B_FULL + 4));
        PT(1);
        mbar_wait(bar + 8 * B_PRO1, 0);
        PT(2);

        constexpr uint64_t dW0 = cdesc(R_W, 1024, 1024, 1);
        constexpr uint64_t dM = cdesc(R_RING, 128, 128, 0);
        constexpr uint64_t dX = cdesc(R_RING, 16, 1024, 1);
        constexpr uint64_t dX0 = cdesc(0, 16, 1024, 1);
        int tb = tid;
        int wq = wid;

        for (int seg = 0; seg < NSEG; seg++) {
            {
            const int s = seg - 1; (void)s;
            float d[16];
            OPAQUE(wq);
            const uint64_t dW = dW0 + (uint64_t)((wq >> 2) * (KS * 128));
#pragma unroll
            for (int p = 0; p < 8; p++) {
                const int slot = p % 5;
                mbar_wait(bar + 8 * (B_FULL + slot), slot < 3 ? (uint32_t)(p / 5) : (uint32_t)(seg & 1));
                PROF2(p);
                const uint64_t db = slot < 3 ? dX + (uint64_t)(slot * 512) : dX0 + (uint64_t)((slot == 3 ? e0 : e1) >> 4);
                wg_fence();
#pragma unroll
                for (int kk = 0; kk < 8; kk++) {
                    const int k = XORD >= 3 ? (kk & 1) * 4 + (kk >> 1) : kk;
                    const int ks = xo(2 * p + (k >> 2)) * 4 + (k & 3);
                    if (ks >= KR) wg_ss32<1>(d, dW + (uint64_t)((ks - KR) * 128), db + (uint64_t)((k >> 2) * 256 + (k & 3) * 2), p + k);
                    else wg_rs32(d, a[ks < KR ? ks : 0], db + (uint64_t)((k >> 2) * 256 + (k & 3) * 2), p + k);
                }
                wg_commit();
                if (p >= 1) {
                    wg_wait<1>();
                    if (p <= 3) {
                        if ((wq & 3) == p) e_arrive(bar + 8 * (B_EMPTY + p - 1));
                        if (wq == p + (p & 1) * 4) {
                            mbar_wait(bar + 8 * (B_EMPTY + p - 1), seg & 1);
                            x_load_pair(sb + R_RING + (p - 1) * 8192, &tm.x, h, p + 4, seg, bar + 8 * (B_FULL + p - 1));
                        }
                    }
                    if (p == 5 && role != 0 && (wq & 3) < 3) e_arrive_remote(mapa(bar + 8 * B_TFREE, wq & 3));
                    if (p == 6 && (wq & 3) == 1) e_arrive(bar + 8 * B_AFREE0);
                    if (p == 7 && (wq & 3) == 2) e_arrive(bar + 8 * B_AFREE1);
                }
            }
            mbar_wait(bar + 8 * B_TFREE, seg & 1);
            asm volatile("wgmma.wait_group.sync.aligned 0;" : ACC16(d)::"memory");
            PROF2(16);
            const uint32_t tilex = sb + (role == 0 ? R_QX + 2048 : (role == 1 ? R_K + 2048 : R_V + 2048));
            {
                OPAQUE(tb);
                const uint32_t gs = role == 0 ? 4096 : 2048;
                const uint32_t sa = tilex + ((tb >> 4) & 1) * gs + (tb >> 5) * 256 + (tb & 15) * 16;
                stsm4(sa, pack_bf16(d[0], d[1]), pack_bf16(d[2], d[3]), pack_bf16(d[4], d[5]), pack_bf16(d[6], d[7]));
                stsm4(sa + 2 * gs, pack_bf16(d[8], d[9]), pack_bf16(d[10], d[11]), pack_bf16(d[12], d[13]), pack_bf16(d[14], d[15]));
            }
            __syncwarp();
            e_arrive(bar + 8 * B_XDONE);
            if (role != 0 && (wq & 3) == 0) {
                mbar_wait(bar + 8 * B_XDONE, seg & 1);
                fence_async();
                uint32_t pr = role + 1 + (wq >> 2); pr = pr >= 3 ? pr - 3 : pr;
                e_bulk_s2s(mapa(tilex, pr), tilex, CPB, mapa(bar + 8 * B_XT, pr));
            }
            }
            {
                const int s = seg;
                OPAQUE(wq);
                const uint64_t dW = dW0 + (uint64_t)((wq >> 2) * (KS * 128));
                float y[4] = {0.f, 0.f, 0.f, 0.f};
                {
                    OPAQUE(tb);
                    const uint32_t ma = sb + R_RING + (tb & 31) * 16;
                    float z[4] = {0.f, 0.f, 0.f, 0.f}, u[4] = {0.f, 0.f, 0.f, 0.f};
                    uint32_t b[QD][4];
                    const int yes = s + 1;
                    mbar_wait(bar + 8 * B_MEM, s & 1);
                    PROF((wq >> 2) * 4 + 0);
                    if (s == 0) PT(3);
                    if (s == 1) PT(4);
#pragma unroll
                    for (int g = 0; g < QD; g++) ldsm4t(b[g], ma + g * 512);
#pragma unroll
                    for (int g = 0; g < KR / 2; g++) {
                        float* c0 = (g % 3 == 0) ? y : (g % 3 == 1) ? u : z;
                        float* c1 = (g % 3 == 0) ? z : (g % 3 == 1) ? y : u;
                        mma16816(c0, a[2 * g][0], a[2 * g][1], a[2 * g][2], a[2 * g][3], b[g % QD][0], b[g % QD][1]);
                        mma16816(c1, a[2 * g + 1][0], a[2 * g + 1][1], a[2 * g + 1][2], a[2 * g + 1][3], b[g % QD][2], b[g % QD][3]);
                        if (g + QD < KR / 2) {
                            if ((g + QD) % 8 == 0) mbar_wait(bar + 8 * (B_MEM + (g + QD) / 8), s & 1);
                            ldsm4t_if(b[g % QD], ma + (g + QD) * 512, yes);
                        }
                    }
                    y[0] += z[0] + u[0]; y[1] += z[1] + u[1]; y[2] += z[2] + u[2]; y[3] += z[3] + u[3];
                }
                PROF2(8);
                mbar_wait(bar + 8 * (B_MEM + 3), s & 1);
                wg_fence();
#pragma unroll
                for (int k = KR; k < 64; k++) wg_ss8<1, 1>(y, dW + (uint64_t)((k - KR) * 128), dM + (uint64_t)(k * 16), 1);
                wg_commit();
                asm volatile("wgmma.wait_group.sync.aligned 0;" : "+f"(y[0]), "+f"(y[1]), "+f"(y[2]), "+f"(y[3])::"memory");
                OPAQUE(tb);
                {
                    const uint32_t wo_ = (tb >> 5) * 256;
                    const uint32_t tile = sb + (role == 0 ? R_QX : (role == 1 ? R_K : R_V)) + wo_;
                    const uint32_t u0 = pack_bf16(y[0], y[1]), u1 = pack_bf16(y[2], y[3]);
                    sts32(tile + (tb & 31) * 4, u0);
                    sts32(tile + (tb & 31) * 4 + 128, u1);
                    __syncwarp();
                    uint4 v = lds128(tile + (tb & 15) * 16);
                    uint32_t peer = role + 1 + ((tb >> 4) & 1);
                    peer = peer >= 3 ? peer - 3 : peer;
                    const uint32_t rt = sb + (role == 0 ? R_QM : (role == 1 ? R_K : R_V)) + wo_ + (tb & 15) * 16;
                    st_async16(mapa(rt, peer), v, mapa(bar + 8 * (role == 2 ? B_HOPV : B_HOP1), peer));
                    if (role == 0) {
                        sts128(tile + 4096 + ((tb >> 4) & 1) * 4096 + (tb & 15) * 16, v);
                        sts32(tile + 12288 + (tb & 31) * 4, u0);
                        sts32(tile + 12288 + (tb & 31) * 4 + 128, u1);
                        __syncwarp();
                    }
                    e_arrive(bar + 8 * (role == 2 ? B_HOPV : B_HOP1));
                }
                PROF((wq >> 2) * 4 + 1);
                if (s < NSEG - 1) {
                    bar_sync(1, 256);
                    if (wq < 3) { fence_async(); x_load_pair(sb + R_RING + wq * 8192, &tm.x, h, wq, s + 1, bar + 8 * (B_FULL + wq)); }
                    else if (role == 0 && wq < 5) x_load_pair(sb + (wq == 3 ? e0 : e1), &tm.x, h, wq, s + 1, bar + 8 * (B_FULL + wq));
                    OPAQUE(tb);
                }
                uint32_t* pp = g_part[s & 3] + (h * 32 + (wo_tile(role, 0) + (tb >> 7)) * 8192 + ((tb >> 5) & 3) * 2048 + (tb & 31));
                asm volatile("" : "+l"(pp));
                if (s == NSEG - 1) break;
                wo_phase<role == 0 ? 2 : 3>(sb, tb, pp, bar + 8 * B_O, s & 1);
                if (wq == 0) PROF(10);
            }
        }
}

#define CLR 0
#define CLEAR(st) do { if (role != 0) { \
                const int w_ = wid & 3; \
                uint32_t* zp = g_part[(st) & 3] + ((rg0 + (w_ >> 1) * 64) * 1024 + (w_ & 1) * 512); \
                e_bulk_s2g(zp, sb + R_Z, 1024); \
                e_bulk_s2g(zp + 256, sb + R_Z, 1024); \
                e_bulk_s2g(&g_mem[(st) & 3][(rg0 + (w_ >> 1) * 64) * 32 + (w_ & 1) * 16], sb + R_Z, 64); \
                bulk_commit(); } } while (0)
template <uint32_t role> DEVINL void r_chain(const RMaps& tm, const bf16* __restrict__ mem0, const int wid) {
    extern __shared__ __align__(1024) unsigned char smem_raw[];
    const uint32_t sb = smem_u32(smem_raw);
    const uint32_t bar = sb + R_BAR;
    const int tid = threadIdx.x;
    int h; asm("mov.u32 %0, %%clusterid.x;" : "=r"(h));
        int t = tid & 127;
        const float sl2 = 0.08838834764831845f * 1.4426950408889634f;
        const float NEGRAW = -1000000000.0f / 0.08838834764831845f;
        const int rg0 = ((int)role - 1) * 32 + h;
        if (role != 0) {
#pragma unroll 1
            for (int r = 0; r < 4; r++) {
                uint32_t* zp = g_part[r] + ((rg0 + (t >> 6) * 64) * 1024 + (t & 63) * 4);
#pragma unroll
                for (int i = 0; i < 4; i++) st_strong16(zp + i * 256, make_uint4(0u, 0u, 0u, 0u));
                if ((t & 63) < 8) st_strong16(&g_mem[r][(rg0 + (t >> 6) * 64) * 32 + (t & 63) * 4], make_uint4(0u, 0u, 0u, 0u));
            }
            __threadfence();
        }
        if (role == 0 && (wid & 3) < 3) e_arrive_remote(mapa(bar + 8 * B_TFREE, wid & 3));
        if (t < 64) sts128(sb + R_Z + t * 16, make_uint4(0u, 0u, 0u, 0u));
        if (role == 0) sts128(sb + R_QM + t * 16, make_uint4(0u, 0u, 0u, 0u));
        {
            uint4 v[8];
#pragma unroll
            for (int r = 0; r < 8; r++) v[r] = __ldg((const uint4*)(mem0 + r * DM) + t);
            mbar_wait(bar + 8 * B_AFREE0, 0);
            mbar_wait(bar + 8 * B_AFREE1, 0);
#define TR2(f, c) \
            sts128(sb + R_RING + t * 128 + (c) * 16, make_uint4(__byte_perm(v[0].f, v[1].f, 0x5410), __byte_perm(v[2].f, v[3].f, 0x5410), __byte_perm(v[4].f, v[5].f, 0x5410), __byte_perm(v[6].f, v[7].f, 0x5410))); \
            sts128(sb + R_RING + t * 128 + (c) * 16 + 16, make_uint4(__byte_perm(v[0].f, v[1].f, 0x7632), __byte_perm(v[2].f, v[3].f, 0x7632), __byte_perm(v[4].f, v[5].f, 0x7632), __byte_perm(v[6].f, v[7].f, 0x7632)));
            TR2(x, 0) TR2(y, 2) TR2(z, 4) TR2(w, 6)
            fence_async();
            __syncwarp();
            e_arrive(bar + 8 * B_MEM + (t >> 5) * 8);
        }
        constexpr uint64_t dQ = role == 0 ? cdesc(R_QX, 128, 2048, 0) : cdesc(R_QM, 128, 0, 0);
        constexpr uint64_t dK = cdesc(R_K, 128, 2048, 0);

        for (int s = 0; s < NSEG; s++) {
            if (role == 0) {
                uint32_t n = 0, gate;
                do { gate = ld_strong4(&g_gate[s * SEG + (t >> 2)]); if (++n > 20000000u) __trap(); } while (gate == 0u);
                sts32(sb + R_G + (t >> 2) * 4, gate);
                __syncwarp();
            }
            mbar_wait(bar + 8 * B_XDONE, s & 1);
            mbar_wait(bar + 8 * B_XT, s & 1);
            if (t >= 1 && t < 3) { uint32_t pr = role + t; pr = pr >= 3 ? pr - 3 : pr; mbar_arrive_remote(mapa(bar + 8 * B_XRECV, pr)); }
            __syncwarp();
            mbar_wait(bar + 8 * B_HOP1, s & 1);
            PROF(8);
            fence_async();
            OPAQUE(t);
            if (s == NSEG - 1 && role != 0) { mbar_wait(bar + 8 * B_HOPV, s & 1); bulk_wait_all(); break; }
            float sc[20];
            wg_fence();
#pragma unroll
            for (int k = 0; k < 8; k++) wg_ss40(sc, dQ + (uint64_t)(k * 16), dK + (uint64_t)(k * 16), k);
            wg_commit();
            uint32_t t_o = clk32() + 500;
            {
                const uint32_t va = sb + R_V + 2048 + (t >> 5) * 512 + ((t >> 4) & 1) * 2048 + (t & 15) * 16;
                uint32_t v0[4], v1[4];
                ldsm4(v0, va); ldsm4(v1, va + 256);
                uint32_t vm[4];
                const bool v_here = mbar_try(bar + 8 * B_HOPV, s & 1);
                if (v_here) ldsm4(vm, sb + R_V + t * 16);
                wg_wait<0>();
                if (role == 0) {
#pragma unroll
                    for (int j = 0; j < 5; j++)
                        asm volatile("st.shared.v2.f32 [%0], {%1,%2};" ::"r"(sb + R_QX + 768 + (t >> 5) * 4096 + j * 256 + (t & 31) * 8), "f"(sc[4 * j + 2]), "f"(sc[4 * j + 3]) : "memory");
                }
                float m = fmaxf(sc[0], sc[1]);
#pragma unroll
                for (int j = 1; j < 5; j++) m = fmaxf(m, fmaxf(sc[4 * j], sc[4 * j + 1]));
                m = fmaxf(m, __shfl_xor_sync(0xffffffffu, m, 1));
                m = fmaxf(m, __shfl_xor_sync(0xffffffffu, m, 2));
                const float mb = m * sl2;
                uint32_t pk[5];
#pragma unroll
                for (int j = 0; j < 5; j++) pk[j] = pack_bf16(ex2(fmaf(sc[4 * j], sl2, -mb)), ex2(fmaf(sc[4 * j + 1], sl2, -mb)));
                float o0[4] = {0.f, 0.f, 0.f, 0.f}, o1[4] = {0.f, 0.f, 0.f, 0.f}, ls[4] = {0.f, 0.f, 0.f, 0.f};
                constexpr uint32_t ONE = 0x3F803F80u;
                mma16816(o0, v0[0], v0[1], v0[2], v0[3], pk[1], pk[2]);
                mma16816(o1, v1[0], v1[1], v1[2], v1[3], pk[1], pk[2]);
                ldsm4(v0, va + 4096); ldsm4(v1, va + 4096 + 256);
                mma16816(ls, ONE, ONE, ONE, ONE, pk[1], pk[2]);
                mma16816(ls, ONE, ONE, ONE, ONE, pk[3], pk[4]);
                mma1688(ls, ONE, ONE, pk[0]);
                mma16816(o0, v0[0], v0[1], v0[2], v0[3], pk[3], pk[4]);
                mma16816(o1, v1[0], v1[1], v1[2], v1[3], pk[3], pk[4]);
                if (!v_here) { mbar_wait(bar + 8 * B_HOPV, s & 1); ldsm4(vm, sb + R_V + t * 16); }
                mma1688(o0, vm[0], vm[1], pk[0]);
                mma1688(o1, vm[2], vm[3], pk[0]);
                const float i0 = rcp(ls[0]), i1 = rcp(ls[1]);
                const uint32_t oa = sb + R_O + (t >> 5) * 512 + (t & 31) * 4;
                sts32(oa, pack_bf16(o0[0] * i0, o0[1] * i1));
                sts32(oa + 128, pack_bf16(o0[2] * i0, o0[3] * i1));
                sts32(oa + 256, pack_bf16(o1[0] * i0, o1[1] * i1));
                sts32(oa + 384, pack_bf16(o1[2] * i0, o1[3] * i1));
                __syncwarp();
                e_arrive(bar + 8 * B_O);
                PROF(9);
                if (role == 0) {
                    OPAQUE(t);
                    const int lim = (t >> 2) - (t & 3) * 2 + 8;
                    float z[10];
#pragma unroll
                    for (int j = 0; j < 5; j++)
                        asm volatile("ld.shared.v2.f32 {%0,%1}, [%2];" : "=f"(z[2 * j]), "=f"(z[2 * j + 1]) : "r"(sb + R_QX + 768 + (t >> 5) * 4096 + j * 256 + (t & 31) * 8) : "memory");
                    float gate; asm volatile("ld.shared.f32 %0, [%1];" : "=f"(gate) : "r"(sb + R_G + (t >> 2) * 4) : "memory");
                    float m1 = fmaxf(z[0], z[1]);
#pragma unroll
                    for (int j = 1; j < 5; j++) {
                        z[2 * j] = 8 * j <= lim ? z[2 * j] : NEGRAW;
                        z[2 * j + 1] = 8 * j + 1 <= lim ? z[2 * j + 1] : NEGRAW;
                        m1 = fmaxf(m1, fmaxf(z[2 * j], z[2 * j + 1]));
                    }
                    m1 = fmaxf(m1, __shfl_xor_sync(0xffffffffu, m1, 1));
                    m1 = fmaxf(m1, __shfl_xor_sync(0xffffffffu, m1, 2));
                    const float mb1 = m1 * sl2;
                    float l1 = 0.f;
                    const uint32_t pa = sb + R_QX + (t >> 5) * 4096 + (t & 31) * 4;
#pragma unroll
                    for (int j = 0; j < 5; j++) {
                        const uint32_t pw = pack_bf16(ex2(fmaf(z[2 * j], sl2, -mb1)), ex2(fmaf(z[2 * j + 1], sl2, -mb1)));
                        l1 += __uint_as_float(pw << 16) + __uint_as_float(pw & 0xffff0000u);
                        sts32(pa + j * 128, pw);
                    }
                    sts32(pa + 5 * 128, 0u);
                    l1 += __shfl_xor_sync(0xffffffffu, l1, 1);
                    l1 += __shfl_xor_sync(0xffffffffu, l1, 2);
                    sts32(sb + R_G + 128 + (t >> 2) * 4, __float_as_uint(gate * rcp(l1)));
                    spin_until(t_o + PVD);
                    if ((wid & 3) == 0 && s >= 1) { bulk_wait_all(); e_count(&g_ocnt[(s - 1) >> 2]); }
                    fence_async();
                    bar_sync(2, 128);
                    constexpr uint64_t dV = cdesc(R_V, 2048, 128, 0);
                    constexpr uint64_t dP = cdesc(R_QX, 128, 4096, 0);
                    float sf[8];
#pragma unroll
                    for (int j = 0; j < 4; j++) asm volatile("ld.shared.v2.f32 {%0,%1}, [%2];" : "=f"(sf[2 * j]), "=f"(sf[2 * j + 1]) : "r"(sb + R_G + 128 + j * 32 + (t & 3) * 8) : "memory");
                    const uint32_t r = ((t >> 4) & 1) * 8 + (t & 7), ch = (t >> 5) * 2 + ((t >> 3) & 1);
                    const uint32_t sa = sb + R_QX + 2048 + r * 128 + ((ch ^ (r & 7)) << 4);
#pragma unroll
                    for (int hf = 0; hf < 2; hf++) {
                        float d[16];
                        wg_fence();
#pragma unroll
                        for (int k = 0; k < 3; k++) wg_ss32<0>(d, dV + (uint64_t)(hf * 64 + k * 256), dP + (uint64_t)(k * 16), k);
                        wg_commit();
                        asm volatile("wgmma.wait_group.sync.aligned 0;" : ACC16(d)::"memory");
                        stsm4t(sa + hf * 8192, pack_bf16(d[0] * sf[0], d[1] * sf[1]), pack_bf16(d[2] * sf[0], d[3] * sf[1]), pack_bf16(d[4] * sf[2], d[5] * sf[3]), pack_bf16(d[6] * sf[2], d[7] * sf[3]));
                        stsm4t(sa + hf * 8192 + 4096, pack_bf16(d[8] * sf[4], d[9] * sf[5]), pack_bf16(d[10] * sf[4], d[11] * sf[5]), pack_bf16(d[12] * sf[6], d[13] * sf[7]), pack_bf16(d[14] * sf[6], d[15] * sf[7]));
                    }
                    fence_async();
                    bar_sync(2, 128);
                    if ((wid & 3) == 0) {
#pragma unroll
                        for (int q = 0; q < 4; q++) e_tma_store(&tm.o, sb + R_QX + 2048 + q * 4096, h * DH + (q >> 1) * 64, s * SEG + (q & 1) * 16);
                        bulk_commit();
                        bulk_wait_read();
                    }
                    if ((wid & 3) < 3) e_arrive_remote(mapa(bar + 8 * B_TFREE, wid & 3));
                }
            }
            if (t < 32) { e_expect(bar + 8 * B_HOP1, role == 2 ? 4096 : 2048); if (role != 2) e_expect(bar + 8 * B_HOPV, 2048); e_expect(bar + 8 * B_XT, role == 0 ? 2 * CPB : CPB); }
            if (s == NSEG - 1) { bulk_wait_all(); break; }
            if (role != 0 && (wid & 3) >= 2) {
                mbar_wait(bar + 8 * B_XRECV, s & 1);
                mbar_wait(bar + 8 * B_O, s & 1);
                fence_async();
                spin_until(t_o + ELD);
                x_load_pair(sb + ((wid & 1) ? R_V + 2048 : R_K + 2048), &tm.x, h, 3 + (wid & 1), s + 1, bar + 8 * (B_FULL + 3 + (wid & 1)));
            }
            OPAQUE(t);
            PROF(11);
            if (role != 0 || DDUP) {
                const int grp = role == 0 ? (t >> 6) * 32 + h : rg0 + (t >> 6) * 64;
                const uint32_t* rp = g_part[s & 3] + (grp * 1024 + ((t >> 2) & 7) * 32 + ((t >> 5) & 1) * 16 + (t & 3) * 4);
                uint32_t* wp = &g_mem[(s + 1) & 3][grp * 32 + ((t >> 5) & 1) * 16 + (t & 3) * 4 + ((t >> 3) & 3)];
                bulk_wait_all();
                spin_until(t_o + D2_BASE + (role == 0 ? DDUP + (t >> 6) * D2_STEP : (role - 1 + (t >> 6) * 2) * D2_STEP));
                PROF3(0, clk32());
#define LO(u) __uint_as_float((u) << 16)
#define HI(u) __uint_as_float((u) & 0xffff0000u)
                uint4 v[4];
                uint32_t n = poll_set<4>(v, rp, 256, (role - 1 + (t >> 6) * 2) * PHQ);
                {
                    PROF3(1, clk32());
                    float f[8];
                    f[0] = (LO(v[0].x) + LO(v[1].x)) + (LO(v[2].x) + LO(v[3].x)); f[1] = (HI(v[0].x) + HI(v[1].x)) + (HI(v[2].x) + HI(v[3].x));
                    f[2] = (LO(v[0].y) + LO(v[1].y)) + (LO(v[2].y) + LO(v[3].y)); f[3] = (HI(v[0].y) + HI(v[1].y)) + (HI(v[2].y) + HI(v[3].y));
                    f[4] = (LO(v[0].z) + LO(v[1].z)) + (LO(v[2].z) + LO(v[3].z)); f[5] = (HI(v[0].z) + HI(v[1].z)) + (HI(v[2].z) + HI(v[3].z));
                    f[6] = (LO(v[0].w) + LO(v[1].w)) + (LO(v[2].w) + LO(v[3].w)); f[7] = (HI(v[0].w) + HI(v[1].w)) + (HI(v[2].w) + HI(v[3].w));
                    const bool b4 = t & 16, b3 = t & 8;
                    float g4[4], g2[2];
#pragma unroll
                    for (int i = 0; i < 4; i++) g4[i] = (b4 ? f[4 + i] : f[i]) + __shfl_xor_sync(0xffffffffu, b4 ? f[i] : f[4 + i], 16);
#pragma unroll
                    for (int i = 0; i < 2; i++) g2[i] = (b3 ? g4[2 + i] : g4[i]) + __shfl_xor_sync(0xffffffffu, b3 ? g4[i] : g4[2 + i], 8);
                    g2[0] += __shfl_xor_sync(0xffffffffu, g2[0], 4);
                    g2[1] += __shfl_xor_sync(0xffffffffu, g2[1], 4);
                    st_strong4(wp, pack_nz(g2[0], g2[1]));
                }
                PROF3(8, n); (void)n;
            }
            t_o += D2_BASE + DQ + D3 + (t >> 5) * D2_STEP;
            OPAQUE(t);
            PROF(12);
            {
                const uint32_t* rp = &g_mem[(s + 1) & 3][((t >> 5) * 256 + (t & 31)) * 4];
                const uint32_t da = sb + R_RING + ((t >> 5) * 256 + (t & 31)) * 16;
                uint4 v[8];
                spin_until(t_o);
                PROF3(2, clk32());
                uint32_t n = poll_set<8>(v, rp, 128, PH3 + (t >> 5) * PHQ);
                PROF(13);
                PROF3(3, clk32()); PROF3(9, n); (void)n;
                mbar_wait(bar + 8 * B_AFREE0 + (t >> 6) * 8, (s + 1) & 1);
                PROF3(4, clk32());
#pragma unroll
                for (int i = 0; i < 8; i++) sts128(da + i * 512, v[i]);
                if (t >= 64) fence_async();
                __syncwarp();
                e_arrive(bar + 8 * B_MEM + (t >> 5) * 8);
                PROF(14);
                PROF3(5, clk32());
            }
            CLEAR(s + 3);
        }
}

__global__ void __launch_bounds__(384, 1) r_kernel(const __grid_constant__ RMaps tm, const bf16* __restrict__ mem0, const bf16* __restrict__ x, const bf16* __restrict__ gate_w) {
    extern __shared__ __align__(1024) unsigned char smem_raw[];
    const uint32_t sb = smem_u32(smem_raw);
    if ((sb & 0x3FFFFu) != SB0) __trap();
    const int tid = threadIdx.x;
    const int wid = __shfl_sync(0xffffffffu, tid >> 5, 0);
    uint32_t role; asm("mov.u32 %0, %%cluster_ctarank;" : "=r"(role));
    int h; asm("mov.u32 %0, %%clusterid.x;" : "=r"(h));
    const uint32_t bar = sb + R_BAR;
    asm volatile("griddepcontrol.launch_dependents;");
    KT(0, 0);
    const int gr = blockIdx.x * 12 + wid;
    uint4 gx0[4], gx1[4], gw[4];
#pragma unroll
    for (int i = 0; i < 4; i++) {
        gx0[i] = ldg_nc((const uint4*)(x + gr * DM) + i * 32 + (tid & 31));
        gx1[i] = ldg_nc((const uint4*)(x + min(gr + 1152, SEQ - 1) * DM) + i * 32 + (tid & 31));
        gw[i] = ldg_nc((const uint4*)gate_w + i * 32 + (tid & 31));
    }

    if (tid == 0) {
        for (int i = 0; i < 5; i++) mbar_init(bar + 8 * (B_FULL + i), 1);
        for (int i = 0; i < 3; i++) mbar_init(bar + 8 * (B_EMPTY + i), 2);
        for (int i = 0; i < 4; i++) mbar_init(bar + 8 * (B_MEM + i), 1);
        mbar_init(bar + 8 * B_HOP1, role == 2 ? 1 : 9);
        mbar_init(bar + 8 * B_HOPV, role == 2 ? 8 : 1);
        mbar_init(bar + 8 * B_XT, 1);
        mbar_init(bar + 8 * B_TFREE, 5);
        mbar_init(bar + 8 * B_P, 4);
        mbar_init(bar + 8 * B_XDONE, 8);
        mbar_init(bar + 8 * B_OST0, 4);
        mbar_init(bar + 8 * B_OST1, 4);
        mbar_init(bar + 8 * B_XRECV, 2);
        mbar_init(bar + 8 * B_O, 4);
        mbar_init(bar + 8 * B_AFREE0, 2);
        mbar_init(bar + 8 * B_AFREE1, 2);
        mbar_init(bar + 8 * B_PRO0, 1);
        mbar_init(bar + 8 * B_PRO1, 8);
        asm volatile("fence.mbarrier_init.release.cluster;" ::: "memory");
        fence_async();
        mbar_expect(bar + 8 * B_PRO0, KR * 4096);
        for (int i = 0; i < 3; i++) mbar_expect(bar + 8 * (B_FULL + i), 8192);
        mbar_expect(bar + 8 * B_HOP1, role == 2 ? 4096 : 2048);
        if (role != 2) mbar_expect(bar + 8 * B_HOPV, 2048);
        mbar_expect(bar + 8 * B_XT, role == 0 ? 2 * CPB : CPB);
    }
    __syncthreads();
    asm volatile("barrier.cluster.arrive.relaxed.aligned;" ::: "memory");
    {
        const CUtensorMap* tw = &tm.w[role];
        if (wid < 11) {
            e_tma_load(sb + wid * 16384, tw, h * DH, KC(wid), bar + 8 * B_PRO0);
            e_tma_load(sb + wid * 16384 + 8192, tw, h * DH + 64, KC(wid), bar + 8 * B_PRO0);
        }
        if (wid < 6) e_tma_load(sb + R_RING + wid * 4096, &tm.x, XC(wid), 0, bar + 8 * (B_FULL + (wid >> 1)));
        if ((tid & 31) == 0) {
            if (wid < 10) tma_prefetch(tw, h * DH + (wid & 1) * 64, KC(KR / 4 + (wid >> 1)));
            if (wid >= 6 && wid - 6 < (role == 0 ? 4 : 6)) tma_prefetch(&tm.wo, wo_tile(role, wid - 6) * 64, h * DH);
        }
        __syncwarp();
        const uint32_t g0 = __float_as_uint(gate_row(gx0, gw)), g1 = __float_as_uint(gate_row(gx1, gw));
        if ((tid & 31) == 0) {
            st_strong4(&g_gate[gr], g0 ? g0 : 0x80000000u);
            if (gr + 1152 < SEQ) st_strong4(&g_gate[gr + 1152], g1 ? g1 : 0x80000000u);
        }
        __syncwarp();
    }
    asm volatile("barrier.cluster.wait.aligned;" ::: "memory");

    if (wid < 8) {
        asm volatile("setmaxnreg.inc.sync.aligned.u32 224;");
        if (role == 0) r_big<0>(tm, wid); else if (role == 1) r_big<1>(tm, wid); else r_big<2>(tm, wid);
    } else {
        asm volatile("setmaxnreg.dec.sync.aligned.u32 56;");
        if (role == 0) r_chain<0>(tm, mem0, wid); else if (role == 1) r_chain<1>(tm, mem0, wid); else r_chain<2>(tm, mem0, wid);
    }
    __syncwarp();
    asm volatile("barrier.cluster.arrive; barrier.cluster.wait;" ::: "memory");
    KT(0, 1);
}

#define STAG 2
constexpr int G_ST = 4;
constexpr int G_STAGE = 16384 + 32768;
constexpr int G_EPI = G_ST * G_STAGE;
constexpr int G_GATE = G_EPI + 32768;
constexpr int G_BAR = G_GATE + 1024;
constexpr int G_SMEM = G_BAR + 128 + 1024;

struct G1Maps { CUtensorMap x, wg, wu, hs, o, h, wo, wd, out; };
constexpr int G1_NB = FF / 128;
constexpr int G1_TILES = 16 * G1_NB;

DEVINL void g_mma_block(float* d, uint32_t sb, uint32_t bar, int it, int wg, int tid, bool first) {
    const int st = it % G_ST;
    mbar_wait(bar + 8 * st, (it / G_ST) & 1);
    const uint64_t da = mkdesc(sb + st * G_STAGE + wg * 8192, 16, 1024, 1);
    const uint64_t db = mkdesc(sb + st * G_STAGE + 16384, 8192, 1024, 1);
    wg_fence();
#pragma unroll
    for (int k = 0; k < 4; k++) wg_ss256(d, da + (uint64_t)(k * 2), db + (uint64_t)(k * 128), (first ? 0 : 1) | k);
    wg_commit();
    if (!first) { wg_wait<1>(); if ((tid & 127) == 0) mbar_arrive(bar + 8 * (G_ST + (it - 1) % G_ST)); }
}
DEVINL void g_load_block(uint32_t sb, uint32_t bar, int it, const CUtensorMap* ta, int k0, int m0, const CUtensorMap* tb, int n0) {
    const int st = it % G_ST;
    mbar_wait(bar + 8 * (G_ST + st), ((it / G_ST) & 1) ^ 1);
    const uint32_t fb = bar + 8 * st, sa = sb + st * G_STAGE;
    mbar_expect(fb, G_STAGE);
    tma_load(sa, ta, k0, m0, fb);
#pragma unroll
    for (int q = 0; q < 4; q++) tma_load(sa + 16384 + q * 8192, tb, n0 + q * 64, k0, fb);
}

DEVINL void g_store_tile(const float* d, const CUtensorMap* tout, uint32_t epi, int mb, int nb, int wg, int tid) {
    const int lane = tid & 31, row = ((tid >> 5) & 3) * 16 + ((lane >> 3) & 1) * 8 + (lane & 7);
#pragma unroll
    for (int half = 0; half < 2; half++) {
        if ((tid & 127) == 0) bulk_wait_read();
        bar_sync(1 + wg, 128);
#pragma unroll
        for (int j = 0; j < 16; j += 2) {
            const float* e = d + half * 64 + 4 * j;
            const int cgp = j + (lane >> 4);
            stsm4(epi + (cgp >> 3) * 8192 + row * 128 + (((cgp & 7) ^ (row & 7)) << 4),
                  pack_bf16(e[0], e[1]), pack_bf16(e[2], e[3]), pack_bf16(e[4], e[5]), pack_bf16(e[6], e[7]));
        }
        fence_async();
        bar_sync(1 + wg, 128);
        if ((tid & 127) == 0) {
            tma_store(tout, epi, nb * 256 + half * 128, mb * 128 + wg * 64);
            tma_store(tout, epi + 8192, nb * 256 + half * 128 + 64, mb * 128 + wg * 64);
            bulk_commit();
        }
    }
}
template <int NS> DEVINL void g_split_finish(const float* d, float4 (&r)[32 / NS], float4* sk, int tile, int ks, bf16* __restrict__ out, int tid) {
    constexpr int Q = 32 / NS;
    float4* mine = sk + ks * (32 * 256) + tid;
#pragma unroll
    for (int c = 0; c < NS; c++) {
        if (c != ks) {
#pragma unroll
            for (int q = c * Q; q < c * Q + Q; q++) __stcg(mine + q * 256, make_float4(d[4 * q], d[4 * q + 1], d[4 * q + 2], d[4 * q + 3]));
        } else {
#pragma unroll
            for (int q = 0; q < Q; q++) { const float* e = d + (c * Q + q) * 4; r[q].x += e[0]; r[q].y += e[1]; r[q].z += e[2]; r[q].w += e[3]; }
        }
    }
    __threadfence();
    bar_sync(3, 256);
    if (tid == 0) {
        atomicAdd(&g_skcnt[tile], 1u);
        uint32_t v, n = 0;
        do {
            asm volatile("ld.acquire.gpu.global.u32 %0, [%1];" : "=r"(v) : "l"(&g_skcnt[tile]) : "memory");
            if (++n > 200000000u) __trap();
        } while (v < NS);
        if (atomicAdd(&g_skcnt[tile], 1u) == 2 * NS - 1) g_skcnt[tile] = 0u;
    }
    bar_sync(3, 256);
#pragma unroll
    for (int c = 1; c < NS; c++) {
        const float4* th = sk + (((ks + c) & (NS - 1)) * 32 + ks * Q) * 256 + tid;
#pragma unroll
        for (int q = 0; q < Q; q++) { const float4 u = __ldcg(th + q * 256); r[q].x += u.x; r[q].y += u.y; r[q].z += u.z; r[q].w += u.w; }
    }
    const int lane = tid & 31;
    uint32_t* op = (uint32_t*)(out + ((tile >> 2) * 128 + (tid >> 5) * 16 + (lane >> 2)) * DM + (tile & 3) * 256 + ks * Q * 8 + (lane & 3) * 2);
#pragma unroll
    for (int q = 0; q < Q; q++) { op[q * 4] = pack_bf16(r[q].x, r[q].y); op[q * 4 + 4 * DM] = pack_bf16(r[q].z, r[q].w); }
}
DEVINL int g1_count(int pass) { return pass == 0 ? NPRE : pass == 1 ? NFULL : pass == 2 ? T_MID - NFULL : (T_LATE - T_MID) * 8; }
DEVINL int g1_first(int pass) { return pass >= 2 ? (int)(gridDim.x - 1 - blockIdx.x) : (int)blockIdx.x; }
constexpr int H_EARLY = 26;

__global__ void __launch_bounds__(384, 1) g1_kernel(const __grid_constant__ G1Maps tm, bf16* __restrict__ out) {
    extern __shared__ __align__(1024) unsigned char smem_raw[];
    const uint32_t sb = (smem_u32(smem_raw) + 1023) & ~1023u;
    const int tid = threadIdx.x, lane = tid & 31;
    const int wg = __shfl_sync(0xffffffffu, tid >> 7, 0);
    const int warp = __shfl_sync(0xffffffffu, (tid >> 5) & 3, 0);
    const uint32_t bar = sb + G_BAR;
    asm volatile("griddepcontrol.launch_dependents;");
    KT(1, 0);
    if (tid == 0) {
        for (int i = 0; i < G_ST; i++) { mbar_init(bar + 8 * i, 1); mbar_init(bar + 8 * (G_ST + i), 2); }
        fence_async();
    }
    __syncthreads();
    if (wg == 2) {
        asm volatile("setmaxnreg.dec.sync.aligned.u32 40;");
        if (warp == 0) {
            if (lane == 0) {
                int it = 0;
                for (int tile = blockIdx.x; tile < G1_TILES; tile += gridDim.x) {
                    const int mb = tile & 15, nb = tile >> 4;
                    for (int kb = 0; kb < 16; kb++, it++) {
                        const int st = it % G_ST;
                        mbar_wait(bar + 8 * (G_ST + st), ((it / G_ST) & 1) ^ 1);
                        const uint32_t fb = bar + 8 * st, sa = sb + st * G_STAGE;
                        mbar_expect(fb, G_STAGE);
                        tma_load(sa, &tm.x, kb * 64, mb * 128, fb);
                        tma_load(sa + 16384, &tm.wg, nb * 128, kb * 64, fb);
                        tma_load(sa + 16384 + 8192, &tm.wg, nb * 128 + 64, kb * 64, fb);
                        tma_load(sa + 16384 + 16384, &tm.wu, nb * 128, kb * 64, fb);
                        tma_load(sa + 16384 + 24576, &tm.wu, nb * 128 + 64, kb * 64, fb);
                    }
                }
                for (int pass = 0; pass < 4; pass++) {
                    for (int i = g1_first(pass); i < g1_count(pass); i += gridDim.x) {
                        const int tile = pass == 1 ? i : pass == 3 ? T_MID + (i >> 3) : NFULL + i, mb = tile >> 2, nb = tile & 3;
                        if (pass < 2) {
                            for (int kb = 0; kb < FF / 64; kb++, it++) {
                                if (kb == 0 || kb == 2 * H_EARLY) {
                                    wait_count(&g_hcnt[kb ? 16 + mb : mb], kb ? 2 * (G1_NB - H_EARLY) : 2 * H_EARLY);
                                    asm volatile("fence.proxy.async;" ::: "memory");
                                }
                                g_load_block(sb, bar, it, &tm.h, kb * 64, mb * 128, &tm.wd, nb * 256);
                            }
                        }
                        if (pass > 0) {
                            const int k0 = pass == 3 ? (i & 7) * 8 : 0, k1 = pass == 3 ? k0 + 8 : HD / 64;
                            wait_count(&g_ocnt[mb], NH * 4);
                            asm volatile("fence.proxy.async;" ::: "memory");
                            for (int kb = k0; kb < k1; kb++, it++) g_load_block(sb, bar, it, &tm.o, kb * 64, mb * 128, &tm.wo, nb * 256);
                        }
                    }
                }
            }
        }
    } else {
        asm volatile("setmaxnreg.inc.sync.aligned.u32 232;");
        float d[128];
        int it = 0;
        const uint32_t epi = sb + G_EPI + wg * 16384;
        const int row = warp * 16 + ((lane >> 3) & 1) * 8 + (lane & 7);
        for (int tile = blockIdx.x; tile < G1_TILES; tile += gridDim.x) {
            const int mb = tile & 15, nb = tile >> 4;
            const uint32_t* gp = &g_gate[mb * 128 + wg * 64 + warp * 16 + (lane >> 2)];
            uint32_t u0 = ld_strong4(gp), u1 = ld_strong4(gp + 8);
            for (int kb = 0; kb < 16; kb++, it++) {
                if (it == (wg ? 0 : STAG)) bar_sync(4, 256);
                g_mma_block(d, sb, bar, it, wg, tid, kb == 0);
            }
            wg_wait<0>();
            for (uint32_t n = 0; u0 == 0u || u1 == 0u; n++) { u0 = ld_strong4(gp); u1 = ld_strong4(gp + 8); if (n > 20000000u) __trap(); }
            __syncwarp();
            const float s0 = 1.0f - __uint_as_float(u0), s1 = 1.0f - __uint_as_float(u1);
            if ((tid & 127) == 0) {
                mbar_arrive(bar + 8 * (G_ST + (it - 1) % G_ST));
                bulk_wait_all();
                const int pt = tile - (int)gridDim.x;
                if (pt >= 0) atomicAdd(&g_hcnt[(pt & 15) + ((pt >> 4) >= H_EARLY ? 16 : 0)], 1u);
            }
            bar_sync(1 + wg, 128);
#pragma unroll
            for (int j = 0; j < 16; j += 2) {
                uint32_t p[4];
#pragma unroll
                for (int q = 0; q < 4; q++) {
                    const int i = (j + (q >> 1)) * 4 + (q & 1) * 2;
                    const float sc = (q & 1) ? s1 : s0;
                    const float g0 = d[i], g1 = d[i + 1];
                    const float h0 = (g0 * rcp(1.0f + ex2(g0 * -1.4426950408889634f))) * (d[64 + i] * sc);
                    const float h1 = (g1 * rcp(1.0f + ex2(g1 * -1.4426950408889634f))) * (d[64 + i + 1] * sc);
                    p[q] = pack_bf16(h0, h1);
                }
                const int cgp = j + (lane >> 4);
                stsm4(epi + (cgp >> 3) * 8192 + row * 128 + (((cgp & 7) ^ (row & 7)) << 4), p[0], p[1], p[2], p[3]);
            }
            fence_async();
            bar_sync(1 + wg, 128);
            if ((tid & 127) == 0) {
                tma_store(&tm.hs, epi, nb * 128, mb * 128 + wg * 64);
                tma_store(&tm.hs, epi + 8192, nb * 128 + 64, mb * 128 + wg * 64);
                bulk_commit();
            }
        }
        if ((tid & 127) == 0) {
            bulk_wait_all();
            const int pt = blockIdx.x + (G1_TILES - 1 - blockIdx.x) / gridDim.x * gridDim.x;
            atomicAdd(&g_hcnt[(pt & 15) + ((pt >> 4) >= H_EARLY ? 16 : 0)], 1u);
        }
        for (int pass = 0; pass < 4; pass++) {
            for (int i = g1_first(pass); i < g1_count(pass); i += gridDim.x) {
                const int tile = pass == 1 ? i : pass == 3 ? T_MID + (i >> 3) : NFULL + i;
                const int nkb = pass == 0 ? FF / 64 : pass == 1 ? (FF + HD) / 64 : pass == 2 ? HD / 64 : 8;
                for (int kb = 0; kb < nkb; kb++, it++) g_mma_block(d, sb, bar, it, wg, tid, kb == 0);
                wg_wait<0>();
                if ((tid & 127) == 0) mbar_arrive(bar + 8 * (G_ST + (it - 1) % G_ST));
                float4* pre = g_pre + (tile - NFULL) * (32 * 256) + tid;
                if (pass >= 2) { if ((tid & 31) == 0) wait_count(&g_pcnt[tile], 8); __syncwarp(); }
                if (pass == 0) {
#pragma unroll
                    for (int q = 0; q < 32; q++) __stcg(pre + q * 256, make_float4(d[4 * q], d[4 * q + 1], d[4 * q + 2], d[4 * q + 3]));
                    __threadfence();
                    __syncwarp();
                    if ((tid & 31) == 0) atomicAdd(&g_pcnt[tile], 1u);
                } else if (pass == 3) {
                    float4 r[4];
#pragma unroll
                    for (int q = 0; q < 4; q++) r[q] = __ldcg(pre + ((i & 7) * 4 + q) * 256);
                    g_split_finish<8>(d, r, g_sk + (tile - T_MID) * 8 * (32 * 256), tile, i & 7, out, tid);
                } else {
                    if (pass == 2) {
#pragma unroll
                        for (int q = 0; q < 32; q++) {
                            const float4 u = __ldcg(pre + q * 256); d[4 * q] += u.x; d[4 * q + 1] += u.y; d[4 * q + 2] += u.z; d[4 * q + 3] += u.w;
                            if ((q & 7) == 7) __syncwarp();
                        }
                    }
                    g_store_tile(d, &tm.out, epi, tile >> 2, tile & 3, wg, tid);
                }
            }
        }
        if ((tid & 127) == 0) bulk_wait_all();
        KT(1, 1);
    }
    __syncwarp();
    asm volatile("griddepcontrol.wait;" ::: "memory");
}

struct G2Maps { CUtensorMap o, wo; };

__global__ void __launch_bounds__(384, 1) g2_kernel(const __grid_constant__ G2Maps tm, bf16* __restrict__ out) {
    extern __shared__ __align__(1024) unsigned char smem_raw[];
    const uint32_t sb = (smem_u32(smem_raw) + 1023) & ~1023u;
    const int tid = threadIdx.x, lane = tid & 31;
    const int wg = __shfl_sync(0xffffffffu, tid >> 7, 0);
    const int warp = __shfl_sync(0xffffffffu, (tid >> 5) & 3, 0);
    const uint32_t bar = sb + G_BAR;
    const int ks = blockIdx.x & 7, tile = T_LATE + (blockIdx.x >> 3), nb = tile & 3, mb = tile >> 2;
    KT(2, 0);
    if (tid == 0) {
        for (int i = 0; i < G_ST; i++) { mbar_init(bar + 8 * i, 1); mbar_init(bar + 8 * (G_ST + i), 2); }
        fence_async();
        for (int it = 0; it < G_ST; it++) mbar_expect(bar + 8 * it, G_STAGE);
    }
    __syncthreads();
    if (tid < 256 && (tid & 7) == 0) {
        const int it = tid >> 5, q = (tid >> 3) & 3;
        if (it < G_ST) tma_load(sb + it * G_STAGE + 16384 + q * 8192, &tm.wo, nb * 256 + q * 64, (ks * 8 + it) * 64, bar + 8 * it);
        else tma_prefetch(&tm.wo, nb * 256 + q * 64, (ks * 8 + it) * 64);
    }
    __syncwarp();
    PT(16);
    asm volatile("griddepcontrol.wait;" ::: "memory");
    PT(17);
    if (wg == 2) {
        asm volatile("setmaxnreg.dec.sync.aligned.u32 40;");
        if (lane == 0) tma_load(sb + warp * G_STAGE, &tm.o, (ks * 8 + warp) * 64, mb * 128, bar + 8 * warp);
        if (warp == 0 && lane == 0) {
            for (int it = G_ST; it < 8; it++) g_load_block(sb, bar, it, &tm.o, (ks * 8 + it) * 64, mb * 128, &tm.wo, nb * 256);
        } else if (warp == 1) {
            if (blockIdx.x < SEQ / 32) g_gate[blockIdx.x * 32 + lane] = 0u;
            if (blockIdx.x == 0) { if (lane < 16) g_ocnt[lane] = 0u; g_hcnt[lane] = 0u; g_pcnt[lane] = 0u; g_pcnt[32 + lane] = 0u; }
        }
    } else {
        asm volatile("setmaxnreg.inc.sync.aligned.u32 232;");
        float d[128];
        float4 r[4];
        const float4* pre = g_pre + ((tile - NFULL) * 32 + ks * 4) * 256 + tid;
#pragma unroll
        for (int q = 0; q < 4; q++) r[q] = __ldcg(pre + q * 256);
        for (int it = 0; it < 8; it++) { g_mma_block(d, sb, bar, it, wg, tid, it == 0); if (it == 0) PT(18); }
        wg_wait<0>();
        PT(19);
        g_split_finish<8>(d, r, g_sk + (tile - T_MID) * 8 * (32 * 256), tile, ks, out, tid);
        KT(2, 1);
    }
}

typedef CUresult (*EncodeFn)(CUtensorMap*, CUtensorMapDataType, cuuint32_t, void*, const cuuint64_t*, const cuuint64_t*, const cuuint32_t*,
                             const cuuint32_t*, CUtensorMapInterleave, CUtensorMapSwizzle, CUtensorMapL2promotion, CUtensorMapFloatOOBfill);

static void make_map(EncodeFn enc, CUtensorMap* m, const void* ptr, uint64_t rows, uint64_t cols, uint32_t box_rows) {
    cuuint64_t dims[2] = {cols, rows};
    cuuint64_t strides[1] = {cols * 2};
    cuuint32_t box[2] = {64, box_rows};
    cuuint32_t es[2] = {1, 1};
    enc(m, CU_TENSOR_MAP_DATA_TYPE_BFLOAT16, 2, (void*)ptr, dims, strides, box, es, CU_TENSOR_MAP_INTERLEAVE_NONE,
        CU_TENSOR_MAP_SWIZZLE_128B, CU_TENSOR_MAP_L2_PROMOTION_L2_256B, CU_TENSOR_MAP_FLOAT_OOB_FILL_NONE);
}

extern "C" void kernel_launch(void* const* d_in, const int* in_sizes, int n_in, void* d_out, int out_size) {
    (void)in_sizes; (void)n_in; (void)out_size;
    const bf16* x = (const bf16*)d_in[0];
    const bf16* mem0 = (const bf16*)d_in[1];
    const bf16* gate_w = (const bf16*)d_in[11];
    static EncodeFn enc = nullptr;
    static int n_sm = 0;
    static void *pO = nullptr, *pH = nullptr;
    if (!enc) {
        void* fn = nullptr;
        cudaDriverEntryPointQueryResult qr;
        cudaGetDriverEntryPoint("cuTensorMapEncodeTiled", &fn, cudaEnableDefault, &qr);
        enc = (EncodeFn)fn;
        cudaDeviceGetAttribute(&n_sm, cudaDevAttrMultiProcessorCount, 0);
        cudaFuncSetAttribute(r_kernel, cudaFuncAttributeMaxDynamicSharedMemorySize, R_SMEM);
        cudaFuncSetAttribute(g1_kernel, cudaFuncAttributeMaxDynamicSharedMemorySize, G_SMEM);
        cudaFuncSetAttribute(g2_kernel, cudaFuncAttributeMaxDynamicSharedMemorySize, G_SMEM);
        cudaGetSymbolAddress(&pO, g_O);
        cudaGetSymbolAddress(&pH, g_H);
    }
    RMaps rm; G1Maps m1; G2Maps m2;
    make_map(enc, &rm.x, x, SEQ, DM, 32);
    for (int i = 0; i < 3; i++) make_map(enc, &rm.w[i], d_in[2 + i], DM, HD, 64);
    make_map(enc, &rm.wo, d_in[5], HD, DM, 128);
    make_map(enc, &rm.o, pO, SEQ, HD, 16);
    make_map(enc, &m1.x, x, SEQ, DM, 128);
    make_map(enc, &m1.wg, d_in[8], DM, FF, 64);
    make_map(enc, &m1.wu, d_in[9], DM, FF, 64);
    make_map(enc, &m1.hs, pH, SEQ, FF, 64);
    make_map(enc, &m1.o, pO, SEQ, HD, 128);
    make_map(enc, &m1.h, pH, SEQ, FF, 128);
    make_map(enc, &m1.wo, d_in[5], HD, DM, 64);
    make_map(enc, &m1.wd, d_in[10], FF, DM, 64);
    make_map(enc, &m1.out, d_out, SEQ, DM, 64);
    m2.o = m1.o; m2.wo = m1.wo;

    cudaStream_t st = cudaStreamPerThread;
    {
        cudaLaunchConfig_t cfg = {};
        cfg.gridDim = dim3(96); cfg.blockDim = dim3(384); cfg.dynamicSmemBytes = R_SMEM; cfg.stream = st;
        cudaLaunchAttribute at[1];
        at[0].id = cudaLaunchAttributeClusterDimension; at[0].val.clusterDim.x = 3; at[0].val.clusterDim.y = 1; at[0].val.clusterDim.z = 1;
        cfg.attrs = at; cfg.numAttrs = 1;
        cudaLaunchKernelEx(&cfg, r_kernel, rm, mem0, x, gate_w);
    }
    {
        cudaLaunchConfig_t cfg = {};
        cfg.gridDim = dim3(n_sm - 96); cfg.blockDim = dim3(384); cfg.dynamicSmemBytes = G_SMEM; cfg.stream = st;
        cudaLaunchAttribute at[1];
        at[0].id = cudaLaunchAttributeProgrammaticStreamSerialization; at[0].val.programmaticStreamSerializationAllowed = 1;
        cfg.attrs = at; cfg.numAttrs = 1;
        cudaLaunchKernelEx(&cfg, g1_kernel, m1, (bf16*)d_out);
    }
    {
        cudaLaunchConfig_t cfg = {};
        cfg.gridDim = dim3((64 - T_LATE) * 8); cfg.blockDim = dim3(384); cfg.dynamicSmemBytes = G_SMEM; cfg.stream = st;
        cudaLaunchAttribute at[1];
        at[0].id = cudaLaunchAttributeProgrammaticStreamSerialization; at[0].val.programmaticStreamSerializationAllowed = 1;
        cfg.attrs = at; cfg.numAttrs = 1;
        cudaLaunchKernelEx(&cfg, g2_kernel, m2, (bf16*)d_out);
    }
}
```

```cpp
#include <cuda_runtime.h>
#include <cuda_bf16.h>
#include <cuda.h>
#include <stdint.h>

typedef __nv_bfloat16 bf16;

constexpr int SEQ = 2048, DM = 1024, NH = 32, DH = 128, NMEM = 8, SEG = 32, NSEG = 64, FF = 3584;
constexpr int HD = NH * DH;

__device__ bf16 g_O[SEQ * HD];
__device__ bf16 g_H[SEQ * FF];
__device__ uint32_t g_gate[SEQ];
__device__ uint32_t g_part[4][128 * 32 * 32];
__device__ uint32_t g_mem[4][DM * 4];
constexpr int NFULL = 36, T_MID = 44, T_LATE = 48;
constexpr int NPRE = 64 - NFULL;
__device__ float4 g_pre[NPRE * 32 * 256];
__device__ uint4 g_sk[(64 - T_MID) * 8 * 16 * 256];
__device__ uint32_t g_skcnt[64], g_pcnt[64];
__device__ uint32_t g_hcnt[32], g_ocnt[16];
#define KT(k, i)
#define PT(i)

#define DEVINL __device__ __forceinline__
constexpr long long SPIN_LIMIT = 4000000000LL;

DEVINL uint32_t smem_u32(const void* p) { return (uint32_t)__cvta_generic_to_shared(p); }
DEVINL void mbar_init(uint32_t bar, uint32_t cnt) { asm volatile("mbarrier.init.shared::cta.b64 [%0], %1;" ::"r"(bar), "r"(cnt) : "memory"); }
DEVINL void mbar_arrive(uint32_t bar) { asm volatile("mbarrier.arrive.shared::cta.b64 _, [%0];" ::"r"(bar) : "memory"); }
DEVINL void mbar_expect(uint32_t bar, uint32_t bytes) { asm volatile("mbarrier.arrive.expect_tx.shared::cta.b64 _, [%0], %1;" ::"r"(bar), "r"(bytes) : "memory"); }
DEVINL void mbar_arrive_remote(uint32_t cbar) { asm volatile("mbarrier.arrive.relaxed.cluster.shared::cluster.b64 _, [%0];" ::"r"(cbar) : "memory"); }
DEVINL bool mbar_try(uint32_t bar, uint32_t par) {
    uint32_t ok;
    asm volatile("{ .reg .pred p; mbarrier.try_wait.parity.shared::cta.b64 p, [%1], %2; selp.u32 %0, 1, 0, p; }" : "=r"(ok) : "r"(bar), "r"(par) : "memory");
    return ok;
}
__device__ __noinline__ void mbar_wait_slow(uint32_t bar, uint32_t par) {
    long long t0 = clock64();
    while (!mbar_try(bar, par)) { if (clock64() - t0 > SPIN_LIMIT) __trap(); }
}
DEVINL void mbar_wait(uint32_t bar, uint32_t par) {
    uint32_t n = 0;
    while (!mbar_try(bar, par)) { if (++n > 200000000u) __trap(); }
}
DEVINL uint32_t mapa(uint32_t a, uint32_t r) { uint32_t o; asm volatile("mapa.shared::cluster.u32 %0, %1, %2;" : "=r"(o) : "r"(a), "r"(r)); return o; }
DEVINL void fence_async() { asm volatile("fence.proxy.async.shared::cta;" ::: "memory"); }
DEVINL void bar_sync(int id, int n) { asm volatile("bar.sync %0, %1;" ::"r"(id), "r"(n) : "memory"); }
DEVINL void cluster_sync() { asm volatile("barrier.cluster.arrive.aligned; barrier.cluster.wait.aligned;" ::: "memory"); }
DEVINL void tma_load(uint32_t dst, const CUtensorMap* tm, int c0, int c1, uint32_t bar) {
    asm volatile("cp.async.bulk.tensor.2d.shared::cluster.global.mbarrier::complete_tx::bytes [%0], [%1, {%3, %4}], [%2];"
                 ::"r"(dst), "l"(tm), "r"(bar), "r"(c0), "r"(c1) : "memory");
}
DEVINL void tma_prefetch(const CUtensorMap* tm, int c0, int c1) {
    asm volatile("cp.async.bulk.prefetch.tensor.2d.L2.global [%0, {%1, %2}];" ::"l"(tm), "r"(c0), "r"(c1) : "memory");
}
DEVINL void tma_store(const CUtensorMap* tm, uint32_t src, int c0, int c1) {
    asm volatile("cp.async.bulk.tensor.2d.global.shared::cta.bulk_group [%0, {%2, %3}], [%1];" ::"l"(tm), "r"(src), "r"(c0), "r"(c1) : "memory");
}
DEVINL void bulk_commit() { asm volatile("cp.async.bulk.commit_group;" ::: "memory"); }
DEVINL void bulk_wait_read() { asm volatile("cp.async.bulk.wait_group.read 0;" ::: "memory"); }
DEVINL void bulk_wait_all() { asm volatile("cp.async.bulk.wait_group 0;" ::: "memory"); }
DEVINL void bulk_s2s(uint32_t cdst, uint32_t src, uint32_t bytes, uint32_t cbar) {
    asm volatile("cp.async.bulk.shared::cluster.shared::cta.mbarrier::complete_tx::bytes [%0], [%1], %2, [%3];" ::"r"(cdst), "r"(src), "r"(bytes), "r"(cbar) : "memory");
}
DEVINL void st_async16(uint32_t cdst, uint4 v, uint32_t cbar) {
    asm volatile("st.async.shared::cluster.mbarrier::complete_tx::bytes.v4.b32 [%0], {%1,%2,%3,%4}, [%5];" ::"r"(cdst), "r"(v.x), "r"(v.y), "r"(v.z), "r"(v.w), "r"(cbar) : "memory");
}
DEVINL uint64_t mkdesc(uint32_t addr, uint32_t lbo, uint32_t sbo, uint32_t swz) {
    return (uint64_t)((addr & 0x3FFFF) >> 4) | ((uint64_t)(lbo >> 4) << 16) | ((uint64_t)(sbo >> 4) << 32) | ((uint64_t)swz << 62);
}
constexpr uint32_t SB0 = 1024;
__host__ __device__ constexpr uint64_t cdesc(uint32_t off, uint32_t lbo, uint32_t sbo, uint32_t swz) {
    return (uint64_t)(((SB0 + off) & 0x3FFFF) >> 4) | ((uint64_t)(lbo >> 4) << 16) | ((uint64_t)(sbo >> 4) << 32) | ((uint64_t)swz << 62);
}
DEVINL float rcp(float x) { float y; asm("rcp.approx.ftz.f32 %0, %1;" : "=f"(y) : "f"(x)); return y; }
DEVINL float ex2(float x) { float y; asm("ex2.approx.ftz.f32 %0, %1;" : "=f"(y) : "f"(x)); return y; }
DEVINL void spin_clk(int d) { uint32_t t0, t1; asm volatile("mov.u32 %0, %%clock;" : "=r"(t0)); do { asm volatile("mov.u32 %0, %%clock;" : "=r"(t1)); } while ((int)(t1 - t0) < d); }
#define PROBE_GAP 150
#define OPAQUE(x) asm volatile("" : "+r"(x))
DEVINL void wg_fence() { asm volatile("wgmma.fence.sync.aligned;" ::: "memory"); }
DEVINL void wg_commit() { asm volatile("wgmma.commit_group.sync.aligned;" ::: "memory"); }
template <int N> DEVINL void wg_wait() { asm volatile("wgmma.wait_group.sync.aligned %0;" ::"n"(N) : "memory"); }
DEVINL uint32_t pack_bf16(float lo, float hi) { uint32_t r; asm("cvt.rn.bf16x2.f32 %0, %1, %2;" : "=r"(r) : "f"(hi), "f"(lo)); return r; }
DEVINL void ldsm4(uint32_t* r, uint32_t a) { asm volatile("ldmatrix.sync.aligned.m8n8.x4.shared.b16 {%0,%1,%2,%3}, [%4];" : "=r"(r[0]), "=r"(r[1]), "=r"(r[2]), "=r"(r[3]) : "r"(a) : "memory"); }
DEVINL void ldsm4t(uint32_t* r, uint32_t a) { asm volatile("ldmatrix.sync.aligned.m8n8.x4.trans.shared.b16 {%0,%1,%2,%3}, [%4];" : "=r"(r[0]), "=r"(r[1]), "=r"(r[2]), "=r"(r[3]) : "r"(a) : "memory"); }
DEVINL void ldsm4t_if(uint32_t* r, uint32_t a, int c) { asm volatile("{ .reg .pred p; setp.ne.s32 p, %5, 0; @p ldmatrix.sync.aligned.m8n8.x4.trans.shared.b16 {%0,%1,%2,%3}, [%4]; }" : "+r"(r[0]), "+r"(r[1]), "+r"(r[2]), "+r"(r[3]) : "r"(a), "r"(c) : "memory"); }
DEVINL void stsm4(uint32_t a, uint32_t r0, uint32_t r1, uint32_t r2, uint32_t r3) { asm volatile("stmatrix.sync.aligned.m8n8.x4.shared.b16 [%0], {%1,%2,%3,%4};" ::"r"(a), "r"(r0), "r"(r1), "r"(r2), "r"(r3) : "memory"); }
DEVINL void stsm4t(uint32_t a, uint32_t r0, uint32_t r1, uint32_t r2, uint32_t r3) { asm volatile("stmatrix.sync.aligned.m8n8.x4.trans.shared.b16 [%0], {%1,%2,%3,%4};" ::"r"(a), "r"(r0), "r"(r1), "r"(r2), "r"(r3) : "memory"); }
DEVINL void sts32(uint32_t a, uint32_t v) { asm volatile("st.shared.b32 [%0], %1;" ::"r"(a), "r"(v) : "memory"); }
DEVINL void sts128(uint32_t a, uint4 v) { asm volatile("st.shared.v4.b32 [%0], {%1,%2,%3,%4};" ::"r"(a), "r"(v.x), "r"(v.y), "r"(v.z), "r"(v.w) : "memory"); }
DEVINL uint4 lds128(uint32_t a) { uint4 v; asm volatile("ld.shared.v4.b32 {%0,%1,%2,%3}, [%4];" : "=r"(v.x), "=r"(v.y), "=r"(v.z), "=r"(v.w) : "r"(a) : "memory"); return v; }
DEVINL uint4 ld_strong16(const void* p) { uint4 v; asm volatile("ld.relaxed.gpu.global.v4.u32 {%0,%1,%2,%3}, [%4];" : "=r"(v.x), "=r"(v.y), "=r"(v.z), "=r"(v.w) : "l"(p) : "memory"); return v; }
DEVINL void st_strong8(void* p, uint32_t a, uint32_t b) { asm volatile("st.relaxed.gpu.global.v2.u32 [%0], {%1,%2};" ::"l"(p), "r"(a), "r"(b) : "memory"); }
DEVINL void st_strong4(void* p, uint32_t a) { asm volatile("st.relaxed.gpu.global.u32 [%0], %1;" ::"l"(p), "r"(a) : "memory"); }
DEVINL void st_strong16(void* p, uint4 v) { asm volatile("st.relaxed.gpu.global.v4.u32 [%0], {%1,%2,%3,%4};" ::"l"(p), "r"(v.x), "r"(v.y), "r"(v.z), "r"(v.w) : "memory"); }
DEVINL uint32_t pack_nz(float lo, float hi) { uint32_t r = pack_bf16(lo, hi); return r == 0u ? 0x8000u : r; }
DEVINL uint32_t min4(uint4 v, uint32_t m) { return __vimin3_u32(__vimin3_u32(v.x, v.y, m), v.z, v.w); }
DEVINL void mma16816(float* d, uint32_t a0, uint32_t a1, uint32_t a2, uint32_t a3, uint32_t b0, uint32_t b1) {
    asm volatile("mma.sync.aligned.m16n8k16.row.col.f32.bf16.bf16.f32 {%0,%1,%2,%3}, {%4,%5,%6,%7}, {%8,%9}, {%0,%1,%2,%3};"
                 : "+f"(d[0]), "+f"(d[1]), "+f"(d[2]), "+f"(d[3]) : "r"(a0), "r"(a1), "r"(a2), "r"(a3), "r"(b0), "r"(b1));
}
DEVINL void mma1688(float* d, uint32_t a0, uint32_t a1, uint32_t b0) {
    asm volatile("mma.sync.aligned.m16n8k8.row.col.f32.bf16.bf16.f32 {%0,%1,%2,%3}, {%4,%5}, {%6}, {%0,%1,%2,%3};"
                 : "+f"(d[0]), "+f"(d[1]), "+f"(d[2]), "+f"(d[3]) : "r"(a0), "r"(a1), "r"(b0));
}
template <int TA, int TB> DEVINL void wg_ss8(float* d, uint64_t da, uint64_t db, int sc) {
    asm volatile("{ .reg .pred p; setp.ne.b32 p, %6, 0; wgmma.mma_async.sync.aligned.m64n8k16.f32.bf16.bf16 {%0,%1,%2,%3}, %4, %5, p, 1, 1, %7, %8; }"
                 : "+f"(d[0]), "+f"(d[1]), "+f"(d[2]), "+f"(d[3]) : "l"(da), "l"(db), "r"(sc), "n"(TA), "n"(TB));
}
template <int TB> DEVINL void wg_rs8(float* d, const uint32_t* a, uint64_t db, int sc) {
    asm volatile("{ .reg .pred p; setp.ne.b32 p, %9, 0; wgmma.mma_async.sync.aligned.m64n8k16.f32.bf16.bf16 {%0,%1,%2,%3}, {%4,%5,%6,%7}, %8, p, 1, 1, %10; }"
                 : "+f"(d[0]), "+f"(d[1]), "+f"(d[2]), "+f"(d[3]) : "r"(a[0]), "r"(a[1]), "r"(a[2]), "r"(a[3]), "l"(db), "r"(sc), "n"(TB));
}
#define ACC16(d) "+f"(d[0]), "+f"(d[1]), "+f"(d[2]), "+f"(d[3]), "+f"(d[4]), "+f"(d[5]), "+f"(d[6]), "+f"(d[7]), "+f"(d[8]), "+f"(d[9]), "+f"(d[10]), "+f"(d[11]), "+f"(d[12]), "+f"(d[13]), "+f"(d[14]), "+f"(d[15])
template <int TA> DEVINL void wg_ss32(float* d, uint64_t da, uint64_t db, int sc) {
    asm volatile("{ .reg .pred p; setp.ne.b32 p, %18, 0; wgmma.mma_async.sync.aligned.m64n32k16.f32.bf16.bf16 {%0,%1,%2,%3,%4,%5,%6,%7,%8,%9,%10,%11,%12,%13,%14,%15}, %16, %17, p, 1, 1, %19, 0; }"
                 : ACC16(d) : "l"(da), "l"(db), "r"(sc), "n"(TA));
}
DEVINL void wg_rs32(float* d, const uint32_t* a, uint64_t db, int sc) {
    asm volatile("{ .reg .pred p; setp.ne.b32 p, %21, 0; wgmma.mma_async.sync.aligned.m64n32k16.f32.bf16.bf16 {%0,%1,%2,%3,%4,%5,%6,%7,%8,%9,%10,%11,%12,%13,%14,%15}, {%16,%17,%18,%19}, %20, p, 1, 1, 0; }"
                 : ACC16(d) : "r"(a[0]), "r"(a[1]), "r"(a[2]), "r"(a[3]), "l"(db), "r"(sc));
}
DEVINL void wg_ss40(float* d, uint64_t da, uint64_t db, int sc) {
    asm volatile("{ .reg .pred p; setp.ne.b32 p, %22, 0; wgmma.mma_async.sync.aligned.m64n40k16.f32.bf16.bf16 {%0,%1,%2,%3,%4,%5,%6,%7,%8,%9,%10,%11,%12,%13,%14,%15,%16,%17,%18,%19}, %20, %21, p, 1, 1, 1, 1; }"
                 : ACC16(d), "+f"(d[16]), "+f"(d[17]), "+f"(d[18]), "+f"(d[19]) : "l"(da), "l"(db), "r"(sc));
}
#define A8(d, o) "+f"(d[o]), "+f"(d[o + 1]), "+f"(d[o + 2]), "+f"(d[o + 3]), "+f"(d[o + 4]), "+f"(d[o + 5]), "+f"(d[o + 6]), "+f"(d[o + 7])
#define A32(d, o) A8(d, o), A8(d, o + 8), A8(d, o + 16), A8(d, o + 24)
DEVINL void wg_ss256(float* d, uint64_t da, uint64_t db, int sc) {
    asm volatile(
        "{ .reg .pred p; setp.ne.b32 p, %130, 0;\n"
        "wgmma.mma_async.sync.aligned.m64n256k16.f32.bf16.bf16 {"
        "%0,%1,%2,%3,%4,%5,%6,%7,%8,%9,%10,%11,%12,%13,%14,%15,%16,%17,%18,%19,%20,%21,%22,%23,%24,%25,%26,%27,%28,%29,%30,%31,"
        "%32,%33,%34,%35,%36,%37,%38,%39,%40,%41,%42,%43,%44,%45,%46,%47,%48,%49,%50,%51,%52,%53,%54,%55,%56,%57,%58,%59,%60,%61,%62,%63,"
        "%64,%65,%66,%67,%68,%69,%70,%71,%72,%73,%74,%75,%76,%77,%78,%79,%80,%81,%82,%83,%84,%85,%86,%87,%88,%89,%90,%91,%92,%93,%94,%95,"
        "%96,%97,%98,%99,%100,%101,%102,%103,%104,%105,%106,%107,%108,%109,%110,%111,%112,%113,%114,%115,%116,%117,%118,%119,%120,%121,%122,%123,%124,%125,%126,%127"
        "}, %128, %129, p, 1, 1, 0, 1; }"
        : A32(d, 0), A32(d, 32), A32(d, 64), A32(d, 96) : "l"(da), "l"(db), "r"(sc));
}

DEVINL float gate_row(const uint4 (&xv)[4], const uint4 (&gv)[4]) {
    float acc = 0.f;
#pragma unroll
    for (int i = 0; i < 4; i++) {
        const uint32_t xa[4] = {xv[i].x, xv[i].y, xv[i].z, xv[i].w}, ga[4] = {gv[i].x, gv[i].y, gv[i].z, gv[i].w};
#pragma unroll
        for (int e = 0; e < 4; e++) {
            acc = fmaf(__uint_as_float(xa[e] << 16), __uint_as_float(ga[e] << 16), acc);
            acc = fmaf(__uint_as_float(xa[e] & 0xffff0000u), __uint_as_float(ga[e] & 0xffff0000u), acc);
        }
    }
#pragma unroll
    for (int o = 16; o > 0; o >>= 1) acc += __shfl_xor_sync(0xffffffffu, acc, o);
    return 1.0f / (1.0f + __expf(-acc));
}
DEVINL uint4 ldg_nc(const void* p) { uint4 v; asm volatile("ld.global.nc.v4.u32 {%0,%1,%2,%3}, [%4];" : "=r"(v.x), "=r"(v.y), "=r"(v.z), "=r"(v.w) : "l"(p) : "memory"); return v; }
DEVINL uint32_t ld_strong4(const void* p) { uint32_t v; asm volatile("ld.relaxed.gpu.global.u32 %0, [%1];" : "=r"(v) : "l"(p) : "memory"); return v; }
DEVINL void wait_count(const uint32_t* p, uint32_t want) {
    uint32_t v, n = 0;
    while (true) {
        asm volatile("ld.acquire.gpu.global.u32 %0, [%1];" : "=r"(v) : "l"(p) : "memory");
        if (v >= want) break;
        __nanosleep(200);
        if (++n > 10000000u) __trap();
    }
}

constexpr int KR = 44;
constexpr int KS = 64 - KR;
constexpr int R_W = 0;
constexpr int R_WO = KS * 4096;
constexpr int R_QX = R_WO + 65536;
constexpr int R_RING = R_WO + 98304;
constexpr int R_K = R_RING + 24576;
constexpr int R_V = R_K + 10240;
constexpr int R_QM = R_V + 10240;
constexpr int R_O = R_QM + 2048;
constexpr int R_BAR = R_O + 2048;
constexpr int R_G = R_BAR + 256 + 512 + 256 + 128;
constexpr int R_Z = R_G + 256;
constexpr int R_SMEM = R_Z + 1024;
enum { B_FULL = 0, B_EMPTY = 5, B_MEM = 8, B_HOP1 = 12, B_XT, B_TFREE, B_O, B_AFREE0, B_AFREE1, B_PRO0, B_PRO1, B_XRECV, B_P, B_XDONE, B_OST0, B_OST1, B_HOPV };
#define D2_BASE 900
#define D2_STEP 200
#define PD2 6
#define CPB 8192
#define DDUP 0
#define WGAP 0
#define PVD 400
#define ELD 700
#define QD 3
#define DQ 1700
#define D3 0

DEVINL uint32_t clk32() { uint32_t c_; asm volatile("mov.u32 %0, %%clock;" : "=r"(c_)); return c_; }
DEVINL void spin_until(uint32_t t) { while ((uint32_t)(t - clk32() - 1u) < 100000u) {} }
#define PROF(i)
#define PROF2(i)
#define PROF3(i, val)
DEVINL void e_arrive(uint32_t bar) { asm volatile("{ .reg .pred p; elect.sync _|p, 0xffffffff; @p mbarrier.arrive.shared::cta.b64 _, [%0]; }" ::"r"(bar) : "memory"); }
DEVINL void e_arrive_remote(uint32_t cbar) { asm volatile("{ .reg .pred p; elect.sync _|p, 0xffffffff; @p mbarrier.arrive.relaxed.cluster.shared::cluster.b64 _, [%0]; }" ::"r"(cbar) : "memory"); }
DEVINL void e_count(uint32_t* p) { asm volatile("{ .reg .pred p; elect.sync _|p, 0xffffffff; @p red.relaxed.gpu.global.add.u32 [%0], 1; }" ::"l"(p) : "memory"); }
DEVINL void e_expect(uint32_t bar, uint32_t bytes) { asm volatile("{ .reg .pred p; elect.sync _|p, 0xffffffff; @p mbarrier.arrive.expect_tx.shared::cta.b64 _, [%0], %1; }" ::"r"(bar), "r"(bytes) : "memory"); }
DEVINL void e_tma_load(uint32_t dst, const CUtensorMap* tm, int c0, int c1, uint32_t bar) {
    asm volatile("{ .reg .pred p; elect.sync _|p, 0xffffffff; @p cp.async.bulk.tensor.2d.shared::cluster.global.mbarrier::complete_tx::bytes [%0], [%1, {%3, %4}], [%2]; }"
                 ::"r"(dst), "l"(tm), "r"(bar), "r"(c0), "r"(c1) : "memory");
}
DEVINL void e_tma_store(const CUtensorMap* tm, uint32_t src, int c0, int c1) {
    asm volatile("{ .reg .pred p; elect.sync _|p, 0xffffffff; @p cp.async.bulk.tensor.2d.global.shared::cta.bulk_group [%0, {%2, %3}], [%1]; }" ::"l"(tm), "r"(src), "r"(c0), "r"(c1) : "memory");
}
DEVINL void e_bulk_s2g(void* dst, uint32_t src, uint32_t bytes) {
    asm volatile("{ .reg .pred p; elect.sync _|p, 0xffffffff; @p cp.async.bulk.global.shared::cta.bulk_group [%0], [%1], %2; }" ::"l"(dst), "r"(src), "r"(bytes) : "memory");
}
DEVINL void e_bulk_s2s(uint32_t cdst, uint32_t src, uint32_t bytes, uint32_t cbar) {
    asm volatile("{ .reg .pred p; elect.sync _|p, 0xffffffff; @p cp.async.bulk.shared::cluster.shared::cta.mbarrier::complete_tx::bytes [%0], [%1], %2, [%3]; }" ::"r"(cdst), "r"(src), "r"(bytes), "r"(cbar) : "memory");
}

#define SLOT 0
#define PH3 0
#define PHQ 0
DEVINL void wait_slot(uint32_t phase) {
    if (SLOT) {
        uint32_t c; asm volatile("mov.u32 %0, %%globaltimer_lo;" : "=r"(c));
        const uint32_t tgt = c + (SLOT ? SLOT : 1) - ((c - phase) % (SLOT ? SLOT : 1));
        do { asm volatile("mov.u32 %0, %%globaltimer_lo;" : "=r"(c)); } while ((uint32_t)(tgt - c - 1u) < 100000u);
    }
}
template <int N> DEVINL uint32_t poll_set(uint4 (&v)[N], const uint32_t* rp, int stride, uint32_t phase, uint32_t wbar = 0, uint32_t wpar = 0) {
    wait_slot(phase);
#pragma unroll
    for (int i = 0; i < N; i++) v[i] = ld_strong16(rp + i * stride);
    if (wbar) mbar_wait(wbar, wpar);
    uint32_t n = 0;
    while (true) {
        uint32_t m = 0xffffffffu;
#pragma unroll
        for (int i = 0; i < N; i++) m = min4(v[i], m);
        if (__all_sync(0xffffffffu, m != 0u)) return n;
        wait_slot(phase);
#pragma unroll
        for (int i = 0; i < N; i++)
            asm volatile("{ .reg .pred p; setp.eq.u32 p, %5, 0; @p ld.relaxed.gpu.global.v4.u32 {%0,%1,%2,%3}, [%4]; }"
                         : "+r"(v[i].x), "+r"(v[i].y), "+r"(v[i].z), "+r"(v[i].w) : "l"(rp + i * stride), "r"(min4(v[i], 0xffffffffu)) : "memory");
        if (++n > 20000000u) __trap();
    }
}

struct RMaps { CUtensorMap x, w[3], wo, o; };
#define KC(c) ((c) * 64)

#define XORD 3
__host__ __device__ constexpr int xo(int i) {
    return XORD == 0 ? i : XORD == 1 ? (i + 14) % 16 : XORD == 2 ? (i + 11) % 16
         : XORD == 3 ? (i < 10 ? ((i & 1) ? i / 2 : 11 + i / 2) : i - 5) : (i < 6 ? i : ((i & 1) ? 6 + (i - 6) / 2 : 11 + (i - 6) / 2));
}
#define XC(i) (xo(i) * 64)
DEVINL void x_load_pair(uint32_t dst, const CUtensorMap* tmx, int h, int p, int seg, uint32_t fbar) {
    e_expect(fbar, 8192);
    e_tma_load(dst, tmx, XC(2 * p), seg * SEG, fbar);
    e_tma_load(dst + 4096, tmx, XC(2 * p + 1), seg * SEG, fbar);
}
__host__ __device__ constexpr int wo_tile(int role, int i) {
    return role == 0 ? (i < 2 ? 8 + i : 12 + i) : (i < 4 ? (i >> 1) * 4 : 10) + (role - 1) * 2 + (i & 1);
}

template <int NT> DEVINL void wo_phase(uint32_t sb, int tb, uint32_t* pp, uint32_t obar, uint32_t opar) {
    const int lane = tb & 31, krow = (lane & 7) + ((lane >> 4) << 3), chunk = ((tb >> 5) & 3) * 2 + ((lane >> 3) & 1);
    uint32_t wa = sb + R_WO + (tb >> 7) * 16384 + krow * 128 + ((chunk ^ (krow & 7)) << 4);
    uint32_t af[4][4], of[4][4];
#pragma unroll
    for (int g = 0; g < 4; g++) ldsm4t(af[g], wa + g * 2048);
    mbar_wait(obar, opar);
#pragma unroll
    for (int g = 0; g < 4; g++) ldsm4t(of[g], sb + R_O + g * 512 + lane * 16);
#pragma unroll 1
    for (int i = 0; i < NT; i++) {
        float w0[4] = {0.f, 0.f, 0.f, 0.f}, w1[4] = {0.f, 0.f, 0.f, 0.f};
        const int more = NT - 1 - i, yes = NT - i;
        mma16816(w0, af[0][0], af[0][1], af[0][2], af[0][3], of[0][0], of[0][1]);
        ldsm4t_if(af[0], wa + 4 * 2048, yes);
        mma16816(w1, af[1][0], af[1][1], af[1][2], af[1][3], of[0][2], of[0][3]);
        ldsm4t_if(af[1], wa + 5 * 2048, yes);
        mma16816(w0, af[2][0], af[2][1], af[2][2], af[2][3], of[1][0], of[1][1]);
        ldsm4t_if(af[2], wa + 6 * 2048, yes);
        mma16816(w1, af[3][0], af[3][1], af[3][2], af[3][3], of[1][2], of[1][3]);
        ldsm4t_if(af[3], wa + 7 * 2048, yes);
        wa += 32768;
        mma16816(w0, af[0][0], af[0][1], af[0][2], af[0][3], of[2][0], of[2][1]);
        ldsm4t_if(af[0], wa, more);
        mma16816(w1, af[1][0], af[1][1], af[1][2], af[1][3], of[2][2], of[2][3]);
        ldsm4t_if(af[1], wa + 2048, more);
        mma16816(w0, af[2][0], af[2][1], af[2][2], af[2][3], of[3][0], of[3][1]);
        ldsm4t_if(af[2], wa + 2 * 2048, more);
        mma16816(w1, af[3][0], af[3][1], af[3][2], af[3][3], of[3][2], of[3][3]);
        ldsm4t_if(af[3], wa + 3 * 2048, more);
        st_strong4(pp, pack_nz(w0[0] + w1[0], w0[1] + w1[1]));
        st_strong4(pp + 1024, pack_nz(w0[2] + w1[2], w0[3] + w1[3]));
        pp += (NT == 3 && i == 0) ? 4 * 8192 : 6 * 8192;
    }
}

template <uint32_t role> DEVINL void r_big(const RMaps& tm, const int wid) {
    extern __shared__ __align__(1024) unsigned char smem_raw[];
    const uint32_t sb = smem_u32(smem_raw);
    const uint32_t bar = sb + R_BAR;
    const int tid = threadIdx.x;
    int h; asm("mov.u32 %0, %%clusterid.x;" : "=r"(h));
        uint32_t a[KR][4];
        mbar_wait(bar + 8 * B_PRO0, 0);
        PT(0);
        {
            const int lane = tid & 31;
            const int krow = (lane & 7) + ((lane >> 4) << 3);
            const int chunk = (wid & 3) * 2 + ((lane >> 3) & 1);
            const uint32_t la = sb + (wid >> 2) * 8192 + krow * 128 + ((chunk ^ (krow & 7)) << 4);
#pragma unroll
            for (int k = 0; k < KR; k++) ldsm4t(a[k], la + (k >> 2) * 16384 + (k & 3) * 2048);
        }
        bar_sync(1, 256);
        {
            fence_async();
            const CUtensorMap* tw = &tm.w[role];
            e_expect(bar + 8 * B_PRO1, (wid < 5 ? 16384 : 0) + (wid < (role == 0 ? 4 : 6) ? 16384 : 0));
            if (wid < 5) {
                e_tma_load(sb + R_W + wid * 8192, tw, h * DH, KC(KR / 4 + wid), bar + 8 * B_PRO1);
                e_tma_load(sb + R_W + KS * 2048 + wid * 8192, tw, h * DH + 64, KC(KR / 4 + wid), bar + 8 * B_PRO1);
            }
            if (wid < (role == 0 ? 4 : 6)) e_tma_load(sb + R_WO + wid * 16384, &tm.wo, wo_tile(role, wid) * 64, h * DH, bar + 8 * B_PRO1);
        }
        constexpr uint32_t e0 = role == 0 ? R_QX + 16384 : R_K + 2048, e1 = role == 0 ? R_QX + 24576 : R_V + 2048;
        if (wid == 6) x_load_pair(sb + e0, &tm.x, h, 3, 0, bar + 8 * (B_FULL + 3));
        if (wid == 7) x_load_pair(sb + e1, &tm.x, h, 4, 0, bar + 8 * (B_FULL + 4));
        PT(1);
        mbar_wait(bar + 8 * B_PRO1, 0);
        PT(2);

        constexpr uint64_t dW0 = cdesc(R_W, 1024, 1024, 1);
        constexpr uint64_t dM = cdesc(R_RING, 128, 128, 0);
        constexpr uint64_t dX = cdesc(R_RING, 16, 1024, 1);
        constexpr uint64_t dX0 = cdesc(0, 16, 1024, 1);
        int tb = tid;
        int wq = wid;

        for (int seg = 0; seg < NSEG; seg++) {
            {
            const int s = seg - 1; (void)s;
            float d[16];
            OPAQUE(wq);
            const uint64_t dW = dW0 + (uint64_t)((wq >> 2) * (KS * 128));
#pragma unroll
            for (int p = 0; p < 8; p++) {
                const int slot = p % 5;
                mbar_wait(bar + 8 * (B_FULL + slot), slot < 3 ? (uint32_t)(p / 5) : (uint32_t)(seg & 1));
                PROF2(p);
                const uint64_t db = slot < 3 ? dX + (uint64_t)(slot * 512) : dX0 + (uint64_t)((slot == 3 ? e0 : e1) >> 4);
                wg_fence();
#pragma unroll
                for (int kk = 0; kk < 8; kk++) {
                    const int k = XORD >= 3 ? (kk & 1) * 4 + (kk >> 1) : kk;
                    const int ks = xo(2 * p + (k >> 2)) * 4 + (k & 3);
                    if (ks >= KR) wg_ss32<1>(d, dW + (uint64_t)((ks - KR) * 128), db + (uint64_t)((k >> 2) * 256 + (k & 3) * 2), p + k);
                    else wg_rs32(d, a[ks < KR ? ks : 0], db + (uint64_t)((k >> 2) * 256 + (k & 3) * 2), p + k);
                }
                wg_commit();
                if (p >= 1) {
                    wg_wait<1>();
                    if (p <= 3) {
                        if ((wq & 3) == p) e_arrive(bar + 8 * (B_EMPTY + p - 1));
                        if (wq == p + (p & 1) * 4) {
                            mbar_wait(bar + 8 * (B_EMPTY + p - 1), seg & 1);
                            x_load_pair(sb + R_RING + (p - 1) * 8192, &tm.x, h, p + 4, seg, bar + 8 * (B_FULL + p - 1));
                        }
                    }
                    if (p == 5 && role != 0 && (wq & 3) < 3) e_arrive_remote(mapa(bar + 8 * B_TFREE, wq & 3));
                    if (p == 6 && (wq & 3) == 1) e_arrive(bar + 8 * B_AFREE0);
                    if (p == 7 && (wq & 3) == 2) e_arrive(bar + 8 * B_AFREE1);
                }
            }
            mbar_wait(bar + 8 * B_TFREE, seg & 1);
            asm volatile("wgmma.wait_group.sync.aligned 0;" : ACC16(d)::"memory");
            PROF2(16);
            const uint32_t tilex = sb + (role == 0 ? R_QX + 2048 : (role == 1 ? R_K + 2048 : R_V + 2048));
            {
                OPAQUE(tb);
                const uint32_t gs = role == 0 ? 4096 : 2048;
                const uint32_t sa = tilex + ((tb >> 4) & 1) * gs + (tb >> 5) * 256 + (tb & 15) * 16;
                stsm4(sa, pack_bf16(d[0], d[1]), pack_bf16(d[2], d[3]), pack_bf16(d[4], d[5]), pack_bf16(d[6], d[7]));
                stsm4(sa + 2 * gs, pack_bf16(d[8], d[9]), pack_bf16(d[10], d[11]), pack_bf16(d[12], d[13]), pack_bf16(d[14], d[15]));
            }
            __syncwarp();
            e_arrive(bar + 8 * B_XDONE);
            if (role != 0 && (wq & 3) == 0) {
                mbar_wait(bar + 8 * B_XDONE, seg & 1);
                fence_async();
                uint32_t pr = role + 1 + (wq >> 2); pr = pr >= 3 ? pr - 3 : pr;
                e_bulk_s2s(mapa(tilex, pr), tilex, CPB, mapa(bar + 8 * B_XT, pr));
            }
            }
            {
                const int s = seg;
                OPAQUE(wq);
                const uint64_t dW = dW0 + (uint64_t)((wq >> 2) * (KS * 128));
                float y[4] = {0.f, 0.f, 0.f, 0.f};
                {
                    OPAQUE(tb);
                    const uint32_t ma = sb + R_RING + (tb & 31) * 16;
                    float z[4] = {0.f, 0.f, 0.f, 0.f}, u[4] = {0.f, 0.f, 0.f, 0.f};
                    uint32_t b[QD][4];
                    const int yes = s + 1;
                    mbar_wait(bar + 8 * B_MEM, s & 1);
                    PROF((wq >> 2) * 4 + 0);
                    if (s == 0) PT(3);
                    if (s == 1) PT(4);
#pragma unroll
                    for (int g = 0; g < QD; g++) ldsm4t(b[g], ma + g * 512);
#pragma unroll
                    for (int g = 0; g < KR / 2; g++) {
                        float* c0 = (g % 3 == 0) ? y : (g % 3 == 1) ? u : z;
                        float* c1 = (g % 3 == 0) ? z : (g % 3 == 1) ? y : u;
                        mma16816(c0, a[2 * g][0], a[2 * g][1], a[2 * g][2], a[2 * g][3], b[g % QD][0], b[g % QD][1]);
                        mma16816(c1, a[2 * g + 1][0], a[2 * g + 1][1], a[2 * g + 1][2], a[2 * g + 1][3], b[g % QD][2], b[g % QD][3]);
                        if (g + QD < KR / 2) {
                            if ((g + QD) % 8 == 0) mbar_wait(bar + 8 * (B_MEM + (g + QD) / 8), s & 1);
                            ldsm4t_if(b[g % QD], ma + (g + QD) * 512, yes);
                        }
                    }
                    y[0] += z[0] + u[0]; y[1] += z[1] + u[1]; y[2] += z[2] + u[2]; y[3] += z[3] + u[3];
                }
                PROF2(8);
                mbar_wait(bar + 8 * (B_MEM + 3), s & 1);
                wg_fence();
#pragma unroll
                for (int k = KR; k < 64; k++) wg_ss8<1, 1>(y, dW + (uint64_t)((k - KR) * 128), dM + (uint64_t)(k * 16), 1);
                wg_commit();
                asm volatile("wgmma.wait_group.sync.aligned 0;" : "+f"(y[0]), "+f"(y[1]), "+f"(y[2]), "+f"(y[3])::"memory");
                OPAQUE(tb);
                {
                    const uint32_t wo_ = (tb >> 5) * 256;
                    const uint32_t tile = sb + (role == 0 ? R_QX : (role == 1 ? R_K : R_V)) + wo_;
                    const uint32_t u0 = pack_bf16(y[0], y[1]), u1 = pack_bf16(y[2], y[3]);
                    sts32(tile + (tb & 31) * 4, u0);
                    sts32(tile + (tb & 31) * 4 + 128, u1);
                    __syncwarp();
                    uint4 v = lds128(tile + (tb & 15) * 16);
                    uint32_t peer = role + 1 + ((tb >> 4) & 1);
                    peer = peer >= 3 ? peer - 3 : peer;
                    const uint32_t rt = sb + (role == 0 ? R_QM : (role == 1 ? R_K : R_V)) + wo_ + (tb & 15) * 16;
                    st_async16(mapa(rt, peer), v, mapa(bar + 8 * (role == 2 ? B_HOPV : B_HOP1), peer));
                    if (role == 0) {
                        sts128(tile + 4096 + ((tb >> 4) & 1) * 4096 + (tb & 15) * 16, v);
                        sts32(tile + 12288 + (tb & 31) * 4, u0);
                        sts32(tile + 12288 + (tb & 31) * 4 + 128, u1);
                        __syncwarp();
                    }
                    e_arrive(bar + 8 * (role == 2 ? B_HOPV : B_HOP1));
                }
                PROF((wq >> 2) * 4 + 1);
                if (s < NSEG - 1) {
                    bar_sync(1, 256);
                    if (wq < 3) { fence_async(); x_load_pair(sb + R_RING + wq * 8192, &tm.x, h, wq, s + 1, bar + 8 * (B_FULL + wq)); }
                    else if (role == 0 && wq < 5) x_load_pair(sb + (wq == 3 ? e0 : e1), &tm.x, h, wq, s + 1, bar + 8 * (B_FULL + wq));
                    OPAQUE(tb);
                }
                uint32_t* pp = g_part[s & 3] + (h * 32 + (wo_tile(role, 0) + (tb >> 7)) * 8192 + ((tb >> 5) & 3) * 2048 + (tb & 31));
                asm volatile("" : "+l"(pp));
                if (s == NSEG - 1) break;
                wo_phase<role == 0 ? 2 : 3>(sb, tb, pp, bar + 8 * B_O, s & 1);
                if (wq == 0) PROF(10);
            }
        }
}

#define CLR 0
#define CLEAR(st) do { if (role != 0) { \
                const int w_ = wid & 3; \
                uint32_t* zp = g_part[(st) & 3] + ((rg0 + (w_ >> 1) * 64) * 1024 + (w_ & 1) * 512); \
                e_bulk_s2g(zp, sb + R_Z, 1024); \
                e_bulk_s2g(zp + 256, sb + R_Z, 1024); \
                e_bulk_s2g(&g_mem[(st) & 3][(rg0 + (w_ >> 1) * 64) * 32 + (w_ & 1) * 16], sb + R_Z, 64); \
                bulk_commit(); } } while (0)
template <uint32_t role> DEVINL void r_chain(const RMaps& tm, const bf16* __restrict__ mem0, const int wid) {
    extern __shared__ __align__(1024) unsigned char smem_raw[];
    const uint32_t sb = smem_u32(smem_raw);
    const uint32_t bar = sb + R_BAR;
    const int tid = threadIdx.x;
    int h; asm("mov.u32 %0, %%clusterid.x;" : "=r"(h));
        int t = tid & 127;
        const float sl2 = 0.08838834764831845f * 1.4426950408889634f;
        const float NEGRAW = -1000000000.0f / 0.08838834764831845f;
        const int rg0 = ((int)role - 1) * 32 + h;
        if (role != 0) {
#pragma unroll 1
            for (int r = 0; r < 4; r++) {
                uint32_t* zp = g_part[r] + ((rg0 + (t >> 6) * 64) * 1024 + (t & 63) * 4);
#pragma unroll
                for (int i = 0; i < 4; i++) st_strong16(zp + i * 256, make_uint4(0u, 0u, 0u, 0u));
                if ((t & 63) < 8) st_strong16(&g_mem[r][(rg0 + (t >> 6) * 64) * 32 + (t & 63) * 4], make_uint4(0u, 0u, 0u, 0u));
            }
            __threadfence();
        }
        if (role == 0 && (wid & 3) < 3) e_arrive_remote(mapa(bar + 8 * B_TFREE, wid & 3));
        if (t < 64) sts128(sb + R_Z + t * 16, make_uint4(0u, 0u, 0u, 0u));
        if (role == 0) sts128(sb + R_QM + t * 16, make_uint4(0u, 0u, 0u, 0u));
        {
            uint4 v[8];
#pragma unroll
            for (int r = 0; r < 8; r++) v[r] = __ldg((const uint4*)(mem0 + r * DM) + t);
            mbar_wait(bar + 8 * B_AFREE0, 0);
            mbar_wait(bar + 8 * B_AFREE1, 0);
#define TR2(f, c) \
            sts128(sb + R_RING + t * 128 + (c) * 16, make_uint4(__byte_perm(v[0].f, v[1].f, 0x5410), __byte_perm(v[2].f, v[3].f, 0x5410), __byte_perm(v[4].f, v[5].f, 0x5410), __byte_perm(v[6].f, v[7].f, 0x5410))); \
            sts128(sb + R_RING + t * 128 + (c) * 16 + 16, make_uint4(__byte_perm(v[0].f, v[1].f, 0x7632), __byte_perm(v[2].f, v[3].f, 0x7632), __byte_perm(v[4].f, v[5].f, 0x7632), __byte_perm(v[6].f, v[7].f, 0x7632)));
            TR2(x, 0) TR2(y, 2) TR2(z, 4) TR2(w, 6)
            fence_async();
            __syncwarp();
            e_arrive(bar + 8 * B_MEM + (t >> 5) * 8);
        }
        constexpr uint64_t dQ = role == 0 ? cdesc(R_QX, 128, 2048, 0) : cdesc(R_QM, 128, 0, 0);
        constexpr uint64_t dK = cdesc(R_K, 128, 2048, 0);

        for (int s = 0; s < NSEG; s++) {
            if (role == 0) {
                uint32_t n = 0, gate;
                do { gate = ld_strong4(&g_gate[s * SEG + (t >> 2)]); if (++n > 20000000u) __trap(); } while (gate == 0u);
                sts32(sb + R_G + (t >> 2) * 4, gate);
                __syncwarp();
            }
            mbar_wait(bar + 8 * B_XDONE, s & 1);
            mbar_wait(bar + 8 * B_XT, s & 1);
            if (t >= 1 && t < 3) { uint32_t pr = role + t; pr = pr >= 3 ? pr - 3 : pr; mbar_arrive_remote(mapa(bar + 8 * B_XRECV, pr)); }
            __syncwarp();
            mbar_wait(bar + 8 * B_HOP1, s & 1);
            PROF(8);
            fence_async();
            OPAQUE(t);
            if (s == NSEG - 1 && role != 0) { mbar_wait(bar + 8 * B_HOPV, s & 1); bulk_wait_all(); break; }
            float sc[20];
            wg_fence();
#pragma unroll
            for (int k = 0; k < 8; k++) wg_ss40(sc, dQ + (uint64_t)(k * 16), dK + (uint64_t)(k * 16), k);
            wg_commit();
            uint32_t t_o = clk32() + 500;
            {
                const uint32_t va = sb + R_V + 2048 + (t >> 5) * 512 + ((t >> 4) & 1) * 2048 + (t & 15) * 16;
                uint32_t v0[4], v1[4];
                ldsm4(v0, va); ldsm4(v1, va + 256);
                uint32_t vm[4];
                const bool v_here = mbar_try(bar + 8 * B_HOPV, s & 1);
                if (v_here) ldsm4(vm, sb + R_V + t * 16);
                wg_wait<0>();
                if (role == 0) {
#pragma unroll
                    for (int j = 0; j < 5; j++)
                        asm volatile("st.shared.v2.f32 [%0], {%1,%2};" ::"r"(sb + R_QX + 768 + (t >> 5) * 4096 + j * 256 + (t & 31) * 8), "f"(sc[4 * j + 2]), "f"(sc[4 * j + 3]) : "memory");
                }
                float m = fmaxf(sc[0], sc[1]);
#pragma unroll
                for (int j = 1; j < 5; j++) m = fmaxf(m, fmaxf(sc[4 * j], sc[4 * j + 1]));
                m = fmaxf(m, __shfl_xor_sync(0xffffffffu, m, 1));
                m = fmaxf(m, __shfl_xor_sync(0xffffffffu, m, 2));
                const float mb = m * sl2;
                uint32_t pk[5];
#pragma unroll
                for (int j = 0; j < 5; j++) pk[j] = pack_bf16(ex2(fmaf(sc[4 * j], sl2, -mb)), ex2(fmaf(sc[4 * j + 1], sl2, -mb)));
                float o0[4] = {0.f, 0.f, 0.f, 0.f}, o1[4] = {0.f, 0.f, 0.f, 0.f}, ls[4] = {0.f, 0.f, 0.f, 0.f};
                constexpr uint32_t ONE = 0x3F803F80u;
                mma16816(o0, v0[0], v0[1], v0[2], v0[3], pk[1], pk[2]);
                mma16816(o1, v1[0], v1[1], v1[2], v1[3], pk[1], pk[2]);
                ldsm4(v0, va + 4096); ldsm4(v1, va + 4096 + 256);
                mma16816(ls, ONE, ONE, ONE, ONE, pk[1], pk[2]);
                mma16816(ls, ONE, ONE, ONE, ONE, pk[3], pk[4]);
                mma1688(ls, ONE, ONE, pk[0]);
                mma16816(o0, v0[0], v0[1], v0[2], v0[3], pk[3], pk[4]);
                mma16816(o1, v1[0], v1[1], v1[2], v1[3], pk[3], pk[4]);
                if (!v_here) { mbar_wait(bar + 8 * B_HOPV, s & 1); ldsm4(vm, sb + R_V + t * 16); }
                mma1688(o0, vm[0], vm[1], pk[0]);
                mma1688(o1, vm[2], vm[3], pk[0]);
                const float i0 = rcp(ls[0]), i1 = rcp(ls[1]);
                const uint32_t oa = sb + R_O + (t >> 5) * 512 + (t & 31) * 4;
                sts32(oa, pack_bf16(o0[0] * i0, o0[1] * i1));
                sts32(oa + 128, pack_bf16(o0[2] * i0, o0[3] * i1));
                sts32(oa + 256, pack_bf16(o1[0] * i0, o1[1] * i1));
                sts32(oa + 384, pack_bf16(o1[2] * i0, o1[3] * i1));
                __syncwarp();
                e_arrive(bar + 8 * B_O);
                PROF(9);
                if (role == 0) {
                    OPAQUE(t);
                    const int lim = (t >> 2) - (t & 3) * 2 + 8;
                    float z[10];
#pragma unroll
                    for (int j = 0; j < 5; j++)
                        asm volatile("ld.shared.v2.f32 {%0,%1}, [%2];" : "=f"(z[2 * j]), "=f"(z[2 * j + 1]) : "r"(sb + R_QX + 768 + (t >> 5) * 4096 + j * 256 + (t & 31) * 8) : "memory");
                    float gate; asm volatile("ld.shared.f32 %0, [%1];" : "=f"(gate) : "r"(sb + R_G + (t >> 2) * 4) : "memory");
                    float m1 = fmaxf(z[0], z[1]);
#pragma unroll
                    for (int j = 1; j < 5; j++) {
                        z[2 * j] = 8 * j <= lim ? z[2 * j] : NEGRAW;
                        z[2 * j + 1] = 8 * j + 1 <= lim ? z[2 * j + 1] : NEGRAW;
                        m1 = fmaxf(m1, fmaxf(z[2 * j], z[2 * j + 1]));
                    }
                    m1 = fmaxf(m1, __shfl_xor_sync(0xffffffffu, m1, 1));
                    m1 = fmaxf(m1, __shfl_xor_sync(0xffffffffu, m1, 2));
                    const float mb1 = m1 * sl2;
                    float l1 = 0.f;
                    const uint32_t pa = sb + R_QX + (t >> 5) * 4096 + (t & 31) * 4;
#pragma unroll
                    for (int j = 0; j < 5; j++) {
                        const uint32_t pw = pack_bf16(ex2(fmaf(z[2 * j], sl2, -mb1)), ex2(fmaf(z[2 * j + 1], sl2, -mb1)));
                        l1 += __uint_as_float(pw << 16) + __uint_as_float(pw & 0xffff0000u);
                        sts32(pa + j * 128, pw);
                    }
                    sts32(pa + 5 * 128, 0u);
                    l1 += __shfl_xor_sync(0xffffffffu, l1, 1);
                    l1 += __shfl_xor_sync(0xffffffffu, l1, 2);
                    sts32(sb + R_G + 128 + (t >> 2) * 4, __float_as_uint(gate * rcp(l1)));
                    spin_until(t_o + PVD);
                    if ((wid & 3) == 0 && s >= 1) { bulk_wait_all(); e_count(&g_ocnt[(s - 1) >> 2]); }
                    fence_async();
                    bar_sync(2, 128);
                    constexpr uint64_t dV = cdesc(R_V, 2048, 128, 0);
                    constexpr uint64_t dP = cdesc(R_QX, 128, 4096, 0);
                    float sf[8];
#pragma unroll
                    for (int j = 0; j < 4; j++) asm volatile("ld.shared.v2.f32 {%0,%1}, [%2];" : "=f"(sf[2 * j]), "=f"(sf[2 * j + 1]) : "r"(sb + R_G + 128 + j * 32 + (t & 3) * 8) : "memory");
                    const uint32_t r = ((t >> 4) & 1) * 8 + (t & 7), ch = (t >> 5) * 2 + ((t >> 3) & 1);
                    const uint32_t sa = sb + R_QX + 2048 + r * 128 + ((ch ^ (r & 7)) << 4);
#pragma unroll
                    for (int hf = 0; hf < 2; hf++) {
                        float d[16];
                        wg_fence();
#pragma unroll
                        for (int k = 0; k < 3; k++) wg_ss32<0>(d, dV + (uint64_t)(hf * 64 + k * 256), dP + (uint64_t)(k * 16), k);
                        wg_commit();
                        asm volatile("wgmma.wait_group.sync.aligned 0;" : ACC16(d)::"memory");
                        stsm4t(sa + hf * 8192, pack_bf16(d[0] * sf[0], d[1] * sf[1]), pack_bf16(d[2] * sf[0], d[3] * sf[1]), pack_bf16(d[4] * sf[2], d[5] * sf[3]), pack_bf16(d[6] * sf[2], d[7] * sf[3]));
                        stsm4t(sa + hf * 8192 + 4096, pack_bf16(d[8] * sf[4], d[9] * sf[5]), pack_bf16(d[10] * sf[4], d[11] * sf[5]), pack_bf16(d[12] * sf[6], d[13] * sf[7]), pack_bf16(d[14] * sf[6], d[15] * sf[7]));
                    }
                    fence_async();
                    bar_sync(2, 128);
                    if ((wid & 3) == 0) {
#pragma unroll
                        for (int q = 0; q < 4; q++) e_tma_store(&tm.o, sb + R_QX + 2048 + q * 4096, h * DH + (q >> 1) * 64, s * SEG + (q & 1) * 16);
                        bulk_commit();
                        bulk_wait_read();
                    }
                    if ((wid & 3) < 3) e_arrive_remote(mapa(bar + 8 * B_TFREE, wid & 3));
                }
            }
            if (t < 32) { e_expect(bar + 8 * B_HOP1, role == 2 ? 4096 : 2048); if (role != 2) e_expect(bar + 8 * B_HOPV, 2048); e_expect(bar + 8 * B_XT, role == 0 ? 2 * CPB : CPB); }
            if (s == NSEG - 1) { bulk_wait_all(); break; }
            if (role != 0 && (wid & 3) >= 2) {
                mbar_wait(bar + 8 * B_XRECV, s & 1);
                mbar_wait(bar + 8 * B_O, s & 1);
                fence_async();
                spin_until(t_o + ELD);
                x_load_pair(sb + ((wid & 1) ? R_V + 2048 : R_K + 2048), &tm.x, h, 3 + (wid & 1), s + 1, bar + 8 * (B_FULL + 3 + (wid & 1)));
            }
            OPAQUE(t);
            PROF(11);
            if (role != 0 || DDUP) {
                const int grp = role == 0 ? (t >> 6) * 32 + h : rg0 + (t >> 6) * 64;
                const uint32_t* rp = g_part[s & 3] + (grp * 1024 + ((t >> 2) & 7) * 32 + ((t >> 5) & 1) * 16 + (t & 3) * 4);
                uint32_t* wp = &g_mem[(s + 1) & 3][grp * 32 + ((t >> 5) & 1) * 16 + (t & 3) * 4 + ((t >> 3) & 3)];
                bulk_wait_all();
                spin_until(t_o + D2_BASE + (role == 0 ? DDUP + (t >> 6) * D2_STEP : (role - 1 + (t >> 6) * 2) * D2_STEP));
                PROF3(0, clk32());
#define LO(u) __uint_as_float((u) << 16)
#define HI(u) __uint_as_float((u) & 0xffff0000u)
                uint4 v[4];
                uint32_t n = poll_set<4>(v, rp, 256, (role - 1 + (t >> 6) * 2) * PHQ);
                {
                    PROF3(1, clk32());
                    float f[8];
                    f[0] = (LO(v[0].x) + LO(v[1].x)) + (LO(v[2].x) + LO(v[3].x)); f[1] = (HI(v[0].x) + HI(v[1].x)) + (HI(v[2].x) + HI(v[3].x));
                    f[2] = (LO(v[0].y) + LO(v[1].y)) + (LO(v[2].y) + LO(v[3].y)); f[3] = (HI(v[0].y) + HI(v[1].y)) + (HI(v[2].y) + HI(v[3].y));
                    f[4] = (LO(v[0].z) + LO(v[1].z)) + (LO(v[2].z) + LO(v[3].z)); f[5] = (HI(v[0].z) + HI(v[1].z)) + (HI(v[2].z) + HI(v[3].z));
                    f[6] = (LO(v[0].w) + LO(v[1].w)) + (LO(v[2].w) + LO(v[3].w)); f[7] = (HI(v[0].w) + HI(v[1].w)) + (HI(v[2].w) + HI(v[3].w));
                    const bool b4 = t & 16, b3 = t & 8;
                    float g4[4], g2[2];
#pragma unroll
                    for (int i = 0; i < 4; i++) g4[i] = (b4 ? f[4 + i] : f[i]) + __shfl_xor_sync(0xffffffffu, b4 ? f[i] : f[4 + i], 16);
#pragma unroll
                    for (int i = 0; i < 2; i++) g2[i] = (b3 ? g4[2 + i] : g4[i]) + __shfl_xor_sync(0xffffffffu, b3 ? g4[i] : g4[2 + i], 8);
                    g2[0] += __shfl_xor_sync(0xffffffffu, g2[0], 4);
                    g2[1] += __shfl_xor_sync(0xffffffffu, g2[1], 4);
                    st_strong4(wp, pack_nz(g2[0], g2[1]));
                }
                PROF3(8, n); (void)n;
            }
            t_o += D2_BASE + DQ + D3 + (t >> 5) * D2_STEP;
            OPAQUE(t);
            PROF(12);
            {
                const uint32_t* rp = &g_mem[(s + 1) & 3][((t >> 5) * 256 + (t & 31)) * 4];
                const uint32_t da = sb + R_RING + ((t >> 5) * 256 + (t & 31)) * 16;
                uint4 v[8];
                spin_until(t_o);
                PROF3(2, clk32());
                uint32_t n = poll_set<8>(v, rp, 128, PH3 + (t >> 5) * PHQ);
                PROF(13);
                PROF3(3, clk32()); PROF3(9, n); (void)n;
                mbar_wait(bar + 8 * B_AFREE0 + (t >> 6) * 8, (s + 1) & 1);
                PROF3(4, clk32());
#pragma unroll
                for (int i = 0; i < 8; i++) sts128(da + i * 512, v[i]);
                if (t >= 64) fence_async();
                __syncwarp();
                e_arrive(bar + 8 * B_MEM + (t >> 5) * 8);
                PROF(14);
                PROF3(5, clk32());
            }
            CLEAR(s + 3);
        }
}

__global__ void __launch_bounds__(384, 1) r_kernel(const __grid_constant__ RMaps tm, const bf16* __restrict__ mem0, const bf16* __restrict__ x, const bf16* __restrict__ gate_w) {
    extern __shared__ __align__(1024) unsigned char smem_raw[];
    const uint32_t sb = smem_u32(smem_raw);
    if ((sb & 0x3FFFFu) != SB0) __trap();
    const int tid = threadIdx.x;
    const int wid = __shfl_sync(0xffffffffu, tid >> 5, 0);
    uint32_t role; asm("mov.u32 %0, %%cluster_ctarank;" : "=r"(role));
    int h; asm("mov.u32 %0, %%clusterid.x;" : "=r"(h));
    const uint32_t bar = sb + R_BAR;
    asm volatile("griddepcontrol.launch_dependents;");
    KT(0, 0);
    const int gr = blockIdx.x * 12 + wid;
    uint4 gx0[4], gx1[4], gw[4];
#pragma unroll
    for (int i = 0; i < 4; i++) {
        gx0[i] = ldg_nc((const uint4*)(x + gr * DM) + i * 32 + (tid & 31));
        gx1[i] = ldg_nc((const uint4*)(x + min(gr + 1152, SEQ - 1) * DM) + i * 32 + (tid & 31));
        gw[i] = ldg_nc((const uint4*)gate_w + i * 32 + (tid & 31));
    }

    if (tid == 0) {
        for (int i = 0; i < 5; i++) mbar_init(bar + 8 * (B_FULL + i), 1);
        for (int i = 0; i < 3; i++) mbar_init(bar + 8 * (B_EMPTY + i), 2);
        for (int i = 0; i < 4; i++) mbar_init(bar + 8 * (B_MEM + i), 1);
        mbar_init(bar + 8 * B_HOP1, role == 2 ? 1 : 9);
        mbar_init(bar + 8 * B_HOPV, role == 2 ? 8 : 1);
        mbar_init(bar + 8 * B_XT, 1);
        mbar_init(bar + 8 * B_TFREE, 5);
        mbar_init(bar + 8 * B_P, 4);
        mbar_init(bar + 8 * B_XDONE, 8);
        mbar_init(bar + 8 * B_OST0, 4);
        mbar_init(bar + 8 * B_OST1, 4);
        mbar_init(bar + 8 * B_XRECV, 2);
        mbar_init(bar + 8 * B_O, 4);
        mbar_init(bar + 8 * B_AFREE0, 2);
        mbar_init(bar + 8 * B_AFREE1, 2);
        mbar_init(bar + 8 * B_PRO0, 1);
        mbar_init(bar + 8 * B_PRO1, 8);
        asm volatile("fence.mbarrier_init.release.cluster;" ::: "memory");
        fence_async();
        mbar_expect(bar + 8 * B_PRO0, KR * 4096);
        for (int i = 0; i < 3; i++) mbar_expect(bar + 8 * (B_FULL + i), 8192);
        mbar_expect(bar + 8 * B_HOP1, role == 2 ? 4096 : 2048);
        if (role != 2) mbar_expect(bar + 8 * B_HOPV, 2048);
        mbar_expect(bar + 8 * B_XT, role == 0 ? 2 * CPB : CPB);
    }
    __syncthreads();
    asm volatile("barrier.cluster.arrive.relaxed.aligned;" ::: "memory");
    {
        const CUtensorMap* tw = &tm.w[role];
        if (wid < 11) {
            e_tma_load(sb + wid * 16384, tw, h * DH, KC(wid), bar + 8 * B_PRO0);
            e_tma_load(sb + wid * 16384 + 8192, tw, h * DH + 64, KC(wid), bar + 8 * B_PRO0);
        }
        if (wid < 6) e_tma_load(sb + R_RING + wid * 4096, &tm.x, XC(wid), 0, bar + 8 * (B_FULL + (wid >> 1)));
        if ((tid & 31) == 0) {
            if (wid < 10) tma_prefetch(tw, h * DH + (wid & 1) * 64, KC(KR / 4 + (wid >> 1)));
            if (wid >= 6 && wid - 6 < (role == 0 ? 4 : 6)) tma_prefetch(&tm.wo, wo_tile(role, wid - 6) * 64, h * DH);
        }
        __syncwarp();
        const uint32_t g0 = __float_as_uint(gate_row(gx0, gw)), g1 = __float_as_uint(gate_row(gx1, gw));
        if ((tid & 31) == 0) {
            st_strong4(&g_gate[gr], g0 ? g0 : 0x80000000u);
            if (gr + 1152 < SEQ) st_strong4(&g_gate[gr + 1152], g1 ? g1 : 0x80000000u);
        }
        __syncwarp();
    }
    asm volatile("barrier.cluster.wait.aligned;" ::: "memory");

    if (wid < 8) {
        asm volatile("setmaxnreg.inc.sync.aligned.u32 224;");
        if (role == 0) r_big<0>(tm, wid); else if (role == 1) r_big<1>(tm, wid); else r_big<2>(tm, wid);
    } else {
        asm volatile("setmaxnreg.dec.sync.aligned.u32 56;");
        if (role == 0) r_chain<0>(tm, mem0, wid); else if (role == 1) r_chain<1>(tm, mem0, wid); else r_chain<2>(tm, mem0, wid);
    }
    __syncwarp();
    asm volatile("barrier.cluster.arrive; barrier.cluster.wait;" ::: "memory");
    KT(0, 1);
}

#define STAG 0
constexpr int G_ST = 4;
constexpr int G_STAGE = 16384 + 32768;
constexpr int G_EPI = G_ST * G_STAGE;
constexpr int G_GATE = G_EPI + 32768;
constexpr int G_BAR = G_GATE + 1024;
constexpr int G_SMEM = G_BAR + 128 + 1024;

struct G1Maps { CUtensorMap x, wg, wu, hs, o, h, wo, wd, out; };
constexpr int G1_NB = FF / 128;
constexpr int G1_TILES = 16 * G1_NB;

DEVINL void g_mma_block(float* d, uint32_t sb, uint32_t bar, int it, int wg, int tid, bool first) {
    const int st = it % G_ST;
    mbar_wait(bar + 8 * st, (it / G_ST) & 1);
    const uint64_t da = mkdesc(sb + st * G_STAGE + wg * 8192, 16, 1024, 1);
    const uint64_t db = mkdesc(sb + st * G_STAGE + 16384, 8192, 1024, 1);
    wg_fence();
#pragma unroll
    for (int k = 0; k < 4; k++) wg_ss256(d, da + (uint64_t)(k * 2), db + (uint64_t)(k * 128), (first ? 0 : 1) | k);
    wg_commit();
    if (!first) { wg_wait<1>(); if ((tid & 127) == 0) mbar_arrive(bar + 8 * (G_ST + (it - 1) % G_ST)); }
}
DEVINL void g_load_block(uint32_t sb, uint32_t bar, int it, const CUtensorMap* ta, int k0, int m0, const CUtensorMap* tb, int n0) {
    const int st = it % G_ST;
    mbar_wait(bar + 8 * (G_ST + st), ((it / G_ST) & 1) ^ 1);
    const uint32_t fb = bar + 8 * st, sa = sb + st * G_STAGE;
    mbar_expect(fb, G_STAGE);
    tma_load(sa, ta, k0, m0, fb);
#pragma unroll
    for (int q = 0; q < 4; q++) tma_load(sa + 16384 + q * 8192, tb, n0 + q * 64, k0, fb);
}

DEVINL void g_store_tile(const float* d, const CUtensorMap* tout, uint32_t epi, int mb, int nb, int wg, int tid) {
    const int lane = tid & 31, row = ((tid >> 5) & 3) * 16 + ((lane >> 3) & 1) * 8 + (lane & 7);
#pragma unroll
    for (int half = 0; half < 2; half++) {
        if ((tid & 127) == 0) bulk_wait_read();
        bar_sync(1 + wg, 128);
#pragma unroll
        for (int j = 0; j < 16; j += 2) {
            const float* e = d + half * 64 + 4 * j;
            const int cgp = j + (lane >> 4);
            stsm4(epi + (cgp >> 3) * 8192 + row * 128 + (((cgp & 7) ^ (row & 7)) << 4),
                  pack_bf16(e[0], e[1]), pack_bf16(e[2], e[3]), pack_bf16(e[4], e[5]), pack_bf16(e[6], e[7]));
        }
        fence_async();
        bar_sync(1 + wg, 128);
        if ((tid & 127) == 0) {
            tma_store(tout, epi, nb * 256 + half * 128, mb * 128 + wg * 64);
            tma_store(tout, epi + 8192, nb * 256 + half * 128 + 64, mb * 128 + wg * 64);
            bulk_commit();
        }
    }
}
template <int NS> DEVINL void g_split_finish(const float* d, float4 (&r)[32 / NS], uint4* sk, int tile, int ks, bf16* __restrict__ out, int tid) {
    constexpr int Q = 32 / NS;
    uint4* mine = sk + ks * (16 * 256) + tid;
#pragma unroll
    for (int c = 0; c < NS; c++) {
        if (c != ks) {
#pragma unroll
            for (int q = c * Q / 2; q < (c + 1) * Q / 2; q++)
                __stcg(mine + q * 256, make_uint4(pack_bf16(d[8 * q], d[8 * q + 1]), pack_bf16(d[8 * q + 2], d[8 * q + 3]), pack_bf16(d[8 * q + 4], d[8 * q + 5]), pack_bf16(d[8 * q + 6], d[8 * q + 7])));
        } else {
#pragma unroll
            for (int q = 0; q < Q; q++) { const float* e = d + (c * Q + q) * 4; r[q].x += e[0]; r[q].y += e[1]; r[q].z += e[2]; r[q].w += e[3]; }
        }
    }
    __threadfence();
    bar_sync(3, 256);
    if (tid == 0) {
        atomicAdd(&g_skcnt[tile], 1u);
        uint32_t v, n = 0;
        do {
            asm volatile("ld.acquire.gpu.global.u32 %0, [%1];" : "=r"(v) : "l"(&g_skcnt[tile]) : "memory");
            if (++n > 200000000u) __trap();
        } while (v < NS);
        if (atomicAdd(&g_skcnt[tile], 1u) == 2 * NS - 1) g_skcnt[tile] = 0u;
    }
    bar_sync(3, 256);
#pragma unroll
    for (int c = 1; c < NS; c++) {
        const uint4* th = sk + (((ks + c) & (NS - 1)) * 16 + ks * (Q / 2)) * 256 + tid;
#pragma unroll
        for (int q = 0; q < Q / 2; q++) {
            const uint4 u = __ldcg(th + q * 256);
            r[2 * q].x += __uint_as_float(u.x << 16); r[2 * q].y += __uint_as_float(u.x & 0xffff0000u);
            r[2 * q].z += __uint_as_float(u.y << 16); r[2 * q].w += __uint_as_float(u.y & 0xffff0000u);
            r[2 * q + 1].x += __uint_as_float(u.z << 16); r[2 * q + 1].y += __uint_as_float(u.z & 0xffff0000u);
            r[2 * q + 1].z += __uint_as_float(u.w << 16); r[2 * q + 1].w += __uint_as_float(u.w & 0xffff0000u);
        }
    }
    const int lane = tid & 31;
    uint32_t* op = (uint32_t*)(out + ((tile >> 2) * 128 + (tid >> 5) * 16 + (lane >> 2)) * DM + (tile & 3) * 256 + ks * Q * 8 + (lane & 3) * 2);
#pragma unroll
    for (int q = 0; q < Q; q++) { op[q * 4] = pack_bf16(r[q].x, r[q].y); op[q * 4 + 4 * DM] = pack_bf16(r[q].z, r[q].w); }
}
DEVINL int g1_count(int pass) { return pass == 0 ? NPRE : pass == 1 ? NFULL : pass == 2 ? T_MID - NFULL : (T_LATE - T_MID) * 8; }
DEVINL int g1_first(int pass) { return pass >= 2 ? (int)(gridDim.x - 1 - blockIdx.x) : (int)blockIdx.x; }
constexpr int H_EARLY = 26;

__global__ void __launch_bounds__(384, 1) g1_kernel(const __grid_constant__ G1Maps tm, bf16* __restrict__ out) {
    extern __shared__ __align__(1024) unsigned char smem_raw[];
    const uint32_t sb = (smem_u32(smem_raw) + 1023) & ~1023u;
    const int tid = threadIdx.x, lane = tid & 31;
    const int wg = __shfl_sync(0xffffffffu, tid >> 7, 0);
    const int warp = __shfl_sync(0xffffffffu, (tid >> 5) & 3, 0);
    const uint32_t bar = sb + G_BAR;
    asm volatile("griddepcontrol.launch_dependents;");
    KT(1, 0);
    if (tid == 0) {
        for (int i = 0; i < G_ST; i++) { mbar_init(bar + 8 * i, 1); mbar_init(bar + 8 * (G_ST + i), 2); }
        fence_async();
    }
    __syncthreads();
    if (wg == 2) {
        asm volatile("setmaxnreg.dec.sync.aligned.u32 40;");
        if (warp == 0) {
            if (lane == 0) {
                int it = 0;
                for (int tile = blockIdx.x; tile < G1_TILES; tile += gridDim.x) {
                    const int mb = tile & 15, nb = tile >> 4;
                    for (int kb = 0; kb < 16; kb++, it++) {
                        const int st = it % G_ST;
                        mbar_wait(bar + 8 * (G_ST + st), ((it / G_ST) & 1) ^ 1);
                        const uint32_t fb = bar + 8 * st, sa = sb + st * G_STAGE;
                        mbar_expect(fb, G_STAGE);
                        tma_load(sa, &tm.x, kb * 64, mb * 128, fb);
                        tma_load(sa + 16384, &tm.wg, nb * 128, kb * 64, fb);
                        tma_load(sa + 16384 + 8192, &tm.wg, nb * 128 + 64, kb * 64, fb);
                        tma_load(sa + 16384 + 16384, &tm.wu, nb * 128, kb * 64, fb);
                        tma_load(sa + 16384 + 24576, &tm.wu, nb * 128 + 64, kb * 64, fb);
                    }
                }
                for (int pass = 0; pass < 4; pass++) {
                    for (int i = g1_first(pass); i < g1_count(pass); i += gridDim.x) {
                        const int tile = pass == 1 ? i : pass == 3 ? T_MID + (i >> 3) : NFULL + i, mb = tile >> 2, nb = tile & 3;
                        if (pass < 2) {
                            for (int kb = 0; kb < FF / 64; kb++, it++) {
                                if (kb == 0 || kb == 2 * H_EARLY) {
                                    wait_count(&g_hcnt[kb ? 16 + mb : mb], kb ? 2 * (G1_NB - H_EARLY) : 2 * H_EARLY);
                                    asm volatile("fence.proxy.async;" ::: "memory");
                                }
                                g_load_block(sb, bar, it, &tm.h, kb * 64, mb * 128, &tm.wd, nb * 256);
                            }
                        }
                        if (pass > 0) {
                            const int k0 = pass == 3 ? (i & 7) * 8 : 0, k1 = pass == 3 ? k0 + 8 : HD / 64;
                            wait_count(&g_ocnt[mb], NH * 4);
                            asm volatile("fence.proxy.async;" ::: "memory");
                            for (int kb = k0; kb < k1; kb++, it++) g_load_block(sb, bar, it, &tm.o, kb * 64, mb * 128, &tm.wo, nb * 256);
                        }
                    }
                }
            }
        }
    } else {
        asm volatile("setmaxnreg.inc.sync.aligned.u32 232;");
        float d[128];
        int it = 0;
        const uint32_t epi = sb + G_EPI + wg * 16384;
        const int row = warp * 16 + ((lane >> 3) & 1) * 8 + (lane & 7);
        for (int tile = blockIdx.x; tile < G1_TILES; tile += gridDim.x) {
            const int mb = tile & 15, nb = tile >> 4;
            const uint32_t* gp = &g_gate[mb * 128 + wg * 64 + warp * 16 + (lane >> 2)];
            uint32_t u0 = ld_strong4(gp), u1 = ld_strong4(gp + 8);
            for (int kb = 0; kb < 16; kb++, it++) {
                if (it == (wg ? 0 : STAG)) bar_sync(4, 256);
                g_mma_block(d, sb, bar, it, wg, tid, kb == 0);
            }
            wg_wait<0>();
            for (uint32_t n = 0; u0 == 0u || u1 == 0u; n++) { u0 = ld_strong4(gp); u1 = ld_strong4(gp + 8); if (n > 20000000u) __trap(); }
            __syncwarp();
            const float s0 = 1.0f - __uint_as_float(u0), s1 = 1.0f - __uint_as_float(u1);
            if ((tid & 127) == 0) {
                mbar_arrive(bar + 8 * (G_ST + (it - 1) % G_ST));
                bulk_wait_all();
                const int pt = tile - (int)gridDim.x;
                if (pt >= 0) atomicAdd(&g_hcnt[(pt & 15) + ((pt >> 4) >= H_EARLY ? 16 : 0)], 1u);
            }
            bar_sync(1 + wg, 128);
#pragma unroll
            for (int j = 0; j < 16; j += 2) {
                uint32_t p[4];
#pragma unroll
                for (int q = 0; q < 4; q++) {
                    const int i = (j + (q >> 1)) * 4 + (q & 1) * 2;
                    const float sc = (q & 1) ? s1 : s0;
                    const float g0 = d[i], g1 = d[i + 1];
                    const float a0 = 1.0f + ex2(fminf(g0 * -1.4426950408889634f, 62.0f)), a1 = 1.0f + ex2(fminf(g1 * -1.4426950408889634f, 62.0f));
                    const float rr = rcp(a0 * a1) * sc;
                    const float h0 = (g0 * d[64 + i]) * (rr * a1);
                    const float h1 = (g1 * d[64 + i + 1]) * (rr * a0);
                    p[q] = pack_bf16(h0, h1);
                }
                const int cgp = j + (lane >> 4);
                stsm4(epi + (cgp >> 3) * 8192 + row * 128 + (((cgp & 7) ^ (row & 7)) << 4), p[0], p[1], p[2], p[3]);
            }
            fence_async();
            bar_sync(1 + wg, 128);
            if ((tid & 127) == 0) {
                tma_store(&tm.hs, epi, nb * 128, mb * 128 + wg * 64);
                tma_store(&tm.hs, epi + 8192, nb * 128 + 64, mb * 128 + wg * 64);
                bulk_commit();
            }
        }
        if ((tid & 127) == 0) {
            bulk_wait_all();
            const int pt = blockIdx.x + (G1_TILES - 1 - blockIdx.x) / gridDim.x * gridDim.x;
            atomicAdd(&g_hcnt[(pt & 15) + ((pt >> 4) >= H_EARLY ? 16 : 0)], 1u);
        }
        for (int pass = 0; pass < 4; pass++) {
            for (int i = g1_first(pass); i < g1_count(pass); i += gridDim.x) {
                const int tile = pass == 1 ? i : pass == 3 ? T_MID + (i >> 3) : NFULL + i;
                const int nkb = pass == 0 ? FF / 64 : pass == 1 ? (FF + HD) / 64 : pass == 2 ? HD / 64 : 8;
                for (int kb = 0; kb < nkb; kb++, it++) g_mma_block(d, sb, bar, it, wg, tid, kb == 0);
                wg_wait<0>();
                if ((tid & 127) == 0) mbar_arrive(bar + 8 * (G_ST + (it - 1) % G_ST));
                float4* pre = g_pre + (tile - NFULL) * (32 * 256) + tid;
                if (pass >= 2) { if ((tid & 31) == 0) wait_count(&g_pcnt[tile], 8); __syncwarp(); }
                if (pass == 0) {
#pragma unroll
                    for (int q = 0; q < 32; q++) __stcg(pre + q * 256, make_float4(d[4 * q], d[4 * q + 1], d[4 * q + 2], d[4 * q + 3]));
                    __threadfence();
                    __syncwarp();
                    if ((tid & 31) == 0) atomicAdd(&g_pcnt[tile], 1u);
                } else if (pass == 3) {
                    float4 r[4];
#pragma unroll
                    for (int q = 0; q < 4; q++) r[q] = __ldcg(pre + ((i & 7) * 4 + q) * 256);
                    g_split_finish<8>(d, r, g_sk + (tile - T_MID) * 8 * (16 * 256), tile, i & 7, out, tid);
                } else {
                    if (pass == 2) {
#pragma unroll
                        for (int q = 0; q < 32; q++) {
                            const float4 u = __ldcg(pre + q * 256); d[4 * q] += u.x; d[4 * q + 1] += u.y; d[4 * q + 2] += u.z; d[4 * q + 3] += u.w;
                            if ((q & 7) == 7) __syncwarp();
                        }
                    }
                    g_store_tile(d, &tm.out, epi, tile >> 2, tile & 3, wg, tid);
                }
            }
        }
        if ((tid & 127) == 0) bulk_wait_all();
        KT(1, 1);
    }
    __syncwarp();
    asm volatile("griddepcontrol.wait;" ::: "memory");
}

struct G2Maps { CUtensorMap o, wo; };

__global__ void __launch_bounds__(384, 1) g2_kernel(const __grid_constant__ G2Maps tm, bf16* __restrict__ out) {
    extern __shared__ __align__(1024) unsigned char smem_raw[];
    const uint32_t sb = (smem_u32(smem_raw) + 1023) & ~1023u;
    const int tid = threadIdx.x, lane = tid & 31;
    const int wg = __shfl_sync(0xffffffffu, tid >> 7, 0);
    const int warp = __shfl_sync(0xffffffffu, (tid >> 5) & 3, 0);
    const uint32_t bar = sb + G_BAR;
    const int ks = blockIdx.x & 7, tile = T_LATE + (blockIdx.x >> 3), nb = tile & 3, mb = tile >> 2;
    KT(2, 0);
    if (tid == 0) {
        for (int i = 0; i < G_ST; i++) { mbar_init(bar + 8 * i, 1); mbar_init(bar + 8 * (G_ST + i), 2); }
        fence_async();
        for (int it = 0; it < G_ST; it++) mbar_expect(bar + 8 * it, G_STAGE);
    }
    __syncthreads();
    if (tid < 256 && (tid & 7) == 0) {
        const int it = tid >> 5, q = (tid >> 3) & 3;
        if (it < G_ST) tma_load(sb + it * G_STAGE + 16384 + q * 8192, &tm.wo, nb * 256 + q * 64, (ks * 8 + it) * 64, bar + 8 * it);
        else tma_prefetch(&tm.wo, nb * 256 + q * 64, (ks * 8 + it) * 64);
    }
    __syncwarp();
    PT(16);
    asm volatile("griddepcontrol.wait;" ::: "memory");
    PT(17);
    if (wg == 2) {
        asm volatile("setmaxnreg.dec.sync.aligned.u32 40;");
        if (lane == 0) tma_load(sb + warp * G_STAGE, &tm.o, (ks * 8 + warp) * 64, mb * 128, bar + 8 * warp);
        if (warp == 0 && lane == 0) {
            for (int it = G_ST; it < 8; it++) g_load_block(sb, bar, it, &tm.o, (ks * 8 + it) * 64, mb * 128, &tm.wo, nb * 256);
        } else if (warp == 1) {
            if (blockIdx.x < SEQ / 32) g_gate[blockIdx.x * 32 + lane] = 0u;
            if (blockIdx.x == 0) { if (lane < 16) g_ocnt[lane] = 0u; g_hcnt[lane] = 0u; g_pcnt[lane] = 0u; g_pcnt[32 + lane] = 0u; }
        }
    } else {
        asm volatile("setmaxnreg.inc.sync.aligned.u32 232;");
        float d[128];
        float4 r[4];
        const float4* pre = g_pre + ((tile - NFULL) * 32 + ks * 4) * 256 + tid;
#pragma unroll
        for (int q = 0; q < 4; q++) r[q] = __ldcg(pre + q * 256);
        for (int it = 0; it < 8; it++) { g_mma_block(d, sb, bar, it, wg, tid, it == 0); if (it == 0) PT(18); }
        wg_wait<0>();
        PT(19);
        g_split_finish<8>(d, r, g_sk + (tile - T_MID) * 8 * (16 * 256), tile, ks, out, tid);
        KT(2, 1);
    }
}

typedef CUresult (*EncodeFn)(CUtensorMap*, CUtensorMapDataType, cuuint32_t, void*, const cuuint64_t*, const cuuint64_t*, const cuuint32_t*,
                             const cuuint32_t*, CUtensorMapInterleave, CUtensorMapSwizzle, CUtensorMapL2promotion, CUtensorMapFloatOOBfill);

static void make_map(EncodeFn enc, CUtensorMap* m, const void* ptr, uint64_t rows, uint64_t cols, uint32_t box_rows) {
    cuuint64_t dims[2] = {cols, rows};
    cuuint64_t strides[1] = {cols * 2};
    cuuint32_t box[2] = {64, box_rows};
    cuuint32_t es[2] = {1, 1};
    enc(m, CU_TENSOR_MAP_DATA_TYPE_BFLOAT16, 2, (void*)ptr, dims, strides, box, es, CU_TENSOR_MAP_INTERLEAVE_NONE,
        CU_TENSOR_MAP_SWIZZLE_128B, CU_TENSOR_MAP_L2_PROMOTION_L2_256B, CU_TENSOR_MAP_FLOAT_OOB_FILL_NONE);
}

extern "C" void kernel_launch(void* const* d_in, const int* in_sizes, int n_in, void* d_out, int out_size) {
    (void)in_sizes; (void)n_in; (void)out_size;
    const bf16* x = (const bf16*)d_in[0];
    const bf16* mem0 = (const bf16*)d_in[1];
    const bf16* gate_w = (const bf16*)d_in[11];
    static EncodeFn enc = nullptr;
    static int n_sm = 0;
    static void *pO = nullptr, *pH = nullptr;
    if (!enc) {
        void* fn = nullptr;
        cudaDriverEntryPointQueryResult qr;
        cudaGetDriverEntryPoint("cuTensorMapEncodeTiled", &fn, cudaEnableDefault, &qr);
        enc = (EncodeFn)fn;
        cudaDeviceGetAttribute(&n_sm, cudaDevAttrMultiProcessorCount, 0);
        cudaFuncSetAttribute(r_kernel, cudaFuncAttributeMaxDynamicSharedMemorySize, R_SMEM);
        cudaFuncSetAttribute(g1_kernel, cudaFuncAttributeMaxDynamicSharedMemorySize, G_SMEM);
        cudaFuncSetAttribute(g2_kernel, cudaFuncAttributeMaxDynamicSharedMemorySize, G_SMEM);
        cudaGetSymbolAddress(&pO, g_O);
        cudaGetSymbolAddress(&pH, g_H);
    }
    RMaps rm; G1Maps m1; G2Maps m2;
    make_map(enc, &rm.x, x, SEQ, DM, 32);
    for (int i = 0; i < 3; i++) make_map(enc, &rm.w[i], d_in[2 + i], DM, HD, 64);
    make_map(enc, &rm.wo, d_in[5], HD, DM, 128);
    make_map(enc, &rm.o, pO, SEQ, HD, 16);
    make_map(enc, &m1.x, x, SEQ, DM, 128);
    make_map(enc, &m1.wg, d_in[8], DM, FF, 64);
    make_map(enc, &m1.wu, d_in[9], DM, FF, 64);
    make_map(enc, &m1.hs, pH, SEQ, FF, 64);
    make_map(enc, &m1.o, pO, SEQ, HD, 128);
    make_map(enc, &m1.h, pH, SEQ, FF, 128);
    make_map(enc, &m1.wo, d_in[5], HD, DM, 64);
    make_map(enc, &m1.wd, d_in[10], FF, DM, 64);
    make_map(enc, &m1.out, d_out, SEQ, DM, 64);
    m2.o = m1.o; m2.wo = m1.wo;

    cudaStream_t st = cudaStreamPerThread;
    {
        cudaLaunchConfig_t cfg = {};
        cfg.gridDim = dim3(96); cfg.blockDim = dim3(384); cfg.dynamicSmemBytes = R_SMEM; cfg.stream = st;
        cudaLaunchAttribute at[1];
        at[0].id = cudaLaunchAttributeClusterDimension; at[0].val.clusterDim.x = 3; at[0].val.clusterDim.y = 1; at[0].val.clusterDim.z = 1;
        cfg.attrs = at; cfg.numAttrs = 1;
        cudaLaunchKernelEx(&cfg, r_kernel, rm, mem0, x, gate_w);
    }
    {
        cudaLaunchConfig_t cfg = {};
        cfg.gridDim = dim3(n_sm - 96); cfg.blockDim = dim3(384); cfg.dynamicSmemBytes = G_SMEM; cfg.stream = st;
        cudaLaunchAttribute at[1];
        at[0].id = cudaLaunchAttributeProgrammaticStreamSerialization; at[0].val.programmaticStreamSerializationAllowed = 1;
        cfg.attrs = at; cfg.numAttrs = 1;
        cudaLaunchKernelEx(&cfg, g1_kernel, m1, (bf16*)d_out);
    }
    {
        cudaLaunchConfig_t cfg = {};
        cfg.gridDim = dim3((64 - T_LATE) * 8); cfg.blockDim = dim3(384); cfg.dynamicSmemBytes = G_SMEM; cfg.stream = st;
        cudaLaunchAttribute at[1];
        at[0].id = cudaLaunchAttributeProgrammaticStreamSerialization; at[0].val.programmaticStreamSerializationAllowed = 1;
        cfg.attrs = at; cfg.numAttrs = 1;
        cudaLaunchKernelEx(&cfg, g2_kernel, m2, (bf16*)d_out);
    }
}
```

```cpp
#include <cuda_runtime.h>
#include <cuda_bf16.h>
#include <cuda.h>
#include <stdint.h>

typedef __nv_bfloat16 bf16;

constexpr int SEQ = 2048, DM = 1024, NH = 32, DH = 128, NMEM = 8, SEG = 32, NSEG = 64, FF = 3584;
constexpr int HD = NH * DH;

__device__ bf16 g_O[SEQ * HD];
__device__ bf16 g_H[SEQ * FF];
__device__ uint32_t g_gate[SEQ];
__device__ uint32_t g_part[4][128 * 32 * 32];
__device__ uint32_t g_mem[4][DM * 4];
constexpr int NFULL = 36, T_MID = 44, T_LATE = 48;
constexpr int NPRE = 64 - NFULL;
__device__ float4 g_pre[NPRE * 32 * 256];
__device__ uint4 g_sk[(64 - T_MID) * 8 * 16 * 256];
__device__ uint32_t g_skcnt[64], g_pcnt[64];
__device__ uint32_t g_hcnt[32], g_ocnt[16];
#define KT(k, i)
#define PT(i)

#define DEVINL __device__ __forceinline__
constexpr long long SPIN_LIMIT = 4000000000LL;

DEVINL uint32_t smem_u32(const void* p) { return (uint32_t)__cvta_generic_to_shared(p); }
DEVINL void mbar_init(uint32_t bar, uint32_t cnt) { asm volatile("mbarrier.init.shared::cta.b64 [%0], %1;" ::"r"(bar), "r"(cnt) : "memory"); }
DEVINL void mbar_arrive(uint32_t bar) { asm volatile("mbarrier.arrive.shared::cta.b64 _, [%0];" ::"r"(bar) : "memory"); }
DEVINL void mbar_expect(uint32_t bar, uint32_t bytes) { asm volatile("mbarrier.arrive.expect_tx.shared::cta.b64 _, [%0], %1;" ::"r"(bar), "r"(bytes) : "memory"); }
DEVINL void mbar_arrive_remote(uint32_t cbar) { asm volatile("mbarrier.arrive.relaxed.cluster.shared::cluster.b64 _, [%0];" ::"r"(cbar) : "memory"); }
DEVINL bool mbar_try(uint32_t bar, uint32_t par) {
    uint32_t ok;
    asm volatile("{ .reg .pred p; mbarrier.try_wait.parity.shared::cta.b64 p, [%1], %2; selp.u32 %0, 1, 0, p; }" : "=r"(ok) : "r"(bar), "r"(par) : "memory");
    return ok;
}
__device__ __noinline__ void mbar_wait_slow(uint32_t bar, uint32_t par) {
    long long t0 = clock64();
    while (!mbar_try(bar, par)) { if (clock64() - t0 > SPIN_LIMIT) __trap(); }
}
DEVINL void mbar_wait(uint32_t bar, uint32_t par) {
    uint32_t n = 0;
    while (!mbar_try(bar, par)) { if (++n > 200000000u) __trap(); }
}
DEVINL uint32_t mapa(uint32_t a, uint32_t r) { uint32_t o; asm volatile("mapa.shared::cluster.u32 %0, %1, %2;" : "=r"(o) : "r"(a), "r"(r)); return o; }
DEVINL void fence_async() { asm volatile("fence.proxy.async.shared::cta;" ::: "memory"); }
DEVINL void bar_sync(int id, int n) { asm volatile("bar.sync %0, %1;" ::"r"(id), "r"(n) : "memory"); }
DEVINL void cluster_sync() { asm volatile("barrier.cluster.arrive.aligned; barrier.cluster.wait.aligned;" ::: "memory"); }
DEVINL void tma_load(uint32_t dst, const CUtensorMap* tm, int c0, int c1, uint32_t bar) {
    asm volatile("cp.async.bulk.tensor.2d.shared::cluster.global.mbarrier::complete_tx::bytes [%0], [%1, {%3, %4}], [%2];"
                 ::"r"(dst), "l"(tm), "r"(bar), "r"(c0), "r"(c1) : "memory");
}
DEVINL void tma_prefetch(const CUtensorMap* tm, int c0, int c1) {
    asm volatile("cp.async.bulk.prefetch.tensor.2d.L2.global [%0, {%1, %2}];" ::"l"(tm), "r"(c0), "r"(c1) : "memory");
}
DEVINL void tma_store(const CUtensorMap* tm, uint32_t src, int c0, int c1) {
    asm volatile("cp.async.bulk.tensor.2d.global.shared::cta.bulk_group [%0, {%2, %3}], [%1];" ::"l"(tm), "r"(src), "r"(c0), "r"(c1) : "memory");
}
DEVINL void bulk_commit() { asm volatile("cp.async.bulk.commit_group;" ::: "memory"); }
DEVINL void bulk_wait_read() { asm volatile("cp.async.bulk.wait_group.read 0;" ::: "memory"); }
DEVINL void bulk_wait_all() { asm volatile("cp.async.bulk.wait_group 0;" ::: "memory"); }
DEVINL void bulk_s2s(uint32_t cdst, uint32_t src, uint32_t bytes, uint32_t cbar) {
    asm volatile("cp.async.bulk.shared::cluster.shared::cta.mbarrier::complete_tx::bytes [%0], [%1], %2, [%3];" ::"r"(cdst), "r"(src), "r"(bytes), "r"(cbar) : "memory");
}
DEVINL void st_async16(uint32_t cdst, uint4 v, uint32_t cbar) {
    asm volatile("st.async.shared::cluster.mbarrier::complete_tx::bytes.v4.b32 [%0], {%1,%2,%3,%4}, [%5];" ::"r"(cdst), "r"(v.x), "r"(v.y), "r"(v.z), "r"(v.w), "r"(cbar) : "memory");
}
DEVINL uint64_t mkdesc(uint32_t addr, uint32_t lbo, uint32_t sbo, uint32_t swz) {
    return (uint64_t)((addr & 0x3FFFF) >> 4) | ((uint64_t)(lbo >> 4) << 16) | ((uint64_t)(sbo >> 4) << 32) | ((uint64_t)swz << 62);
}
constexpr uint32_t SB0 = 1024;
__host__ __device__ constexpr uint64_t cdesc(uint32_t off, uint32_t lbo, uint32_t sbo, uint32_t swz) {
    return (uint64_t)(((SB0 + off) & 0x3FFFF) >> 4) | ((uint64_t)(lbo >> 4) << 16) | ((uint64_t)(sbo >> 4) << 32) | ((uint64_t)swz << 62);
}
DEVINL float rcp(float x) { float y; asm("rcp.approx.ftz.f32 %0, %1;" : "=f"(y) : "f"(x)); return y; }
DEVINL float ex2(float x) { float y; asm("ex2.approx.ftz.f32 %0, %1;" : "=f"(y) : "f"(x)); return y; }
DEVINL void spin_clk(int d) { uint32_t t0, t1; asm volatile("mov.u32 %0, %%clock;" : "=r"(t0)); do { asm volatile("mov.u32 %0, %%clock;" : "=r"(t1)); } while ((int)(t1 - t0) < d); }
#define PROBE_GAP 150
#define OPAQUE(x) asm volatile("" : "+r"(x))
DEVINL void wg_fence() { asm volatile("wgmma.fence.sync.aligned;" ::: "memory"); }
DEVINL void wg_commit() { asm volatile("wgmma.commit_group.sync.aligned;" ::: "memory"); }
template <int N> DEVINL void wg_wait() { asm volatile("wgmma.wait_group.sync.aligned %0;" ::"n"(N) : "memory"); }
DEVINL uint32_t pack_bf16(float lo, float hi) { uint32_t r; asm("cvt.rn.bf16x2.f32 %0, %1, %2;" : "=r"(r) : "f"(hi), "f"(lo)); return r; }
DEVINL void ldsm4(uint32_t* r, uint32_t a) { asm volatile("ldmatrix.sync.aligned.m8n8.x4.shared.b16 {%0,%1,%2,%3}, [%4];" : "=r"(r[0]), "=r"(r[1]), "=r"(r[2]), "=r"(r[3]) : "r"(a) : "memory"); }
DEVINL void ldsm4t(uint32_t* r, uint32_t a) { asm volatile("ldmatrix.sync.aligned.m8n8.x4.trans.shared.b16 {%0,%1,%2,%3}, [%4];" : "=r"(r[0]), "=r"(r[1]), "=r"(r[2]), "=r"(r[3]) : "r"(a) : "memory"); }
DEVINL void ldsm4t_if(uint32_t* r, uint32_t a, int c) { asm volatile("{ .reg .pred p; setp.ne.s32 p, %5, 0; @p ldmatrix.sync.aligned.m8n8.x4.trans.shared.b16 {%0,%1,%2,%3}, [%4]; }" : "+r"(r[0]), "+r"(r[1]), "+r"(r[2]), "+r"(r[3]) : "r"(a), "r"(c) : "memory"); }
DEVINL void stsm4(uint32_t a, uint32_t r0, uint32_t r1, uint32_t r2, uint32_t r3) { asm volatile("stmatrix.sync.aligned.m8n8.x4.shared.b16 [%0], {%1,%2,%3,%4};" ::"r"(a), "r"(r0), "r"(r1), "r"(r2), "r"(r3) : "memory"); }
DEVINL void stsm4t(uint32_t a, uint32_t r0, uint32_t r1, uint32_t r2, uint32_t r3) { asm volatile("stmatrix.sync.aligned.m8n8.x4.trans.shared.b16 [%0], {%1,%2,%3,%4};" ::"r"(a), "r"(r0), "r"(r1), "r"(r2), "r"(r3) : "memory"); }
DEVINL void sts32(uint32_t a, uint32_t v) { asm volatile("st.shared.b32 [%0], %1;" ::"r"(a), "r"(v) : "memory"); }
DEVINL void sts128(uint32_t a, uint4 v) { asm volatile("st.shared.v4.b32 [%0], {%1,%2,%3,%4};" ::"r"(a), "r"(v.x), "r"(v.y), "r"(v.z), "r"(v.w) : "memory"); }
DEVINL uint4 lds128(uint32_t a) { uint4 v; asm volatile("ld.shared.v4.b32 {%0,%1,%2,%3}, [%4];" : "=r"(v.x), "=r"(v.y), "=r"(v.z), "=r"(v.w) : "r"(a) : "memory"); return v; }
DEVINL uint4 ld_strong16(const void* p) { uint4 v; asm volatile("ld.relaxed.gpu.global.v4.u32 {%0,%1,%2,%3}, [%4];" : "=r"(v.x), "=r"(v.y), "=r"(v.z), "=r"(v.w) : "l"(p) : "memory"); return v; }
DEVINL void st_strong8(void* p, uint32_t a, uint32_t b) { asm volatile("st.relaxed.gpu.global.v2.u32 [%0], {%1,%2};" ::"l"(p), "r"(a), "r"(b) : "memory"); }
DEVINL void st_strong4(void* p, uint32_t a) { asm volatile("st.relaxed.gpu.global.u32 [%0], %1;" ::"l"(p), "r"(a) : "memory"); }
DEVINL void st_strong16(void* p, uint4 v) { asm volatile("st.relaxed.gpu.global.v4.u32 [%0], {%1,%2,%3,%4};" ::"l"(p), "r"(v.x), "r"(v.y), "r"(v.z), "r"(v.w) : "memory"); }
DEVINL uint32_t pack_nz(float lo, float hi) { uint32_t r = pack_bf16(lo, hi); return r == 0u ? 0x8000u : r; }
DEVINL uint32_t min4(uint4 v, uint32_t m) { return __vimin3_u32(__vimin3_u32(v.x, v.y, m), v.z, v.w); }
DEVINL void mma16816(float* d, uint32_t a0, uint32_t a1, uint32_t a2, uint32_t a3, uint32_t b0, uint32_t b1) {
    asm volatile("mma.sync.aligned.m16n8k16.row.col.f32.bf16.bf16.f32 {%0,%1,%2,%3}, {%4,%5,%6,%7}, {%8,%9}, {%0,%1,%2,%3};"
                 : "+f"(d[0]), "+f"(d[1]), "+f"(d[2]), "+f"(d[3]) : "r"(a0), "r"(a1), "r"(a2), "r"(a3), "r"(b0), "r"(b1));
}
DEVINL void mma1688(float* d, uint32_t a0, uint32_t a1, uint32_t b0) {
    asm volatile("mma.sync.aligned.m16n8k8.row.col.f32.bf16.bf16.f32 {%0,%1,%2,%3}, {%4,%5}, {%6}, {%0,%1,%2,%3};"
                 : "+f"(d[0]), "+f"(d[1]), "+f"(d[2]), "+f"(d[3]) : "r"(a0), "r"(a1), "r"(b0));
}
template <int TA, int TB> DEVINL void wg_ss8(float* d, uint64_t da, uint64_t db, int sc) {
    asm volatile("{ .reg .pred p; setp.ne.b32 p, %6, 0; wgmma.mma_async.sync.aligned.m64n8k16.f32.bf16.bf16 {%0,%1,%2,%3}, %4, %5, p, 1, 1, %7, %8; }"
                 : "+f"(d[0]), "+f"(d[1]), "+f"(d[2]), "+f"(d[3]) : "l"(da), "l"(db), "r"(sc), "n"(TA), "n"(TB));
}
template <int TB> DEVINL void wg_rs8(float* d, const uint32_t* a, uint64_t db, int sc) {
    asm volatile("{ .reg .pred p; setp.ne.b32 p, %9, 0; wgmma.mma_async.sync.aligned.m64n8k16.f32.bf16.bf16 {%0,%1,%2,%3}, {%4,%5,%6,%7}, %8, p, 1, 1, %10; }"
                 : "+f"(d[0]), "+f"(d[1]), "+f"(d[2]), "+f"(d[3]) : "r"(a[0]), "r"(a[1]), "r"(a[2]), "r"(a[3]), "l"(db), "r"(sc), "n"(TB));
}
#define ACC16(d) "+f"(d[0]), "+f"(d[1]), "+f"(d[2]), "+f"(d[3]), "+f"(d[4]), "+f"(d[5]), "+f"(d[6]), "+f"(d[7]), "+f"(d[8]), "+f"(d[9]), "+f"(d[10]), "+f"(d[11]), "+f"(d[12]), "+f"(d[13]), "+f"(d[14]), "+f"(d[15])
template <int TA> DEVINL void wg_ss32(float* d, uint64_t da, uint64_t db, int sc) {
    asm volatile("{ .reg .pred p; setp.ne.b32 p, %18, 0; wgmma.mma_async.sync.aligned.m64n32k16.f32.bf16.bf16 {%0,%1,%2,%3,%4,%5,%6,%7,%8,%9,%10,%11,%12,%13,%14,%15}, %16, %17, p, 1, 1, %19, 0; }"
                 : ACC16(d) : "l"(da), "l"(db), "r"(sc), "n"(TA));
}
DEVINL void wg_rs32(float* d, const uint32_t* a, uint64_t db, int sc) {
    asm volatile("{ .reg .pred p; setp.ne.b32 p, %21, 0; wgmma.mma_async.sync.aligned.m64n32k16.f32.bf16.bf16 {%0,%1,%2,%3,%4,%5,%6,%7,%8,%9,%10,%11,%12,%13,%14,%15}, {%16,%17,%18,%19}, %20, p, 1, 1, 0; }"
                 : ACC16(d) : "r"(a[0]), "r"(a[1]), "r"(a[2]), "r"(a[3]), "l"(db), "r"(sc));
}
DEVINL void wg_ss40(float* d, uint64_t da, uint64_t db, int sc) {
    asm volatile("{ .reg .pred p; setp.ne.b32 p, %22, 0; wgmma.mma_async.sync.aligned.m64n40k16.f32.bf16.bf16 {%0,%1,%2,%3,%4,%5,%6,%7,%8,%9,%10,%11,%12,%13,%14,%15,%16,%17,%18,%19}, %20, %21, p, 1, 1, 1, 1; }"
                 : ACC16(d), "+f"(d[16]), "+f"(d[17]), "+f"(d[18]), "+f"(d[19]) : "l"(da), "l"(db), "r"(sc));
}
#define A8(d, o) "+f"(d[o]), "+f"(d[o + 1]), "+f"(d[o + 2]), "+f"(d[o + 3]), "+f"(d[o + 4]), "+f"(d[o + 5]), "+f"(d[o + 6]), "+f"(d[o + 7])
#define A32(d, o) A8(d, o), A8(d, o + 8), A8(d, o + 16), A8(d, o + 24)
DEVINL void wg_ss256(float* d, uint64_t da, uint64_t db, int sc) {
    asm volatile(
        "{ .reg .pred p; setp.ne.b32 p, %130, 0;\n"
        "wgmma.mma_async.sync.aligned.m64n256k16.f32.bf16.bf16 {"
        "%0,%1,%2,%3,%4,%5,%6,%7,%8,%9,%10,%11,%12,%13,%14,%15,%16,%17,%18,%19,%20,%21,%22,%23,%24,%25,%26,%27,%28,%29,%30,%31,"
        "%32,%33,%34,%35,%36,%37,%38,%39,%40,%41,%42,%43,%44,%45,%46,%47,%48,%49,%50,%51,%52,%53,%54,%55,%56,%57,%58,%59,%60,%61,%62,%63,"
        "%64,%65,%66,%67,%68,%69,%70,%71,%72,%73,%74,%75,%76,%77,%78,%79,%80,%81,%82,%83,%84,%85,%86,%87,%88,%89,%90,%91,%92,%93,%94,%95,"
        "%96,%97,%98,%99,%100,%101,%102,%103,%104,%105,%106,%107,%108,%109,%110,%111,%112,%113,%114,%115,%116,%117,%118,%119,%120,%121,%122,%123,%124,%125,%126,%127"
        "}, %128, %129, p, 1, 1, 0, 1; }"
        : A32(d, 0), A32(d, 32), A32(d, 64), A32(d, 96) : "l"(da), "l"(db), "r"(sc));
}

DEVINL float gate_row(const uint4 (&xv)[4], const uint4 (&gv)[4]) {
    float acc = 0.f;
#pragma unroll
    for (int i = 0; i < 4; i++) {
        const uint32_t xa[4] = {xv[i].x, xv[i].y, xv[i].z, xv[i].w}, ga[4] = {gv[i].x, gv[i].y, gv[i].z, gv[i].w};
#pragma unroll
        for (int e = 0; e < 4; e++) {
            acc = fmaf(__uint_as_float(xa[e] << 16), __uint_as_float(ga[e] << 16), acc);
            acc = fmaf(__uint_as_float(xa[e] & 0xffff0000u), __uint_as_float(ga[e] & 0xffff0000u), acc);
        }
    }
#pragma unroll
    for (int o = 16; o > 0; o >>= 1) acc += __shfl_xor_sync(0xffffffffu, acc, o);
    return 1.0f / (1.0f + __expf(-acc));
}
DEVINL uint4 ldg_nc(const void* p) { uint4 v; asm volatile("ld.global.nc.v4.u32 {%0,%1,%2,%3}, [%4];" : "=r"(v.x), "=r"(v.y), "=r"(v.z), "=r"(v.w) : "l"(p) : "memory"); return v; }
DEVINL uint32_t ld_strong4(const void* p) { uint32_t v; asm volatile("ld.relaxed.gpu.global.u32 %0, [%1];" : "=r"(v) : "l"(p) : "memory"); return v; }
DEVINL void wait_count(const uint32_t* p, uint32_t want) {
    uint32_t v, n = 0;
    while (true) {
        asm volatile("ld.acquire.gpu.global.u32 %0, [%1];" : "=r"(v) : "l"(p) : "memory");
        if (v >= want) break;
        __nanosleep(200);
        if (++n > 10000000u) __trap();
    }
}

constexpr int KR = 44;
constexpr int KS = 64 - KR;
constexpr int R_W = 0;
constexpr int R_WO = KS * 4096;
constexpr int R_QX = R_WO + 65536;
constexpr int R_RING = R_WO + 98304;
constexpr int R_K = R_RING + 24576;
constexpr int R_V = R_K + 10240;
constexpr int R_QM = R_V + 10240;
constexpr int R_O = R_QM + 2048;
constexpr int R_BAR = R_O + 2048;
constexpr int R_G = R_BAR + 256 + 512 + 256 + 128;
constexpr int R_Z = R_G + 256;
constexpr int R_SMEM = R_Z + 1024;
enum { B_FULL = 0, B_EMPTY = 5, B_MEM = 8, B_HOP1 = 12, B_XT, B_TFREE, B_O, B_AFREE0, B_AFREE1, B_PRO0, B_PRO1, B_XRECV, B_P, B_XDONE, B_OST0, B_OST1, B_HOPV };
#define D2_BASE 900
#define D2_STEP 200
#define PD2 6
#define CPB 8192
#define DDUP 0
#define WGAP 0
#define PVD 400
#define ELD 700
#define QD 3
#define DQ 1700
#define D3 0

DEVINL uint32_t clk32() { uint32_t c_; asm volatile("mov.u32 %0, %%clock;" : "=r"(c_)); return c_; }
DEVINL void spin_until(uint32_t t) { while ((uint32_t)(t - clk32() - 1u) < 100000u) {} }
#define PROF(i)
#define PROF2(i)
#define PROF3(i, val)
DEVINL void e_arrive(uint32_t bar) { asm volatile("{ .reg .pred p; elect.sync _|p, 0xffffffff; @p mbarrier.arrive.shared::cta.b64 _, [%0]; }" ::"r"(bar) : "memory"); }
DEVINL void e_arrive_remote(uint32_t cbar) { asm volatile("{ .reg .pred p; elect.sync _|p, 0xffffffff; @p mbarrier.arrive.relaxed.cluster.shared::cluster.b64 _, [%0]; }" ::"r"(cbar) : "memory"); }
DEVINL void e_count(uint32_t* p) { asm volatile("{ .reg .pred p; elect.sync _|p, 0xffffffff; @p red.relaxed.gpu.global.add.u32 [%0], 1; }" ::"l"(p) : "memory"); }
DEVINL void e_expect(uint32_t bar, uint32_t bytes) { asm volatile("{ .reg .pred p; elect.sync _|p, 0xffffffff; @p mbarrier.arrive.expect_tx.shared::cta.b64 _, [%0], %1; }" ::"r"(bar), "r"(bytes) : "memory"); }
DEVINL void e_tma_load(uint32_t dst, const CUtensorMap* tm, int c0, int c1, uint32_t bar) {
    asm volatile("{ .reg .pred p; elect.sync _|p, 0xffffffff; @p cp.async.bulk.tensor.2d.shared::cluster.global.mbarrier::complete_tx::bytes [%0], [%1, {%3, %4}], [%2]; }"
                 ::"r"(dst), "l"(tm), "r"(bar), "r"(c0), "r"(c1) : "memory");
}
DEVINL void e_tma_store(const CUtensorMap* tm, uint32_t src, int c0, int c1) {
    asm volatile("{ .reg .pred p; elect.sync _|p, 0xffffffff; @p cp.async.bulk.tensor.2d.global.shared::cta.bulk_group [%0, {%2, %3}], [%1]; }" ::"l"(tm), "r"(src), "r"(c0), "r"(c1) : "memory");
}
DEVINL void e_bulk_s2g(void* dst, uint32_t src, uint32_t bytes) {
    asm volatile("{ .reg .pred p; elect.sync _|p, 0xffffffff; @p cp.async.bulk.global.shared::cta.bulk_group [%0], [%1], %2; }" ::"l"(dst), "r"(src), "r"(bytes) : "memory");
}
DEVINL void e_bulk_s2s(uint32_t cdst, uint32_t src, uint32_t bytes, uint32_t cbar) {
    asm volatile("{ .reg .pred p; elect.sync _|p, 0xffffffff; @p cp.async.bulk.shared::cluster.shared::cta.mbarrier::complete_tx::bytes [%0], [%1], %2, [%3]; }" ::"r"(cdst), "r"(src), "r"(bytes), "r"(cbar) : "memory");
}

#define SLOT 0
#define PH3 0
#define PHQ 0
DEVINL void wait_slot(uint32_t phase) {
    if (SLOT) {
        uint32_t c; asm volatile("mov.u32 %0, %%globaltimer_lo;" : "=r"(c));
        const uint32_t tgt = c + (SLOT ? SLOT : 1) - ((c - phase) % (SLOT ? SLOT : 1));
        do { asm volatile("mov.u32 %0, %%globaltimer_lo;" : "=r"(c)); } while ((uint32_t)(tgt - c - 1u) < 100000u);
    }
}
template <int N> DEVINL uint32_t poll_set(uint4 (&v)[N], const uint32_t* rp, int stride, uint32_t phase, uint32_t wbar = 0, uint32_t wpar = 0) {
    wait_slot(phase);
#pragma unroll
    for (int i = 0; i < N; i++) v[i] = ld_strong16(rp + i * stride);
    if (wbar) mbar_wait(wbar, wpar);
    uint32_t n = 0;
    while (true) {
        uint32_t m = 0xffffffffu;
#pragma unroll
        for (int i = 0; i < N; i++) m = min4(v[i], m);
        if (__all_sync(0xffffffffu, m != 0u)) return n;
        wait_slot(phase);
#pragma unroll
        for (int i = 0; i < N; i++)
            asm volatile("{ .reg .pred p; setp.eq.u32 p, %5, 0; @p ld.relaxed.gpu.global.v4.u32 {%0,%1,%2,%3}, [%4]; }"
                         : "+r"(v[i].x), "+r"(v[i].y), "+r"(v[i].z), "+r"(v[i].w) : "l"(rp + i * stride), "r"(min4(v[i], 0xffffffffu)) : "memory");
        if (++n > 20000000u) __trap();
    }
}

struct RMaps { CUtensorMap x, w[3], wo, o; };
#define KC(c) ((c) * 64)

#define XORD 3
__host__ __device__ constexpr int xo(int i) {
    return XORD == 0 ? i : XORD == 1 ? (i + 14) % 16 : XORD == 2 ? (i + 11) % 16
         : XORD == 3 ? (i < 10 ? ((i & 1) ? i / 2 : 11 + i / 2) : i - 5) : (i < 6 ? i : ((i & 1) ? 6 + (i - 6) / 2 : 11 + (i - 6) / 2));
}
#define XC(i) (xo(i) * 64)
DEVINL void x_load_pair(uint32_t dst, const CUtensorMap* tmx, int h, int p, int seg, uint32_t fbar) {
    e_expect(fbar, 8192);
    e_tma_load(dst, tmx, XC(2 * p), seg * SEG, fbar);
    e_tma_load(dst + 4096, tmx, XC(2 * p + 1), seg * SEG, fbar);
}
__host__ __device__ constexpr int wo_tile(int role, int i) {
    return role == 0 ? (i < 2 ? 8 + i : 12 + i) : (i < 4 ? (i >> 1) * 4 : 10) + (role - 1) * 2 + (i & 1);
}

template <int NT> DEVINL void wo_phase(uint32_t sb, int tb, uint32_t* pp, uint32_t obar, uint32_t opar) {
    const int lane = tb & 31, krow = (lane & 7) + ((lane >> 4) << 3), chunk = ((tb >> 5) & 3) * 2 + ((lane >> 3) & 1);
    uint32_t wa = sb + R_WO + (tb >> 7) * 16384 + krow * 128 + ((chunk ^ (krow & 7)) << 4);
    uint32_t af[4][4], of[4][4];
#pragma unroll
    for (int g = 0; g < 4; g++) ldsm4t(af[g], wa + g * 2048);
    mbar_wait(obar, opar);
#pragma unroll
    for (int g = 0; g < 4; g++) ldsm4t(of[g], sb + R_O + g * 512 + lane * 16);
#pragma unroll 1
    for (int i = 0; i < NT; i++) {
        float w0[4] = {0.f, 0.f, 0.f, 0.f}, w1[4] = {0.f, 0.f, 0.f, 0.f};
        const int more = NT - 1 - i, yes = NT - i;
        mma16816(w0, af[0][0], af[0][1], af[0][2], af[0][3], of[0][0], of[0][1]);
        ldsm4t_if(af[0], wa + 4 * 2048, yes);
        mma16816(w1, af[1][0], af[1][1], af[1][2], af[1][3], of[0][2], of[0][3]);
        ldsm4t_if(af[1], wa + 5 * 2048, yes);
        mma16816(w0, af[2][0], af[2][1], af[2][2], af[2][3], of[1][0], of[1][1]);
        ldsm4t_if(af[2], wa + 6 * 2048, yes);
        mma16816(w1, af[3][0], af[3][1], af[3][2], af[3][3], of[1][2], of[1][3]);
        ldsm4t_if(af[3], wa + 7 * 2048, yes);
        wa += 32768;
        mma16816(w0, af[0][0], af[0][1], af[0][2], af[0][3], of[2][0], of[2][1]);
        ldsm4t_if(af[0], wa, more);
        mma16816(w1, af[1][0], af[1][1], af[1][2], af[1][3], of[2][2], of[2][3]);
        ldsm4t_if(af[1], wa + 2048, more);
        mma16816(w0, af[2][0], af[2][1], af[2][2], af[2][3], of[3][0], of[3][1]);
        ldsm4t_if(af[2], wa + 2 * 2048, more);
        mma16816(w1, af[3][0], af[3][1], af[3][2], af[3][3], of[3][2], of[3][3]);
        ldsm4t_if(af[3], wa + 3 * 2048, more);
        st_strong4(pp, pack_nz(w0[0] + w1[0], w0[1] + w1[1]));
        st_strong4(pp + 1024, pack_nz(w0[2] + w1[2], w0[3] + w1[3]));
        pp += (NT == 3 && i == 0) ? 4 * 8192 : 6 * 8192;
    }
}

template <uint32_t role> DEVINL void r_big(const RMaps& tm, const int wid) {
    extern __shared__ __align__(1024) unsigned char smem_raw[];
    const uint32_t sb = smem_u32(smem_raw);
    const uint32_t bar = sb + R_BAR;
    const int tid = threadIdx.x;
    int h; asm("mov.u32 %0, %%clusterid.x;" : "=r"(h));
        uint32_t a[KR][4];
        mbar_wait(bar + 8 * B_PRO0, 0);
        PT(0);
        {
            const int lane = tid & 31;
            const int krow = (lane & 7) + ((lane >> 4) << 3);
            const int chunk = (wid & 3) * 2 + ((lane >> 3) & 1);
            const uint32_t la = sb + (wid >> 2) * 8192 + krow * 128 + ((chunk ^ (krow & 7)) << 4);
#pragma unroll
            for (int k = 0; k < KR; k++) ldsm4t(a[k], la + (k >> 2) * 16384 + (k & 3) * 2048);
        }
        bar_sync(1, 256);
        {
            fence_async();
            const CUtensorMap* tw = &tm.w[role];
            e_expect(bar + 8 * B_PRO1, (wid < 5 ? 16384 : 0) + (wid < (role == 0 ? 4 : 6) ? 16384 : 0));
            if (wid < 5) {
                e_tma_load(sb + R_W + wid * 8192, tw, h * DH, KC(KR / 4 + wid), bar + 8 * B_PRO1);
                e_tma_load(sb + R_W + KS * 2048 + wid * 8192, tw, h * DH + 64, KC(KR / 4 + wid), bar + 8 * B_PRO1);
            }
            if (wid < (role == 0 ? 4 : 6)) e_tma_load(sb + R_WO + wid * 16384, &tm.wo, wo_tile(role, wid) * 64, h * DH, bar + 8 * B_PRO1);
        }
        constexpr uint32_t e0 = role == 0 ? R_QX + 16384 : R_K + 2048, e1 = role == 0 ? R_QX + 24576 : R_V + 2048;
        if (wid == 6) x_load_pair(sb + e0, &tm.x, h, 3, 0, bar + 8 * (B_FULL + 3));
        if (wid == 7) x_load_pair(sb + e1, &tm.x, h, 4, 0, bar + 8 * (B_FULL + 4));
        PT(1);
        mbar_wait(bar + 8 * B_PRO1, 0);
        PT(2);

        constexpr uint64_t dW0 = cdesc(R_W, 1024, 1024, 1);
        constexpr uint64_t dM = cdesc(R_RING, 128, 128, 0);
        constexpr uint64_t dX = cdesc(R_RING, 16, 1024, 1);
        constexpr uint64_t dX0 = cdesc(0, 16, 1024, 1);
        int tb = tid;
        int wq = wid;

        for (int seg = 0; seg < NSEG; seg++) {
            {
            const int s = seg - 1; (void)s;
            float d[16];
            OPAQUE(wq);
            const uint64_t dW = dW0 + (uint64_t)((wq >> 2) * (KS * 128));
#pragma unroll
            for (int p = 0; p < 8; p++) {
                const int slot = p % 5;
                mbar_wait(bar + 8 * (B_FULL + slot), slot < 3 ? (uint32_t)(p / 5) : (uint32_t)(seg & 1));
                PROF2(p);
                const uint64_t db = slot < 3 ? dX + (uint64_t)(slot * 512) : dX0 + (uint64_t)((slot == 3 ? e0 : e1) >> 4);
                wg_fence();
#pragma unroll
                for (int kk = 0; kk < 8; kk++) {
                    const int k = XORD >= 3 ? (kk & 1) * 4 + (kk >> 1) : kk;
                    const int ks = xo(2 * p + (k >> 2)) * 4 + (k & 3);
                    if (ks >= KR) wg_ss32<1>(d, dW + (uint64_t)((ks - KR) * 128), db + (uint64_t)((k >> 2) * 256 + (k & 3) * 2), p + k);
                    else wg_rs32(d, a[ks < KR ? ks : 0], db + (uint64_t)((k >> 2) * 256 + (k & 3) * 2), p + k);
                }
                wg_commit();
                if (p >= 1) {
                    wg_wait<1>();
                    if (p <= 3) {
                        if ((wq & 3) == p) e_arrive(bar + 8 * (B_EMPTY + p - 1));
                        if (wq == p + (p & 1) * 4) {
                            mbar_wait(bar + 8 * (B_EMPTY + p - 1), seg & 1);
                            x_load_pair(sb + R_RING + (p - 1) * 8192, &tm.x, h, p + 4, seg, bar + 8 * (B_FULL + p - 1));
                        }
                    }
                    if (p == 5 && role != 0 && (wq & 3) < 3) e_arrive_remote(mapa(bar + 8 * B_TFREE, wq & 3));
                    if (p == 6 && (wq & 3) == 1) e_arrive(bar + 8 * B_AFREE0);
                    if (p == 7 && (wq & 3) == 2) e_arrive(bar + 8 * B_AFREE1);
                }
            }
            mbar_wait(bar + 8 * B_TFREE, seg & 1);
            asm volatile("wgmma.wait_group.sync.aligned 0;" : ACC16(d)::"memory");
            PROF2(16);
            const uint32_t tilex = sb + (role == 0 ? R_QX + 2048 : (role == 1 ? R_K + 2048 : R_V + 2048));
            {
                OPAQUE(tb);
                const uint32_t gs = role == 0 ? 4096 : 2048;
                const uint32_t sa = tilex + ((tb >> 4) & 1) * gs + (tb >> 5) * 256 + (tb & 15) * 16;
                stsm4(sa, pack_bf16(d[0], d[1]), pack_bf16(d[2], d[3]), pack_bf16(d[4], d[5]), pack_bf16(d[6], d[7]));
                stsm4(sa + 2 * gs, pack_bf16(d[8], d[9]), pack_bf16(d[10], d[11]), pack_bf16(d[12], d[13]), pack_bf16(d[14], d[15]));
            }
            __syncwarp();
            e_arrive(bar + 8 * B_XDONE);
            if (role != 0 && (wq & 3) == 0) {
                mbar_wait(bar + 8 * B_XDONE, seg & 1);
                fence_async();
                uint32_t pr = role + 1 + (wq >> 2); pr = pr >= 3 ? pr - 3 : pr;
                e_bulk_s2s(mapa(tilex, pr), tilex, CPB, mapa(bar + 8 * B_XT, pr));
            }
            }
            {
                const int s = seg;
                OPAQUE(wq);
                const uint64_t dW = dW0 + (uint64_t)((wq >> 2) * (KS * 128));
                float y[4] = {0.f, 0.f, 0.f, 0.f};
                {
                    OPAQUE(tb);
                    const uint32_t ma = sb + R_RING + (tb & 31) * 16;
                    float z[4] = {0.f, 0.f, 0.f, 0.f}, u[4] = {0.f, 0.f, 0.f, 0.f};
                    uint32_t b[QD][4];
                    const int yes = s + 1;
                    mbar_wait(bar + 8 * B_MEM, s & 1);
                    PROF((wq >> 2) * 4 + 0);
                    if (s == 0) PT(3);
                    if (s == 1) PT(4);
#pragma unroll
                    for (int g = 0; g < QD; g++) ldsm4t(b[g], ma + g * 512);
#pragma unroll
                    for (int g = 0; g < KR / 2; g++) {
                        float* c0 = (g % 3 == 0) ? y : (g % 3 == 1) ? u : z;
                        float* c1 = (g % 3 == 0) ? z : (g % 3 == 1) ? y : u;
                        mma16816(c0, a[2 * g][0], a[2 * g][1], a[2 * g][2], a[2 * g][3], b[g % QD][0], b[g % QD][1]);
                        mma16816(c1, a[2 * g + 1][0], a[2 * g + 1][1], a[2 * g + 1][2], a[2 * g + 1][3], b[g % QD][2], b[g % QD][3]);
                        if (g + QD < KR / 2) {
                            if ((g + QD) % 8 == 0) mbar_wait(bar + 8 * (B_MEM + (g + QD) / 8), s & 1);
                            ldsm4t_if(b[g % QD], ma + (g + QD) * 512, yes);
                        }
                    }
                    y[0] += z[0] + u[0]; y[1] += z[1] + u[1]; y[2] += z[2] + u[2]; y[3] += z[3] + u[3];
                }
                PROF2(8);
                mbar_wait(bar + 8 * (B_MEM + 3), s & 1);
                wg_fence();
#pragma unroll
                for (int k = KR; k < 64; k++) wg_ss8<1, 1>(y, dW + (uint64_t)((k - KR) * 128), dM + (uint64_t)(k * 16), 1);
                wg_commit();
                asm volatile("wgmma.wait_group.sync.aligned 0;" : "+f"(y[0]), "+f"(y[1]), "+f"(y[2]), "+f"(y[3])::"memory");
                OPAQUE(tb);
                {
                    const uint32_t wo_ = (tb >> 5) * 256;
                    const uint32_t tile = sb + (role == 0 ? R_QX : (role == 1 ? R_K : R_V)) + wo_;
                    const uint32_t u0 = pack_bf16(y[0], y[1]), u1 = pack_bf16(y[2], y[3]);
                    sts32(tile + (tb & 31) * 4, u0);
                    sts32(tile + (tb & 31) * 4 + 128, u1);
                    __syncwarp();
                    uint4 v = lds128(tile + (tb & 15) * 16);
                    uint32_t peer = role + 1 + ((tb >> 4) & 1);
                    peer = peer >= 3 ? peer - 3 : peer;
                    const uint32_t rt = sb + (role == 0 ? R_QM : (role == 1 ? R_K : R_V)) + wo_ + (tb & 15) * 16;
                    st_async16(mapa(rt, peer), v, mapa(bar + 8 * (role == 2 ? B_HOPV : B_HOP1), peer));
                    if (role == 0) {
                        sts128(tile + 4096 + ((tb >> 4) & 1) * 4096 + (tb & 15) * 16, v);
                        sts32(tile + 12288 + (tb & 31) * 4, u0);
                        sts32(tile + 12288 + (tb & 31) * 4 + 128, u1);
                        __syncwarp();
                    }
                    e_arrive(bar + 8 * (role == 2 ? B_HOPV : B_HOP1));
                }
                PROF((wq >> 2) * 4 + 1);
                if (s < NSEG - 1) {
                    bar_sync(1, 256);
                    if (wq < 3) { fence_async(); x_load_pair(sb + R_RING + wq * 8192, &tm.x, h, wq, s + 1, bar + 8 * (B_FULL + wq)); }
                    else if (role == 0 && wq < 5) x_load_pair(sb + (wq == 3 ? e0 : e1), &tm.x, h, wq, s + 1, bar + 8 * (B_FULL + wq));
                    OPAQUE(tb);
                }
                uint32_t* pp = g_part[s & 3] + (h * 32 + (wo_tile(role, 0) + (tb >> 7)) * 8192 + ((tb >> 5) & 3) * 2048 + (tb & 31));
                asm volatile("" : "+l"(pp));
                if (s == NSEG - 1) break;
                wo_phase<role == 0 ? 2 : 3>(sb, tb, pp, bar + 8 * B_O, s & 1);
                if (wq == 0) PROF(10);
            }
        }
}

#define CLR 0
#define CLEAR(st) do { if (role != 0) { \
                const int w_ = wid & 3; \
                uint32_t* zp = g_part[(st) & 3] + ((rg0 + (w_ >> 1) * 64) * 1024 + (w_ & 1) * 512); \
                e_bulk_s2g(zp, sb + R_Z, 1024); \
                e_bulk_s2g(zp + 256, sb + R_Z, 1024); \
                e_bulk_s2g(&g_mem[(st) & 3][(rg0 + (w_ >> 1) * 64) * 32 + (w_ & 1) * 16], sb + R_Z, 64); \
                bulk_commit(); } } while (0)
template <uint32_t role> DEVINL void r_chain(const RMaps& tm, const bf16* __restrict__ mem0, const int wid) {
    extern __shared__ __align__(1024) unsigned char smem_raw[];
    const uint32_t sb = smem_u32(smem_raw);
    const uint32_t bar = sb + R_BAR;
    const int tid = threadIdx.x;
    int h; asm("mov.u32 %0, %%clusterid.x;" : "=r"(h));
        int t = tid & 127;
        const float sl2 = 0.08838834764831845f * 1.4426950408889634f;
        const float NEGRAW = -1000000000.0f / 0.08838834764831845f;
        const int rg0 = ((int)role - 1) * 32 + h;
        if (role != 0) {
#pragma unroll 1
            for (int r = 0; r < 4; r++) {
                uint32_t* zp = g_part[r] + ((rg0 + (t >> 6) * 64) * 1024 + (t & 63) * 4);
#pragma unroll
                for (int i = 0; i < 4; i++) st_strong16(zp + i * 256, make_uint4(0u, 0u, 0u, 0u));
                if ((t & 63) < 8) st_strong16(&g_mem[r][(rg0 + (t >> 6) * 64) * 32 + (t & 63) * 4], make_uint4(0u, 0u, 0u, 0u));
            }
            __threadfence();
        }
        if (role == 0 && (wid & 3) < 3) e_arrive_remote(mapa(bar + 8 * B_TFREE, wid & 3));
        if (t < 64) sts128(sb + R_Z + t * 16, make_uint4(0u, 0u, 0u, 0u));
        if (role == 0) sts128(sb + R_QM + t * 16, make_uint4(0u, 0u, 0u, 0u));
        {
            uint4 v[8];
#pragma unroll
            for (int r = 0; r < 8; r++) v[r] = __ldg((const uint4*)(mem0 + r * DM) + t);
            mbar_wait(bar + 8 * B_AFREE0, 0);
            mbar_wait(bar + 8 * B_AFREE1, 0);
#define TR2(f, c) \
            sts128(sb + R_RING + t * 128 + (c) * 16, make_uint4(__byte_perm(v[0].f, v[1].f, 0x5410), __byte_perm(v[2].f, v[3].f, 0x5410), __byte_perm(v[4].f, v[5].f, 0x5410), __byte_perm(v[6].f, v[7].f, 0x5410))); \
            sts128(sb + R_RING + t * 128 + (c) * 16 + 16, make_uint4(__byte_perm(v[0].f, v[1].f, 0x7632), __byte_perm(v[2].f, v[3].f, 0x7632), __byte_perm(v[4].f, v[5].f, 0x7632), __byte_perm(v[6].f, v[7].f, 0x7632)));
            TR2(x, 0) TR2(y, 2) TR2(z, 4) TR2(w, 6)
            fence_async();
            __syncwarp();
            e_arrive(bar + 8 * B_MEM + (t >> 5) * 8);
        }
        constexpr uint64_t dQ = role == 0 ? cdesc(R_QX, 128, 2048, 0) : cdesc(R_QM, 128, 0, 0);
        constexpr uint64_t dK = cdesc(R_K, 128, 2048, 0);

        for (int s = 0; s < NSEG; s++) {
            if (role == 0) {
                uint32_t n = 0, gate;
                do { gate = ld_strong4(&g_gate[s * SEG + (t >> 2)]); if (++n > 20000000u) __trap(); } while (gate == 0u);
                sts32(sb + R_G + (t >> 2) * 4, gate);
                __syncwarp();
            }
            mbar_wait(bar + 8 * B_XDONE, s & 1);
            mbar_wait(bar + 8 * B_XT, s & 1);
            if (t >= 1 && t < 3) { uint32_t pr = role + t; pr = pr >= 3 ? pr - 3 : pr; mbar_arrive_remote(mapa(bar + 8 * B_XRECV, pr)); }
            __syncwarp();
            mbar_wait(bar + 8 * B_HOP1, s & 1);
            PROF(8);
            fence_async();
            OPAQUE(t);
            if (s == NSEG - 1 && role != 0) { mbar_wait(bar + 8 * B_HOPV, s & 1); bulk_wait_all(); break; }
            float sc[20];
            wg_fence();
#pragma unroll
            for (int k = 0; k < 8; k++) wg_ss40(sc, dQ + (uint64_t)(k * 16), dK + (uint64_t)(k * 16), k);
            wg_commit();
            uint32_t t_o = clk32() + 500;
            {
                const uint32_t va = sb + R_V + 2048 + (t >> 5) * 512 + ((t >> 4) & 1) * 2048 + (t & 15) * 16;
                uint32_t v0[4], v1[4];
                ldsm4(v0, va); ldsm4(v1, va + 256);
                uint32_t vm[4];
                const bool v_here = mbar_try(bar + 8 * B_HOPV, s & 1);
                if (v_here) ldsm4(vm, sb + R_V + t * 16);
                wg_wait<0>();
                if (role == 0) {
#pragma unroll
                    for (int j = 0; j < 5; j++)
                        asm volatile("st.shared.v2.f32 [%0], {%1,%2};" ::"r"(sb + R_QX + 768 + (t >> 5) * 4096 + j * 256 + (t & 31) * 8), "f"(sc[4 * j + 2]), "f"(sc[4 * j + 3]) : "memory");
                }
                float m = fmaxf(sc[0], sc[1]);
#pragma unroll
                for (int j = 1; j < 5; j++) m = fmaxf(m, fmaxf(sc[4 * j], sc[4 * j + 1]));
                m = fmaxf(m, __shfl_xor_sync(0xffffffffu, m, 1));
                m = fmaxf(m, __shfl_xor_sync(0xffffffffu, m, 2));
                const float mb = m * sl2;
                uint32_t pk[5];
#pragma unroll
                for (int j = 0; j < 5; j++) pk[j] = pack_bf16(ex2(fmaf(sc[4 * j], sl2, -mb)), ex2(fmaf(sc[4 * j + 1], sl2, -mb)));
                float o0[4] = {0.f, 0.f, 0.f, 0.f}, o1[4] = {0.f, 0.f, 0.f, 0.f}, ls[4] = {0.f, 0.f, 0.f, 0.f};
                constexpr uint32_t ONE = 0x3F803F80u;
                mma16816(o0, v0[0], v0[1], v0[2], v0[3], pk[1], pk[2]);
                mma16816(o1, v1[0], v1[1], v1[2], v1[3], pk[1], pk[2]);
                ldsm4(v0, va + 4096); ldsm4(v1, va + 4096 + 256);
                mma16816(ls, ONE, ONE, ONE, ONE, pk[1], pk[2]);
                mma16816(ls, ONE, ONE, ONE, ONE, pk[3], pk[4]);
                mma1688(ls, ONE, ONE, pk[0]);
                mma16816(o0, v0[0], v0[1], v0[2], v0[3], pk[3], pk[4]);
                mma16816(o1, v1[0], v1[1], v1[2], v1[3], pk[3], pk[4]);
                if (!v_here) { mbar_wait(bar + 8 * B_HOPV, s & 1); ldsm4(vm, sb + R_V + t * 16); }
                mma1688(o0, vm[0], vm[1], pk[0]);
                mma1688(o1, vm[2], vm[3], pk[0]);
                const float i0 = rcp(ls[0]), i1 = rcp(ls[1]);
                const uint32_t oa = sb + R_O + (t >> 5) * 512 + (t & 31) * 4;
                sts32(oa, pack_bf16(o0[0] * i0, o0[1] * i1));
                sts32(oa + 128, pack_bf16(o0[2] * i0, o0[3] * i1));
                sts32(oa + 256, pack_bf16(o1[0] * i0, o1[1] * i1));
                sts32(oa + 384, pack_bf16(o1[2] * i0, o1[3] * i1));
                __syncwarp();
                e_arrive(bar + 8 * B_O);
                PROF(9);
                if (role == 0) {
                    OPAQUE(t);
                    const int lim = (t >> 2) - (t & 3) * 2 + 8;
                    float z[10];
#pragma unroll
                    for (int j = 0; j < 5; j++)
                        asm volatile("ld.shared.v2.f32 {%0,%1}, [%2];" : "=f"(z[2 * j]), "=f"(z[2 * j + 1]) : "r"(sb + R_QX + 768 + (t >> 5) * 4096 + j * 256 + (t & 31) * 8) : "memory");
                    float gate; asm volatile("ld.shared.f32 %0, [%1];" : "=f"(gate) : "r"(sb + R_G + (t >> 2) * 4) : "memory");
                    float m1 = fmaxf(z[0], z[1]);
#pragma unroll
                    for (int j = 1; j < 5; j++) {
                        z[2 * j] = 8 * j <= lim ? z[2 * j] : NEGRAW;
                        z[2 * j + 1] = 8 * j + 1 <= lim ? z[2 * j + 1] : NEGRAW;
                        m1 = fmaxf(m1, fmaxf(z[2 * j], z[2 * j + 1]));
                    }
                    m1 = fmaxf(m1, __shfl_xor_sync(0xffffffffu, m1, 1));
                    m1 = fmaxf(m1, __shfl_xor_sync(0xffffffffu, m1, 2));
                    const float mb1 = m1 * sl2;
                    float l1 = 0.f;
                    const uint32_t pa = sb + R_QX + (t >> 5) * 4096 + (t & 31) * 4;
#pragma unroll
                    for (int j = 0; j < 5; j++) {
                        const uint32_t pw = pack_bf16(ex2(fmaf(z[2 * j], sl2, -mb1)), ex2(fmaf(z[2 * j + 1], sl2, -mb1)));
                        l1 += __uint_as_float(pw << 16) + __uint_as_float(pw & 0xffff0000u);
                        sts32(pa + j * 128, pw);
                    }
                    sts32(pa + 5 * 128, 0u);
                    l1 += __shfl_xor_sync(0xffffffffu, l1, 1);
                    l1 += __shfl_xor_sync(0xffffffffu, l1, 2);
                    sts32(sb + R_G + 128 + (t >> 2) * 4, __float_as_uint(gate * rcp(l1)));
                    spin_until(t_o + PVD);
                    if ((wid & 3) == 0 && s >= 1) { bulk_wait_all(); e_count(&g_ocnt[(s - 1) >> 2]); }
                    fence_async();
                    bar_sync(2, 128);
                    constexpr uint64_t dV = cdesc(R_V, 2048, 128, 0);
                    constexpr uint64_t dP = cdesc(R_QX, 128, 4096, 0);
                    float sf[8];
#pragma unroll
                    for (int j = 0; j < 4; j++) asm volatile("ld.shared.v2.f32 {%0,%1}, [%2];" : "=f"(sf[2 * j]), "=f"(sf[2 * j + 1]) : "r"(sb + R_G + 128 + j * 32 + (t & 3) * 8) : "memory");
                    const uint32_t r = ((t >> 4) & 1) * 8 + (t & 7), ch = (t >> 5) * 2 + ((t >> 3) & 1);
                    const uint32_t sa = sb + R_QX + 2048 + r * 128 + ((ch ^ (r & 7)) << 4);
#pragma unroll
                    for (int hf = 0; hf < 2; hf++) {
                        float d[16];
                        wg_fence();
#pragma unroll
                        for (int k = 0; k < 3; k++) wg_ss32<0>(d, dV + (uint64_t)(hf * 64 + k * 256), dP + (uint64_t)(k * 16), k);
                        wg_commit();
                        asm volatile("wgmma.wait_group.sync.aligned 0;" : ACC16(d)::"memory");
                        stsm4t(sa + hf * 8192, pack_bf16(d[0] * sf[0], d[1] * sf[1]), pack_bf16(d[2] * sf[0], d[3] * sf[1]), pack_bf16(d[4] * sf[2], d[5] * sf[3]), pack_bf16(d[6] * sf[2], d[7] * sf[3]));
                        stsm4t(sa + hf * 8192 + 4096, pack_bf16(d[8] * sf[4], d[9] * sf[5]), pack_bf16(d[10] * sf[4], d[11] * sf[5]), pack_bf16(d[12] * sf[6], d[13] * sf[7]), pack_bf16(d[14] * sf[6], d[15] * sf[7]));
                    }
                    fence_async();
                    bar_sync(2, 128);
                    if ((wid & 3) == 0) {
#pragma unroll
                        for (int q = 0; q < 4; q++) e_tma_store(&tm.o, sb + R_QX + 2048 + q * 4096, h * DH + (q >> 1) * 64, s * SEG + (q & 1) * 16);
                        bulk_commit();
                        bulk_wait_read();
                    }
                    if ((wid & 3) < 3) e_arrive_remote(mapa(bar + 8 * B_TFREE, wid & 3));
                }
            }
            if (t < 32) { e_expect(bar + 8 * B_HOP1, role == 2 ? 4096 : 2048); if (role != 2) e_expect(bar + 8 * B_HOPV, 2048); e_expect(bar + 8 * B_XT, role == 0 ? 2 * CPB : CPB); }
            if (s == NSEG - 1) { bulk_wait_all(); break; }
            if (role != 0 && (wid & 3) >= 2) {
                mbar_wait(bar + 8 * B_XRECV, s & 1);
                mbar_wait(bar + 8 * B_O, s & 1);
                fence_async();
                spin_until(t_o + ELD);
                x_load_pair(sb + ((wid & 1) ? R_V + 2048 : R_K + 2048), &tm.x, h, 3 + (wid & 1), s + 1, bar + 8 * (B_FULL + 3 + (wid & 1)));
            }
            OPAQUE(t);
            PROF(11);
            if (role != 0 || DDUP) {
                const int grp = role == 0 ? (t >> 6) * 32 + h : rg0 + (t >> 6) * 64;
                const uint32_t* rp = g_part[s & 3] + (grp * 1024 + ((t >> 2) & 7) * 32 + ((t >> 5) & 1) * 16 + (t & 3) * 4);
                uint32_t* wp = &g_mem[(s + 1) & 3][grp * 32 + ((t >> 5) & 1) * 16 + (t & 3) * 4 + ((t >> 3) & 3)];
                bulk_wait_all();
                spin_until(t_o + D2_BASE + (role == 0 ? DDUP + (t >> 6) * D2_STEP : (role - 1 + (t >> 6) * 2) * D2_STEP));
                PROF3(0, clk32());
#define LO(u) __uint_as_float((u) << 16)
#define HI(u) __uint_as_float((u) & 0xffff0000u)
                uint4 v[4];
                uint32_t n = poll_set<4>(v, rp, 256, (role - 1 + (t >> 6) * 2) * PHQ);
                {
                    PROF3(1, clk32());
                    float f[8];
                    f[0] = (LO(v[0].x) + LO(v[1].x)) + (LO(v[2].x) + LO(v[3].x)); f[1] = (HI(v[0].x) + HI(v[1].x)) + (HI(v[2].x) + HI(v[3].x));
                    f[2] = (LO(v[0].y) + LO(v[1].y)) + (LO(v[2].y) + LO(v[3].y)); f[3] = (HI(v[0].y) + HI(v[1].y)) + (HI(v[2].y) + HI(v[3].y));
                    f[4] = (LO(v[0].z) + LO(v[1].z)) + (LO(v[2].z) + LO(v[3].z)); f[5] = (HI(v[0].z) + HI(v[1].z)) + (HI(v[2].z) + HI(v[3].z));
                    f[6] = (LO(v[0].w) + LO(v[1].w)) + (LO(v[2].w) + LO(v[3].w)); f[7] = (HI(v[0].w) + HI(v[1].w)) + (HI(v[2].w) + HI(v[3].w));
                    const bool b4 = t & 16, b3 = t & 8;
                    float g4[4], g2[2];
#pragma unroll
                    for (int i = 0; i < 4; i++) g4[i] = (b4 ? f[4 + i] : f[i]) + __shfl_xor_sync(0xffffffffu, b4 ? f[i] : f[4 + i], 16);
#pragma unroll
                    for (int i = 0; i < 2; i++) g2[i] = (b3 ? g4[2 + i] : g4[i]) + __shfl_xor_sync(0xffffffffu, b3 ? g4[i] : g4[2 + i], 8);
                    g2[0] += __shfl_xor_sync(0xffffffffu, g2[0], 4);
                    g2[1] += __shfl_xor_sync(0xffffffffu, g2[1], 4);
                    st_strong4(wp, pack_nz(g2[0], g2[1]));
                }
                PROF3(8, n); (void)n;
            }
            t_o += D2_BASE + DQ + D3 + (t >> 5) * D2_STEP;
            OPAQUE(t);
            PROF(12);
            {
                const uint32_t* rp = &g_mem[(s + 1) & 3][((t >> 5) * 256 + (t & 31)) * 4];
                const uint32_t da = sb + R_RING + ((t >> 5) * 256 + (t & 31)) * 16;
                uint4 v[8];
                spin_until(t_o);
                PROF3(2, clk32());
                uint32_t n = poll_set<8>(v, rp, 128, PH3 + (t >> 5) * PHQ);
                PROF(13);
                PROF3(3, clk32()); PROF3(9, n); (void)n;
                mbar_wait(bar + 8 * B_AFREE0 + (t >> 6) * 8, (s + 1) & 1);
                PROF3(4, clk32());
#pragma unroll
                for (int i = 0; i < 8; i++) sts128(da + i * 512, v[i]);
                if (t >= 64) fence_async();
                __syncwarp();
                e_arrive(bar + 8 * B_MEM + (t >> 5) * 8);
                PROF(14);
                PROF3(5, clk32());
            }
            CLEAR(s + 3);
        }
}

__global__ void __launch_bounds__(384, 1) r_kernel(const __grid_constant__ RMaps tm, const bf16* __restrict__ mem0, const bf16* __restrict__ x, const bf16* __restrict__ gate_w) {
    extern __shared__ __align__(1024) unsigned char smem_raw[];
    const uint32_t sb = smem_u32(smem_raw);
    if ((sb & 0x3FFFFu) != SB0) __trap();
    const int tid = threadIdx.x;
    const int wid = __shfl_sync(0xffffffffu, tid >> 5, 0);
    uint32_t role; asm("mov.u32 %0, %%cluster_ctarank;" : "=r"(role));
    int h; asm("mov.u32 %0, %%clusterid.x;" : "=r"(h));
    const uint32_t bar = sb + R_BAR;
    asm volatile("griddepcontrol.launch_dependents;");
    KT(0, 0);
    const int gr = blockIdx.x * 12 + wid;
    uint4 gx0[4], gx1[4], gw[4];
#pragma unroll
    for (int i = 0; i < 4; i++) {
        gx0[i] = ldg_nc((const uint4*)(x + gr * DM) + i * 32 + (tid & 31));
        gx1[i] = ldg_nc((const uint4*)(x + min(gr + 1152, SEQ - 1) * DM) + i * 32 + (tid & 31));
        gw[i] = ldg_nc((const uint4*)gate_w + i * 32 + (tid & 31));
    }

    if (tid == 0) {
        for (int i = 0; i < 5; i++) mbar_init(bar + 8 * (B_FULL + i), 1);
        for (int i = 0; i < 3; i++) mbar_init(bar + 8 * (B_EMPTY + i), 2);
        for (int i = 0; i < 4; i++) mbar_init(bar + 8 * (B_MEM + i), 1);
        mbar_init(bar + 8 * B_HOP1, role == 2 ? 1 : 9);
        mbar_init(bar + 8 * B_HOPV, role == 2 ? 8 : 1);
        mbar_init(bar + 8 * B_XT, 1);
        mbar_init(bar + 8 * B_TFREE, 5);
        mbar_init(bar + 8 * B_P, 4);
        mbar_init(bar + 8 * B_XDONE, 8);
        mbar_init(bar + 8 * B_OST0, 4);
        mbar_init(bar + 8 * B_OST1, 4);
        mbar_init(bar + 8 * B_XRECV, 2);
        mbar_init(bar + 8 * B_O, 4);
        mbar_init(bar + 8 * B_AFREE0, 2);
        mbar_init(bar + 8 * B_AFREE1, 2);
        mbar_init(bar + 8 * B_PRO0, 1);
        mbar_init(bar + 8 * B_PRO1, 8);
        asm volatile("fence.mbarrier_init.release.cluster;" ::: "memory");
        fence_async();
        mbar_expect(bar + 8 * B_PRO0, KR * 4096);
        for (int i = 0; i < 3; i++) mbar_expect(bar + 8 * (B_FULL + i), 8192);
        mbar_expect(bar + 8 * B_HOP1, role == 2 ? 4096 : 2048);
        if (role != 2) mbar_expect(bar + 8 * B_HOPV, 2048);
        mbar_expect(bar + 8 * B_XT, role == 0 ? 2 * CPB : CPB);
    }
    __syncthreads();
    asm volatile("barrier.cluster.arrive.relaxed.aligned;" ::: "memory");
    {
        const CUtensorMap* tw = &tm.w[role];
        if (wid < 11) {
            e_tma_load(sb + wid * 16384, tw, h * DH, KC(wid), bar + 8 * B_PRO0);
            e_tma_load(sb + wid * 16384 + 8192, tw, h * DH + 64, KC(wid), bar + 8 * B_PRO0);
        }
        if (wid < 6) e_tma_load(sb + R_RING + wid * 4096, &tm.x, XC(wid), 0, bar + 8 * (B_FULL + (wid >> 1)));
        if ((tid & 31) == 0) {
            if (wid < 10) tma_prefetch(tw, h * DH + (wid & 1) * 64, KC(KR / 4 + (wid >> 1)));
            if (wid >= 6 && wid - 6 < (role == 0 ? 4 : 6)) tma_prefetch(&tm.wo, wo_tile(role, wid - 6) * 64, h * DH);
        }
        __syncwarp();
        const uint32_t g0 = __float_as_uint(gate_row(gx0, gw)), g1 = __float_as_uint(gate_row(gx1, gw));
        if ((tid & 31) == 0) {
            st_strong4(&g_gate[gr], g0 ? g0 : 0x80000000u);
            if (gr + 1152 < SEQ) st_strong4(&g_gate[gr + 1152], g1 ? g1 : 0x80000000u);
        }
        __syncwarp();
    }
    asm volatile("barrier.cluster.wait.aligned;" ::: "memory");

    if (wid < 8) {
        asm volatile("setmaxnreg.inc.sync.aligned.u32 224;");
        if (role == 0) r_big<0>(tm, wid); else if (role == 1) r_big<1>(tm, wid); else r_big<2>(tm, wid);
    } else {
        asm volatile("setmaxnreg.dec.sync.aligned.u32 56;");
        if (role == 0) r_chain<0>(tm, mem0, wid); else if (role == 1) r_chain<1>(tm, mem0, wid); else r_chain<2>(tm, mem0, wid);
    }
    __syncwarp();
    asm volatile("barrier.cluster.arrive; barrier.cluster.wait;" ::: "memory");
    KT(0, 1);
}

#define STAG 0
constexpr int G_ST = 4;
constexpr int G_STAGE = 16384 + 32768;
constexpr int G_EPI = G_ST * G_STAGE;
constexpr int G_GATE = G_EPI + 32768;
constexpr int G_BAR = G_GATE + 1024;
constexpr int G_SMEM = G_BAR + 128 + 1024;

struct G1Maps { CUtensorMap x, wg, wu, hs, o, h, wo, wd, out; };
constexpr int G1_NB = FF / 128;
constexpr int G1_TILES = 16 * G1_NB;

DEVINL void g_mma_block(float* d, uint32_t sb, uint32_t bar, int it, int wg, int tid, bool first) {
    const int st = it % G_ST;
    mbar_wait(bar + 8 * st, (it / G_ST) & 1);
    const uint64_t da = mkdesc(sb + st * G_STAGE + wg * 8192, 16, 1024, 1);
    const uint64_t db = mkdesc(sb + st * G_STAGE + 16384, 8192, 1024, 1);
    wg_fence();
#pragma unroll
    for (int k = 0; k < 4; k++) wg_ss256(d, da + (uint64_t)(k * 2), db + (uint64_t)(k * 128), (first ? 0 : 1) | k);
    wg_commit();
    if (!first) { wg_wait<1>(); if ((tid & 127) == 0) mbar_arrive(bar + 8 * (G_ST + (it - 1) % G_ST)); }
}
DEVINL void g_load_block(uint32_t sb, uint32_t bar, int it, const CUtensorMap* ta, int k0, int m0, const CUtensorMap* tb, int n0) {
    const int st = it % G_ST;
    mbar_wait(bar + 8 * (G_ST + st), ((it / G_ST) & 1) ^ 1);
    const uint32_t fb = bar + 8 * st, sa = sb + st * G_STAGE;
    mbar_expect(fb, G_STAGE);
    tma_load(sa, ta, k0, m0, fb);
#pragma unroll
    for (int q = 0; q < 4; q++) tma_load(sa + 16384 + q * 8192, tb, n0 + q * 64, k0, fb);
}

DEVINL void g_store_tile(const float* d, const CUtensorMap* tout, uint32_t epi, int mb, int nb, int wg, int tid) {
    const int lane = tid & 31, row = ((tid >> 5) & 3) * 16 + ((lane >> 3) & 1) * 8 + (lane & 7);
#pragma unroll
    for (int half = 0; half < 2; half++) {
        if ((tid & 127) == 0) bulk_wait_read();
        bar_sync(1 + wg, 128);
#pragma unroll
        for (int j = 0; j < 16; j += 2) {
            const float* e = d + half * 64 + 4 * j;
            const int cgp = j + (lane >> 4);
            stsm4(epi + (cgp >> 3) * 8192 + row * 128 + (((cgp & 7) ^ (row & 7)) << 4),
                  pack_bf16(e[0], e[1]), pack_bf16(e[2], e[3]), pack_bf16(e[4], e[5]), pack_bf16(e[6], e[7]));
        }
        fence_async();
        bar_sync(1 + wg, 128);
        if ((tid & 127) == 0) {
            tma_store(tout, epi, nb * 256 + half * 128, mb * 128 + wg * 64);
            tma_store(tout, epi + 8192, nb * 256 + half * 128 + 64, mb * 128 + wg * 64);
            bulk_commit();
        }
    }
}
template <int NS> DEVINL void g_split_finish(const float* d, float4 (&r)[32 / NS], uint4* sk, int tile, int ks, bf16* __restrict__ out, int tid) {
    constexpr int Q = 32 / NS;
    uint4* mine = sk + ks * (16 * 256) + tid;
#pragma unroll
    for (int c = 0; c < NS; c++) {
        if (c != ks) {
#pragma unroll
            for (int q = c * Q / 2; q < (c + 1) * Q / 2; q++)
                __stcg(mine + q * 256, make_uint4(pack_bf16(d[8 * q], d[8 * q + 1]), pack_bf16(d[8 * q + 2], d[8 * q + 3]), pack_bf16(d[8 * q + 4], d[8 * q + 5]), pack_bf16(d[8 * q + 6], d[8 * q + 7])));
        } else {
#pragma unroll
            for (int q = 0; q < Q; q++) { const float* e = d + (c * Q + q) * 4; r[q].x += e[0]; r[q].y += e[1]; r[q].z += e[2]; r[q].w += e[3]; }
        }
    }
    __threadfence();
    bar_sync(3, 256);
    if (tid == 0) {
        atomicAdd(&g_skcnt[tile], 1u);
        uint32_t v, n = 0;
        do {
            asm volatile("ld.acquire.gpu.global.u32 %0, [%1];" : "=r"(v) : "l"(&g_skcnt[tile]) : "memory");
            if (++n > 200000000u) __trap();
        } while (v < NS);
        if (atomicAdd(&g_skcnt[tile], 1u) == 2 * NS - 1) g_skcnt[tile] = 0u;
    }
    bar_sync(3, 256);
#pragma unroll
    for (int c = 1; c < NS; c++) {
        const uint4* th = sk + (((ks + c) & (NS - 1)) * 16 + ks * (Q / 2)) * 256 + tid;
#pragma unroll
        for (int q = 0; q < Q / 2; q++) {
            const uint4 u = __ldcg(th + q * 256);
            r[2 * q].x += __uint_as_float(u.x << 16); r[2 * q].y += __uint_as_float(u.x & 0xffff0000u);
            r[2 * q].z += __uint_as_float(u.y << 16); r[2 * q].w += __uint_as_float(u.y & 0xffff0000u);
            r[2 * q + 1].x += __uint_as_float(u.z << 16); r[2 * q + 1].y += __uint_as_float(u.z & 0xffff0000u);
            r[2 * q + 1].z += __uint_as_float(u.w << 16); r[2 * q + 1].w += __uint_as_float(u.w & 0xffff0000u);
        }
    }
    const int lane = tid & 31;
    uint32_t* op = (uint32_t*)(out + ((tile >> 2) * 128 + (tid >> 5) * 16 + (lane >> 2)) * DM + (tile & 3) * 256 + ks * Q * 8 + (lane & 3) * 2);
#pragma unroll
    for (int q = 0; q < Q; q++) { op[q * 4] = pack_bf16(r[q].x, r[q].y); op[q * 4 + 4 * DM] = pack_bf16(r[q].z, r[q].w); }
}
DEVINL int g1_count(int pass, int tail) { return pass == 0 ? NPRE : pass == 1 ? NFULL : pass == 2 ? T_MID - NFULL : tail ? (64 - T_LATE) * 8 : (T_LATE - T_MID) * 8; }
DEVINL int g1_first(int pass) { return pass >= 2 ? (int)(gridDim.x - 1 - blockIdx.x) : (int)blockIdx.x; }
constexpr int H_EARLY = 26;

__global__ void __launch_bounds__(384, 1) g1_kernel(const __grid_constant__ G1Maps tm, bf16* __restrict__ out, const int tail) {
    extern __shared__ __align__(1024) unsigned char smem_raw[];
    const uint32_t sb = (smem_u32(smem_raw) + 1023) & ~1023u;
    const int tid = threadIdx.x, lane = tid & 31;
    const int wg = __shfl_sync(0xffffffffu, tid >> 7, 0);
    const int warp = __shfl_sync(0xffffffffu, (tid >> 5) & 3, 0);
    const uint32_t bar = sb + G_BAR;
    asm volatile("griddepcontrol.launch_dependents;");
    KT(1 + tail, 0);
    const int ntiles = tail ? 0 : G1_TILES;
    if (tid == 0) {
        for (int i = 0; i < G_ST; i++) { mbar_init(bar + 8 * i, 1); mbar_init(bar + 8 * (G_ST + i), 2); }
        fence_async();
    }
    __syncthreads();
    if (tail) asm volatile("griddepcontrol.wait;" ::: "memory");
    if (wg == 2) {
        asm volatile("setmaxnreg.dec.sync.aligned.u32 40;");
        if (tail && warp == 1) {
            if (blockIdx.x < SEQ / 32) g_gate[blockIdx.x * 32 + lane] = 0u;
            if (blockIdx.x == 0) { if (lane < 16) g_ocnt[lane] = 0u; g_hcnt[lane] = 0u; g_pcnt[lane] = 0u; g_pcnt[32 + lane] = 0u; }
        }
        if (warp == 0) {
            if (lane == 0) {
                int it = 0;
                for (int tile = blockIdx.x; tile < ntiles; tile += gridDim.x) {
                    const int mb = tile & 15, nb = tile >> 4;
                    for (int kb = 0; kb < 16; kb++, it++) {
                        const int st = it % G_ST;
                        mbar_wait(bar + 8 * (G_ST + st), ((it / G_ST) & 1) ^ 1);
                        const uint32_t fb = bar + 8 * st, sa = sb + st * G_STAGE;
                        mbar_expect(fb, G_STAGE);
                        tma_load(sa, &tm.x, kb * 64, mb * 128, fb);
                        tma_load(sa + 16384, &tm.wg, nb * 128, kb * 64, fb);
                        tma_load(sa + 16384 + 8192, &tm.wg, nb * 128 + 64, kb * 64, fb);
                        tma_load(sa + 16384 + 16384, &tm.wu, nb * 128, kb * 64, fb);
                        tma_load(sa + 16384 + 24576, &tm.wu, nb * 128 + 64, kb * 64, fb);
                    }
                }
                for (int pass = tail ? 3 : 0; pass < 4; pass++) {
                    for (int i = g1_first(pass); i < g1_count(pass, tail); i += gridDim.x) {
                        const int tile = pass == 1 ? i : pass == 3 ? (tail ? T_LATE : T_MID) + (i >> 3) : NFULL + i, mb = tile >> 2, nb = tile & 3;
                        if (pass < 2) {
                            for (int kb = 0; kb < FF / 64; kb++, it++) {
                                if (kb == 0 || kb == 2 * H_EARLY) {
                                    wait_count(&g_hcnt[kb ? 16 + mb : mb], kb ? 2 * (G1_NB - H_EARLY) : 2 * H_EARLY);
                                    asm volatile("fence.proxy.async;" ::: "memory");
                                }
                                g_load_block(sb, bar, it, &tm.h, kb * 64, mb * 128, &tm.wd, nb * 256);
                            }
                        }
                        if (pass > 0) {
                            const int k0 = pass == 3 ? (i & 7) * 8 : 0, k1 = pass == 3 ? k0 + 8 : HD / 64;
                            if (!tail) wait_count(&g_ocnt[mb], NH * 4);
                            asm volatile("fence.proxy.async;" ::: "memory");
                            for (int kb = k0; kb < k1; kb++, it++) g_load_block(sb, bar, it, &tm.o, kb * 64, mb * 128, &tm.wo, nb * 256);
                        }
                    }
                }
            }
        }
    } else {
        asm volatile("setmaxnreg.inc.sync.aligned.u32 232;");
        float d[128];
        int it = 0;
        const uint32_t epi = sb + G_EPI + wg * 16384;
        const int row = warp * 16 + ((lane >> 3) & 1) * 8 + (lane & 7);
        for (int tile = blockIdx.x; tile < ntiles; tile += gridDim.x) {
            const int mb = tile & 15, nb = tile >> 4;
            const uint32_t* gp = &g_gate[mb * 128 + wg * 64 + warp * 16 + (lane >> 2)];
            uint32_t u0 = ld_strong4(gp), u1 = ld_strong4(gp + 8);
            for (int kb = 0; kb < 16; kb++, it++) {
                if (it == (wg ? 0 : STAG)) bar_sync(4, 256);
                g_mma_block(d, sb, bar, it, wg, tid, kb == 0);
            }
            wg_wait<0>();
            for (uint32_t n = 0; u0 == 0u || u1 == 0u; n++) { u0 = ld_strong4(gp); u1 = ld_strong4(gp + 8); if (n > 20000000u) __trap(); }
            __syncwarp();
            const float s0 = 1.0f - __uint_as_float(u0), s1 = 1.0f - __uint_as_float(u1);
            if ((tid & 127) == 0) {
                mbar_arrive(bar + 8 * (G_ST + (it - 1) % G_ST));
                bulk_wait_all();
                const int pt = tile - (int)gridDim.x;
                if (pt >= 0) atomicAdd(&g_hcnt[(pt & 15) + ((pt >> 4) >= H_EARLY ? 16 : 0)], 1u);
            }
            bar_sync(1 + wg, 128);
#pragma unroll
            for (int j = 0; j < 16; j += 2) {
                uint32_t p[4];
#pragma unroll
                for (int q = 0; q < 4; q++) {
                    const int i = (j + (q >> 1)) * 4 + (q & 1) * 2;
                    const float sc = (q & 1) ? s1 : s0;
                    const float g0 = d[i], g1 = d[i + 1];
                    const float a0 = 1.0f + ex2(fminf(g0 * -1.4426950408889634f, 62.0f)), a1 = 1.0f + ex2(fminf(g1 * -1.4426950408889634f, 62.0f));
                    const float rr = rcp(a0 * a1) * sc;
                    const float h0 = (g0 * d[64 + i]) * (rr * a1);
                    const float h1 = (g1 * d[64 + i + 1]) * (rr * a0);
                    p[q] = pack_bf16(h0, h1);
                }
                const int cgp = j + (lane >> 4);
                stsm4(epi + (cgp >> 3) * 8192 + row * 128 + (((cgp & 7) ^ (row & 7)) << 4), p[0], p[1], p[2], p[3]);
            }
            fence_async();
            bar_sync(1 + wg, 128);
            if ((tid & 127) == 0) {
                tma_store(&tm.hs, epi, nb * 128, mb * 128 + wg * 64);
                tma_store(&tm.hs, epi + 8192, nb * 128 + 64, mb * 128 + wg * 64);
                bulk_commit();
            }
        }
        if ((tid & 127) == 0 && !tail) {
            bulk_wait_all();
            const int pt = blockIdx.x + (G1_TILES - 1 - blockIdx.x) / gridDim.x * gridDim.x;
            atomicAdd(&g_hcnt[(pt & 15) + ((pt >> 4) >= H_EARLY ? 16 : 0)], 1u);
        }
        for (int pass = tail ? 3 : 0; pass < 4; pass++) {
            for (int i = g1_first(pass); i < g1_count(pass, tail); i += gridDim.x) {
                const int tile = pass == 1 ? i : pass == 3 ? (tail ? T_LATE : T_MID) + (i >> 3) : NFULL + i;
                const int nkb = pass == 0 ? FF / 64 : pass == 1 ? (FF + HD) / 64 : pass == 2 ? HD / 64 : 8;
                float4* pre = g_pre + (tile - NFULL) * (32 * 256) + tid;
                if (tail) asm volatile("prefetch.global.L2 [%0];" ::"l"(pre - tid + (i & 7) * 1024 + tid * 4));
                for (int kb = 0; kb < nkb; kb++, it++) g_mma_block(d, sb, bar, it, wg, tid, kb == 0);
                wg_wait<0>();
                if ((tid & 127) == 0) mbar_arrive(bar + 8 * (G_ST + (it - 1) % G_ST));
                if (pass >= 2 && !tail) { if ((tid & 31) == 0) wait_count(&g_pcnt[tile], 8); __syncwarp(); }
                if (pass == 0) {
#pragma unroll
                    for (int q = 0; q < 32; q++) __stcg(pre + q * 256, make_float4(d[4 * q], d[4 * q + 1], d[4 * q + 2], d[4 * q + 3]));
                    __threadfence();
                    __syncwarp();
                    if ((tid & 31) == 0) atomicAdd(&g_pcnt[tile], 1u);
                } else if (pass == 3) {
                    float4 r[4];
#pragma unroll
                    for (int q = 0; q < 4; q++) r[q] = __ldcg(pre + ((i & 7) * 4 + q) * 256);
                    g_split_finish<8>(d, r, g_sk + (tile - T_MID) * 8 * (16 * 256), tile, i & 7, out, tid);
                } else {
                    if (pass == 2) {
#pragma unroll
                        for (int q = 0; q < 32; q++) {
                            const float4 u = __ldcg(pre + q * 256); d[4 * q] += u.x; d[4 * q + 1] += u.y; d[4 * q + 2] += u.z; d[4 * q + 3] += u.w;
                            if ((q & 7) == 7) __syncwarp();
                        }
                    }
                    g_store_tile(d, &tm.out, epi, tile >> 2, tile & 3, wg, tid);
                }
            }
        }
        if ((tid & 127) == 0) bulk_wait_all();
        KT(1 + tail, 1);
    }
    __syncwarp();
    asm volatile("griddepcontrol.wait;" ::: "memory");
}

typedef CUresult (*EncodeFn)(CUtensorMap*, CUtensorMapDataType, cuuint32_t, void*, const cuuint64_t*, const cuuint64_t*, const cuuint32_t*,
                             const cuuint32_t*, CUtensorMapInterleave, CUtensorMapSwizzle, CUtensorMapL2promotion, CUtensorMapFloatOOBfill);

static void make_map(EncodeFn enc, CUtensorMap* m, const void* ptr, uint64_t rows, uint64_t cols, uint32_t box_rows) {
    cuuint64_t dims[2] = {cols, rows};
    cuuint64_t strides[1] = {cols * 2};
    cuuint32_t box[2] = {64, box_rows};
    cuuint32_t es[2] = {1, 1};
    enc(m, CU_TENSOR_MAP_DATA_TYPE_BFLOAT16, 2, (void*)ptr, dims, strides, box, es, CU_TENSOR_MAP_INTERLEAVE_NONE,
        CU_TENSOR_MAP_SWIZZLE_128B, CU_TENSOR_MAP_L2_PROMOTION_L2_256B, CU_TENSOR_MAP_FLOAT_OOB_FILL_NONE);
}

extern "C" void kernel_launch(void* const* d_in, const int* in_sizes, int n_in, void* d_out, int out_size) {
    (void)in_sizes; (void)n_in; (void)out_size;
    const bf16* x = (const bf16*)d_in[0];
    const bf16* mem0 = (const bf16*)d_in[1];
    const bf16* gate_w = (const bf16*)d_in[11];
    static EncodeFn enc = nullptr;
    static int n_sm = 0;
    static void *pO = nullptr, *pH = nullptr;
    if (!enc) {
        void* fn = nullptr;
        cudaDriverEntryPointQueryResult qr;
        cudaGetDriverEntryPoint("cuTensorMapEncodeTiled", &fn, cudaEnableDefault, &qr);
        enc = (EncodeFn)fn;
        cudaDeviceGetAttribute(&n_sm, cudaDevAttrMultiProcessorCount, 0);
        cudaFuncSetAttribute(r_kernel, cudaFuncAttributeMaxDynamicSharedMemorySize, R_SMEM);
        cudaFuncSetAttribute(g1_kernel, cudaFuncAttributeMaxDynamicSharedMemorySize, G_SMEM);
        cudaGetSymbolAddress(&pO, g_O);
        cudaGetSymbolAddress(&pH, g_H);
    }
    RMaps rm; G1Maps m1;
    make_map(enc, &rm.x, x, SEQ, DM, 32);
    for (int i = 0; i < 3; i++) make_map(enc, &rm.w[i], d_in[2 + i], DM, HD, 64);
    make_map(enc, &rm.wo, d_in[5], HD, DM, 128);
    make_map(enc, &rm.o, pO, SEQ, HD, 16);
    make_map(enc, &m1.x, x, SEQ, DM, 128);
    make_map(enc, &m1.wg, d_in[8], DM, FF, 64);
    make_map(enc, &m1.wu, d_in[9], DM, FF, 64);
    make_map(enc, &m1.hs, pH, SEQ, FF, 64);
    make_map(enc, &m1.o, pO, SEQ, HD, 128);
    make_map(enc, &m1.h, pH, SEQ, FF, 128);
    make_map(enc, &m1.wo, d_in[5], HD, DM, 64);
    make_map(enc, &m1.wd, d_in[10], FF, DM, 64);
    make_map(enc, &m1.out, d_out, SEQ, DM, 64);

    cudaStream_t st = cudaStreamPerThread;
    {
        cudaLaunchConfig_t cfg = {};
        cfg.gridDim = dim3(96); cfg.blockDim = dim3(384); cfg.dynamicSmemBytes = R_SMEM; cfg.stream = st;
        cudaLaunchAttribute at[1];
        at[0].id = cudaLaunchAttributeClusterDimension; at[0].val.clusterDim.x = 3; at[0].val.clusterDim.y = 1; at[0].val.clusterDim.z = 1;
        cfg.attrs = at; cfg.numAttrs = 1;
        cudaLaunchKernelEx(&cfg, r_kernel, rm, mem0, x, gate_w);
    }
    {
        cudaLaunchConfig_t cfg = {};
        cfg.gridDim = dim3(n_sm - 96); cfg.blockDim = dim3(384); cfg.dynamicSmemBytes = G_SMEM; cfg.stream = st;
        cudaLaunchAttribute at[1];
        at[0].id = cudaLaunchAttributeProgrammaticStreamSerialization; at[0].val.programmaticStreamSerializationAllowed = 1;
        cfg.attrs = at; cfg.numAttrs = 1;
        cudaLaunchKernelEx(&cfg, g1_kernel, m1, (bf16*)d_out, 0);
    }
    {
        cudaLaunchConfig_t cfg = {};
        cfg.gridDim = dim3((64 - T_LATE) * 8); cfg.blockDim = dim3(384); cfg.dynamicSmemBytes = G_SMEM; cfg.stream = st;
        cudaLaunchAttribute at[1];
        at[0].id = cudaLaunchAttributeProgrammaticStreamSerialization; at[0].val.programmaticStreamSerializationAllowed = 1;
        cfg.attrs = at; cfg.numAttrs = 1;
        cudaLaunchKernelEx(&cfg, g1_kernel, m1, (bf16*)d_out, 1);
    }
}
```

```cpp
#include <cuda_runtime.h>
#include <cuda_bf16.h>
#include <cuda.h>
#include <stdint.h>

typedef __nv_bfloat16 bf16;

constexpr int SEQ = 2048, DM = 1024, NH = 32, DH = 128, NMEM = 8, SEG = 32, NSEG = 64, FF = 3584;
constexpr int HD = NH * DH;

__device__ bf16 g_O[SEQ * HD];
__device__ bf16 g_H[SEQ * FF];
__device__ uint32_t g_gate[SEQ];
__device__ uint32_t g_part[4][128 * 32 * 32];
__device__ uint32_t g_mem[4][DM * 4];
constexpr int NFULL = 36, T_MID = 44, T_MID2 = 48, T_LATE = 52;
constexpr int NPRE = 64 - NFULL;
__device__ float4 g_pre[NPRE * 32 * 256];
__device__ uint4 g_sk[(64 - T_MID) * 8 * 16 * 256];
__device__ uint32_t g_skcnt[64], g_pcnt[64];
__device__ uint32_t g_hcnt[32], g_ocnt[16];
#define KT(k, i)
#define PT(i)

#define DEVINL __device__ __forceinline__
constexpr long long SPIN_LIMIT = 4000000000LL;

DEVINL uint32_t smem_u32(const void* p) { return (uint32_t)__cvta_generic_to_shared(p); }
DEVINL void mbar_init(uint32_t bar, uint32_t cnt) { asm volatile("mbarrier.init.shared::cta.b64 [%0], %1;" ::"r"(bar), "r"(cnt) : "memory"); }
DEVINL void mbar_arrive(uint32_t bar) { asm volatile("mbarrier.arrive.shared::cta.b64 _, [%0];" ::"r"(bar) : "memory"); }
DEVINL void mbar_expect(uint32_t bar, uint32_t bytes) { asm volatile("mbarrier.arrive.expect_tx.shared::cta.b64 _, [%0], %1;" ::"r"(bar), "r"(bytes) : "memory"); }
DEVINL void mbar_arrive_remote(uint32_t cbar) { asm volatile("mbarrier.arrive.relaxed.cluster.shared::cluster.b64 _, [%0];" ::"r"(cbar) : "memory"); }
DEVINL bool mbar_try(uint32_t bar, uint32_t par) {
    uint32_t ok;
    asm volatile("{ .reg .pred p; mbarrier.try_wait.parity.shared::cta.b64 p, [%1], %2; selp.u32 %0, 1, 0, p; }" : "=r"(ok) : "r"(bar), "r"(par) : "memory");
    return ok;
}
__device__ __noinline__ void mbar_wait_slow(uint32_t bar, uint32_t par) {
    long long t0 = clock64();
    while (!mbar_try(bar, par)) { if (clock64() - t0 > SPIN_LIMIT) __trap(); }
}
DEVINL void mbar_wait(uint32_t bar, uint32_t par) {
    uint32_t n = 0;
    while (!mbar_try(bar, par)) { if (++n > 200000000u) __trap(); }
}
DEVINL uint32_t mapa(uint32_t a, uint32_t r) { uint32_t o; asm volatile("mapa.shared::cluster.u32 %0, %1, %2;" : "=r"(o) : "r"(a), "r"(r)); return o; }
DEVINL void fence_async() { asm volatile("fence.proxy.async.shared::cta;" ::: "memory"); }
DEVINL void bar_sync(int id, int n) { asm volatile("bar.sync %0, %1;" ::"r"(id), "r"(n) : "memory"); }
DEVINL void cluster_sync() { asm volatile("barrier.cluster.arrive.aligned; barrier.cluster.wait.aligned;" ::: "memory"); }
DEVINL void tma_load(uint32_t dst, const CUtensorMap* tm, int c0, int c1, uint32_t bar) {
    asm volatile("cp.async.bulk.tensor.2d.shared::cluster.global.mbarrier::complete_tx::bytes [%0], [%1, {%3, %4}], [%2];"
                 ::"r"(dst), "l"(tm), "r"(bar), "r"(c0), "r"(c1) : "memory");
}
DEVINL void tma_prefetch(const CUtensorMap* tm, int c0, int c1) {
    asm volatile("cp.async.bulk.prefetch.tensor.2d.L2.global [%0, {%1, %2}];" ::"l"(tm), "r"(c0), "r"(c1) : "memory");
}
DEVINL void tma_store(const CUtensorMap* tm, uint32_t src, int c0, int c1) {
    asm volatile("cp.async.bulk.tensor.2d.global.shared::cta.bulk_group [%0, {%2, %3}], [%1];" ::"l"(tm), "r"(src), "r"(c0), "r"(c1) : "memory");
}
DEVINL void bulk_commit() { asm volatile("cp.async.bulk.commit_group;" ::: "memory"); }
DEVINL void bulk_wait_read() { asm volatile("cp.async.bulk.wait_group.read 0;" ::: "memory"); }
DEVINL void bulk_wait_all() { asm volatile("cp.async.bulk.wait_group 0;" ::: "memory"); }
DEVINL void bulk_s2s(uint32_t cdst, uint32_t src, uint32_t bytes, uint32_t cbar) {
    asm volatile("cp.async.bulk.shared::cluster.shared::cta.mbarrier::complete_tx::bytes [%0], [%1], %2, [%3];" ::"r"(cdst), "r"(src), "r"(bytes), "r"(cbar) : "memory");
}
DEVINL void st_async16(uint32_t cdst, uint4 v, uint32_t cbar) {
    asm volatile("st.async.shared::cluster.mbarrier::complete_tx::bytes.v4.b32 [%0], {%1,%2,%3,%4}, [%5];" ::"r"(cdst), "r"(v.x), "r"(v.y), "r"(v.z), "r"(v.w), "r"(cbar) : "memory");
}
DEVINL uint64_t mkdesc(uint32_t addr, uint32_t lbo, uint32_t sbo, uint32_t swz) {
    return (uint64_t)((addr & 0x3FFFF) >> 4) | ((uint64_t)(lbo >> 4) << 16) | ((uint64_t)(sbo >> 4) << 32) | ((uint64_t)swz << 62);
}
constexpr uint32_t SB0 = 1024;
__host__ __device__ constexpr uint64_t cdesc(uint32_t off, uint32_t lbo, uint32_t sbo, uint32_t swz) {
    return (uint64_t)(((SB0 + off) & 0x3FFFF) >> 4) | ((uint64_t)(lbo >> 4) << 16) | ((uint64_t)(sbo >> 4) << 32) | ((uint64_t)swz << 62);
}
DEVINL float rcp(float x) { float y; asm("rcp.approx.ftz.f32 %0, %1;" : "=f"(y) : "f"(x)); return y; }
DEVINL float ex2(float x) { float y; asm("ex2.approx.ftz.f32 %0, %1;" : "=f"(y) : "f"(x)); return y; }
DEVINL void spin_clk(int d) { uint32_t t0, t1; asm volatile("mov.u32 %0, %%clock;" : "=r"(t0)); do { asm volatile("mov.u32 %0, %%clock;" : "=r"(t1)); } while ((int)(t1 - t0) < d); }
#define PROBE_GAP 150
#define OPAQUE(x) asm volatile("" : "+r"(x))
DEVINL void wg_fence() { asm volatile("wgmma.fence.sync.aligned;" ::: "memory"); }
DEVINL void wg_commit() { asm volatile("wgmma.commit_group.sync.aligned;" ::: "memory"); }
template <int N> DEVINL void wg_wait() { asm volatile("wgmma.wait_group.sync.aligned %0;" ::"n"(N) : "memory"); }
DEVINL uint32_t pack_bf16(float lo, float hi) { uint32_t r; asm("cvt.rn.bf16x2.f32 %0, %1, %2;" : "=r"(r) : "f"(hi), "f"(lo)); return r; }
DEVINL void ldsm4(uint32_t* r, uint32_t a) { asm volatile("ldmatrix.sync.aligned.m8n8.x4.shared.b16 {%0,%1,%2,%3}, [%4];" : "=r"(r[0]), "=r"(r[1]), "=r"(r[2]), "=r"(r[3]) : "r"(a) : "memory"); }
DEVINL void ldsm4t(uint32_t* r, uint32_t a) { asm volatile("ldmatrix.sync.aligned.m8n8.x4.trans.shared.b16 {%0,%1,%2,%3}, [%4];" : "=r"(r[0]), "=r"(r[1]), "=r"(r[2]), "=r"(r[3]) : "r"(a) : "memory"); }
DEVINL void ldsm4t_if(uint32_t* r, uint32_t a, int c) { asm volatile("{ .reg .pred p; setp.ne.s32 p, %5, 0; @p ldmatrix.sync.aligned.m8n8.x4.trans.shared.b16 {%0,%1,%2,%3}, [%4]; }" : "+r"(r[0]), "+r"(r[1]), "+r"(r[2]), "+r"(r[3]) : "r"(a), "r"(c) : "memory"); }
DEVINL void stsm4(uint32_t a, uint32_t r0, uint32_t r1, uint32_t r2, uint32_t r3) { asm volatile("stmatrix.sync.aligned.m8n8.x4.shared.b16 [%0], {%1,%2,%3,%4};" ::"r"(a), "r"(r0), "r"(r1), "r"(r2), "r"(r3) : "memory"); }
DEVINL void stsm4t(uint32_t a, uint32_t r0, uint32_t r1, uint32_t r2, uint32_t r3) { asm volatile("stmatrix.sync.aligned.m8n8.x4.trans.shared.b16 [%0], {%1,%2,%3,%4};" ::"r"(a), "r"(r0), "r"(r1), "r"(r2), "r"(r3) : "memory"); }
DEVINL void sts32(uint32_t a, uint32_t v) { asm volatile("st.shared.b32 [%0], %1;" ::"r"(a), "r"(v) : "memory"); }
DEVINL void sts128(uint32_t a, uint4 v) { asm volatile("st.shared.v4.b32 [%0], {%1,%2,%3,%4};" ::"r"(a), "r"(v.x), "r"(v.y), "r"(v.z), "r"(v.w) : "memory"); }
DEVINL uint4 lds128(uint32_t a) { uint4 v; asm volatile("ld.shared.v4.b32 {%0,%1,%2,%3}, [%4];" : "=r"(v.x), "=r"(v.y), "=r"(v.z), "=r"(v.w) : "r"(a) : "memory"); return v; }
DEVINL uint4 ld_strong16(const void* p) { uint4 v; asm volatile("ld.relaxed.gpu.global.v4.u32 {%0,%1,%2,%3}, [%4];" : "=r"(v.x), "=r"(v.y), "=r"(v.z), "=r"(v.w) : "l"(p) : "memory"); return v; }
DEVINL void st_strong8(void* p, uint32_t a, uint32_t b) { asm volatile("st.relaxed.gpu.global.v2.u32 [%0], {%1,%2};" ::"l"(p), "r"(a), "r"(b) : "memory"); }
DEVINL void st_strong4(void* p, uint32_t a) { asm volatile("st.relaxed.gpu.global.u32 [%0], %1;" ::"l"(p), "r"(a) : "memory"); }
DEVINL void st_strong16(void* p, uint4 v) { asm volatile("st.relaxed.gpu.global.v4.u32 [%0], {%1,%2,%3,%4};" ::"l"(p), "r"(v.x), "r"(v.y), "r"(v.z), "r"(v.w) : "memory"); }
DEVINL uint32_t pack_nz(float lo, float hi) { uint32_t r = pack_bf16(lo, hi); return r == 0u ? 0x8000u : r; }
DEVINL uint32_t min4(uint4 v, uint32_t m) { return __vimin3_u32(__vimin3_u32(v.x, v.y, m), v.z, v.w); }
DEVINL void mma16816(float* d, uint32_t a0, uint32_t a1, uint32_t a2, uint32_t a3, uint32_t b0, uint32_t b1) {
    asm volatile("mma.sync.aligned.m16n8k16.row.col.f32.bf16.bf16.f32 {%0,%1,%2,%3}, {%4,%5,%6,%7}, {%8,%9}, {%0,%1,%2,%3};"
                 : "+f"(d[0]), "+f"(d[1]), "+f"(d[2]), "+f"(d[3]) : "r"(a0), "r"(a1), "r"(a2), "r"(a3), "r"(b0), "r"(b1));
}
DEVINL void mma1688(float* d, uint32_t a0, uint32_t a1, uint32_t b0) {
    asm volatile("mma.sync.aligned.m16n8k8.row.col.f32.bf16.bf16.f32 {%0,%1,%2,%3}, {%4,%5}, {%6}, {%0,%1,%2,%3};"
                 : "+f"(d[0]), "+f"(d[1]), "+f"(d[2]), "+f"(d[3]) : "r"(a0), "r"(a1), "r"(b0));
}
template <int TA, int TB> DEVINL void wg_ss8(float* d, uint64_t da, uint64_t db, int sc) {
    asm volatile("{ .reg .pred p; setp.ne.b32 p, %6, 0; wgmma.mma_async.sync.aligned.m64n8k16.f32.bf16.bf16 {%0,%1,%2,%3}, %4, %5, p, 1, 1, %7, %8; }"
                 : "+f"(d[0]), "+f"(d[1]), "+f"(d[2]), "+f"(d[3]) : "l"(da), "l"(db), "r"(sc), "n"(TA), "n"(TB));
}
template <int TB> DEVINL void wg_rs8(float* d, const uint32_t* a, uint64_t db, int sc) {
    asm volatile("{ .reg .pred p; setp.ne.b32 p, %9, 0; wgmma.mma_async.sync.aligned.m64n8k16.f32.bf16.bf16 {%0,%1,%2,%3}, {%4,%5,%6,%7}, %8, p, 1, 1, %10; }"
                 : "+f"(d[0]), "+f"(d[1]), "+f"(d[2]), "+f"(d[3]) : "r"(a[0]), "r"(a[1]), "r"(a[2]), "r"(a[3]), "l"(db), "r"(sc), "n"(TB));
}
#define ACC16(d) "+f"(d[0]), "+f"(d[1]), "+f"(d[2]), "+f"(d[3]), "+f"(d[4]), "+f"(d[5]), "+f"(d[6]), "+f"(d[7]), "+f"(d[8]), "+f"(d[9]), "+f"(d[10]), "+f"(d[11]), "+f"(d[12]), "+f"(d[13]), "+f"(d[14]), "+f"(d[15])
template <int TA> DEVINL void wg_ss32(float* d, uint64_t da, uint64_t db, int sc) {
    asm volatile("{ .reg .pred p; setp.ne.b32 p, %18, 0; wgmma.mma_async.sync.aligned.m64n32k16.f32.bf16.bf16 {%0,%1,%2,%3,%4,%5,%6,%7,%8,%9,%10,%11,%12,%13,%14,%15}, %16, %17, p, 1, 1, %19, 0; }"
                 : ACC16(d) : "l"(da), "l"(db), "r"(sc), "n"(TA));
}
DEVINL void wg_rs32(float* d, const uint32_t* a, uint64_t db, int sc) {
    asm volatile("{ .reg .pred p; setp.ne.b32 p, %21, 0; wgmma.mma_async.sync.aligned.m64n32k16.f32.bf16.bf16 {%0,%1,%2,%3,%4,%5,%6,%7,%8,%9,%10,%11,%12,%13,%14,%15}, {%16,%17,%18,%19}, %20, p, 1, 1, 0; }"
                 : ACC16(d) : "r"(a[0]), "r"(a[1]), "r"(a[2]), "r"(a[3]), "l"(db), "r"(sc));
}
DEVINL void wg_ss40(float* d, uint64_t da, uint64_t db, int sc) {
    asm volatile("{ .reg .pred p; setp.ne.b32 p, %22, 0; wgmma.mma_async.sync.aligned.m64n40k16.f32.bf16.bf16 {%0,%1,%2,%3,%4,%5,%6,%7,%8,%9,%10,%11,%12,%13,%14,%15,%16,%17,%18,%19}, %20, %21, p, 1, 1, 1, 1; }"
                 : ACC16(d), "+f"(d[16]), "+f"(d[17]), "+f"(d[18]), "+f"(d[19]) : "l"(da), "l"(db), "r"(sc));
}
#define A8(d, o) "+f"(d[o]), "+f"(d[o + 1]), "+f"(d[o + 2]), "+f"(d[o + 3]), "+f"(d[o + 4]), "+f"(d[o + 5]), "+f"(d[o + 6]), "+f"(d[o + 7])
#define A32(d, o) A8(d, o), A8(d, o + 8), A8(d, o + 16), A8(d, o + 24)
DEVINL void wg_ss256(float* d, uint64_t da, uint64_t db, int sc) {
    asm volatile(
        "{ .reg .pred p; setp.ne.b32 p, %130, 0;\n"
        "wgmma.mma_async.sync.aligned.m64n256k16.f32.bf16.bf16 {"
        "%0,%1,%2,%3,%4,%5,%6,%7,%8,%9,%10,%11,%12,%13,%14,%15,%16,%17,%18,%19,%20,%21,%22,%23,%24,%25,%26,%27,%28,%29,%30,%31,"
        "%32,%33,%34,%35,%36,%37,%38,%39,%40,%41,%42,%43,%44,%45,%46,%47,%48,%49,%50,%51,%52,%53,%54,%55,%56,%57,%58,%59,%60,%61,%62,%63,"
        "%64,%65,%66,%67,%68,%69,%70,%71,%72,%73,%74,%75,%76,%77,%78,%79,%80,%81,%82,%83,%84,%85,%86,%87,%88,%89,%90,%91,%92,%93,%94,%95,"
        "%96,%97,%98,%99,%100,%101,%102,%103,%104,%105,%106,%107,%108,%109,%110,%111,%112,%113,%114,%115,%116,%117,%118,%119,%120,%121,%122,%123,%124,%125,%126,%127"
        "}, %128, %129, p, 1, 1, 0, 1; }"
        : A32(d, 0), A32(d, 32), A32(d, 64), A32(d, 96) : "l"(da), "l"(db), "r"(sc));
}

DEVINL float gate_row(const uint4 (&xv)[4], const uint4 (&gv)[4]) {
    float acc = 0.f;
#pragma unroll
    for (int i = 0; i < 4; i++) {
        const uint32_t xa[4] = {xv[i].x, xv[i].y, xv[i].z, xv[i].w}, ga[4] = {gv[i].x, gv[i].y, gv[i].z, gv[i].w};
#pragma unroll
        for (int e = 0; e < 4; e++) {
            acc = fmaf(__uint_as_float(xa[e] << 16), __uint_as_float(ga[e] << 16), acc);
            acc = fmaf(__uint_as_float(xa[e] & 0xffff0000u), __uint_as_float(ga[e] & 0xffff0000u), acc);
        }
    }
#pragma unroll
    for (int o = 16; o > 0; o >>= 1) acc += __shfl_xor_sync(0xffffffffu, acc, o);
    return 1.0f / (1.0f + __expf(-acc));
}
DEVINL uint4 ldg_nc(const void* p) { uint4 v; asm volatile("ld.global.nc.v4.u32 {%0,%1,%2,%3}, [%4];" : "=r"(v.x), "=r"(v.y), "=r"(v.z), "=r"(v.w) : "l"(p) : "memory"); return v; }
DEVINL uint32_t ld_strong4(const void* p) { uint32_t v; asm volatile("ld.relaxed.gpu.global.u32 %0, [%1];" : "=r"(v) : "l"(p) : "memory"); return v; }
DEVINL void wait_count(const uint32_t* p, uint32_t want) {
    uint32_t v, n = 0;
    while (true) {
        asm volatile("ld.acquire.gpu.global.u32 %0, [%1];" : "=r"(v) : "l"(p) : "memory");
        if (v >= want) break;
        __nanosleep(200);
        if (++n > 10000000u) __trap();
    }
}

constexpr int KR = 44;
constexpr int KS = 64 - KR;
constexpr int R_W = 0;
constexpr int R_WO = KS * 4096;
constexpr int R_QX = R_WO + 65536;
constexpr int R_RING = R_WO + 98304;
constexpr int R_K = R_RING + 24576;
constexpr int R_V = R_K + 10240;
constexpr int R_QM = R_V + 10240;
constexpr int R_O = R_QM + 2048;
constexpr int R_BAR = R_O + 2048;
constexpr int R_G = R_BAR + 256 + 512 + 256 + 128;
constexpr int R_Z = R_G + 256;
constexpr int R_SMEM = R_Z + 1024;
enum { B_FULL = 0, B_EMPTY = 5, B_MEM = 8, B_HOP1 = 12, B_XT, B_TFREE, B_O, B_AFREE0, B_AFREE1, B_PRO0, B_PRO1, B_XRECV, B_P, B_XDONE, B_OST0, B_OST1, B_HOPV };
#define D2_BASE 900
#define D2_STEP 200
#define PD2 6
#define CPB 8192
#define DDUP 0
#define WGAP 0
#define PVD 400
#define ELD 700
#define QD 3
#define DQ 1700
#define D3 0

DEVINL uint32_t clk32() { uint32_t c_; asm volatile("mov.u32 %0, %%clock;" : "=r"(c_)); return c_; }
DEVINL void spin_until(uint32_t t) { while ((uint32_t)(t - clk32() - 1u) < 100000u) {} }
#define PROF(i)
#define PROF2(i)
#define PROF3(i, val)
DEVINL void e_arrive(uint32_t bar) { asm volatile("{ .reg .pred p; elect.sync _|p, 0xffffffff; @p mbarrier.arrive.shared::cta.b64 _, [%0]; }" ::"r"(bar) : "memory"); }
DEVINL void e_arrive_remote(uint32_t cbar) { asm volatile("{ .reg .pred p; elect.sync _|p, 0xffffffff; @p mbarrier.arrive.relaxed.cluster.shared::cluster.b64 _, [%0]; }" ::"r"(cbar) : "memory"); }
DEVINL void e_count(uint32_t* p) { asm volatile("{ .reg .pred p; elect.sync _|p, 0xffffffff; @p red.relaxed.gpu.global.add.u32 [%0], 1; }" ::"l"(p) : "memory"); }
DEVINL void e_expect(uint32_t bar, uint32_t bytes) { asm volatile("{ .reg .pred p; elect.sync _|p, 0xffffffff; @p mbarrier.arrive.expect_tx.shared::cta.b64 _, [%0], %1; }" ::"r"(bar), "r"(bytes) : "memory"); }
DEVINL void e_tma_load(uint32_t dst, const CUtensorMap* tm, int c0, int c1, uint32_t bar) {
    asm volatile("{ .reg .pred p; elect.sync _|p, 0xffffffff; @p cp.async.bulk.tensor.2d.shared::cluster.global.mbarrier::complete_tx::bytes [%0], [%1, {%3, %4}], [%2]; }"
                 ::"r"(dst), "l"(tm), "r"(bar), "r"(c0), "r"(c1) : "memory");
}
DEVINL void e_tma_store(const CUtensorMap* tm, uint32_t src, int c0, int c1) {
    asm volatile("{ .reg .pred p; elect.sync _|p, 0xffffffff; @p cp.async.bulk.tensor.2d.global.shared::cta.bulk_group [%0, {%2, %3}], [%1]; }" ::"l"(tm), "r"(src), "r"(c0), "r"(c1) : "memory");
}
DEVINL void e_bulk_s2g(void* dst, uint32_t src, uint32_t bytes) {
    asm volatile("{ .reg .pred p; elect.sync _|p, 0xffffffff; @p cp.async.bulk.global.shared::cta.bulk_group [%0], [%1], %2; }" ::"l"(dst), "r"(src), "r"(bytes) : "memory");
}
DEVINL void e_bulk_s2s(uint32_t cdst, uint32_t src, uint32_t bytes, uint32_t cbar) {
    asm volatile("{ .reg .pred p; elect.sync _|p, 0xffffffff; @p cp.async.bulk.shared::cluster.shared::cta.mbarrier::complete_tx::bytes [%0], [%1], %2, [%3]; }" ::"r"(cdst), "r"(src), "r"(bytes), "r"(cbar) : "memory");
}

#define SLOT 0
#define PH3 0
#define PHQ 0
DEVINL void wait_slot(uint32_t phase) {
    if (SLOT) {
        uint32_t c; asm volatile("mov.u32 %0, %%globaltimer_lo;" : "=r"(c));
        const uint32_t tgt = c + (SLOT ? SLOT : 1) - ((c - phase) % (SLOT ? SLOT : 1));
        do { asm volatile("mov.u32 %0, %%globaltimer_lo;" : "=r"(c)); } while ((uint32_t)(tgt - c - 1u) < 100000u);
    }
}
template <int N> DEVINL uint32_t poll_set(uint4 (&v)[N], const uint32_t* rp, int stride, uint32_t phase, uint32_t wbar = 0, uint32_t wpar = 0) {
    wait_slot(phase);
#pragma unroll
    for (int i = 0; i < N; i++) v[i] = ld_strong16(rp + i * stride);
    if (wbar) mbar_wait(wbar, wpar);
    uint32_t n = 0;
    while (true) {
        uint32_t m = 0xffffffffu;
#pragma unroll
        for (int i = 0; i < N; i++) m = min4(v[i], m);
        if (__all_sync(0xffffffffu, m != 0u)) return n;
        wait_slot(phase);
#pragma unroll
        for (int i = 0; i < N; i++)
            asm volatile("{ .reg .pred p; setp.eq.u32 p, %5, 0; @p ld.relaxed.gpu.global.v4.u32 {%0,%1,%2,%3}, [%4]; }"
                         : "+r"(v[i].x), "+r"(v[i].y), "+r"(v[i].z), "+r"(v[i].w) : "l"(rp + i * stride), "r"(min4(v[i], 0xffffffffu)) : "memory");
        if (++n > 20000000u) __trap();
    }
}

struct RMaps { CUtensorMap x, w[3], wo, o; };
#define KC(c) ((c) * 64)

#define XORD 3
__host__ __device__ constexpr int xo(int i) {
    return XORD == 0 ? i : XORD == 1 ? (i + 14) % 16 : XORD == 2 ? (i + 11) % 16
         : XORD == 3 ? (i < 10 ? ((i & 1) ? i / 2 : 11 + i / 2) : i - 5) : (i < 6 ? i : ((i & 1) ? 6 + (i - 6) / 2 : 11 + (i - 6) / 2));
}
#define XC(i) (xo(i) * 64)
DEVINL void x_load_pair(uint32_t dst, const CUtensorMap* tmx, int h, int p, int seg, uint32_t fbar) {
    e_expect(fbar, 8192);
    e_tma_load(dst, tmx, XC(2 * p), seg * SEG, fbar);
    e_tma_load(dst + 4096, tmx, XC(2 * p + 1), seg * SEG, fbar);
}
__host__ __device__ constexpr int wo_tile(int role, int i) {
    return role == 0 ? (i < 2 ? 8 + i : 12 + i) : (i < 4 ? (i >> 1) * 4 : 10) + (role - 1) * 2 + (i & 1);
}

template <int NT> DEVINL void wo_phase(uint32_t sb, int tb, uint32_t* pp, uint32_t obar, uint32_t opar) {
    const int lane = tb & 31, krow = (lane & 7) + ((lane >> 4) << 3), chunk = ((tb >> 5) & 3) * 2 + ((lane >> 3) & 1);
    uint32_t wa = sb + R_WO + (tb >> 7) * 16384 + krow * 128 + ((chunk ^ (krow & 7)) << 4);
    uint32_t af[4][4], of[4][4];
#pragma unroll
    for (int g = 0; g < 4; g++) ldsm4t(af[g], wa + g * 2048);
    mbar_wait(obar, opar);
#pragma unroll
    for (int g = 0; g < 4; g++) ldsm4t(of[g], sb + R_O + g * 512 + lane * 16);
#pragma unroll 1
    for (int i = 0; i < NT; i++) {
        float w0[4] = {0.f, 0.f, 0.f, 0.f}, w1[4] = {0.f, 0.f, 0.f, 0.f};
        const int more = NT - 1 - i, yes = NT - i;
        mma16816(w0, af[0][0], af[0][1], af[0][2], af[0][3], of[0][0], of[0][1]);
        ldsm4t_if(af[0], wa + 4 * 2048, yes);
        mma16816(w1, af[1][0], af[1][1], af[1][2], af[1][3], of[0][2], of[0][3]);
        ldsm4t_if(af[1], wa + 5 * 2048, yes);
        mma16816(w0, af[2][0], af[2][1], af[2][2], af[2][3], of[1][0], of[1][1]);
        ldsm4t_if(af[2], wa + 6 * 2048, yes);
        mma16816(w1, af[3][0], af[3][1], af[3][2], af[3][3], of[1][2], of[1][3]);
        ldsm4t_if(af[3], wa + 7 * 2048, yes);
        wa += 32768;
        mma16816(w0, af[0][0], af[0][1], af[0][2], af[0][3], of[2][0], of[2][1]);
        ldsm4t_if(af[0], wa, more);
        mma16816(w1, af[1][0], af[1][1], af[1][2], af[1][3], of[2][2], of[2][3]);
        ldsm4t_if(af[1], wa + 2048, more);
        mma16816(w0, af[2][0], af[2][1], af[2][2], af[2][3], of[3][0], of[3][1]);
        ldsm4t_if(af[2], wa + 2 * 2048, more);
        mma16816(w1, af[3][0], af[3][1], af[3][2], af[3][3], of[3][2], of[3][3]);
        ldsm4t_if(af[3], wa + 3 * 2048, more);
        st_strong4(pp, pack_nz(w0[0] + w1[0], w0[1] + w1[1]));
        st_strong4(pp + 1024, pack_nz(w0[2] + w1[2], w0[3] + w1[3]));
        pp += (NT == 3 && i == 0) ? 4 * 8192 : 6 * 8192;
    }
}

template <uint32_t role> DEVINL void r_big(const RMaps& tm, const int wid) {
    extern __shared__ __align__(1024) unsigned char smem_raw[];
    const uint32_t sb = smem_u32(smem_raw);
    const uint32_t bar = sb + R_BAR;
    const int tid = threadIdx.x;
    int h; asm("mov.u32 %0, %%clusterid.x;" : "=r"(h));
        uint32_t a[KR][4];
        mbar_wait(bar + 8 * B_PRO0, 0);
        PT(0);
        {
            const int lane = tid & 31;
            const int krow = (lane & 7) + ((lane >> 4) << 3);
            const int chunk = (wid & 3) * 2 + ((lane >> 3) & 1);
            const uint32_t la = sb + (wid >> 2) * 8192 + krow * 128 + ((chunk ^ (krow & 7)) << 4);
#pragma unroll
            for (int k = 0; k < KR; k++) ldsm4t(a[k], la + (k >> 2) * 16384 + (k & 3) * 2048);
        }
        bar_sync(1, 256);
        {
            fence_async();
            const CUtensorMap* tw = &tm.w[role];
            e_expect(bar + 8 * B_PRO1, (wid < 5 ? 16384 : 0) + (wid < (role == 0 ? 4 : 6) ? 16384 : 0));
            if (wid < 5) {
                e_tma_load(sb + R_W + wid * 8192, tw, h * DH, KC(KR / 4 + wid), bar + 8 * B_PRO1);
                e_tma_load(sb + R_W + KS * 2048 + wid * 8192, tw, h * DH + 64, KC(KR / 4 + wid), bar + 8 * B_PRO1);
            }
            if (wid < (role == 0 ? 4 : 6)) e_tma_load(sb + R_WO + wid * 16384, &tm.wo, wo_tile(role, wid) * 64, h * DH, bar + 8 * B_PRO1);
        }
        constexpr uint32_t e0 = role == 0 ? R_QX + 16384 : R_K + 2048, e1 = role == 0 ? R_QX + 24576 : R_V + 2048;
        if (wid == 6) x_load_pair(sb + e0, &tm.x, h, 3, 0, bar + 8 * (B_FULL + 3));
        if (wid == 7) x_load_pair(sb + e1, &tm.x, h, 4, 0, bar + 8 * (B_FULL + 4));
        PT(1);
        mbar_wait(bar + 8 * B_PRO1, 0);
        PT(2);

        constexpr uint64_t dW0 = cdesc(R_W, 1024, 1024, 1);
        constexpr uint64_t dM = cdesc(R_RING, 128, 128, 0);
        constexpr uint64_t dX = cdesc(R_RING, 16, 1024, 1);
        constexpr uint64_t dX0 = cdesc(0, 16, 1024, 1);
        int tb = tid;
        int wq = wid;

        for (int seg = 0; seg < NSEG; seg++) {
            {
            const int s = seg - 1; (void)s;
            float d[16];
            OPAQUE(wq);
            const uint64_t dW = dW0 + (uint64_t)((wq >> 2) * (KS * 128));
#pragma unroll
            for (int p = 0; p < 8; p++) {
                const int slot = p % 5;
                mbar_wait(bar + 8 * (B_FULL + slot), slot < 3 ? (uint32_t)(p / 5) : (uint32_t)(seg & 1));
                PROF2(p);
                const uint64_t db = slot < 3 ? dX + (uint64_t)(slot * 512) : dX0 + (uint64_t)((slot == 3 ? e0 : e1) >> 4);
                wg_fence();
#pragma unroll
                for (int kk = 0; kk < 8; kk++) {
                    const int k = XORD >= 3 ? (kk & 1) * 4 + (kk >> 1) : kk;
                    const int ks = xo(2 * p + (k >> 2)) * 4 + (k & 3);
                    if (ks >= KR) wg_ss32<1>(d, dW + (uint64_t)((ks - KR) * 128), db + (uint64_t)((k >> 2) * 256 + (k & 3) * 2), p + k);
                    else wg_rs32(d, a[ks < KR ? ks : 0], db + (uint64_t)((k >> 2) * 256 + (k & 3) * 2), p + k);
                }
                wg_commit();
                if (p >= 1) {
                    wg_wait<1>();
                    if (p <= 3) {
                        if ((wq & 3) == p) e_arrive(bar + 8 * (B_EMPTY + p - 1));
                        if (wq == p + (p & 1) * 4) {
                            mbar_wait(bar + 8 * (B_EMPTY + p - 1), seg & 1);
                            x_load_pair(sb + R_RING + (p - 1) * 8192, &tm.x, h, p + 4, seg, bar + 8 * (B_FULL + p - 1));
                        }
                    }
                    if (p == 5 && role != 0 && (wq & 3) < 3) e_arrive_remote(mapa(bar + 8 * B_TFREE, wq & 3));
                    if (p == 6 && (wq & 3) == 1) e_arrive(bar + 8 * B_AFREE0);
                    if (p == 7 && (wq & 3) == 2) e_arrive(bar + 8 * B_AFREE1);
                }
            }
            mbar_wait(bar + 8 * B_TFREE, seg & 1);
            asm volatile("wgmma.wait_group.sync.aligned 0;" : ACC16(d)::"memory");
            PROF2(16);
            const uint32_t tilex = sb + (role == 0 ? R_QX + 2048 : (role == 1 ? R_K + 2048 : R_V + 2048));
            {
                OPAQUE(tb);
                const uint32_t gs = role == 0 ? 4096 : 2048;
                const uint32_t sa = tilex + ((tb >> 4) & 1) * gs + (tb >> 5) * 256 + (tb & 15) * 16;
                stsm4(sa, pack_bf16(d[0], d[1]), pack_bf16(d[2], d[3]), pack_bf16(d[4], d[5]), pack_bf16(d[6], d[7]));
                stsm4(sa + 2 * gs, pack_bf16(d[8], d[9]), pack_bf16(d[10], d[11]), pack_bf16(d[12], d[13]), pack_bf16(d[14], d[15]));
            }
            __syncwarp();
            e_arrive(bar + 8 * B_XDONE);
            if (role != 0 && (wq & 3) == 0) {
                mbar_wait(bar + 8 * B_XDONE, seg & 1);
                fence_async();
                uint32_t pr = role + 1 + (wq >> 2); pr = pr >= 3 ? pr - 3 : pr;
                e_bulk_s2s(mapa(tilex, pr), tilex, CPB, mapa(bar + 8 * B_XT, pr));
            }
            }
            {
                const int s = seg;
                OPAQUE(wq);
                const uint64_t dW = dW0 + (uint64_t)((wq >> 2) * (KS * 128));
                float y[4] = {0.f, 0.f, 0.f, 0.f};
                {
                    OPAQUE(tb);
                    const uint32_t ma = sb + R_RING + (tb & 31) * 16;
                    float z[4] = {0.f, 0.f, 0.f, 0.f}, u[4] = {0.f, 0.f, 0.f, 0.f};
                    uint32_t b[QD][4];
                    const int yes = s + 1;
                    mbar_wait(bar + 8 * B_MEM, s & 1);
                    PROF((wq >> 2) * 4 + 0);
                    if (s == 0) PT(3);
                    if (s == 1) PT(4);
#pragma unroll
                    for (int g = 0; g < QD; g++) ldsm4t(b[g], ma + g * 512);
#pragma unroll
                    for (int g = 0; g < KR / 2; g++) {
                        float* c0 = (g % 3 == 0) ? y : (g % 3 == 1) ? u : z;
                        float* c1 = (g % 3 == 0) ? z : (g % 3 == 1) ? y : u;
                        mma16816(c0, a[2 * g][0], a[2 * g][1], a[2 * g][2], a[2 * g][3], b[g % QD][0], b[g % QD][1]);
                        mma16816(c1, a[2 * g + 1][0], a[2 * g + 1][1], a[2 * g + 1][2], a[2 * g + 1][3], b[g % QD][2], b[g % QD][3]);
                        if (g + QD < KR / 2) {
                            if ((g + QD) % 8 == 0) mbar_wait(bar + 8 * (B_MEM + (g + QD) / 8), s & 1);
                            ldsm4t_if(b[g % QD], ma + (g + QD) * 512, yes);
                        }
                    }
                    y[0] += z[0] + u[0]; y[1] += z[1] + u[1]; y[2] += z[2] + u[2]; y[3] += z[3] + u[3];
                }
                PROF2(8);
                mbar_wait(bar + 8 * (B_MEM + 3), s & 1);
                wg_fence();
#pragma unroll
                for (int k = KR; k < 64; k++) wg_ss8<1, 1>(y, dW + (uint64_t)((k - KR) * 128), dM + (uint64_t)(k * 16), 1);
                wg_commit();
                asm volatile("wgmma.wait_group.sync.aligned 0;" : "+f"(y[0]), "+f"(y[1]), "+f"(y[2]), "+f"(y[3])::"memory");
                OPAQUE(tb);
                {
                    const uint32_t wo_ = (tb >> 5) * 256;
                    const uint32_t tile = sb + (role == 0 ? R_QX : (role == 1 ? R_K : R_V)) + wo_;
                    const uint32_t u0 = pack_bf16(y[0], y[1]), u1 = pack_bf16(y[2], y[3]);
                    sts32(tile + (tb & 31) * 4, u0);
                    sts32(tile + (tb & 31) * 4 + 128, u1);
                    __syncwarp();
                    uint4 v = lds128(tile + (tb & 15) * 16);
                    uint32_t peer = role + 1 + ((tb >> 4) & 1);
                    peer = peer >= 3 ? peer - 3 : peer;
                    const uint32_t rt = sb + (role == 0 ? R_QM : (role == 1 ? R_K : R_V)) + wo_ + (tb & 15) * 16;
                    st_async16(mapa(rt, peer), v, mapa(bar + 8 * (role == 2 ? B_HOPV : B_HOP1), peer));
                    if (role == 0) {
                        sts128(tile + 4096 + ((tb >> 4) & 1) * 4096 + (tb & 15) * 16, v);
                        sts32(tile + 12288 + (tb & 31) * 4, u0);
                        sts32(tile + 12288 + (tb & 31) * 4 + 128, u1);
                        __syncwarp();
                    }
                    e_arrive(bar + 8 * (role == 2 ? B_HOPV : B_HOP1));
                }
                PROF((wq >> 2) * 4 + 1);
                if (s < NSEG - 1) {
                    bar_sync(1, 256);
                    if (wq < 3) { fence_async(); x_load_pair(sb + R_RING + wq * 8192, &tm.x, h, wq, s + 1, bar + 8 * (B_FULL + wq)); }
                    else if (role == 0 && wq < 5) x_load_pair(sb + (wq == 3 ? e0 : e1), &tm.x, h, wq, s + 1, bar + 8 * (B_FULL + wq));
                    OPAQUE(tb);
                }
                uint32_t* pp = g_part[s & 3] + (h * 32 + (wo_tile(role, 0) + (tb >> 7)) * 8192 + ((tb >> 5) & 3) * 2048 + (tb & 31));
                asm volatile("" : "+l"(pp));
                if (s == NSEG - 1) break;
                wo_phase<role == 0 ? 2 : 3>(sb, tb, pp, bar + 8 * B_O, s & 1);
                if (wq == 0) PROF(10);
            }
        }
}

#define CLR 0
#define CLEAR(st) do { if (role != 0) { \
                const int w_ = wid & 3; \
                uint32_t* zp = g_part[(st) & 3] + ((rg0 + (w_ >> 1) * 64) * 1024 + (w_ & 1) * 512); \
                e_bulk_s2g(zp, sb + R_Z, 1024); \
                e_bulk_s2g(zp + 256, sb + R_Z, 1024); \
                e_bulk_s2g(&g_mem[(st) & 3][(rg0 + (w_ >> 1) * 64) * 32 + (w_ & 1) * 16], sb + R_Z, 64); \
                bulk_commit(); } } while (0)
template <uint32_t role> DEVINL void r_chain(const RMaps& tm, const bf16* __restrict__ mem0, const int wid) {
    extern __shared__ __align__(1024) unsigned char smem_raw[];
    const uint32_t sb = smem_u32(smem_raw);
    const uint32_t bar = sb + R_BAR;
    const int tid = threadIdx.x;
    int h; asm("mov.u32 %0, %%clusterid.x;" : "=r"(h));
        int t = tid & 127;
        const float sl2 = 0.08838834764831845f * 1.4426950408889634f;
        const float NEGRAW = -1000000000.0f / 0.08838834764831845f;
        const int rg0 = ((int)role - 1) * 32 + h;
        if (role != 0) {
#pragma unroll 1
            for (int r = 0; r < 4; r++) {
                uint32_t* zp = g_part[r] + ((rg0 + (t >> 6) * 64) * 1024 + (t & 63) * 4);
#pragma unroll
                for (int i = 0; i < 4; i++) st_strong16(zp + i * 256, make_uint4(0u, 0u, 0u, 0u));
                if ((t & 63) < 8) st_strong16(&g_mem[r][(rg0 + (t >> 6) * 64) * 32 + (t & 63) * 4], make_uint4(0u, 0u, 0u, 0u));
            }
            __threadfence();
        }
        if (role == 0 && (wid & 3) < 3) e_arrive_remote(mapa(bar + 8 * B_TFREE, wid & 3));
        if (t < 64) sts128(sb + R_Z + t * 16, make_uint4(0u, 0u, 0u, 0u));
        if (role == 0) sts128(sb + R_QM + t * 16, make_uint4(0u, 0u, 0u, 0u));
        {
            uint4 v[8];
#pragma unroll
            for (int r = 0; r < 8; r++) v[r] = __ldg((const uint4*)(mem0 + r * DM) + t);
            mbar_wait(bar + 8 * B_AFREE0, 0);
            mbar_wait(bar + 8 * B_AFREE1, 0);
#define TR2(f, c) \
            sts128(sb + R_RING + t * 128 + (c) * 16, make_uint4(__byte_perm(v[0].f, v[1].f, 0x5410), __byte_perm(v[2].f, v[3].f, 0x5410), __byte_perm(v[4].f, v[5].f, 0x5410), __byte_perm(v[6].f, v[7].f, 0x5410))); \
            sts128(sb + R_RING + t * 128 + (c) * 16 + 16, make_uint4(__byte_perm(v[0].f, v[1].f, 0x7632), __byte_perm(v[2].f, v[3].f, 0x7632), __byte_perm(v[4].f, v[5].f, 0x7632), __byte_perm(v[6].f, v[7].f, 0x7632)));
            TR2(x, 0) TR2(y, 2) TR2(z, 4) TR2(w, 6)
            fence_async();
            __syncwarp();
            e_arrive(bar + 8 * B_MEM + (t >> 5) * 8);
        }
        constexpr uint64_t dQ = role == 0 ? cdesc(R_QX, 128, 2048, 0) : cdesc(R_QM, 128, 0, 0);
        constexpr uint64_t dK = cdesc(R_K, 128, 2048, 0);

        for (int s = 0; s < NSEG; s++) {
            if (role == 0) {
                uint32_t n = 0, gate;
                do { gate = ld_strong4(&g_gate[s * SEG + (t >> 2)]); if (++n > 20000000u) __trap(); } while (gate == 0u);
                sts32(sb + R_G + (t >> 2) * 4, gate);
                __syncwarp();
            }
            mbar_wait(bar + 8 * B_XDONE, s & 1);
            mbar_wait(bar + 8 * B_XT, s & 1);
            if (t >= 1 && t < 3) { uint32_t pr = role + t; pr = pr >= 3 ? pr - 3 : pr; mbar_arrive_remote(mapa(bar + 8 * B_XRECV, pr)); }
            __syncwarp();
            mbar_wait(bar + 8 * B_HOP1, s & 1);
            PROF(8);
            fence_async();
            OPAQUE(t);
            if (s == NSEG - 1 && role != 0) { mbar_wait(bar + 8 * B_HOPV, s & 1); bulk_wait_all(); break; }
            float sc[20];
            wg_fence();
#pragma unroll
            for (int k = 0; k < 8; k++) wg_ss40(sc, dQ + (uint64_t)(k * 16), dK + (uint64_t)(k * 16), k);
            wg_commit();
            uint32_t t_o = clk32() + 500;
            {
                const uint32_t va = sb + R_V + 2048 + (t >> 5) * 512 + ((t >> 4) & 1) * 2048 + (t & 15) * 16;
                uint32_t v0[4], v1[4];
                ldsm4(v0, va); ldsm4(v1, va + 256);
                uint32_t vm[4];
                const bool v_here = mbar_try(bar + 8 * B_HOPV, s & 1);
                if (v_here) ldsm4(vm, sb + R_V + t * 16);
                wg_wait<0>();
                if (role == 0) {
#pragma unroll
                    for (int j = 0; j < 5; j++)
                        asm volatile("st.shared.v2.f32 [%0], {%1,%2};" ::"r"(sb + R_QX + 768 + (t >> 5) * 4096 + j * 256 + (t & 31) * 8), "f"(sc[4 * j + 2]), "f"(sc[4 * j + 3]) : "memory");
                }
                float m = fmaxf(sc[0], sc[1]);
#pragma unroll
                for (int j = 1; j < 5; j++) m = fmaxf(m, fmaxf(sc[4 * j], sc[4 * j + 1]));
                m = fmaxf(m, __shfl_xor_sync(0xffffffffu, m, 1));
                m = fmaxf(m, __shfl_xor_sync(0xffffffffu, m, 2));
                const float mb = m * sl2;
                uint32_t pk[5];
#pragma unroll
                for (int j = 0; j < 5; j++) pk[j] = pack_bf16(ex2(fmaf(sc[4 * j], sl2, -mb)), ex2(fmaf(sc[4 * j + 1], sl2, -mb)));
                float o0[4] = {0.f, 0.f, 0.f, 0.f}, o1[4] = {0.f, 0.f, 0.f, 0.f}, ls[4] = {0.f, 0.f, 0.f, 0.f};
                constexpr uint32_t ONE = 0x3F803F80u;
                mma16816(o0, v0[0], v0[1], v0[2], v0[3], pk[1], pk[2]);
                mma16816(o1, v1[0], v1[1], v1[2], v1[3], pk[1], pk[2]);
                ldsm4(v0, va + 4096); ldsm4(v1, va + 4096 + 256);
                mma16816(ls, ONE, ONE, ONE, ONE, pk[1], pk[2]);
                mma16816(ls, ONE, ONE, ONE, ONE, pk[3], pk[4]);
                mma1688(ls, ONE, ONE, pk[0]);
                mma16816(o0, v0[0], v0[1], v0[2], v0[3], pk[3], pk[4]);
                mma16816(o1, v1[0], v1[1], v1[2], v1[3], pk[3], pk[4]);
                if (!v_here) { mbar_wait(bar + 8 * B_HOPV, s & 1); ldsm4(vm, sb + R_V + t * 16); }
                mma1688(o0, vm[0], vm[1], pk[0]);
                mma1688(o1, vm[2], vm[3], pk[0]);
                const float i0 = rcp(ls[0]), i1 = rcp(ls[1]);
                const uint32_t oa = sb + R_O + (t >> 5) * 512 + (t & 31) * 4;
                sts32(oa, pack_bf16(o0[0] * i0, o0[1] * i1));
                sts32(oa + 128, pack_bf16(o0[2] * i0, o0[3] * i1));
                sts32(oa + 256, pack_bf16(o1[0] * i0, o1[1] * i1));
                sts32(oa + 384, pack_bf16(o1[2] * i0, o1[3] * i1));
                __syncwarp();
                e_arrive(bar + 8 * B_O);
                PROF(9);
                if (role == 0) {
                    OPAQUE(t);
                    const int lim = (t >> 2) - (t & 3) * 2 + 8;
                    float z[10];
#pragma unroll
                    for (int j = 0; j < 5; j++)
                        asm volatile("ld.shared.v2.f32 {%0,%1}, [%2];" : "=f"(z[2 * j]), "=f"(z[2 * j + 1]) : "r"(sb + R_QX + 768 + (t >> 5) * 4096 + j * 256 + (t & 31) * 8) : "memory");
                    float gate; asm volatile("ld.shared.f32 %0, [%1];" : "=f"(gate) : "r"(sb + R_G + (t >> 2) * 4) : "memory");
                    float m1 = fmaxf(z[0], z[1]);
#pragma unroll
                    for (int j = 1; j < 5; j++) {
                        z[2 * j] = 8 * j <= lim ? z[2 * j] : NEGRAW;
                        z[2 * j + 1] = 8 * j + 1 <= lim ? z[2 * j + 1] : NEGRAW;
                        m1 = fmaxf(m1, fmaxf(z[2 * j], z[2 * j + 1]));
                    }
                    m1 = fmaxf(m1, __shfl_xor_sync(0xffffffffu, m1, 1));
                    m1 = fmaxf(m1, __shfl_xor_sync(0xffffffffu, m1, 2));
                    const float mb1 = m1 * sl2;
                    float l1 = 0.f;
                    const uint32_t pa = sb + R_QX + (t >> 5) * 4096 + (t & 31) * 4;
#pragma unroll
                    for (int j = 0; j < 5; j++) {
                        const uint32_t pw = pack_bf16(ex2(fmaf(z[2 * j], sl2, -mb1)), ex2(fmaf(z[2 * j + 1], sl2, -mb1)));
                        l1 += __uint_as_float(pw << 16) + __uint_as_float(pw & 0xffff0000u);
                        sts32(pa + j * 128, pw);
                    }
                    sts32(pa + 5 * 128, 0u);
                    l1 += __shfl_xor_sync(0xffffffffu, l1, 1);
                    l1 += __shfl_xor_sync(0xffffffffu, l1, 2);
                    sts32(sb + R_G + 128 + (t >> 2) * 4, __float_as_uint(gate * rcp(l1)));
                    spin_until(t_o + PVD);
                    if ((wid & 3) == 0 && s >= 1) { bulk_wait_all(); e_count(&g_ocnt[(s - 1) >> 2]); }
                    fence_async();
                    bar_sync(2, 128);
                    constexpr uint64_t dV = cdesc(R_V, 2048, 128, 0);
                    constexpr uint64_t dP = cdesc(R_QX, 128, 4096, 0);
                    float sf[8];
#pragma unroll
                    for (int j = 0; j < 4; j++) asm volatile("ld.shared.v2.f32 {%0,%1}, [%2];" : "=f"(sf[2 * j]), "=f"(sf[2 * j + 1]) : "r"(sb + R_G + 128 + j * 32 + (t & 3) * 8) : "memory");
                    const uint32_t r = ((t >> 4) & 1) * 8 + (t & 7), ch = (t >> 5) * 2 + ((t >> 3) & 1);
                    const uint32_t sa = sb + R_QX + 2048 + r * 128 + ((ch ^ (r & 7)) << 4);
#pragma unroll
                    for (int hf = 0; hf < 2; hf++) {
                        float d[16];
                        wg_fence();
#pragma unroll
                        for (int k = 0; k < 3; k++) wg_ss32<0>(d, dV + (uint64_t)(hf * 64 + k * 256), dP + (uint64_t)(k * 16), k);
                        wg_commit();
                        asm volatile("wgmma.wait_group.sync.aligned 0;" : ACC16(d)::"memory");
                        stsm4t(sa + hf * 8192, pack_bf16(d[0] * sf[0], d[1] * sf[1]), pack_bf16(d[2] * sf[0], d[3] * sf[1]), pack_bf16(d[4] * sf[2], d[5] * sf[3]), pack_bf16(d[6] * sf[2], d[7] * sf[3]));
                        stsm4t(sa + hf * 8192 + 4096, pack_bf16(d[8] * sf[4], d[9] * sf[5]), pack_bf16(d[10] * sf[4], d[11] * sf[5]), pack_bf16(d[12] * sf[6], d[13] * sf[7]), pack_bf16(d[14] * sf[6], d[15] * sf[7]));
                    }
                    fence_async();
                    bar_sync(2, 128);
                    if ((wid & 3) == 0) {
#pragma unroll
                        for (int q = 0; q < 4; q++) e_tma_store(&tm.o, sb + R_QX + 2048 + q * 4096, h * DH + (q >> 1) * 64, s * SEG + (q & 1) * 16);
                        bulk_commit();
                        bulk_wait_read();
                    }
                    if ((wid & 3) < 3) e_arrive_remote(mapa(bar + 8 * B_TFREE, wid & 3));
                }
            }
            if (t < 32) { e_expect(bar + 8 * B_HOP1, role == 2 ? 4096 : 2048); if (role != 2) e_expect(bar + 8 * B_HOPV, 2048); e_expect(bar + 8 * B_XT, role == 0 ? 2 * CPB : CPB); }
            if (s == NSEG - 1) { bulk_wait_all(); break; }
            if (role != 0 && (wid & 3) >= 2) {
                mbar_wait(bar + 8 * B_XRECV, s & 1);
                mbar_wait(bar + 8 * B_O, s & 1);
                fence_async();
                spin_until(t_o + ELD);
                x_load_pair(sb + ((wid & 1) ? R_V + 2048 : R_K + 2048), &tm.x, h, 3 + (wid & 1), s + 1, bar + 8 * (B_FULL + 3 + (wid & 1)));
            }
            OPAQUE(t);
            PROF(11);
            if (role != 0 || DDUP) {
                const int grp = role == 0 ? (t >> 6) * 32 + h : rg0 + (t >> 6) * 64;
                const uint32_t* rp = g_part[s & 3] + (grp * 1024 + ((t >> 2) & 7) * 32 + ((t >> 5) & 1) * 16 + (t & 3) * 4);
                uint32_t* wp = &g_mem[(s + 1) & 3][grp * 32 + ((t >> 5) & 1) * 16 + (t & 3) * 4 + ((t >> 3) & 3)];
                bulk_wait_all();
                spin_until(t_o + D2_BASE + (role == 0 ? DDUP + (t >> 6) * D2_STEP : (role - 1 + (t >> 6) * 2) * D2_STEP));
                PROF3(0, clk32());
#define LO(u) __uint_as_float((u) << 16)
#define HI(u) __uint_as_float((u) & 0xffff0000u)
                uint4 v[4];
                uint32_t n = poll_set<4>(v, rp, 256, (role - 1 + (t >> 6) * 2) * PHQ);
                {
                    PROF3(1, clk32());
                    float f[8];
                    f[0] = (LO(v[0].x) + LO(v[1].x)) + (LO(v[2].x) + LO(v[3].x)); f[1] = (HI(v[0].x) + HI(v[1].x)) + (HI(v[2].x) + HI(v[3].x));
                    f[2] = (LO(v[0].y) + LO(v[1].y)) + (LO(v[2].y) + LO(v[3].y)); f[3] = (HI(v[0].y) + HI(v[1].y)) + (HI(v[2].y) + HI(v[3].y));
                    f[4] = (LO(v[0].z) + LO(v[1].z)) + (LO(v[2].z) + LO(v[3].z)); f[5] = (HI(v[0].z) + HI(v[1].z)) + (HI(v[2].z) + HI(v[3].z));
                    f[6] = (LO(v[0].w) + LO(v[1].w)) + (LO(v[2].w) + LO(v[3].w)); f[7] = (HI(v[0].w) + HI(v[1].w)) + (HI(v[2].w) + HI(v[3].w));
                    const bool b4 = t & 16, b3 = t & 8;
                    float g4[4], g2[2];
#pragma unroll
                    for (int i = 0; i < 4; i++) g4[i] = (b4 ? f[4 + i] : f[i]) + __shfl_xor_sync(0xffffffffu, b4 ? f[i] : f[4 + i], 16);
#pragma unroll
                    for (int i = 0; i < 2; i++) g2[i] = (b3 ? g4[2 + i] : g4[i]) + __shfl_xor_sync(0xffffffffu, b3 ? g4[i] : g4[2 + i], 8);
                    g2[0] += __shfl_xor_sync(0xffffffffu, g2[0], 4);
                    g2[1] += __shfl_xor_sync(0xffffffffu, g2[1], 4);
                    st_strong4(wp, pack_nz(g2[0], g2[1]));
                }
                PROF3(8, n); (void)n;
            }
            t_o += D2_BASE + DQ + D3 + (t >> 5) * D2_STEP;
            OPAQUE(t);
            PROF(12);
            {
                const uint32_t* rp = &g_mem[(s + 1) & 3][((t >> 5) * 256 + (t & 31)) * 4];
                const uint32_t da = sb + R_RING + ((t >> 5) * 256 + (t & 31)) * 16;
                uint4 v[8];
                spin_until(t_o);
                PROF3(2, clk32());
                uint32_t n = poll_set<8>(v, rp, 128, PH3 + (t >> 5) * PHQ);
                PROF(13);
                PROF3(3, clk32()); PROF3(9, n); (void)n;
                mbar_wait(bar + 8 * B_AFREE0 + (t >> 6) * 8, (s + 1) & 1);
                PROF3(4, clk32());
#pragma unroll
                for (int i = 0; i < 8; i++) sts128(da + i * 512, v[i]);
                if (t >= 64) fence_async();
                __syncwarp();
                e_arrive(bar + 8 * B_MEM + (t >> 5) * 8);
                PROF(14);
                PROF3(5, clk32());
            }
            CLEAR(s + 3);
        }
}

__global__ void __launch_bounds__(384, 1) r_kernel(const __grid_constant__ RMaps tm, const bf16* __restrict__ mem0, const bf16* __restrict__ x, const bf16* __restrict__ gate_w) {
    extern __shared__ __align__(1024) unsigned char smem_raw[];
    const uint32_t sb = smem_u32(smem_raw);
    if ((sb & 0x3FFFFu) != SB0) __trap();
    const int tid = threadIdx.x;
    const int wid = __shfl_sync(0xffffffffu, tid >> 5, 0);
    uint32_t role; asm("mov.u32 %0, %%cluster_ctarank;" : "=r"(role));
    int h; asm("mov.u32 %0, %%clusterid.x;" : "=r"(h));
    const uint32_t bar = sb + R_BAR;
    asm volatile("griddepcontrol.launch_dependents;");
    KT(0, 0);
    const int gr = blockIdx.x * 12 + wid;
    uint4 gx0[4], gx1[4], gw[4];
#pragma unroll
    for (int i = 0; i < 4; i++) {
        gx0[i] = ldg_nc((const uint4*)(x + gr * DM) + i * 32 + (tid & 31));
        gx1[i] = ldg_nc((const uint4*)(x + min(gr + 1152, SEQ - 1) * DM) + i * 32 + (tid & 31));
        gw[i] = ldg_nc((const uint4*)gate_w + i * 32 + (tid & 31));
    }

    if (tid == 0) {
        for (int i = 0; i < 5; i++) mbar_init(bar + 8 * (B_FULL + i), 1);
        for (int i = 0; i < 3; i++) mbar_init(bar + 8 * (B_EMPTY + i), 2);
        for (int i = 0; i < 4; i++) mbar_init(bar + 8 * (B_MEM + i), 1);
        mbar_init(bar + 8 * B_HOP1, role == 2 ? 1 : 9);
        mbar_init(bar + 8 * B_HOPV, role == 2 ? 8 : 1);
        mbar_init(bar + 8 * B_XT, 1);
        mbar_init(bar + 8 * B_TFREE, 5);
        mbar_init(bar + 8 * B_P, 4);
        mbar_init(bar + 8 * B_XDONE, 8);
        mbar_init(bar + 8 * B_OST0, 4);
        mbar_init(bar + 8 * B_OST1, 4);
        mbar_init(bar + 8 * B_XRECV, 2);
        mbar_init(bar + 8 * B_O, 4);
        mbar_init(bar + 8 * B_AFREE0, 2);
        mbar_init(bar + 8 * B_AFREE1, 2);
        mbar_init(bar + 8 * B_PRO0, 1);
        mbar_init(bar + 8 * B_PRO1, 8);
        asm volatile("fence.mbarrier_init.release.cluster;" ::: "memory");
        fence_async();
        mbar_expect(bar + 8 * B_PRO0, KR * 4096);
        for (int i = 0; i < 3; i++) mbar_expect(bar + 8 * (B_FULL + i), 8192);
        mbar_expect(bar + 8 * B_HOP1, role == 2 ? 4096 : 2048);
        if (role != 2) mbar_expect(bar + 8 * B_HOPV, 2048);
        mbar_expect(bar + 8 * B_XT, role == 0 ? 2 * CPB : CPB);
    }
    __syncthreads();
    asm volatile("barrier.cluster.arrive.relaxed.aligned;" ::: "memory");
    {
        const CUtensorMap* tw = &tm.w[role];
        if (wid < 11) {
            e_tma_load(sb + wid * 16384, tw, h * DH, KC(wid), bar + 8 * B_PRO0);
            e_tma_load(sb + wid * 16384 + 8192, tw, h * DH + 64, KC(wid), bar + 8 * B_PRO0);
        }
        if (wid < 6) e_tma_load(sb + R_RING + wid * 4096, &tm.x, XC(wid), 0, bar + 8 * (B_FULL + (wid >> 1)));
        if ((tid & 31) == 0) {
            if (wid < 10) tma_prefetch(tw, h * DH + (wid & 1) * 64, KC(KR / 4 + (wid >> 1)));
            if (wid >= 6 && wid - 6 < (role == 0 ? 4 : 6)) tma_prefetch(&tm.wo, wo_tile(role, wid - 6) * 64, h * DH);
        }
        __syncwarp();
        const uint32_t g0 = __float_as_uint(gate_row(gx0, gw)), g1 = __float_as_uint(gate_row(gx1, gw));
        if ((tid & 31) == 0) {
            st_strong4(&g_gate[gr], g0 ? g0 : 0x80000000u);
            if (gr + 1152 < SEQ) st_strong4(&g_gate[gr + 1152], g1 ? g1 : 0x80000000u);
        }
        __syncwarp();
    }
    asm volatile("barrier.cluster.wait.aligned;" ::: "memory");

    if (wid < 8) {
        asm volatile("setmaxnreg.inc.sync.aligned.u32 224;");
        if (role == 0) r_big<0>(tm, wid); else if (role == 1) r_big<1>(tm, wid); else r_big<2>(tm, wid);
    } else {
        asm volatile("setmaxnreg.dec.sync.aligned.u32 56;");
        if (role == 0) r_chain<0>(tm, mem0, wid); else if (role == 1) r_chain<1>(tm, mem0, wid); else r_chain<2>(tm, mem0, wid);
    }
    __syncwarp();
    asm volatile("barrier.cluster.arrive; barrier.cluster.wait;" ::: "memory");
    KT(0, 1);
}

#define STAG 0
constexpr int G_ST = 4;
constexpr int G_STAGE = 16384 + 32768;
constexpr int G_EPI = G_ST * G_STAGE;
constexpr int G_GATE = G_EPI + 32768;
constexpr int G_BAR = G_GATE + 1024;
constexpr int G_SMEM = G_BAR + 128 + 1024;

struct G1Maps { CUtensorMap x, wg, wu, hs, o, h, wo, wd, out; };
constexpr int G1_NB = FF / 128;
constexpr int G1_TILES = 16 * G1_NB;

DEVINL void g_mma_block(float* d, uint32_t sb, uint32_t bar, int it, int wg, int tid, bool first) {
    const int st = it % G_ST;
    mbar_wait(bar + 8 * st, (it / G_ST) & 1);
    const uint64_t da = mkdesc(sb + st * G_STAGE + wg * 8192, 16, 1024, 1);
    const uint64_t db = mkdesc(sb + st * G_STAGE + 16384, 8192, 1024, 1);
    wg_fence();
#pragma unroll
    for (int k = 0; k < 4; k++) wg_ss256(d, da + (uint64_t)(k * 2), db + (uint64_t)(k * 128), (first ? 0 : 1) | k);
    wg_commit();
    if (!first) { wg_wait<1>(); if ((tid & 127) == 0) mbar_arrive(bar + 8 * (G_ST + (it - 1) % G_ST)); }
}
DEVINL void g_load_block(uint32_t sb, uint32_t bar, int it, const CUtensorMap* ta, int k0, int m0, const CUtensorMap* tb, int n0) {
    const int st = it % G_ST;
    mbar_wait(bar + 8 * (G_ST + st), ((it / G_ST) & 1) ^ 1);
    const uint32_t fb = bar + 8 * st, sa = sb + st * G_STAGE;
    mbar_expect(fb, G_STAGE);
    tma_load(sa, ta, k0, m0, fb);
#pragma unroll
    for (int q = 0; q < 4; q++) tma_load(sa + 16384 + q * 8192, tb, n0 + q * 64, k0, fb);
}

DEVINL void g_store_tile(const float* d, const CUtensorMap* tout, uint32_t epi, int mb, int nb, int wg, int tid) {
    const int lane = tid & 31, row = ((tid >> 5) & 3) * 16 + ((lane >> 3) & 1) * 8 + (lane & 7);
#pragma unroll
    for (int half = 0; half < 2; half++) {
        if ((tid & 127) == 0) bulk_wait_read();
        bar_sync(1 + wg, 128);
#pragma unroll
        for (int j = 0; j < 16; j += 2) {
            const float* e = d + half * 64 + 4 * j;
            const int cgp = j + (lane >> 4);
            stsm4(epi + (cgp >> 3) * 8192 + row * 128 + (((cgp & 7) ^ (row & 7)) << 4),
                  pack_bf16(e[0], e[1]), pack_bf16(e[2], e[3]), pack_bf16(e[4], e[5]), pack_bf16(e[6], e[7]));
        }
        fence_async();
        bar_sync(1 + wg, 128);
        if ((tid & 127) == 0) {
            tma_store(tout, epi, nb * 256 + half * 128, mb * 128 + wg * 64);
            tma_store(tout, epi + 8192, nb * 256 + half * 128 + 64, mb * 128 + wg * 64);
            bulk_commit();
        }
    }
}
template <int NS> DEVINL void g_split_finish(const float* d, float4 (&r)[32 / NS], uint4* sk, int tile, int ks, bf16* __restrict__ out, int tid) {
    constexpr int Q = 32 / NS;
    uint4* mine = sk + ks * (16 * 256) + tid;
#pragma unroll
    for (int c = 0; c < NS; c++) {
        if (c != ks) {
#pragma unroll
            for (int q = c * Q / 2; q < (c + 1) * Q / 2; q++)
                __stcg(mine + q * 256, make_uint4(pack_bf16(d[8 * q], d[8 * q + 1]), pack_bf16(d[8 * q + 2], d[8 * q + 3]), pack_bf16(d[8 * q + 4], d[8 * q + 5]), pack_bf16(d[8 * q + 6], d[8 * q + 7])));
        } else {
#pragma unroll
            for (int q = 0; q < Q; q++) { const float* e = d + (c * Q + q) * 4; r[q].x += e[0]; r[q].y += e[1]; r[q].z += e[2]; r[q].w += e[3]; }
        }
    }
    __threadfence();
    bar_sync(3, 256);
    if (tid == 0) {
        atomicAdd(&g_skcnt[tile], 1u);
        uint32_t v, n = 0;
        do {
            asm volatile("ld.acquire.gpu.global.u32 %0, [%1];" : "=r"(v) : "l"(&g_skcnt[tile]) : "memory");
            if (++n > 200000000u) __trap();
        } while (v < NS);
        if (atomicAdd(&g_skcnt[tile], 1u) == 2 * NS - 1) g_skcnt[tile] = 0u;
    }
    bar_sync(3, 256);
#pragma unroll
    for (int c = 1; c < NS; c++) {
        const uint4* th = sk + (((ks + c) & (NS - 1)) * 16 + ks * (Q / 2)) * 256 + tid;
#pragma unroll
        for (int q = 0; q < Q / 2; q++) {
            const uint4 u = __ldcg(th + q * 256);
            r[2 * q].x += __uint_as_float(u.x << 16); r[2 * q].y += __uint_as_float(u.x & 0xffff0000u);
            r[2 * q].z += __uint_as_float(u.y << 16); r[2 * q].w += __uint_as_float(u.y & 0xffff0000u);
            r[2 * q + 1].x += __uint_as_float(u.z << 16); r[2 * q + 1].y += __uint_as_float(u.z & 0xffff0000u);
            r[2 * q + 1].z += __uint_as_float(u.w << 16); r[2 * q + 1].w += __uint_as_float(u.w & 0xffff0000u);
        }
    }
    const int lane = tid & 31;
    uint32_t* op = (uint32_t*)(out + ((tile >> 2) * 128 + (tid >> 5) * 16 + (lane >> 2)) * DM + (tile & 3) * 256 + ks * Q * 8 + (lane & 3) * 2);
#pragma unroll
    for (int q = 0; q < Q; q++) { op[q * 4] = pack_bf16(r[q].x, r[q].y); op[q * 4 + 4 * DM] = pack_bf16(r[q].z, r[q].w); }
}
DEVINL int g1_count(int pass, int tail) {
    return pass == 0 ? NPRE : pass == 1 ? NFULL : pass == 2 ? T_MID - NFULL : pass == 3 ? (T_MID2 - T_MID) * 4 : tail ? (64 - T_LATE) * 8 : (T_LATE - T_MID2) * 8;
}
DEVINL int g1_first(int pass, int tail) {
    const int b = blockIdx.x, n = gridDim.x;
    return (pass < 2 || tail) ? b : pass == 2 ? n - 1 - b : (b + n - (pass == 3 ? 16 : 32)) % n;
}
DEVINL int g1_tile(int pass, int tail, int i) {
    return pass == 1 ? i : pass == 3 ? T_MID + (i >> 2) : pass == 4 ? (tail ? T_LATE : T_MID2) + (i >> 3) : NFULL + i;
}
constexpr int H_EARLY = 24;

__global__ void __launch_bounds__(384, 1) g1_kernel(const __grid_constant__ G1Maps tm, bf16* __restrict__ out, const int tail) {
    extern __shared__ __align__(1024) unsigned char smem_raw[];
    const uint32_t sb = (smem_u32(smem_raw) + 1023) & ~1023u;
    const int tid = threadIdx.x, lane = tid & 31;
    const int wg = __shfl_sync(0xffffffffu, tid >> 7, 0);
    const int warp = __shfl_sync(0xffffffffu, (tid >> 5) & 3, 0);
    const uint32_t bar = sb + G_BAR;
    asm volatile("griddepcontrol.launch_dependents;");
    KT(1 + tail, 0);
    const int ntiles = tail ? 0 : G1_TILES;
    if (tid == 0) {
        for (int i = 0; i < G_ST; i++) { mbar_init(bar + 8 * i, 1); mbar_init(bar + 8 * (G_ST + i), 2); }
        fence_async();
    }
    __syncthreads();
    if (tail) asm volatile("griddepcontrol.wait;" ::: "memory");
    if (wg == 2) {
        asm volatile("setmaxnreg.dec.sync.aligned.u32 40;");
        if (tail && warp == 1) {
            if (blockIdx.x < SEQ / 32) g_gate[blockIdx.x * 32 + lane] = 0u;
            if (blockIdx.x == 0) { if (lane < 16) g_ocnt[lane] = 0u; g_hcnt[lane] = 0u; g_pcnt[lane] = 0u; g_pcnt[32 + lane] = 0u; }
        }
        if (warp == 0) {
            if (lane == 0) {
                int it = 0;
                for (int tile = blockIdx.x; tile < ntiles; tile += gridDim.x) {
                    const int mb = tile & 15, nb = tile >> 4;
                    for (int kb = 0; kb < 16; kb++, it++) {
                        const int st = it % G_ST;
                        mbar_wait(bar + 8 * (G_ST + st), ((it / G_ST) & 1) ^ 1);
                        const uint32_t fb = bar + 8 * st, sa = sb + st * G_STAGE;
                        mbar_expect(fb, G_STAGE);
                        tma_load(sa, &tm.x, kb * 64, mb * 128, fb);
                        tma_load(sa + 16384, &tm.wg, nb * 128, kb * 64, fb);
                        tma_load(sa + 16384 + 8192, &tm.wg, nb * 128 + 64, kb * 64, fb);
                        tma_load(sa + 16384 + 16384, &tm.wu, nb * 128, kb * 64, fb);
                        tma_load(sa + 16384 + 24576, &tm.wu, nb * 128 + 64, kb * 64, fb);
                    }
                }
                for (int pass = tail ? 4 : 0; pass < 5; pass++) {
                    for (int i = g1_first(pass, tail); i < g1_count(pass, tail); i += gridDim.x) {
                        const int tile = g1_tile(pass, tail, i), mb = tile >> 2, nb = tile & 3;
                        if (pass < 2) {
                            for (int kb = 0; kb < FF / 64; kb++, it++) {
                                if (kb == 0 || kb == 2 * H_EARLY) {
                                    wait_count(&g_hcnt[kb ? 16 + mb : mb], kb ? 2 * (G1_NB - H_EARLY) : 2 * H_EARLY);
                                    asm volatile("fence.proxy.async;" ::: "memory");
                                }
                                g_load_block(sb, bar, it, &tm.h, kb * 64, mb * 128, &tm.wd, nb * 256);
                            }
                        }
                        if (pass > 0) {
                            const int k0 = pass == 3 ? (i & 3) * 16 : pass == 4 ? (i & 7) * 8 : 0, k1 = pass == 3 ? k0 + 16 : pass == 4 ? k0 + 8 : HD / 64;
                            if (!tail) wait_count(&g_ocnt[mb], NH * 4);
                            asm volatile("fence.proxy.async;" ::: "memory");
                            for (int kb = k0; kb < k1; kb++, it++) g_load_block(sb, bar, it, &tm.o, kb * 64, mb * 128, &tm.wo, nb * 256);
                        }
                    }
                }
            }
        }
    } else {
        asm volatile("setmaxnreg.inc.sync.aligned.u32 232;");
        float d[128];
        int it = 0;
        const uint32_t epi = sb + G_EPI + wg * 16384;
        const int row = warp * 16 + ((lane >> 3) & 1) * 8 + (lane & 7);
        for (int tile = blockIdx.x; tile < ntiles; tile += gridDim.x) {
            const int mb = tile & 15, nb = tile >> 4;
            const uint32_t* gp = &g_gate[mb * 128 + wg * 64 + warp * 16 + (lane >> 2)];
            uint32_t u0 = ld_strong4(gp), u1 = ld_strong4(gp + 8);
            for (int kb = 0; kb < 16; kb++, it++) {
                if (it == (wg ? 0 : STAG)) bar_sync(4, 256);
                g_mma_block(d, sb, bar, it, wg, tid, kb == 0);
            }
            wg_wait<0>();
            for (uint32_t n = 0; u0 == 0u || u1 == 0u; n++) { u0 = ld_strong4(gp); u1 = ld_strong4(gp + 8); if (n > 20000000u) __trap(); }
            __syncwarp();
            const float s0 = 1.0f - __uint_as_float(u0), s1 = 1.0f - __uint_as_float(u1);
            if ((tid & 127) == 0) {
                mbar_arrive(bar + 8 * (G_ST + (it - 1) % G_ST));
                bulk_wait_all();
                const int pt = tile - (int)gridDim.x;
                if (pt >= 0) atomicAdd(&g_hcnt[(pt & 15) + ((pt >> 4) >= H_EARLY ? 16 : 0)], 1u);
            }
            bar_sync(1 + wg, 128);
#pragma unroll
            for (int j = 0; j < 16; j += 2) {
                uint32_t p[4];
#pragma unroll
                for (int q = 0; q < 4; q++) {
                    const int i = (j + (q >> 1)) * 4 + (q & 1) * 2;
                    const float sc = (q & 1) ? s1 : s0;
                    const float g0 = d[i], g1 = d[i + 1];
                    const float a0 = 1.0f + ex2(fminf(g0 * -1.4426950408889634f, 62.0f)), a1 = 1.0f + ex2(fminf(g1 * -1.4426950408889634f, 62.0f));
                    const float rr = rcp(a0 * a1) * sc;
                    const float h0 = (g0 * d[64 + i]) * (rr * a1);
                    const float h1 = (g1 * d[64 + i + 1]) * (rr * a0);
                    p[q] = pack_bf16(h0, h1);
                }
                const int cgp = j + (lane >> 4);
                stsm4(epi + (cgp >> 3) * 8192 + row * 128 + (((cgp & 7) ^ (row & 7)) << 4), p[0], p[1], p[2], p[3]);
            }
            fence_async();
            bar_sync(1 + wg, 128);
            if ((tid & 127) == 0) {
                tma_store(&tm.hs, epi, nb * 128, mb * 128 + wg * 64);
                tma_store(&tm.hs, epi + 8192, nb * 128 + 64, mb * 128 + wg * 64);
                bulk_commit();
            }
        }
        if ((tid & 127) == 0 && !tail) {
            bulk_wait_all();
            const int pt = blockIdx.x + (G1_TILES - 1 - blockIdx.x) / gridDim.x * gridDim.x;
            atomicAdd(&g_hcnt[(pt & 15) + ((pt >> 4) >= H_EARLY ? 16 : 0)], 1u);
        }
        for (int pass = tail ? 4 : 0; pass < 5; pass++) {
            for (int i = g1_first(pass, tail); i < g1_count(pass, tail); i += gridDim.x) {
                const int tile = g1_tile(pass, tail, i);
                const int nkb = pass == 0 ? FF / 64 : pass == 1 ? (FF + HD) / 64 : pass == 2 ? HD / 64 : pass == 3 ? 16 : 8;
                float4* pre = g_pre + (tile - NFULL) * (32 * 256) + tid;
                if (tail) asm volatile("prefetch.global.L2 [%0];" ::"l"(pre - tid + (i & 7) * 1024 + tid * 4));
                for (int kb = 0; kb < nkb; kb++, it++) g_mma_block(d, sb, bar, it, wg, tid, kb == 0);
                wg_wait<0>();
                if ((tid & 127) == 0) mbar_arrive(bar + 8 * (G_ST + (it - 1) % G_ST));
                if (pass >= 2 && !tail) { if ((tid & 31) == 0) wait_count(&g_pcnt[tile], 8); __syncwarp(); }
                if (pass == 0) {
#pragma unroll
                    for (int q = 0; q < 32; q++) __stcg(pre + q * 256, make_float4(d[4 * q], d[4 * q + 1], d[4 * q + 2], d[4 * q + 3]));
                    __threadfence();
                    __syncwarp();
                    if ((tid & 31) == 0) atomicAdd(&g_pcnt[tile], 1u);
                } else if (pass == 3) {
                    float4 r[8];
#pragma unroll
                    for (int q = 0; q < 8; q++) r[q] = __ldcg(pre + ((i & 3) * 8 + q) * 256);
                    g_split_finish<4>(d, r, g_sk + (tile - T_MID) * 8 * (16 * 256), tile, i & 3, out, tid);
                } else if (pass == 4) {
                    float4 r[4];
#pragma unroll
                    for (int q = 0; q < 4; q++) r[q] = __ldcg(pre + ((i & 7) * 4 + q) * 256);
                    g_split_finish<8>(d, r, g_sk + (tile - T_MID) * 8 * (16 * 256), tile, i & 7, out, tid);
                } else {
                    if (pass == 2) {
#pragma unroll
                        for (int q = 0; q < 32; q++) {
                            const float4 u = __ldcg(pre + q * 256); d[4 * q] += u.x; d[4 * q + 1] += u.y; d[4 * q + 2] += u.z; d[4 * q + 3] += u.w;
                            if ((q & 7) == 7) __syncwarp();
                        }
                    }
                    g_store_tile(d, &tm.out, epi, tile >> 2, tile & 3, wg, tid);
                }
            }
        }
        if ((tid & 127) == 0) bulk_wait_all();
        KT(1 + tail, 1);
    }
    __syncwarp();
    asm volatile("griddepcontrol.wait;" ::: "memory");
}

typedef CUresult (*EncodeFn)(CUtensorMap*, CUtensorMapDataType, cuuint32_t, void*, const cuuint64_t*, const cuuint64_t*, const cuuint32_t*,
                             const cuuint32_t*, CUtensorMapInterleave, CUtensorMapSwizzle, CUtensorMapL2promotion, CUtensorMapFloatOOBfill);

static void make_map(EncodeFn enc, CUtensorMap* m, const void* ptr, uint64_t rows, uint64_t cols, uint32_t box_rows) {
    cuuint64_t dims[2] = {cols, rows};
    cuuint64_t strides[1] = {cols * 2};
    cuuint32_t box[2] = {64, box_rows};
    cuuint32_t es[2] = {1, 1};
    enc(m, CU_TENSOR_MAP_DATA_TYPE_BFLOAT16, 2, (void*)ptr, dims, strides, box, es, CU_TENSOR_MAP_INTERLEAVE_NONE,
        CU_TENSOR_MAP_SWIZZLE_128B, CU_TENSOR_MAP_L2_PROMOTION_L2_256B, CU_TENSOR_MAP_FLOAT_OOB_FILL_NONE);
}

extern "C" void kernel_launch(void* const* d_in, const int* in_sizes, int n_in, void* d_out, int out_size) {
    (void)in_sizes; (void)n_in; (void)out_size;
    const bf16* x = (const bf16*)d_in[0];
    const bf16* mem0 = (const bf16*)d_in[1];
    const bf16* gate_w = (const bf16*)d_in[11];
    static EncodeFn enc = nullptr;
    static int n_sm = 0;
    static void *pO = nullptr, *pH = nullptr;
    if (!enc) {
        void* fn = nullptr;
        cudaDriverEntryPointQueryResult qr;
        cudaGetDriverEntryPoint("cuTensorMapEncodeTiled", &fn, cudaEnableDefault, &qr);
        enc = (EncodeFn)fn;
        cudaDeviceGetAttribute(&n_sm, cudaDevAttrMultiProcessorCount, 0);
        cudaFuncSetAttribute(r_kernel, cudaFuncAttributeMaxDynamicSharedMemorySize, R_SMEM);
        cudaFuncSetAttribute(g1_kernel, cudaFuncAttributeMaxDynamicSharedMemorySize, G_SMEM);
        cudaGetSymbolAddress(&pO, g_O);
        cudaGetSymbolAddress(&pH, g_H);
    }
    RMaps rm; G1Maps m1;
    make_map(enc, &rm.x, x, SEQ, DM, 32);
    for (int i = 0; i < 3; i++) make_map(enc, &rm.w[i], d_in[2 + i], DM, HD, 64);
    make_map(enc, &rm.wo, d_in[5], HD, DM, 128);
    make_map(enc, &rm.o, pO, SEQ, HD, 16);
    make_map(enc, &m1.x, x, SEQ, DM, 128);
    make_map(enc, &m1.wg, d_in[8], DM, FF, 64);
    make_map(enc, &m1.wu, d_in[9], DM, FF, 64);
    make_map(enc, &m1.hs, pH, SEQ, FF, 64);
    make_map(enc, &m1.o, pO, SEQ, HD, 128);
    make_map(enc, &m1.h, pH, SEQ, FF, 128);
    make_map(enc, &m1.wo, d_in[5], HD, DM, 64);
    make_map(enc, &m1.wd, d_in[10], FF, DM, 64);
    make_map(enc, &m1.out, d_out, SEQ, DM, 64);

    cudaStream_t st = cudaStreamPerThread;
    {
        cudaLaunchConfig_t cfg = {};
        cfg.gridDim = dim3(96); cfg.blockDim = dim3(384); cfg.dynamicSmemBytes = R_SMEM; cfg.stream = st;
        cudaLaunchAttribute at[1];
        at[0].id = cudaLaunchAttributeClusterDimension; at[0].val.clusterDim.x = 3; at[0].val.clusterDim.y = 1; at[0].val.clusterDim.z = 1;
        cfg.attrs = at; cfg.numAttrs = 1;
        cudaLaunchKernelEx(&cfg, r_kernel, rm, mem0, x, gate_w);
    }
    {
        cudaLaunchConfig_t cfg = {};
        cfg.gridDim = dim3(n_sm - 96); cfg.blockDim = dim3(384); cfg.dynamicSmemBytes = G_SMEM; cfg.stream = st;
        cudaLaunchAttribute at[1];
        at[0].id = cudaLaunchAttributeProgrammaticStreamSerialization; at[0].val.programmaticStreamSerializationAllowed = 1;
        cfg.attrs = at; cfg.numAttrs = 1;
        cudaLaunchKernelEx(&cfg, g1_kernel, m1, (bf16*)d_out, 0);
    }
    {
        cudaLaunchConfig_t cfg = {};
        cfg.gridDim = dim3((64 - T_LATE) * 8); cfg.blockDim = dim3(384); cfg.dynamicSmemBytes = G_SMEM; cfg.stream = st;
        cudaLaunchAttribute at[1];
        at[0].id = cudaLaunchAttributeProgrammaticStreamSerialization; at[0].val.programmaticStreamSerializationAllowed = 1;
        cfg.attrs = at; cfg.numAttrs = 1;
        cudaLaunchKernelEx(&cfg, g1_kernel, m1, (bf16*)d_out, 1);
    }
}
```

```cpp
#include <cuda_runtime.h>
#include <cuda_bf16.h>
#include <cuda.h>
#include <stdint.h>

typedef __nv_bfloat16 bf16;

constexpr int SEQ = 2048, DM = 1024, NH = 32, DH = 128, NMEM = 8, SEG = 32, NSEG = 64, FF = 3584;
constexpr int HD = NH * DH;

__device__ bf16 g_O[SEQ * HD];
__device__ bf16 g_H[SEQ * FF];
__device__ uint32_t g_gate[SEQ];
__device__ uint32_t g_part[4][128 * 32 * 32];
__device__ uint32_t g_mem[4][DM * 4];
constexpr int NFULL = 36, T_MID = 44, T_MID2 = 48, T_LATE = 52;
constexpr int NPRE = 64 - NFULL;
__device__ float4 g_pre[NPRE * 32 * 256];
__device__ uint4 g_sk[(64 - T_MID) * 8 * 16 * 256];
__device__ uint32_t g_skcnt[64], g_pcnt[64];
__device__ uint32_t g_hcnt[32], g_ocnt[16];
#define KT(k, i)
#define PT(i)

#define DEVINL __device__ __forceinline__
constexpr long long SPIN_LIMIT = 4000000000LL;

DEVINL uint32_t smem_u32(const void* p) { return (uint32_t)__cvta_generic_to_shared(p); }
DEVINL void mbar_init(uint32_t bar, uint32_t cnt) { asm volatile("mbarrier.init.shared::cta.b64 [%0], %1;" ::"r"(bar), "r"(cnt) : "memory"); }
DEVINL void mbar_arrive(uint32_t bar) { asm volatile("mbarrier.arrive.shared::cta.b64 _, [%0];" ::"r"(bar) : "memory"); }
DEVINL void mbar_expect(uint32_t bar, uint32_t bytes) { asm volatile("mbarrier.arrive.expect_tx.shared::cta.b64 _, [%0], %1;" ::"r"(bar), "r"(bytes) : "memory"); }
DEVINL void mbar_arrive_remote(uint32_t cbar) { asm volatile("mbarrier.arrive.relaxed.cluster.shared::cluster.b64 _, [%0];" ::"r"(cbar) : "memory"); }
DEVINL bool mbar_try(uint32_t bar, uint32_t par) {
    uint32_t ok;
    asm volatile("{ .reg .pred p; mbarrier.try_wait.parity.shared::cta.b64 p, [%1], %2; selp.u32 %0, 1, 0, p; }" : "=r"(ok) : "r"(bar), "r"(par) : "memory");
    return ok;
}
__device__ __noinline__ void mbar_wait_slow(uint32_t bar, uint32_t par) {
    long long t0 = clock64();
    while (!mbar_try(bar, par)) { if (clock64() - t0 > SPIN_LIMIT) __trap(); }
}
DEVINL void mbar_wait(uint32_t bar, uint32_t par) {
    uint32_t n = 0;
    while (!mbar_try(bar, par)) { if (++n > 200000000u) __trap(); }
}
DEVINL uint32_t mapa(uint32_t a, uint32_t r) { uint32_t o; asm volatile("mapa.shared::cluster.u32 %0, %1, %2;" : "=r"(o) : "r"(a), "r"(r)); return o; }
DEVINL void fence_async() { asm volatile("fence.proxy.async.shared::cta;" ::: "memory"); }
DEVINL void bar_sync(int id, int n) { asm volatile("bar.sync %0, %1;" ::"r"(id), "r"(n) : "memory"); }
DEVINL void cluster_sync() { asm volatile("barrier.cluster.arrive.aligned; barrier.cluster.wait.aligned;" ::: "memory"); }
DEVINL void tma_load(uint32_t dst, const CUtensorMap* tm, int c0, int c1, uint32_t bar) {
    asm volatile("cp.async.bulk.tensor.2d.shared::cluster.global.mbarrier::complete_tx::bytes [%0], [%1, {%3, %4}], [%2];"
                 ::"r"(dst), "l"(tm), "r"(bar), "r"(c0), "r"(c1) : "memory");
}
DEVINL void tma_prefetch(const CUtensorMap* tm, int c0, int c1) {
    asm volatile("cp.async.bulk.prefetch.tensor.2d.L2.global [%0, {%1, %2}];" ::"l"(tm), "r"(c0), "r"(c1) : "memory");
}
DEVINL void tma_store(const CUtensorMap* tm, uint32_t src, int c0, int c1) {
    asm volatile("cp.async.bulk.tensor.2d.global.shared::cta.bulk_group [%0, {%2, %3}], [%1];" ::"l"(tm), "r"(src), "r"(c0), "r"(c1) : "memory");
}
DEVINL void bulk_commit() { asm volatile("cp.async.bulk.commit_group;" ::: "memory"); }
DEVINL void bulk_wait_read() { asm volatile("cp.async.bulk.wait_group.read 0;" ::: "memory"); }
DEVINL void bulk_wait_all() { asm volatile("cp.async.bulk.wait_group 0;" ::: "memory"); }
DEVINL void bulk_s2s(uint32_t cdst, uint32_t src, uint32_t bytes, uint32_t cbar) {
    asm volatile("cp.async.bulk.shared::cluster.shared::cta.mbarrier::complete_tx::bytes [%0], [%1], %2, [%3];" ::"r"(cdst), "r"(src), "r"(bytes), "r"(cbar) : "memory");
}
DEVINL void st_async16(uint32_t cdst, uint4 v, uint32_t cbar) {
    asm volatile("st.async.shared::cluster.mbarrier::complete_tx::bytes.v4.b32 [%0], {%1,%2,%3,%4}, [%5];" ::"r"(cdst), "r"(v.x), "r"(v.y), "r"(v.z), "r"(v.w), "r"(cbar) : "memory");
}
DEVINL uint64_t mkdesc(uint32_t addr, uint32_t lbo, uint32_t sbo, uint32_t swz) {
    return (uint64_t)((addr & 0x3FFFF) >> 4) | ((uint64_t)(lbo >> 4) << 16) | ((uint64_t)(sbo >> 4) << 32) | ((uint64_t)swz << 62);
}
constexpr uint32_t SB0 = 1024;
__host__ __device__ constexpr uint64_t cdesc(uint32_t off, uint32_t lbo, uint32_t sbo, uint32_t swz) {
    return (uint64_t)(((SB0 + off) & 0x3FFFF) >> 4) | ((uint64_t)(lbo >> 4) << 16) | ((uint64_t)(sbo >> 4) << 32) | ((uint64_t)swz << 62);
}
DEVINL float rcp(float x) { float y; asm("rcp.approx.ftz.f32 %0, %1;" : "=f"(y) : "f"(x)); return y; }
DEVINL float ex2(float x) { float y; asm("ex2.approx.ftz.f32 %0, %1;" : "=f"(y) : "f"(x)); return y; }
DEVINL void spin_clk(int d) { uint32_t t0, t1; asm volatile("mov.u32 %0, %%clock;" : "=r"(t0)); do { asm volatile("mov.u32 %0, %%clock;" : "=r"(t1)); } while ((int)(t1 - t0) < d); }
#define PROBE_GAP 150
#define OPAQUE(x) asm volatile("" : "+r"(x))
DEVINL void wg_fence() { asm volatile("wgmma.fence.sync.aligned;" ::: "memory"); }
DEVINL void wg_commit() { asm volatile("wgmma.commit_group.sync.aligned;" ::: "memory"); }
template <int N> DEVINL void wg_wait() { asm volatile("wgmma.wait_group.sync.aligned %0;" ::"n"(N) : "memory"); }
DEVINL uint32_t pack_bf16(float lo, float hi) { uint32_t r; asm("cvt.rn.bf16x2.f32 %0, %1, %2;" : "=r"(r) : "f"(hi), "f"(lo)); return r; }
DEVINL void ldsm4(uint32_t* r, uint32_t a) { asm volatile("ldmatrix.sync.aligned.m8n8.x4.shared.b16 {%0,%1,%2,%3}, [%4];" : "=r"(r[0]), "=r"(r[1]), "=r"(r[2]), "=r"(r[3]) : "r"(a) : "memory"); }
DEVINL void ldsm4t(uint32_t* r, uint32_t a) { asm volatile("ldmatrix.sync.aligned.m8n8.x4.trans.shared.b16 {%0,%1,%2,%3}, [%4];" : "=r"(r[0]), "=r"(r[1]), "=r"(r[2]), "=r"(r[3]) : "r"(a) : "memory"); }
DEVINL void ldsm4t_if(uint32_t* r, uint32_t a, int c) { asm volatile("{ .reg .pred p; setp.ne.s32 p, %5, 0; @p ldmatrix.sync.aligned.m8n8.x4.trans.shared.b16 {%0,%1,%2,%3}, [%4]; }" : "+r"(r[0]), "+r"(r[1]), "+r"(r[2]), "+r"(r[3]) : "r"(a), "r"(c) : "memory"); }
DEVINL void stsm4(uint32_t a, uint32_t r0, uint32_t r1, uint32_t r2, uint32_t r3) { asm volatile("stmatrix.sync.aligned.m8n8.x4.shared.b16 [%0], {%1,%2,%3,%4};" ::"r"(a), "r"(r0), "r"(r1), "r"(r2), "r"(r3) : "memory"); }
DEVINL void stsm4t(uint32_t a, uint32_t r0, uint32_t r1, uint32_t r2, uint32_t r3) { asm volatile("stmatrix.sync.aligned.m8n8.x4.trans.shared.b16 [%0], {%1,%2,%3,%4};" ::"r"(a), "r"(r0), "r"(r1), "r"(r2), "r"(r3) : "memory"); }
DEVINL void sts32(uint32_t a, uint32_t v) { asm volatile("st.shared.b32 [%0], %1;" ::"r"(a), "r"(v) : "memory"); }
DEVINL void sts128(uint32_t a, uint4 v) { asm volatile("st.shared.v4.b32 [%0], {%1,%2,%3,%4};" ::"r"(a), "r"(v.x), "r"(v.y), "r"(v.z), "r"(v.w) : "memory"); }
DEVINL uint4 lds128(uint32_t a) { uint4 v; asm volatile("ld.shared.v4.b32 {%0,%1,%2,%3}, [%4];" : "=r"(v.x), "=r"(v.y), "=r"(v.z), "=r"(v.w) : "r"(a) : "memory"); return v; }
DEVINL uint4 ld_strong16(const void* p) { uint4 v; asm volatile("ld.relaxed.gpu.global.v4.u32 {%0,%1,%2,%3}, [%4];" : "=r"(v.x), "=r"(v.y), "=r"(v.z), "=r"(v.w) : "l"(p) : "memory"); return v; }
DEVINL void st_strong8(void* p, uint32_t a, uint32_t b) { asm volatile("st.relaxed.gpu.global.v2.u32 [%0], {%1,%2};" ::"l"(p), "r"(a), "r"(b) : "memory"); }
DEVINL void st_strong4(void* p, uint32_t a) { asm volatile("st.relaxed.gpu.global.u32 [%0], %1;" ::"l"(p), "r"(a) : "memory"); }
DEVINL void st_strong16(void* p, uint4 v) { asm volatile("st.relaxed.gpu.global.v4.u32 [%0], {%1,%2,%3,%4};" ::"l"(p), "r"(v.x), "r"(v.y), "r"(v.z), "r"(v.w) : "memory"); }
DEVINL uint32_t pack_nz(float lo, float hi) { uint32_t r = pack_bf16(lo, hi); return r == 0u ? 0x8000u : r; }
DEVINL uint32_t min4(uint4 v, uint32_t m) { return __vimin3_u32(__vimin3_u32(v.x, v.y, m), v.z, v.w); }
DEVINL void mma16816(float* d, uint32_t a0, uint32_t a1, uint32_t a2, uint32_t a3, uint32_t b0, uint32_t b1) {
    asm volatile("mma.sync.aligned.m16n8k16.row.col.f32.bf16.bf16.f32 {%0,%1,%2,%3}, {%4,%5,%6,%7}, {%8,%9}, {%0,%1,%2,%3};"
                 : "+f"(d[0]), "+f"(d[1]), "+f"(d[2]), "+f"(d[3]) : "r"(a0), "r"(a1), "r"(a2), "r"(a3), "r"(b0), "r"(b1));
}
DEVINL void mma1688(float* d, uint32_t a0, uint32_t a1, uint32_t b0) {
    asm volatile("mma.sync.aligned.m16n8k8.row.col.f32.bf16.bf16.f32 {%0,%1,%2,%3}, {%4,%5}, {%6}, {%0,%1,%2,%3};"
                 : "+f"(d[0]), "+f"(d[1]), "+f"(d[2]), "+f"(d[3]) : "r"(a0), "r"(a1), "r"(b0));
}
template <int TA, int TB> DEVINL void wg_ss8(float* d, uint64_t da, uint64_t db, int sc) {
    asm volatile("{ .reg .pred p; setp.ne.b32 p, %6, 0; wgmma.mma_async.sync.aligned.m64n8k16.f32.bf16.bf16 {%0,%1,%2,%3}, %4, %5, p, 1, 1, %7, %8; }"
                 : "+f"(d[0]), "+f"(d[1]), "+f"(d[2]), "+f"(d[3]) : "l"(da), "l"(db), "r"(sc), "n"(TA), "n"(TB));
}
template <int TB> DEVINL void wg_rs8(float* d, const uint32_t* a, uint64_t db, int sc) {
    asm volatile("{ .reg .pred p; setp.ne.b32 p, %9, 0; wgmma.mma_async.sync.aligned.m64n8k16.f32.bf16.bf16 {%0,%1,%2,%3}, {%4,%5,%6,%7}, %8, p, 1, 1, %10; }"
                 : "+f"(d[0]), "+f"(d[1]), "+f"(d[2]), "+f"(d[3]) : "r"(a[0]), "r"(a[1]), "r"(a[2]), "r"(a[3]), "l"(db), "r"(sc), "n"(TB));
}
#define ACC16(d) "+f"(d[0]), "+f"(d[1]), "+f"(d[2]), "+f"(d[3]), "+f"(d[4]), "+f"(d[5]), "+f"(d[6]), "+f"(d[7]), "+f"(d[8]), "+f"(d[9]), "+f"(d[10]), "+f"(d[11]), "+f"(d[12]), "+f"(d[13]), "+f"(d[14]), "+f"(d[15])
template <int TA> DEVINL void wg_ss32(float* d, uint64_t da, uint64_t db, int sc) {
    asm volatile("{ .reg .pred p; setp.ne.b32 p, %18, 0; wgmma.mma_async.sync.aligned.m64n32k16.f32.bf16.bf16 {%0,%1,%2,%3,%4,%5,%6,%7,%8,%9,%10,%11,%12,%13,%14,%15}, %16, %17, p, 1, 1, %19, 0; }"
                 : ACC16(d) : "l"(da), "l"(db), "r"(sc), "n"(TA));
}
DEVINL void wg_rs32(float* d, const uint32_t* a, uint64_t db, int sc) {
    asm volatile("{ .reg .pred p; setp.ne.b32 p, %21, 0; wgmma.mma_async.sync.aligned.m64n32k16.f32.bf16.bf16 {%0,%1,%2,%3,%4,%5,%6,%7,%8,%9,%10,%11,%12,%13,%14,%15}, {%16,%17,%18,%19}, %20, p, 1, 1, 0; }"
                 : ACC16(d) : "r"(a[0]), "r"(a[1]), "r"(a[2]), "r"(a[3]), "l"(db), "r"(sc));
}
DEVINL void wg_ss40(float* d, uint64_t da, uint64_t db, int sc) {
    asm volatile("{ .reg .pred p; setp.ne.b32 p, %22, 0; wgmma.mma_async.sync.aligned.m64n40k16.f32.bf16.bf16 {%0,%1,%2,%3,%4,%5,%6,%7,%8,%9,%10,%11,%12,%13,%14,%15,%16,%17,%18,%19}, %20, %21, p, 1, 1, 1, 1; }"
                 : ACC16(d), "+f"(d[16]), "+f"(d[17]), "+f"(d[18]), "+f"(d[19]) : "l"(da), "l"(db), "r"(sc));
}
#define A8(d, o) "+f"(d[o]), "+f"(d[o + 1]), "+f"(d[o + 2]), "+f"(d[o + 3]), "+f"(d[o + 4]), "+f"(d[o + 5]), "+f"(d[o + 6]), "+f"(d[o + 7])
#define A32(d, o) A8(d, o), A8(d, o + 8), A8(d, o + 16), A8(d, o + 24)
DEVINL void wg_ss256(float* d, uint64_t da, uint64_t db, int sc) {
    asm volatile(
        "{ .reg .pred p; setp.ne.b32 p, %130, 0;\n"
        "wgmma.mma_async.sync.aligned.m64n256k16.f32.bf16.bf16 {"
        "%0,%1,%2,%3,%4,%5,%6,%7,%8,%9,%10,%11,%12,%13,%14,%15,%16,%17,%18,%19,%20,%21,%22,%23,%24,%25,%26,%27,%28,%29,%30,%31,"
        "%32,%33,%34,%35,%36,%37,%38,%39,%40,%41,%42,%43,%44,%45,%46,%47,%48,%49,%50,%51,%52,%53,%54,%55,%56,%57,%58,%59,%60,%61,%62,%63,"
        "%64,%65,%66,%67,%68,%69,%70,%71,%72,%73,%74,%75,%76,%77,%78,%79,%80,%81,%82,%83,%84,%85,%86,%87,%88,%89,%90,%91,%92,%93,%94,%95,"
        "%96,%97,%98,%99,%100,%101,%102,%103,%104,%105,%106,%107,%108,%109,%110,%111,%112,%113,%114,%115,%116,%117,%118,%119,%120,%121,%122,%123,%124,%125,%126,%127"
        "}, %128, %129, p, 1, 1, 0, 1; }"
        : A32(d, 0), A32(d, 32), A32(d, 64), A32(d, 96) : "l"(da), "l"(db), "r"(sc));
}

DEVINL float gate_row(const uint4 (&xv)[4], const uint4 (&gv)[4]) {
    float acc = 0.f;
#pragma unroll
    for (int i = 0; i < 4; i++) {
        const uint32_t xa[4] = {xv[i].x, xv[i].y, xv[i].z, xv[i].w}, ga[4] = {gv[i].x, gv[i].y, gv[i].z, gv[i].w};
#pragma unroll
        for (int e = 0; e < 4; e++) {
            acc = fmaf(__uint_as_float(xa[e] << 16), __uint_as_float(ga[e] << 16), acc);
            acc = fmaf(__uint_as_float(xa[e] & 0xffff0000u), __uint_as_float(ga[e] & 0xffff0000u), acc);
        }
    }
#pragma unroll
    for (int o = 16; o > 0; o >>= 1) acc += __shfl_xor_sync(0xffffffffu, acc, o);
    return 1.0f / (1.0f + __expf(-acc));
}
DEVINL uint4 ldg_nc(const void* p) { uint4 v; asm volatile("ld.global.nc.v4.u32 {%0,%1,%2,%3}, [%4];" : "=r"(v.x), "=r"(v.y), "=r"(v.z), "=r"(v.w) : "l"(p) : "memory"); return v; }
DEVINL uint32_t ld_strong4(const void* p) { uint32_t v; asm volatile("ld.relaxed.gpu.global.u32 %0, [%1];" : "=r"(v) : "l"(p) : "memory"); return v; }
DEVINL void wait_count(const uint32_t* p, uint32_t want) {
    uint32_t v, n = 0;
    while (true) {
        asm volatile("ld.acquire.gpu.global.u32 %0, [%1];" : "=r"(v) : "l"(p) : "memory");
        if (v >= want) break;
        __nanosleep(200);
        if (++n > 10000000u) __trap();
    }
}

constexpr int KR = 44;
constexpr int KS = 64 - KR;
constexpr int R_W = 0;
constexpr int R_WO = KS * 4096;
constexpr int R_QX = R_WO + 65536;
constexpr int R_RING = R_WO + 98304;
constexpr int R_K = R_RING + 24576;
constexpr int R_V = R_K + 10240;
constexpr int R_QM = R_V + 10240;
constexpr int R_O = R_QM + 2048;
constexpr int R_BAR = R_O + 2048;
constexpr int R_G = R_BAR + 256 + 512 + 256 + 128;
constexpr int R_Z = R_G + 256;
constexpr int R_SMEM = R_Z + 1024;
enum { B_FULL = 0, B_EMPTY = 5, B_MEM = 8, B_HOP1 = 12, B_XT, B_TFREE, B_O, B_AFREE0, B_AFREE1, B_PRO0, B_PRO1, B_XRECV, B_P, B_XDONE, B_OST0, B_OST1, B_HOPV };
#define D2_BASE 900
#define D2_STEP 200
#define PD2 6
#define CPB 8192
#define DDUP 0
#define WGAP 0
#define PVD 400
#define ELD 700
#define QD 3
#define DQ 1700
#define D3 0

DEVINL uint32_t clk32() { uint32_t c_; asm volatile("mov.u32 %0, %%clock;" : "=r"(c_)); return c_; }
DEVINL void spin_until(uint32_t t) { while ((uint32_t)(t - clk32() - 1u) < 100000u) {} }
#define PROF(i)
#define PROF2(i)
#define PROF3(i, val)
DEVINL void e_arrive(uint32_t bar) { asm volatile("{ .reg .pred p; elect.sync _|p, 0xffffffff; @p mbarrier.arrive.shared::cta.b64 _, [%0]; }" ::"r"(bar) : "memory"); }
DEVINL void e_arrive_remote(uint32_t cbar) { asm volatile("{ .reg .pred p; elect.sync _|p, 0xffffffff; @p mbarrier.arrive.relaxed.cluster.shared::cluster.b64 _, [%0]; }" ::"r"(cbar) : "memory"); }
DEVINL void e_count(uint32_t* p) { asm volatile("{ .reg .pred p; elect.sync _|p, 0xffffffff; @p red.relaxed.gpu.global.add.u32 [%0], 1; }" ::"l"(p) : "memory"); }
DEVINL void e_expect(uint32_t bar, uint32_t bytes) { asm volatile("{ .reg .pred p; elect.sync _|p, 0xffffffff; @p mbarrier.arrive.expect_tx.shared::cta.b64 _, [%0], %1; }" ::"r"(bar), "r"(bytes) : "memory"); }
DEVINL void e_tma_load(uint32_t dst, const CUtensorMap* tm, int c0, int c1, uint32_t bar) {
    asm volatile("{ .reg .pred p; elect.sync _|p, 0xffffffff; @p cp.async.bulk.tensor.2d.shared::cluster.global.mbarrier::complete_tx::bytes [%0], [%1, {%3, %4}], [%2]; }"
                 ::"r"(dst), "l"(tm), "r"(bar), "r"(c0), "r"(c1) : "memory");
}
DEVINL void e_tma_store(const CUtensorMap* tm, uint32_t src, int c0, int c1) {
    asm volatile("{ .reg .pred p; elect.sync _|p, 0xffffffff; @p cp.async.bulk.tensor.2d.global.shared::cta.bulk_group [%0, {%2, %3}], [%1]; }" ::"l"(tm), "r"(src), "r"(c0), "r"(c1) : "memory");
}
DEVINL void e_bulk_s2g(void* dst, uint32_t src, uint32_t bytes) {
    asm volatile("{ .reg .pred p; elect.sync _|p, 0xffffffff; @p cp.async.bulk.global.shared::cta.bulk_group [%0], [%1], %2; }" ::"l"(dst), "r"(src), "r"(bytes) : "memory");
}
DEVINL void e_bulk_s2s(uint32_t cdst, uint32_t src, uint32_t bytes, uint32_t cbar) {
    asm volatile("{ .reg .pred p; elect.sync _|p, 0xffffffff; @p cp.async.bulk.shared::cluster.shared::cta.mbarrier::complete_tx::bytes [%0], [%1], %2, [%3]; }" ::"r"(cdst), "r"(src), "r"(bytes), "r"(cbar) : "memory");
}

#define SLOT 0
#define PH3 0
#define PHQ 0
DEVINL void wait_slot(uint32_t phase) {
    if (SLOT) {
        uint32_t c; asm volatile("mov.u32 %0, %%globaltimer_lo;" : "=r"(c));
        const uint32_t tgt = c + (SLOT ? SLOT : 1) - ((c - phase) % (SLOT ? SLOT : 1));
        do { asm volatile("mov.u32 %0, %%globaltimer_lo;" : "=r"(c)); } while ((uint32_t)(tgt - c - 1u) < 100000u);
    }
}
template <int N> DEVINL uint32_t poll_set(uint4 (&v)[N], const uint32_t* rp, int stride, uint32_t phase, uint32_t wbar = 0, uint32_t wpar = 0) {
    wait_slot(phase);
#pragma unroll
    for (int i = 0; i < N; i++) v[i] = ld_strong16(rp + i * stride);
    if (wbar) mbar_wait(wbar, wpar);
    uint32_t n = 0;
    while (true) {
        uint32_t m = 0xffffffffu;
#pragma unroll
        for (int i = 0; i < N; i++) m = min4(v[i], m);
        if (__all_sync(0xffffffffu, m != 0u)) return n;
        wait_slot(phase);
#pragma unroll
        for (int i = 0; i < N; i++)
            asm volatile("{ .reg .pred p; setp.eq.u32 p, %5, 0; @p ld.relaxed.gpu.global.v4.u32 {%0,%1,%2,%3}, [%4]; }"
                         : "+r"(v[i].x), "+r"(v[i].y), "+r"(v[i].z), "+r"(v[i].w) : "l"(rp + i * stride), "r"(min4(v[i], 0xffffffffu)) : "memory");
        if (++n > 20000000u) __trap();
    }
}

struct RMaps { CUtensorMap x, w[3], wo, o; };
#define KC(c) ((c) * 64)

#define XORD 3
__host__ __device__ constexpr int xo(int i) {
    return XORD == 0 ? i : XORD == 1 ? (i + 14) % 16 : XORD == 2 ? (i + 11) % 16
         : XORD == 3 ? (i < 10 ? ((i & 1) ? i / 2 : 11 + i / 2) : i - 5) : (i < 6 ? i : ((i & 1) ? 6 + (i - 6) / 2 : 11 + (i - 6) / 2));
}
#define XC(i) (xo(i) * 64)
DEVINL void x_load_pair(uint32_t dst, const CUtensorMap* tmx, int h, int p, int seg, uint32_t fbar) {
    e_expect(fbar, 8192);
    e_tma_load(dst, tmx, XC(2 * p), seg * SEG, fbar);
    e_tma_load(dst + 4096, tmx, XC(2 * p + 1), seg * SEG, fbar);
}
__host__ __device__ constexpr int wo_tile(int role, int i) {
    return role == 0 ? (i < 2 ? 8 + i : 12 + i) : (i < 4 ? (i >> 1) * 4 : 10) + (role - 1) * 2 + (i & 1);
}

template <int NT> DEVINL void wo_phase(uint32_t sb, int tb, uint32_t* pp, uint32_t obar, uint32_t opar) {
    const int lane = tb & 31, krow = (lane & 7) + ((lane >> 4) << 3), chunk = ((tb >> 5) & 3) * 2 + ((lane >> 3) & 1);
    uint32_t wa = sb + R_WO + (tb >> 7) * 16384 + krow * 128 + ((chunk ^ (krow & 7)) << 4);
    uint32_t af[4][4], of[4][4];
#pragma unroll
    for (int g = 0; g < 4; g++) ldsm4t(af[g], wa + g * 2048);
    mbar_wait(obar, opar);
#pragma unroll
    for (int g = 0; g < 4; g++) ldsm4t(of[g], sb + R_O + g * 512 + lane * 16);
#pragma unroll 1
    for (int i = 0; i < NT; i++) {
        float w0[4] = {0.f, 0.f, 0.f, 0.f}, w1[4] = {0.f, 0.f, 0.f, 0.f};
        const int more = NT - 1 - i, yes = NT - i;
        mma16816(w0, af[0][0], af[0][1], af[0][2], af[0][3], of[0][0], of[0][1]);
        ldsm4t_if(af[0], wa + 4 * 2048, yes);
        mma16816(w1, af[1][0], af[1][1], af[1][2], af[1][3], of[0][2], of[0][3]);
        ldsm4t_if(af[1], wa + 5 * 2048, yes);
        mma16816(w0, af[2][0], af[2][1], af[2][2], af[2][3], of[1][0], of[1][1]);
        ldsm4t_if(af[2], wa + 6 * 2048, yes);
        mma16816(w1, af[3][0], af[3][1], af[3][2], af[3][3], of[1][2], of[1][3]);
        ldsm4t_if(af[3], wa + 7 * 2048, yes);
        wa += 32768;
        mma16816(w0, af[0][0], af[0][1], af[0][2], af[0][3], of[2][0], of[2][1]);
        ldsm4t_if(af[0], wa, more);
        mma16816(w1, af[1][0], af[1][1], af[1][2], af[1][3], of[2][2], of[2][3]);
        ldsm4t_if(af[1], wa + 2048, more);
        mma16816(w0, af[2][0], af[2][1], af[2][2], af[2][3], of[3][0], of[3][1]);
        ldsm4t_if(af[2], wa + 2 * 2048, more);
        mma16816(w1, af[3][0], af[3][1], af[3][2], af[3][3], of[3][2], of[3][3]);
        ldsm4t_if(af[3], wa + 3 * 2048, more);
        st_strong4(pp, pack_nz(w0[0] + w1[0], w0[1] + w1[1]));
        st_strong4(pp + 1024, pack_nz(w0[2] + w1[2], w0[3] + w1[3]));
        pp += (NT == 3 && i == 0) ? 4 * 8192 : 6 * 8192;
    }
}

template <uint32_t role> DEVINL void r_big(const RMaps& tm, const int wid) {
    extern __shared__ __align__(1024) unsigned char smem_raw[];
    const uint32_t sb = smem_u32(smem_raw);
    const uint32_t bar = sb + R_BAR;
    const int tid = threadIdx.x;
    int h; asm("mov.u32 %0, %%clusterid.x;" : "=r"(h));
        uint32_t a[KR][4];
        mbar_wait(bar + 8 * B_PRO0, 0);
        PT(0);
        {
            const int lane = tid & 31;
            const int krow = (lane & 7) + ((lane >> 4) << 3);
            const int chunk = (wid & 3) * 2 + ((lane >> 3) & 1);
            const uint32_t la = sb + (wid >> 2) * 8192 + krow * 128 + ((chunk ^ (krow & 7)) << 4);
#pragma unroll
            for (int k = 0; k < KR; k++) ldsm4t(a[k], la + (k >> 2) * 16384 + (k & 3) * 2048);
        }
        bar_sync(1, 256);
        {
            fence_async();
            const CUtensorMap* tw = &tm.w[role];
            e_expect(bar + 8 * B_PRO1, (wid < 5 ? 16384 : 0) + (wid < (role == 0 ? 4 : 6) ? 16384 : 0));
            if (wid < 5) {
                e_tma_load(sb + R_W + wid * 8192, tw, h * DH, KC(KR / 4 + wid), bar + 8 * B_PRO1);
                e_tma_load(sb + R_W + KS * 2048 + wid * 8192, tw, h * DH + 64, KC(KR / 4 + wid), bar + 8 * B_PRO1);
            }
            if (wid < (role == 0 ? 4 : 6)) e_tma_load(sb + R_WO + wid * 16384, &tm.wo, wo_tile(role, wid) * 64, h * DH, bar + 8 * B_PRO1);
        }
        constexpr uint32_t e0 = role == 0 ? R_QX + 16384 : R_K + 2048, e1 = role == 0 ? R_QX + 24576 : R_V + 2048;
        if (wid == 6) x_load_pair(sb + e0, &tm.x, h, 3, 0, bar + 8 * (B_FULL + 3));
        if (wid == 7) x_load_pair(sb + e1, &tm.x, h, 4, 0, bar + 8 * (B_FULL + 4));
        PT(1);
        mbar_wait(bar + 8 * B_PRO1, 0);
        PT(2);

        constexpr uint64_t dW0 = cdesc(R_W, 1024, 1024, 1);
        constexpr uint64_t dM = cdesc(R_RING, 128, 128, 0);
        constexpr uint64_t dX = cdesc(R_RING, 16, 1024, 1);
        constexpr uint64_t dX0 = cdesc(0, 16, 1024, 1);
        int tb = tid;
        int wq = wid;

        for (int seg = 0; seg < NSEG; seg++) {
            {
            const int s = seg - 1; (void)s;
            float d[16];
            OPAQUE(wq);
            const uint64_t dW = dW0 + (uint64_t)((wq >> 2) * (KS * 128));
#pragma unroll
            for (int p = 0; p < 8; p++) {
                const int slot = p % 5;
                mbar_wait(bar + 8 * (B_FULL + slot), slot < 3 ? (uint32_t)(p / 5) : (uint32_t)(seg & 1));
                PROF2(p);
                const uint64_t db = slot < 3 ? dX + (uint64_t)(slot * 512) : dX0 + (uint64_t)((slot == 3 ? e0 : e1) >> 4);
                wg_fence();
#pragma unroll
                for (int kk = 0; kk < 8; kk++) {
                    const int k = XORD >= 3 ? (kk & 1) * 4 + (kk >> 1) : kk;
                    const int ks = xo(2 * p + (k >> 2)) * 4 + (k & 3);
                    if (ks >= KR) wg_ss32<1>(d, dW + (uint64_t)((ks - KR) * 128), db + (uint64_t)((k >> 2) * 256 + (k & 3) * 2), p + k);
                    else wg_rs32(d, a[ks < KR ? ks : 0], db + (uint64_t)((k >> 2) * 256 + (k & 3) * 2), p + k);
                }
                wg_commit();
                if (p >= 1) {
                    wg_wait<1>();
                    if (p <= 3) {
                        if ((wq & 3) == p) e_arrive(bar + 8 * (B_EMPTY + p - 1));
                        if (wq == p + (p & 1) * 4) {
                            mbar_wait(bar + 8 * (B_EMPTY + p - 1), seg & 1);
                            x_load_pair(sb + R_RING + (p - 1) * 8192, &tm.x, h, p + 4, seg, bar + 8 * (B_FULL + p - 1));
                        }
                    }
                    if (p == 5 && role != 0 && (wq & 3) < 3) e_arrive_remote(mapa(bar + 8 * B_TFREE, wq & 3));
                    if (p == 6 && (wq & 3) == 1) e_arrive(bar + 8 * B_AFREE0);
                    if (p == 7 && (wq & 3) == 2) e_arrive(bar + 8 * B_AFREE1);
                }
            }
            mbar_wait(bar + 8 * B_TFREE, seg & 1);
            asm volatile("wgmma.wait_group.sync.aligned 0;" : ACC16(d)::"memory");
            PROF2(16);
            const uint32_t tilex = sb + (role == 0 ? R_QX + 2048 : (role == 1 ? R_K + 2048 : R_V + 2048));
            {
                OPAQUE(tb);
                const uint32_t gs = role == 0 ? 4096 : 2048;
                const uint32_t sa = tilex + ((tb >> 4) & 1) * gs + (tb >> 5) * 256 + (tb & 15) * 16;
                stsm4(sa, pack_bf16(d[0], d[1]), pack_bf16(d[2], d[3]), pack_bf16(d[4], d[5]), pack_bf16(d[6], d[7]));
                stsm4(sa + 2 * gs, pack_bf16(d[8], d[9]), pack_bf16(d[10], d[11]), pack_bf16(d[12], d[13]), pack_bf16(d[14], d[15]));
            }
            __syncwarp();
            e_arrive(bar + 8 * B_XDONE);
            if (role != 0 && (wq & 3) == 0) {
                mbar_wait(bar + 8 * B_XDONE, seg & 1);
                fence_async();
                uint32_t pr = role + 1 + (wq >> 2); pr = pr >= 3 ? pr - 3 : pr;
                e_bulk_s2s(mapa(tilex, pr), tilex, CPB, mapa(bar + 8 * B_XT, pr));
            }
            }
            {
                const int s = seg;
                OPAQUE(wq);
                const uint64_t dW = dW0 + (uint64_t)((wq >> 2) * (KS * 128));
                float y[4] = {0.f, 0.f, 0.f, 0.f};
                {
                    OPAQUE(tb);
                    const uint32_t ma = sb + R_RING + (tb & 31) * 16;
                    float z[4] = {0.f, 0.f, 0.f, 0.f}, u[4] = {0.f, 0.f, 0.f, 0.f};
                    uint32_t b[QD][4];
                    const int yes = s + 1;
                    mbar_wait(bar + 8 * B_MEM, s & 1);
                    PROF((wq >> 2) * 4 + 0);
                    if (s == 0) PT(3);
                    if (s == 1) PT(4);
#pragma unroll
                    for (int g = 0; g < QD; g++) ldsm4t(b[g], ma + g * 512);
#pragma unroll
                    for (int g = 0; g < KR / 2; g++) {
                        float* c0 = (g % 3 == 0) ? y : (g % 3 == 1) ? u : z;
                        float* c1 = (g % 3 == 0) ? z : (g % 3 == 1) ? y : u;
                        mma16816(c0, a[2 * g][0], a[2 * g][1], a[2 * g][2], a[2 * g][3], b[g % QD][0], b[g % QD][1]);
                        mma16816(c1, a[2 * g + 1][0], a[2 * g + 1][1], a[2 * g + 1][2], a[2 * g + 1][3], b[g % QD][2], b[g % QD][3]);
                        if (g + QD < KR / 2) {
                            if ((g + QD) % 8 == 0) mbar_wait(bar + 8 * (B_MEM + (g + QD) / 8), s & 1);
                            ldsm4t_if(b[g % QD], ma + (g + QD) * 512, yes);
                        }
                    }
                    y[0] += z[0] + u[0]; y[1] += z[1] + u[1]; y[2] += z[2] + u[2]; y[3] += z[3] + u[3];
                }
                PROF2(8);
                mbar_wait(bar + 8 * (B_MEM + 3), s & 1);
                wg_fence();
#pragma unroll
                for (int k = KR; k < 64; k++) wg_ss8<1, 1>(y, dW + (uint64_t)((k - KR) * 128), dM + (uint64_t)(k * 16), 1);
                wg_commit();
                asm volatile("wgmma.wait_group.sync.aligned 0;" : "+f"(y[0]), "+f"(y[1]), "+f"(y[2]), "+f"(y[3])::"memory");
                OPAQUE(tb);
                {
                    const uint32_t wo_ = (tb >> 5) * 256;
                    const uint32_t tile = sb + (role == 0 ? R_QX : (role == 1 ? R_K : R_V)) + wo_;
                    const uint32_t u0 = pack_bf16(y[0], y[1]), u1 = pack_bf16(y[2], y[3]);
                    sts32(tile + (tb & 31) * 4, u0);
                    sts32(tile + (tb & 31) * 4 + 128, u1);
                    __syncwarp();
                    uint4 v = lds128(tile + (tb & 15) * 16);
                    uint32_t peer = role + 1 + ((tb >> 4) & 1);
                    peer = peer >= 3 ? peer - 3 : peer;
                    const uint32_t rt = sb + (role == 0 ? R_QM : (role == 1 ? R_K : R_V)) + wo_ + (tb & 15) * 16;
                    st_async16(mapa(rt, peer), v, mapa(bar + 8 * (role == 2 ? B_HOPV : B_HOP1), peer));
                    if (role == 0) {
                        sts128(tile + 4096 + ((tb >> 4) & 1) * 4096 + (tb & 15) * 16, v);
                        sts32(tile + 12288 + (tb & 31) * 4, u0);
                        sts32(tile + 12288 + (tb & 31) * 4 + 128, u1);
                        __syncwarp();
                    }
                    e_arrive(bar + 8 * (role == 2 ? B_HOPV : B_HOP1));
                }
                PROF((wq >> 2) * 4 + 1);
                if (s < NSEG - 1) {
                    bar_sync(1, 256);
                    if (wq < 3) { fence_async(); x_load_pair(sb + R_RING + wq * 8192, &tm.x, h, wq, s + 1, bar + 8 * (B_FULL + wq)); }
                    else if (role == 0 && wq < 5) x_load_pair(sb + (wq == 3 ? e0 : e1), &tm.x, h, wq, s + 1, bar + 8 * (B_FULL + wq));
                    OPAQUE(tb);
                }
                uint32_t* pp = g_part[s & 3] + (h * 32 + (wo_tile(role, 0) + (tb >> 7)) * 8192 + ((tb >> 5) & 3) * 2048 + (tb & 31));
                asm volatile("" : "+l"(pp));
                if (s == NSEG - 1) break;
                wo_phase<role == 0 ? 2 : 3>(sb, tb, pp, bar + 8 * B_O, s & 1);
                if (wq == 0) PROF(10);
            }
        }
}

#define CLR 0
#define CLEAR(st) do { if (role != 0) { \
                const int w_ = wid & 3; \
                uint32_t* zp = g_part[(st) & 3] + ((rg0 + (w_ >> 1) * 64) * 1024 + (w_ & 1) * 512); \
                e_bulk_s2g(zp, sb + R_Z, 1024); \
                e_bulk_s2g(zp + 256, sb + R_Z, 1024); \
                e_bulk_s2g(&g_mem[(st) & 3][(rg0 + (w_ >> 1) * 64) * 32 + (w_ & 1) * 16], sb + R_Z, 64); \
                bulk_commit(); } } while (0)
template <uint32_t role> DEVINL void r_chain(const RMaps& tm, const bf16* __restrict__ mem0, const int wid) {
    extern __shared__ __align__(1024) unsigned char smem_raw[];
    const uint32_t sb = smem_u32(smem_raw);
    const uint32_t bar = sb + R_BAR;
    const int tid = threadIdx.x;
    int h; asm("mov.u32 %0, %%clusterid.x;" : "=r"(h));
        int t = tid & 127;
        const float sl2 = 0.08838834764831845f * 1.4426950408889634f;
        const float NEGRAW = -1000000000.0f / 0.08838834764831845f;
        const int rg0 = ((int)role - 1) * 32 + h;
        if (role != 0) {
#pragma unroll 1
            for (int r = 0; r < 4; r++) {
                uint32_t* zp = g_part[r] + ((rg0 + (t >> 6) * 64) * 1024 + (t & 63) * 4);
#pragma unroll
                for (int i = 0; i < 4; i++) st_strong16(zp + i * 256, make_uint4(0u, 0u, 0u, 0u));
                if ((t & 63) < 8) st_strong16(&g_mem[r][(rg0 + (t >> 6) * 64) * 32 + (t & 63) * 4], make_uint4(0u, 0u, 0u, 0u));
            }
            __threadfence();
        }
        if (role == 0 && (wid & 3) < 3) e_arrive_remote(mapa(bar + 8 * B_TFREE, wid & 3));
        if (t < 64) sts128(sb + R_Z + t * 16, make_uint4(0u, 0u, 0u, 0u));
        if (role == 0) sts128(sb + R_QM + t * 16, make_uint4(0u, 0u, 0u, 0u));
        {
            uint4 v[8];
#pragma unroll
            for (int r = 0; r < 8; r++) v[r] = __ldg((const uint4*)(mem0 + r * DM) + t);
            mbar_wait(bar + 8 * B_AFREE0, 0);
            mbar_wait(bar + 8 * B_AFREE1, 0);
#define TR2(f, c) \
            sts128(sb + R_RING + t * 128 + (c) * 16, make_uint4(__byte_perm(v[0].f, v[1].f, 0x5410), __byte_perm(v[2].f, v[3].f, 0x5410), __byte_perm(v[4].f, v[5].f, 0x5410), __byte_perm(v[6].f, v[7].f, 0x5410))); \
            sts128(sb + R_RING + t * 128 + (c) * 16 + 16, make_uint4(__byte_perm(v[0].f, v[1].f, 0x7632), __byte_perm(v[2].f, v[3].f, 0x7632), __byte_perm(v[4].f, v[5].f, 0x7632), __byte_perm(v[6].f, v[7].f, 0x7632)));
            TR2(x, 0) TR2(y, 2) TR2(z, 4) TR2(w, 6)
            fence_async();
            __syncwarp();
            e_arrive(bar + 8 * B_MEM + (t >> 5) * 8);
        }
        constexpr uint64_t dQ = role == 0 ? cdesc(R_QX, 128, 2048, 0) : cdesc(R_QM, 128, 0, 0);
        constexpr uint64_t dK = cdesc(R_K, 128, 2048, 0);

        for (int s = 0; s < NSEG; s++) {
            if (role == 0) {
                uint32_t n = 0, gate;
                do { gate = ld_strong4(&g_gate[s * SEG + (t >> 2)]); if (++n > 20000000u) __trap(); } while (gate == 0u);
                sts32(sb + R_G + (t >> 2) * 4, gate);
                __syncwarp();
            }
            mbar_wait(bar + 8 * B_XDONE, s & 1);
            mbar_wait(bar + 8 * B_XT, s & 1);
            if (t >= 1 && t < 3) { uint32_t pr = role + t; pr = pr >= 3 ? pr - 3 : pr; mbar_arrive_remote(mapa(bar + 8 * B_XRECV, pr)); }
            __syncwarp();
            mbar_wait(bar + 8 * B_HOP1, s & 1);
            PROF(8);
            fence_async();
            OPAQUE(t);
            if (s == NSEG - 1 && role != 0) { mbar_wait(bar + 8 * B_HOPV, s & 1); bulk_wait_all(); break; }
            float sc[20];
            wg_fence();
#pragma unroll
            for (int k = 0; k < 8; k++) wg_ss40(sc, dQ + (uint64_t)(k * 16), dK + (uint64_t)(k * 16), k);
            wg_commit();
            uint32_t t_o = clk32() + 500;
            {
                const uint32_t va = sb + R_V + 2048 + (t >> 5) * 512 + ((t >> 4) & 1) * 2048 + (t & 15) * 16;
                uint32_t v0[4], v1[4];
                ldsm4(v0, va); ldsm4(v1, va + 256);
                uint32_t vm[4];
                const bool v_here = mbar_try(bar + 8 * B_HOPV, s & 1);
                if (v_here) ldsm4(vm, sb + R_V + t * 16);
                wg_wait<0>();
                if (role == 0) {
#pragma unroll
                    for (int j = 0; j < 5; j++)
                        asm volatile("st.shared.v2.f32 [%0], {%1,%2};" ::"r"(sb + R_QX + 768 + (t >> 5) * 4096 + j * 256 + (t & 31) * 8), "f"(sc[4 * j + 2]), "f"(sc[4 * j + 3]) : "memory");
                }
                float m = fmaxf(sc[0], sc[1]);
#pragma unroll
                for (int j = 1; j < 5; j++) m = fmaxf(m, fmaxf(sc[4 * j], sc[4 * j + 1]));
                m = fmaxf(m, __shfl_xor_sync(0xffffffffu, m, 1));
                m = fmaxf(m, __shfl_xor_sync(0xffffffffu, m, 2));
                const float mb = m * sl2;
                uint32_t pk[5];
#pragma unroll
                for (int j = 0; j < 5; j++) pk[j] = pack_bf16(ex2(fmaf(sc[4 * j], sl2, -mb)), ex2(fmaf(sc[4 * j + 1], sl2, -mb)));
                float o0[4] = {0.f, 0.f, 0.f, 0.f}, o1[4] = {0.f, 0.f, 0.f, 0.f}, ls[4] = {0.f, 0.f, 0.f, 0.f};
                constexpr uint32_t ONE = 0x3F803F80u;
                mma16816(o0, v0[0], v0[1], v0[2], v0[3], pk[1], pk[2]);
                mma16816(o1, v1[0], v1[1], v1[2], v1[3], pk[1], pk[2]);
                ldsm4(v0, va + 4096); ldsm4(v1, va + 4096 + 256);
                mma16816(ls, ONE, ONE, ONE, ONE, pk[1], pk[2]);
                mma16816(ls, ONE, ONE, ONE, ONE, pk[3], pk[4]);
                mma1688(ls, ONE, ONE, pk[0]);
                mma16816(o0, v0[0], v0[1], v0[2], v0[3], pk[3], pk[4]);
                mma16816(o1, v1[0], v1[1], v1[2], v1[3], pk[3], pk[4]);
                if (!v_here) { mbar_wait(bar + 8 * B_HOPV, s & 1); ldsm4(vm, sb + R_V + t * 16); }
                mma1688(o0, vm[0], vm[1], pk[0]);
                mma1688(o1, vm[2], vm[3], pk[0]);
                const float i0 = rcp(ls[0]), i1 = rcp(ls[1]);
                const uint32_t oa = sb + R_O + (t >> 5) * 512 + (t & 31) * 4;
                sts32(oa, pack_bf16(o0[0] * i0, o0[1] * i1));
                sts32(oa + 128, pack_bf16(o0[2] * i0, o0[3] * i1));
                sts32(oa + 256, pack_bf16(o1[0] * i0, o1[1] * i1));
                sts32(oa + 384, pack_bf16(o1[2] * i0, o1[3] * i1));
                __syncwarp();
                e_arrive(bar + 8 * B_O);
                PROF(9);
                if (role == 0) {
                    OPAQUE(t);
                    const int lim = (t >> 2) - (t & 3) * 2 + 8;
                    float z[10];
#pragma unroll
                    for (int j = 0; j < 5; j++)
                        asm volatile("ld.shared.v2.f32 {%0,%1}, [%2];" : "=f"(z[2 * j]), "=f"(z[2 * j + 1]) : "r"(sb + R_QX + 768 + (t >> 5) * 4096 + j * 256 + (t & 31) * 8) : "memory");
                    float gate; asm volatile("ld.shared.f32 %0, [%1];" : "=f"(gate) : "r"(sb + R_G + (t >> 2) * 4) : "memory");
                    float m1 = fmaxf(z[0], z[1]);
#pragma unroll
                    for (int j = 1; j < 5; j++) {
                        z[2 * j] = 8 * j <= lim ? z[2 * j] : NEGRAW;
                        z[2 * j + 1] = 8 * j + 1 <= lim ? z[2 * j + 1] : NEGRAW;
                        m1 = fmaxf(m1, fmaxf(z[2 * j], z[2 * j + 1]));
                    }
                    m1 = fmaxf(m1, __shfl_xor_sync(0xffffffffu, m1, 1));
                    m1 = fmaxf(m1, __shfl_xor_sync(0xffffffffu, m1, 2));
                    const float mb1 = m1 * sl2;
                    float l1 = 0.f;
                    const uint32_t pa = sb + R_QX + (t >> 5) * 4096 + (t & 31) * 4;
#pragma unroll
                    for (int j = 0; j < 5; j++) {
                        const uint32_t pw = pack_bf16(ex2(fmaf(z[2 * j], sl2, -mb1)), ex2(fmaf(z[2 * j + 1], sl2, -mb1)));
                        l1 += __uint_as_float(pw << 16) + __uint_as_float(pw & 0xffff0000u);
                        sts32(pa + j * 128, pw);
                    }
                    sts32(pa + 5 * 128, 0u);
                    l1 += __shfl_xor_sync(0xffffffffu, l1, 1);
                    l1 += __shfl_xor_sync(0xffffffffu, l1, 2);
                    sts32(sb + R_G + 128 + (t >> 2) * 4, __float_as_uint(gate * rcp(l1)));
                    spin_until(t_o + PVD);
                    if ((wid & 3) == 0 && s >= 1) { bulk_wait_all(); e_count(&g_ocnt[(s - 1) >> 2]); }
                    fence_async();
                    bar_sync(2, 128);
                    constexpr uint64_t dV = cdesc(R_V, 2048, 128, 0);
                    constexpr uint64_t dP = cdesc(R_QX, 128, 4096, 0);
                    float sf[8];
#pragma unroll
                    for (int j = 0; j < 4; j++) asm volatile("ld.shared.v2.f32 {%0,%1}, [%2];" : "=f"(sf[2 * j]), "=f"(sf[2 * j + 1]) : "r"(sb + R_G + 128 + j * 32 + (t & 3) * 8) : "memory");
                    const uint32_t r = ((t >> 4) & 1) * 8 + (t & 7), ch = (t >> 5) * 2 + ((t >> 3) & 1);
                    const uint32_t sa = sb + R_QX + 2048 + r * 128 + ((ch ^ (r & 7)) << 4);
#pragma unroll
                    for (int hf = 0; hf < 2; hf++) {
                        float d[16];
                        wg_fence();
#pragma unroll
                        for (int k = 0; k < 3; k++) wg_ss32<0>(d, dV + (uint64_t)(hf * 64 + k * 256), dP + (uint64_t)(k * 16), k);
                        wg_commit();
                        asm volatile("wgmma.wait_group.sync.aligned 0;" : ACC16(d)::"memory");
                        stsm4t(sa + hf * 8192, pack_bf16(d[0] * sf[0], d[1] * sf[1]), pack_bf16(d[2] * sf[0], d[3] * sf[1]), pack_bf16(d[4] * sf[2], d[5] * sf[3]), pack_bf16(d[6] * sf[2], d[7] * sf[3]));
                        stsm4t(sa + hf * 8192 + 4096, pack_bf16(d[8] * sf[4], d[9] * sf[5]), pack_bf16(d[10] * sf[4], d[11] * sf[5]), pack_bf16(d[12] * sf[6], d[13] * sf[7]), pack_bf16(d[14] * sf[6], d[15] * sf[7]));
                    }
                    fence_async();
                    bar_sync(2, 128);
                    if ((wid & 3) == 0) {
#pragma unroll
                        for (int q = 0; q < 4; q++) e_tma_store(&tm.o, sb + R_QX + 2048 + q * 4096, h * DH + (q >> 1) * 64, s * SEG + (q & 1) * 16);
                        bulk_commit();
                        bulk_wait_read();
                    }
                    if ((wid & 3) < 3) e_arrive_remote(mapa(bar + 8 * B_TFREE, wid & 3));
                }
            }
            if (t < 32) { e_expect(bar + 8 * B_HOP1, role == 2 ? 4096 : 2048); if (role != 2) e_expect(bar + 8 * B_HOPV, 2048); e_expect(bar + 8 * B_XT, role == 0 ? 2 * CPB : CPB); }
            if (s == NSEG - 1) { bulk_wait_all(); break; }
            if (role != 0 && (wid & 3) >= 2) {
                mbar_wait(bar + 8 * B_XRECV, s & 1);
                mbar_wait(bar + 8 * B_O, s & 1);
                fence_async();
                spin_until(t_o + ELD);
                x_load_pair(sb + ((wid & 1) ? R_V + 2048 : R_K + 2048), &tm.x, h, 3 + (wid & 1), s + 1, bar + 8 * (B_FULL + 3 + (wid & 1)));
            }
            OPAQUE(t);
            PROF(11);
            if (role != 0 || DDUP) {
                const int grp = role == 0 ? (t >> 6) * 32 + h : rg0 + (t >> 6) * 64;
                const uint32_t* rp = g_part[s & 3] + (grp * 1024 + ((t >> 2) & 7) * 32 + ((t >> 5) & 1) * 16 + (t & 3) * 4);
                uint32_t* wp = &g_mem[(s + 1) & 3][grp * 32 + ((t >> 5) & 1) * 16 + (t & 3) * 4 + ((t >> 3) & 3)];
                bulk_wait_all();
                spin_until(t_o + D2_BASE + (role == 0 ? DDUP + (t >> 6) * D2_STEP : (role - 1 + (t >> 6) * 2) * D2_STEP));
                PROF3(0, clk32());
#define LO(u) __uint_as_float((u) << 16)
#define HI(u) __uint_as_float((u) & 0xffff0000u)
                uint4 v[4];
                uint32_t n = poll_set<4>(v, rp, 256, (role - 1 + (t >> 6) * 2) * PHQ);
                {
                    PROF3(1, clk32());
                    float f[8];
                    f[0] = (LO(v[0].x) + LO(v[1].x)) + (LO(v[2].x) + LO(v[3].x)); f[1] = (HI(v[0].x) + HI(v[1].x)) + (HI(v[2].x) + HI(v[3].x));
                    f[2] = (LO(v[0].y) + LO(v[1].y)) + (LO(v[2].y) + LO(v[3].y)); f[3] = (HI(v[0].y) + HI(v[1].y)) + (HI(v[2].y) + HI(v[3].y));
                    f[4] = (LO(v[0].z) + LO(v[1].z)) + (LO(v[2].z) + LO(v[3].z)); f[5] = (HI(v[0].z) + HI(v[1].z)) + (HI(v[2].z) + HI(v[3].z));
                    f[6] = (LO(v[0].w) + LO(v[1].w)) + (LO(v[2].w) + LO(v[3].w)); f[7] = (HI(v[0].w) + HI(v[1].w)) + (HI(v[2].w) + HI(v[3].w));
                    const bool b4 = t & 16, b3 = t & 8;
                    float g4[4], g2[2];
#pragma unroll
                    for (int i = 0; i < 4; i++) g4[i] = (b4 ? f[4 + i] : f[i]) + __shfl_xor_sync(0xffffffffu, b4 ? f[i] : f[4 + i], 16);
#pragma unroll
                    for (int i = 0; i < 2; i++) g2[i] = (b3 ? g4[2 + i] : g4[i]) + __shfl_xor_sync(0xffffffffu, b3 ? g4[i] : g4[2 + i], 8);
                    g2[0] += __shfl_xor_sync(0xffffffffu, g2[0], 4);
                    g2[1] += __shfl_xor_sync(0xffffffffu, g2[1], 4);
                    st_strong4(wp, pack_nz(g2[0], g2[1]));
                }
                PROF3(8, n); (void)n;
            }
            t_o += D2_BASE + DQ + D3 + (t >> 5) * D2_STEP;
            OPAQUE(t);
            PROF(12);
            {
                const uint32_t* rp = &g_mem[(s + 1) & 3][((t >> 5) * 256 + (t & 31)) * 4];
                const uint32_t da = sb + R_RING + ((t >> 5) * 256 + (t & 31)) * 16;
                uint4 v[8];
                spin_until(t_o);
                PROF3(2, clk32());
                uint32_t n = poll_set<8>(v, rp, 128, PH3 + (t >> 5) * PHQ);
                PROF(13);
                PROF3(3, clk32()); PROF3(9, n); (void)n;
                mbar_wait(bar + 8 * B_AFREE0 + (t >> 6) * 8, (s + 1) & 1);
                PROF3(4, clk32());
#pragma unroll
                for (int i = 0; i < 8; i++) sts128(da + i * 512, v[i]);
                if (t >= 64) fence_async();
                __syncwarp();
                e_arrive(bar + 8 * B_MEM + (t >> 5) * 8);
                PROF(14);
                PROF3(5, clk32());
            }
            CLEAR(s + 3);
        }
}

__global__ void __launch_bounds__(384, 1) r_kernel(const __grid_constant__ RMaps tm, const bf16* __restrict__ mem0, const bf16* __restrict__ x, const bf16* __restrict__ gate_w) {
    extern __shared__ __align__(1024) unsigned char smem_raw[];
    const uint32_t sb = smem_u32(smem_raw);
    if ((sb & 0x3FFFFu) != SB0) __trap();
    const int tid = threadIdx.x;
    const int wid = __shfl_sync(0xffffffffu, tid >> 5, 0);
    uint32_t role; asm("mov.u32 %0, %%cluster_ctarank;" : "=r"(role));
    int h; asm("mov.u32 %0, %%clusterid.x;" : "=r"(h));
    const uint32_t bar = sb + R_BAR;
    asm volatile("griddepcontrol.launch_dependents;");
    KT(0, 0);
    const int gr = blockIdx.x * 12 + wid;
    uint4 gx0[4], gx1[4], gw[4];
#pragma unroll
    for (int i = 0; i < 4; i++) {
        gx0[i] = ldg_nc((const uint4*)(x + gr * DM) + i * 32 + (tid & 31));
        gx1[i] = ldg_nc((const uint4*)(x + min(gr + 1152, SEQ - 1) * DM) + i * 32 + (tid & 31));
        gw[i] = ldg_nc((const uint4*)gate_w + i * 32 + (tid & 31));
    }

    if (tid == 0) {
        for (int i = 0; i < 5; i++) mbar_init(bar + 8 * (B_FULL + i), 1);
        for (int i = 0; i < 3; i++) mbar_init(bar + 8 * (B_EMPTY + i), 2);
        for (int i = 0; i < 4; i++) mbar_init(bar + 8 * (B_MEM + i), 1);
        mbar_init(bar + 8 * B_HOP1, role == 2 ? 1 : 9);
        mbar_init(bar + 8 * B_HOPV, role == 2 ? 8 : 1);
        mbar_init(bar + 8 * B_XT, 1);
        mbar_init(bar + 8 * B_TFREE, 5);
        mbar_init(bar + 8 * B_P, 4);
        mbar_init(bar + 8 * B_XDONE, 8);
        mbar_init(bar + 8 * B_OST0, 4);
        mbar_init(bar + 8 * B_OST1, 4);
        mbar_init(bar + 8 * B_XRECV, 2);
        mbar_init(bar + 8 * B_O, 4);
        mbar_init(bar + 8 * B_AFREE0, 2);
        mbar_init(bar + 8 * B_AFREE1, 2);
        mbar_init(bar + 8 * B_PRO0, 1);
        mbar_init(bar + 8 * B_PRO1, 8);
        asm volatile("fence.mbarrier_init.release.cluster;" ::: "memory");
        fence_async();
        mbar_expect(bar + 8 * B_PRO0, KR * 4096);
        for (int i = 0; i < 3; i++) mbar_expect(bar + 8 * (B_FULL + i), 8192);
        mbar_expect(bar + 8 * B_HOP1, role == 2 ? 4096 : 2048);
        if (role != 2) mbar_expect(bar + 8 * B_HOPV, 2048);
        mbar_expect(bar + 8 * B_XT, role == 0 ? 2 * CPB : CPB);
    }
    __syncthreads();
    asm volatile("barrier.cluster.arrive.relaxed.aligned;" ::: "memory");
    {
        const CUtensorMap* tw = &tm.w[role];
        if (wid < 11) {
            e_tma_load(sb + wid * 16384, tw, h * DH, KC(wid), bar + 8 * B_PRO0);
            e_tma_load(sb + wid * 16384 + 8192, tw, h * DH + 64, KC(wid), bar + 8 * B_PRO0);
        }
        if (wid < 6) e_tma_load(sb + R_RING + wid * 4096, &tm.x, XC(wid), 0, bar + 8 * (B_FULL + (wid >> 1)));
        if ((tid & 31) == 0) {
            if (wid < 10) tma_prefetch(tw, h * DH + (wid & 1) * 64, KC(KR / 4 + (wid >> 1)));
            if (wid >= 6 && wid - 6 < (role == 0 ? 4 : 6)) tma_prefetch(&tm.wo, wo_tile(role, wid - 6) * 64, h * DH);
        }
        __syncwarp();
        const uint32_t g0 = __float_as_uint(gate_row(gx0, gw)), g1 = __float_as_uint(gate_row(gx1, gw));
        if ((tid & 31) == 0) {
            st_strong4(&g_gate[gr], g0 ? g0 : 0x80000000u);
            if (gr + 1152 < SEQ) st_strong4(&g_gate[gr + 1152], g1 ? g1 : 0x80000000u);
        }
        __syncwarp();
    }
    asm volatile("barrier.cluster.wait.aligned;" ::: "memory");

    if (wid < 8) {
        asm volatile("setmaxnreg.inc.sync.aligned.u32 224;");
        if (role == 0) r_big<0>(tm, wid); else if (role == 1) r_big<1>(tm, wid); else r_big<2>(tm, wid);
    } else {
        asm volatile("setmaxnreg.dec.sync.aligned.u32 56;");
        if (role == 0) r_chain<0>(tm, mem0, wid); else if (role == 1) r_chain<1>(tm, mem0, wid); else r_chain<2>(tm, mem0, wid);
    }
    __syncwarp();
    asm volatile("barrier.cluster.arrive; barrier.cluster.wait;" ::: "memory");
    KT(0, 1);
}

#define STAG 0
constexpr int G_ST = 4;
constexpr int G_STAGE = 16384 + 32768;
constexpr int G_EPI = G_ST * G_STAGE;
constexpr int G_GATE = G_EPI + 32768;
constexpr int G_BAR = G_GATE + 1024;
constexpr int G_SMEM = G_BAR + 128 + 1024;

struct G1Maps { CUtensorMap x, wg, wu, hs, o, h, wo, wd, out; };
constexpr int G1_NB = FF / 128;
constexpr int G1_TILES = 16 * G1_NB;

DEVINL void g_mma_block(float* d, uint32_t sb, uint32_t bar, int it, int wg, int tid, bool first) {
    const int st = it % G_ST;
    mbar_wait(bar + 8 * st, (it / G_ST) & 1);
    const uint64_t da = mkdesc(sb + st * G_STAGE + wg * 8192, 16, 1024, 1);
    const uint64_t db = mkdesc(sb + st * G_STAGE + 16384, 8192, 1024, 1);
    wg_fence();
#pragma unroll
    for (int k = 0; k < 4; k++) wg_ss256(d, da + (uint64_t)(k * 2), db + (uint64_t)(k * 128), (first ? 0 : 1) | k);
    wg_commit();
    if (!first) { wg_wait<1>(); if ((tid & 127) == 0) mbar_arrive(bar + 8 * (G_ST + (it - 1) % G_ST)); }
}
DEVINL void g_load_block(uint32_t sb, uint32_t bar, int it, const CUtensorMap* ta, int k0, int m0, const CUtensorMap* tb, int n0) {
    const int st = it % G_ST;
    mbar_wait(bar + 8 * (G_ST + st), ((it / G_ST) & 1) ^ 1);
    const uint32_t fb = bar + 8 * st, sa = sb + st * G_STAGE;
    mbar_expect(fb, G_STAGE);
    tma_load(sa, ta, k0, m0, fb);
#pragma unroll
    for (int q = 0; q < 4; q++) tma_load(sa + 16384 + q * 8192, tb, n0 + q * 64, k0, fb);
}

DEVINL void g_store_tile(const float* d, const CUtensorMap* tout, uint32_t epi, int mb, int nb, int wg, int tid) {
    const int lane = tid & 31, row = ((tid >> 5) & 3) * 16 + ((lane >> 3) & 1) * 8 + (lane & 7);
#pragma unroll
    for (int half = 0; half < 2; half++) {
        if ((tid & 127) == 0) bulk_wait_read();
        bar_sync(1 + wg, 128);
#pragma unroll
        for (int j = 0; j < 16; j += 2) {
            const float* e = d + half * 64 + 4 * j;
            const int cgp = j + (lane >> 4);
            stsm4(epi + (cgp >> 3) * 8192 + row * 128 + (((cgp & 7) ^ (row & 7)) << 4),
                  pack_bf16(e[0], e[1]), pack_bf16(e[2], e[3]), pack_bf16(e[4], e[5]), pack_bf16(e[6], e[7]));
        }
        fence_async();
        bar_sync(1 + wg, 128);
        if ((tid & 127) == 0) {
            tma_store(tout, epi, nb * 256 + half * 128, mb * 128 + wg * 64);
            tma_store(tout, epi + 8192, nb * 256 + half * 128 + 64, mb * 128 + wg * 64);
            bulk_commit();
        }
    }
}
template <int NS> DEVINL void g_split_finish(const float* d, float4 (&r)[32 / NS], uint4* sk, int tile, int ks, bf16* __restrict__ out, int tid) {
    constexpr int Q = 32 / NS;
    uint4* mine = sk + ks * (16 * 256) + tid;
#pragma unroll
    for (int c = 0; c < NS; c++) {
        if (c != ks) {
#pragma unroll
            for (int q = c * Q / 2; q < (c + 1) * Q / 2; q++)
                __stcg(mine + q * 256, make_uint4(pack_bf16(d[8 * q], d[8 * q + 1]), pack_bf16(d[8 * q + 2], d[8 * q + 3]), pack_bf16(d[8 * q + 4], d[8 * q + 5]), pack_bf16(d[8 * q + 6], d[8 * q + 7])));
        } else {
#pragma unroll
            for (int q = 0; q < Q; q++) { const float* e = d + (c * Q + q) * 4; r[q].x += e[0]; r[q].y += e[1]; r[q].z += e[2]; r[q].w += e[3]; }
        }
    }
    __threadfence();
    bar_sync(3, 256);
    if (tile >= T_LATE) PT(20);
    if (tid == 0) {
        atomicAdd(&g_skcnt[tile], 1u);
        uint32_t v, n = 0;
        do {
            asm volatile("ld.acquire.gpu.global.u32 %0, [%1];" : "=r"(v) : "l"(&g_skcnt[tile]) : "memory");
            if (++n > 200000000u) __trap();
        } while (v < NS);
        if (atomicAdd(&g_skcnt[tile], 1u) == 2 * NS - 1) g_skcnt[tile] = 0u;
    }
    bar_sync(3, 256);
    if (tile >= T_LATE) PT(21);
#pragma unroll
    for (int c = 1; c < NS; c++) {
        const uint4* th = sk + (((ks + c) & (NS - 1)) * 16 + ks * (Q / 2)) * 256 + tid;
#pragma unroll
        for (int q = 0; q < Q / 2; q++) {
            const uint4 u = __ldcg(th + q * 256);
            r[2 * q].x += __uint_as_float(u.x << 16); r[2 * q].y += __uint_as_float(u.x & 0xffff0000u);
            r[2 * q].z += __uint_as_float(u.y << 16); r[2 * q].w += __uint_as_float(u.y & 0xffff0000u);
            r[2 * q + 1].x += __uint_as_float(u.z << 16); r[2 * q + 1].y += __uint_as_float(u.z & 0xffff0000u);
            r[2 * q + 1].z += __uint_as_float(u.w << 16); r[2 * q + 1].w += __uint_as_float(u.w & 0xffff0000u);
        }
    }
    const int lane = tid & 31;
    uint32_t* op = (uint32_t*)(out + ((tile >> 2) * 128 + (tid >> 5) * 16 + (lane >> 2)) * DM + (tile & 3) * 256 + ks * Q * 8 + (lane & 3) * 2);
#pragma unroll
    for (int q = 0; q < Q; q++) { op[q * 4] = pack_bf16(r[q].x, r[q].y); op[q * 4 + 4 * DM] = pack_bf16(r[q].z, r[q].w); }
}
DEVINL int g1_count(int pass, int tail) {
    return pass == 0 ? NPRE : pass == 1 ? NFULL : pass == 2 ? T_MID - NFULL : pass == 3 ? (T_MID2 - T_MID) * 4 : tail ? (64 - T_LATE) * 8 : (T_LATE - T_MID2) * 8;
}
DEVINL int g1_first(int pass, int tail) {
    const int b = blockIdx.x, n = gridDim.x;
    return (pass < 2 || tail) ? b : pass == 2 ? n - 1 - b : (b + n - (pass == 3 ? 16 : 32)) % n;
}
DEVINL int g1_tile(int pass, int tail, int i) {
    return pass == 1 ? i : pass == 3 ? T_MID + (i >> 2) : pass == 4 ? (tail ? T_LATE : T_MID2) + (i >> 3) : NFULL + i;
}
constexpr int H_EARLY = 24;

__global__ void __launch_bounds__(384, 1) g1_kernel(const __grid_constant__ G1Maps tm, bf16* __restrict__ out, const int tail) {
    extern __shared__ __align__(1024) unsigned char smem_raw[];
    const uint32_t sb = (smem_u32(smem_raw) + 1023) & ~1023u;
    const int tid = threadIdx.x, lane = tid & 31;
    const int wg = __shfl_sync(0xffffffffu, tid >> 7, 0);
    const int warp = __shfl_sync(0xffffffffu, (tid >> 5) & 3, 0);
    const uint32_t bar = sb + G_BAR;
    asm volatile("griddepcontrol.launch_dependents;");
    KT(1 + tail, 0);
    if (tail && (tid == 32 || tid == 64)) asm volatile("prefetch.tensormap [%0];" ::"l"(tid == 32 ? &tm.o : &tm.wo) : "memory");
    const int ntiles = tail ? 0 : G1_TILES;
    if (tid == 0) {
        for (int i = 0; i < G_ST; i++) { mbar_init(bar + 8 * i, 1); mbar_init(bar + 8 * (G_ST + i), 2); }
        fence_async();
    }
    __syncthreads();
    if (tail) PT(16);
    if (tail) asm volatile("griddepcontrol.wait;" ::: "memory");
    if (tail) PT(17);
    if (tail && tid < 32 * G_ST) {
        const int it = tid >> 5, tile = T_LATE + (blockIdx.x >> 3), k0 = ((blockIdx.x & 7) * 8 + it) * 64;
        e_expect(bar + 8 * it, G_STAGE);
        e_tma_load(sb + it * G_STAGE, &tm.o, k0, (tile >> 2) * 128, bar + 8 * it);
#pragma unroll
        for (int q = 0; q < 4; q++) e_tma_load(sb + it * G_STAGE + 16384 + q * 8192, &tm.wo, (tile & 3) * 256 + q * 64, k0, bar + 8 * it);
    }
    if (wg == 2) {
        asm volatile("setmaxnreg.dec.sync.aligned.u32 40;");
        if (tail && warp == 1) {
            if (blockIdx.x < SEQ / 32) g_gate[blockIdx.x * 32 + lane] = 0u;
            if (blockIdx.x == 0) { if (lane < 16) g_ocnt[lane] = 0u; g_hcnt[lane] = 0u; g_pcnt[lane] = 0u; g_pcnt[32 + lane] = 0u; }
        }
        if (warp == 0) {
            if (lane == 0) {
                int it = 0;
                for (int tile = blockIdx.x; tile < ntiles; tile += gridDim.x) {
                    const int mb = tile & 15, nb = tile >> 4;
                    for (int kb = 0; kb < 16; kb++, it++) {
                        const int st = it % G_ST;
                        mbar_wait(bar + 8 * (G_ST + st), ((it / G_ST) & 1) ^ 1);
                        const uint32_t fb = bar + 8 * st, sa = sb + st * G_STAGE;
                        mbar_expect(fb, G_STAGE);
                        tma_load(sa, &tm.x, kb * 64, mb * 128, fb);
                        tma_load(sa + 16384, &tm.wg, nb * 128, kb * 64, fb);
                        tma_load(sa + 16384 + 8192, &tm.wg, nb * 128 + 64, kb * 64, fb);
                        tma_load(sa + 16384 + 16384, &tm.wu, nb * 128, kb * 64, fb);
                        tma_load(sa + 16384 + 24576, &tm.wu, nb * 128 + 64, kb * 64, fb);
                    }
                }
                for (int pass = tail ? 4 : 0; pass < 5; pass++) {
                    for (int i = g1_first(pass, tail); i < g1_count(pass, tail); i += gridDim.x) {
                        const int tile = g1_tile(pass, tail, i), mb = tile >> 2, nb = tile & 3;
                        if (pass < 2) {
                            for (int kb = 0; kb < FF / 64; kb++, it++) {
                                if (kb == 0 || kb == 2 * H_EARLY) {
                                    wait_count(&g_hcnt[kb ? 16 + mb : mb], kb ? 2 * (G1_NB - H_EARLY) : 2 * H_EARLY);
                                    asm volatile("fence.proxy.async;" ::: "memory");
                                }
                                g_load_block(sb, bar, it, &tm.h, kb * 64, mb * 128, &tm.wd, nb * 256);
                            }
                        }
                        if (pass > 0) {
                            const int k0 = pass == 3 ? (i & 3) * 16 : pass == 4 ? (i & 7) * 8 : 0, k1 = pass == 3 ? k0 + 16 : pass == 4 ? k0 + 8 : HD / 64;
                            if (!tail) wait_count(&g_ocnt[mb], NH * 4);
                            asm volatile("fence.proxy.async;" ::: "memory");
                            for (int kb = k0; kb < k1; kb++, it++) if (!tail || it >= G_ST) g_load_block(sb, bar, it, &tm.o, kb * 64, mb * 128, &tm.wo, nb * 256);
                        }
                    }
                }
            }
        }
    } else {
        asm volatile("setmaxnreg.inc.sync.aligned.u32 232;");
        float d[128];
        int it = 0;
        const uint32_t epi = sb + G_EPI + wg * 16384;
        const int row = warp * 16 + ((lane >> 3) & 1) * 8 + (lane & 7);
        for (int tile = blockIdx.x; tile < ntiles; tile += gridDim.x) {
            const int mb = tile & 15, nb = tile >> 4;
            const uint32_t* gp = &g_gate[mb * 128 + wg * 64 + warp * 16 + (lane >> 2)];
            uint32_t u0 = ld_strong4(gp), u1 = ld_strong4(gp + 8);
            for (int kb = 0; kb < 16; kb++, it++) {
                if (it == (wg ? 0 : STAG)) bar_sync(4, 256);
                g_mma_block(d, sb, bar, it, wg, tid, kb == 0);
            }
            wg_wait<0>();
            for (uint32_t n = 0; u0 == 0u || u1 == 0u; n++) { u0 = ld_strong4(gp); u1 = ld_strong4(gp + 8); if (n > 20000000u) __trap(); }
            __syncwarp();
            const float s0 = 1.0f - __uint_as_float(u0), s1 = 1.0f - __uint_as_float(u1);
            if ((tid & 127) == 0) {
                mbar_arrive(bar + 8 * (G_ST + (it - 1) % G_ST));
                bulk_wait_all();
                const int pt = tile - (int)gridDim.x;
                if (pt >= 0) atomicAdd(&g_hcnt[(pt & 15) + ((pt >> 4) >= H_EARLY ? 16 : 0)], 1u);
            }
            bar_sync(1 + wg, 128);
#pragma unroll
            for (int j = 0; j < 16; j += 2) {
                uint32_t p[4];
#pragma unroll
                for (int q = 0; q < 4; q++) {
                    const int i = (j + (q >> 1)) * 4 + (q & 1) * 2;
                    const float sc = (q & 1) ? s1 : s0;
                    const float g0 = d[i], g1 = d[i + 1];
                    const float a0 = 1.0f + ex2(fminf(g0 * -1.4426950408889634f, 62.0f)), a1 = 1.0f + ex2(fminf(g1 * -1.4426950408889634f, 62.0f));
                    const float rr = rcp(a0 * a1) * sc;
                    const float h0 = (g0 * d[64 + i]) * (rr * a1);
                    const float h1 = (g1 * d[64 + i + 1]) * (rr * a0);
                    p[q] = pack_bf16(h0, h1);
                }
                const int cgp = j + (lane >> 4);
                stsm4(epi + (cgp >> 3) * 8192 + row * 128 + (((cgp & 7) ^ (row & 7)) << 4), p[0], p[1], p[2], p[3]);
            }
            fence_async();
            bar_sync(1 + wg, 128);
            if ((tid & 127) == 0) {
                tma_store(&tm.hs, epi, nb * 128, mb * 128 + wg * 64);
                tma_store(&tm.hs, epi + 8192, nb * 128 + 64, mb * 128 + wg * 64);
                bulk_commit();
            }
        }
        if ((tid & 127) == 0 && !tail) {
            bulk_wait_all();
            const int pt = blockIdx.x + (G1_TILES - 1 - blockIdx.x) / gridDim.x * gridDim.x;
            atomicAdd(&g_hcnt[(pt & 15) + ((pt >> 4) >= H_EARLY ? 16 : 0)], 1u);
        }
        for (int pass = tail ? 4 : 0; pass < 5; pass++) {
            for (int i = g1_first(pass, tail); i < g1_count(pass, tail); i += gridDim.x) {
                const int tile = g1_tile(pass, tail, i);
                const int nkb = pass == 0 ? FF / 64 : pass == 1 ? (FF + HD) / 64 : pass == 2 ? HD / 64 : pass == 3 ? 16 : 8;
                float4* pre = g_pre + (tile - NFULL) * (32 * 256) + tid;
                if (tail) asm volatile("prefetch.global.L2 [%0];" ::"l"(pre - tid + (i & 7) * 1024 + tid * 4));
                for (int kb = 0; kb < nkb; kb++, it++) { g_mma_block(d, sb, bar, it, wg, tid, kb == 0); if (tail && kb == 0) PT(18); }
                wg_wait<0>();
                if (tail) PT(19);
                if ((tid & 127) == 0) mbar_arrive(bar + 8 * (G_ST + (it - 1) % G_ST));
                if (pass >= 2 && !tail) { if ((tid & 31) == 0) wait_count(&g_pcnt[tile], 8); __syncwarp(); }
                if (pass == 0) {
#pragma unroll
                    for (int q = 0; q < 32; q++) __stcg(pre + q * 256, make_float4(d[4 * q], d[4 * q + 1], d[4 * q + 2], d[4 * q + 3]));
                    __threadfence();
                    __syncwarp();
                    if ((tid & 31) == 0) atomicAdd(&g_pcnt[tile], 1u);
                } else if (pass == 3) {
                    float4 r[8];
#pragma unroll
                    for (int q = 0; q < 8; q++) r[q] = __ldcg(pre + ((i & 3) * 8 + q) * 256);
                    g_split_finish<4>(d, r, g_sk + (tile - T_MID) * 8 * (16 * 256), tile, i & 3, out, tid);
                } else if (pass == 4) {
                    float4 r[4];
#pragma unroll
                    for (int q = 0; q < 4; q++) r[q] = __ldcg(pre + ((i & 7) * 4 + q) * 256);
                    g_split_finish<8>(d, r, g_sk + (tile - T_MID) * 8 * (16 * 256), tile, i & 7, out, tid);
                } else {
                    if (pass == 2) {
#pragma unroll
                        for (int q = 0; q < 32; q++) {
                            const float4 u = __ldcg(pre + q * 256); d[4 * q] += u.x; d[4 * q + 1] += u.y; d[4 * q + 2] += u.z; d[4 * q + 3] += u.w;
                            if ((q & 7) == 7) __syncwarp();
                        }
                    }
                    g_store_tile(d, &tm.out, epi, tile >> 2, tile & 3, wg, tid);
                }
            }
        }
        if ((tid & 127) == 0) bulk_wait_all();
        KT(1 + tail, 1);
    }
    __syncwarp();
    asm volatile("griddepcontrol.wait;" ::: "memory");
}

typedef CUresult (*EncodeFn)(CUtensorMap*, CUtensorMapDataType, cuuint32_t, void*, const cuuint64_t*, const cuuint64_t*, const cuuint32_t*,
                             const cuuint32_t*, CUtensorMapInterleave, CUtensorMapSwizzle, CUtensorMapL2promotion, CUtensorMapFloatOOBfill);

static void make_map(EncodeFn enc, CUtensorMap* m, const void* ptr, uint64_t rows, uint64_t cols, uint32_t box_rows) {
    cuuint64_t dims[2] = {cols, rows};
    cuuint64_t strides[1] = {cols * 2};
    cuuint32_t box[2] = {64, box_rows};
    cuuint32_t es[2] = {1, 1};
    enc(m, CU_TENSOR_MAP_DATA_TYPE_BFLOAT16, 2, (void*)ptr, dims, strides, box, es, CU_TENSOR_MAP_INTERLEAVE_NONE,
        CU_TENSOR_MAP_SWIZZLE_128B, CU_TENSOR_MAP_L2_PROMOTION_L2_256B, CU_TENSOR_MAP_FLOAT_OOB_FILL_NONE);
}

extern "C" void kernel_launch(void* const* d_in, const int* in_sizes, int n_in, void* d_out, int out_size) {
    (void)in_sizes; (void)n_in; (void)out_size;
    const bf16* x = (const bf16*)d_in[0];
    const bf16* mem0 = (const bf16*)d_in[1];
    const bf16* gate_w = (const bf16*)d_in[11];
    static EncodeFn enc = nullptr;
    static int n_sm = 0;
    static void *pO = nullptr, *pH = nullptr;
    if (!enc) {
        void* fn = nullptr;
        cudaDriverEntryPointQueryResult qr;
        cudaGetDriverEntryPoint("cuTensorMapEncodeTiled", &fn, cudaEnableDefault, &qr);
        enc = (EncodeFn)fn;
        cudaDeviceGetAttribute(&n_sm, cudaDevAttrMultiProcessorCount, 0);
        cudaFuncSetAttribute(r_kernel, cudaFuncAttributeMaxDynamicSharedMemorySize, R_SMEM);
        cudaFuncSetAttribute(g1_kernel, cudaFuncAttributeMaxDynamicSharedMemorySize, G_SMEM);
        cudaGetSymbolAddress(&pO, g_O);
        cudaGetSymbolAddress(&pH, g_H);
    }
    RMaps rm; G1Maps m1;
    make_map(enc, &rm.x, x, SEQ, DM, 32);
    for (int i = 0; i < 3; i++) make_map(enc, &rm.w[i], d_in[2 + i], DM, HD, 64);
    make_map(enc, &rm.wo, d_in[5], HD, DM, 128);
    make_map(enc, &rm.o, pO, SEQ, HD, 16);
    make_map(enc, &m1.x, x, SEQ, DM, 128);
    make_map(enc, &m1.wg, d_in[8], DM, FF, 64);
    make_map(enc, &m1.wu, d_in[9], DM, FF, 64);
    make_map(enc, &m1.hs, pH, SEQ, FF, 64);
    make_map(enc, &m1.o, pO, SEQ, HD, 128);
    make_map(enc, &m1.h, pH, SEQ, FF, 128);
    make_map(enc, &m1.wo, d_in[5], HD, DM, 64);
    make_map(enc, &m1.wd, d_in[10], FF, DM, 64);
    make_map(enc, &m1.out, d_out, SEQ, DM, 64);

    cudaStream_t st = cudaStreamPerThread;
    {
        cudaLaunchConfig_t cfg = {};
        cfg.gridDim = dim3(96); cfg.blockDim = dim3(384); cfg.dynamicSmemBytes = R_SMEM; cfg.stream = st;
        cudaLaunchAttribute at[1];
        at[0].id = cudaLaunchAttributeClusterDimension; at[0].val.clusterDim.x = 3; at[0].val.clusterDim.y = 1; at[0].val.clusterDim.z = 1;
        cfg.attrs = at; cfg.numAttrs = 1;
        cudaLaunchKernelEx(&cfg, r_kernel, rm, mem0, x, gate_w);
    }
    {
        cudaLaunchConfig_t cfg = {};
        cfg.gridDim = dim3(n_sm - 96); cfg.blockDim = dim3(384); cfg.dynamicSmemBytes = G_SMEM; cfg.stream = st;
        cudaLaunchAttribute at[1];
        at[0].id = cudaLaunchAttributeProgrammaticStreamSerialization; at[0].val.programmaticStreamSerializationAllowed = 1;
        cfg.attrs = at; cfg.numAttrs = 1;
        cudaLaunchKernelEx(&cfg, g1_kernel, m1, (bf16*)d_out, 0);
    }
    {
        cudaLaunchConfig_t cfg = {};
        cfg.gridDim = dim3((64 - T_LATE) * 8); cfg.blockDim = dim3(384); cfg.dynamicSmemBytes = G_SMEM; cfg.stream = st;
        cudaLaunchAttribute at[1];
        at[0].id = cudaLaunchAttributeProgrammaticStreamSerialization; at[0].val.programmaticStreamSerializationAllowed = 1;
        cfg.attrs = at; cfg.numAttrs = 1;
        cudaLaunchKernelEx(&cfg, g1_kernel, m1, (bf16*)d_out, 1);
    }
}
```

```cpp
#include <cuda_runtime.h>
#include <cuda_bf16.h>
#include <cuda.h>
#include <stdint.h>

typedef __nv_bfloat16 bf16;

constexpr int SEQ = 2048, DM = 1024, NH = 32, DH = 128, NMEM = 8, SEG = 32, NSEG = 64, FF = 3584;
constexpr int HD = NH * DH;

__device__ bf16 g_O[SEQ * HD];
__device__ bf16 g_H[SEQ * FF];
__device__ uint32_t g_gate[SEQ];
__device__ uint32_t g_part[4][128 * 32 * 32];
__device__ uint32_t g_mem[4][DM * 4];
#define TLATE 56
constexpr int NFULL = 36, T_MID = 44, T_MID2 = 48, T_LATE = TLATE;
constexpr int NPRE = 64 - NFULL;
__device__ float4 g_pre[NPRE * 32 * 256];
__device__ uint4 g_sk[(64 - T_MID) * 8 * 16 * 256];
__device__ uint32_t g_skcnt[64], g_pcnt[64];
__device__ uint32_t g_hcnt[32], g_ocnt[16];
#define KT(k, i)
#define PT(i)

#define DEVINL __device__ __forceinline__
constexpr long long SPIN_LIMIT = 4000000000LL;

DEVINL uint32_t smem_u32(const void* p) { return (uint32_t)__cvta_generic_to_shared(p); }
DEVINL void mbar_init(uint32_t bar, uint32_t cnt) { asm volatile("mbarrier.init.shared::cta.b64 [%0], %1;" ::"r"(bar), "r"(cnt) : "memory"); }
DEVINL void mbar_arrive(uint32_t bar) { asm volatile("mbarrier.arrive.shared::cta.b64 _, [%0];" ::"r"(bar) : "memory"); }
DEVINL void mbar_expect(uint32_t bar, uint32_t bytes) { asm volatile("mbarrier.arrive.expect_tx.shared::cta.b64 _, [%0], %1;" ::"r"(bar), "r"(bytes) : "memory"); }
DEVINL void mbar_arrive_remote(uint32_t cbar) { asm volatile("mbarrier.arrive.relaxed.cluster.shared::cluster.b64 _, [%0];" ::"r"(cbar) : "memory"); }
DEVINL bool mbar_try(uint32_t bar, uint32_t par) {
    uint32_t ok;
    asm volatile("{ .reg .pred p; mbarrier.try_wait.parity.shared::cta.b64 p, [%1], %2; selp.u32 %0, 1, 0, p; }" : "=r"(ok) : "r"(bar), "r"(par) : "memory");
    return ok;
}
__device__ __noinline__ void mbar_wait_slow(uint32_t bar, uint32_t par) {
    long long t0 = clock64();
    while (!mbar_try(bar, par)) { if (clock64() - t0 > SPIN_LIMIT) __trap(); }
}
DEVINL void mbar_wait(uint32_t bar, uint32_t par) {
    uint32_t n = 0;
    while (!mbar_try(bar, par)) { if (++n > 200000000u) __trap(); }
}
DEVINL uint32_t mapa(uint32_t a, uint32_t r) { uint32_t o; asm volatile("mapa.shared::cluster.u32 %0, %1, %2;" : "=r"(o) : "r"(a), "r"(r)); return o; }
DEVINL void fence_async() { asm volatile("fence.proxy.async.shared::cta;" ::: "memory"); }
DEVINL void bar_sync(int id, int n) { asm volatile("bar.sync %0, %1;" ::"r"(id), "r"(n) : "memory"); }
DEVINL void cluster_sync() { asm volatile("barrier.cluster.arrive.aligned; barrier.cluster.wait.aligned;" ::: "memory"); }
DEVINL void tma_load(uint32_t dst, const CUtensorMap* tm, int c0, int c1, uint32_t bar) {
    asm volatile("cp.async.bulk.tensor.2d.shared::cluster.global.mbarrier::complete_tx::bytes [%0], [%1, {%3, %4}], [%2];"
                 ::"r"(dst), "l"(tm), "r"(bar), "r"(c0), "r"(c1) : "memory");
}
DEVINL void tma_prefetch(const CUtensorMap* tm, int c0, int c1) {
    asm volatile("cp.async.bulk.prefetch.tensor.2d.L2.global [%0, {%1, %2}];" ::"l"(tm), "r"(c0), "r"(c1) : "memory");
}
DEVINL void tma_store(const CUtensorMap* tm, uint32_t src, int c0, int c1) {
    asm volatile("cp.async.bulk.tensor.2d.global.shared::cta.bulk_group [%0, {%2, %3}], [%1];" ::"l"(tm), "r"(src), "r"(c0), "r"(c1) : "memory");
}
DEVINL void bulk_commit() { asm volatile("cp.async.bulk.commit_group;" ::: "memory"); }
DEVINL void bulk_wait_read() { asm volatile("cp.async.bulk.wait_group.read 0;" ::: "memory"); }
DEVINL void bulk_wait_all() { asm volatile("cp.async.bulk.wait_group 0;" ::: "memory"); }
DEVINL void bulk_s2s(uint32_t cdst, uint32_t src, uint32_t bytes, uint32_t cbar) {
    asm volatile("cp.async.bulk.shared::cluster.shared::cta.mbarrier::complete_tx::bytes [%0], [%1], %2, [%3];" ::"r"(cdst), "r"(src), "r"(bytes), "r"(cbar) : "memory");
}
DEVINL void st_async16(uint32_t cdst, uint4 v, uint32_t cbar) {
    asm volatile("st.async.shared::cluster.mbarrier::complete_tx::bytes.v4.b32 [%0], {%1,%2,%3,%4}, [%5];" ::"r"(cdst), "r"(v.x), "r"(v.y), "r"(v.z), "r"(v.w), "r"(cbar) : "memory");
}
DEVINL uint64_t mkdesc(uint32_t addr, uint32_t lbo, uint32_t sbo, uint32_t swz) {
    return (uint64_t)((addr & 0x3FFFF) >> 4) | ((uint64_t)(lbo >> 4) << 16) | ((uint64_t)(sbo >> 4) << 32) | ((uint64_t)swz << 62);
}
constexpr uint32_t SB0 = 1024;
__host__ __device__ constexpr uint64_t cdesc(uint32_t off, uint32_t lbo, uint32_t sbo, uint32_t swz) {
    return (uint64_t)(((SB0 + off) & 0x3FFFF) >> 4) | ((uint64_t)(lbo >> 4) << 16) | ((uint64_t)(sbo >> 4) << 32) | ((uint64_t)swz << 62);
}
DEVINL float rcp(float x) { float y; asm("rcp.approx.ftz.f32 %0, %1;" : "=f"(y) : "f"(x)); return y; }
DEVINL float ex2(float x) { float y; asm("ex2.approx.ftz.f32 %0, %1;" : "=f"(y) : "f"(x)); return y; }
DEVINL void spin_clk(int d) { uint32_t t0, t1; asm volatile("mov.u32 %0, %%clock;" : "=r"(t0)); do { asm volatile("mov.u32 %0, %%clock;" : "=r"(t1)); } while ((int)(t1 - t0) < d); }
#define PROBE_GAP 150
#define OPAQUE(x) asm volatile("" : "+r"(x))
DEVINL void wg_fence() { asm volatile("wgmma.fence.sync.aligned;" ::: "memory"); }
DEVINL void wg_commit() { asm volatile("wgmma.commit_group.sync.aligned;" ::: "memory"); }
template <int N> DEVINL void wg_wait() { asm volatile("wgmma.wait_group.sync.aligned %0;" ::"n"(N) : "memory"); }
DEVINL uint32_t pack_bf16(float lo, float hi) { uint32_t r; asm("cvt.rn.bf16x2.f32 %0, %1, %2;" : "=r"(r) : "f"(hi), "f"(lo)); return r; }
DEVINL void ldsm4(uint32_t* r, uint32_t a) { asm volatile("ldmatrix.sync.aligned.m8n8.x4.shared.b16 {%0,%1,%2,%3}, [%4];" : "=r"(r[0]), "=r"(r[1]), "=r"(r[2]), "=r"(r[3]) : "r"(a) : "memory"); }
DEVINL void ldsm4t(uint32_t* r, uint32_t a) { asm volatile("ldmatrix.sync.aligned.m8n8.x4.trans.shared.b16 {%0,%1,%2,%3}, [%4];" : "=r"(r[0]), "=r"(r[1]), "=r"(r[2]), "=r"(r[3]) : "r"(a) : "memory"); }
DEVINL void ldsm4t_if(uint32_t* r, uint32_t a, int c) { asm volatile("{ .reg .pred p; setp.ne.s32 p, %5, 0; @p ldmatrix.sync.aligned.m8n8.x4.trans.shared.b16 {%0,%1,%2,%3}, [%4]; }" : "+r"(r[0]), "+r"(r[1]), "+r"(r[2]), "+r"(r[3]) : "r"(a), "r"(c) : "memory"); }
DEVINL void stsm4(uint32_t a, uint32_t r0, uint32_t r1, uint32_t r2, uint32_t r3) { asm volatile("stmatrix.sync.aligned.m8n8.x4.shared.b16 [%0], {%1,%2,%3,%4};" ::"r"(a), "r"(r0), "r"(r1), "r"(r2), "r"(r3) : "memory"); }
DEVINL void stsm4t(uint32_t a, uint32_t r0, uint32_t r1, uint32_t r2, uint32_t r3) { asm volatile("stmatrix.sync.aligned.m8n8.x4.trans.shared.b16 [%0], {%1,%2,%3,%4};" ::"r"(a), "r"(r0), "r"(r1), "r"(r2), "r"(r3) : "memory"); }
DEVINL void sts32(uint32_t a, uint32_t v) { asm volatile("st.shared.b32 [%0], %1;" ::"r"(a), "r"(v) : "memory"); }
DEVINL void sts128(uint32_t a, uint4 v) { asm volatile("st.shared.v4.b32 [%0], {%1,%2,%3,%4};" ::"r"(a), "r"(v.x), "r"(v.y), "r"(v.z), "r"(v.w) : "memory"); }
DEVINL uint4 lds128(uint32_t a) { uint4 v; asm volatile("ld.shared.v4.b32 {%0,%1,%2,%3}, [%4];" : "=r"(v.x), "=r"(v.y), "=r"(v.z), "=r"(v.w) : "r"(a) : "memory"); return v; }
DEVINL uint4 ld_strong16(const void* p) { uint4 v; asm volatile("ld.relaxed.gpu.global.v4.u32 {%0,%1,%2,%3}, [%4];" : "=r"(v.x), "=r"(v.y), "=r"(v.z), "=r"(v.w) : "l"(p) : "memory"); return v; }
DEVINL void st_strong8(void* p, uint32_t a, uint32_t b) { asm volatile("st.relaxed.gpu.global.v2.u32 [%0], {%1,%2};" ::"l"(p), "r"(a), "r"(b) : "memory"); }
DEVINL void st_strong4(void* p, uint32_t a) { asm volatile("st.relaxed.gpu.global.u32 [%0], %1;" ::"l"(p), "r"(a) : "memory"); }
DEVINL void st_strong16(void* p, uint4 v) { asm volatile("st.relaxed.gpu.global.v4.u32 [%0], {%1,%2,%3,%4};" ::"l"(p), "r"(v.x), "r"(v.y), "r"(v.z), "r"(v.w) : "memory"); }
DEVINL uint32_t pack_nz(float lo, float hi) { uint32_t r = pack_bf16(lo, hi); return r == 0u ? 0x8000u : r; }
DEVINL uint32_t min4(uint4 v, uint32_t m) { return __vimin3_u32(__vimin3_u32(v.x, v.y, m), v.z, v.w); }
DEVINL void mma16816(float* d, uint32_t a0, uint32_t a1, uint32_t a2, uint32_t a3, uint32_t b0, uint32_t b1) {
    asm volatile("mma.sync.aligned.m16n8k16.row.col.f32.bf16.bf16.f32 {%0,%1,%2,%3}, {%4,%5,%6,%7}, {%8,%9}, {%0,%1,%2,%3};"
                 : "+f"(d[0]), "+f"(d[1]), "+f"(d[2]), "+f"(d[3]) : "r"(a0), "r"(a1), "r"(a2), "r"(a3), "r"(b0), "r"(b1));
}
DEVINL void mma1688(float* d, uint32_t a0, uint32_t a1, uint32_t b0) {
    asm volatile("mma.sync.aligned.m16n8k8.row.col.f32.bf16.bf16.f32 {%0,%1,%2,%3}, {%4,%5}, {%6}, {%0,%1,%2,%3};"
                 : "+f"(d[0]), "+f"(d[1]), "+f"(d[2]), "+f"(d[3]) : "r"(a0), "r"(a1), "r"(b0));
}
template <int TA, int TB> DEVINL void wg_ss8(float* d, uint64_t da, uint64_t db, int sc) {
    asm volatile("{ .reg .pred p; setp.ne.b32 p, %6, 0; wgmma.mma_async.sync.aligned.m64n8k16.f32.bf16.bf16 {%0,%1,%2,%3}, %4, %5, p, 1, 1, %7, %8; }"
                 : "+f"(d[0]), "+f"(d[1]), "+f"(d[2]), "+f"(d[3]) : "l"(da), "l"(db), "r"(sc), "n"(TA), "n"(TB));
}
template <int TB> DEVINL void wg_rs8(float* d, const uint32_t* a, uint64_t db, int sc) {
    asm volatile("{ .reg .pred p; setp.ne.b32 p, %9, 0; wgmma.mma_async.sync.aligned.m64n8k16.f32.bf16.bf16 {%0,%1,%2,%3}, {%4,%5,%6,%7}, %8, p, 1, 1, %10; }"
                 : "+f"(d[0]), "+f"(d[1]), "+f"(d[2]), "+f"(d[3]) : "r"(a[0]), "r"(a[1]), "r"(a[2]), "r"(a[3]), "l"(db), "r"(sc), "n"(TB));
}
#define ACC16(d) "+f"(d[0]), "+f"(d[1]), "+f"(d[2]), "+f"(d[3]), "+f"(d[4]), "+f"(d[5]), "+f"(d[6]), "+f"(d[7]), "+f"(d[8]), "+f"(d[9]), "+f"(d[10]), "+f"(d[11]), "+f"(d[12]), "+f"(d[13]), "+f"(d[14]), "+f"(d[15])
template <int TA> DEVINL void wg_ss32(float* d, uint64_t da, uint64_t db, int sc) {
    asm volatile("{ .reg .pred p; setp.ne.b32 p, %18, 0; wgmma.mma_async.sync.aligned.m64n32k16.f32.bf16.bf16 {%0,%1,%2,%3,%4,%5,%6,%7,%8,%9,%10,%11,%12,%13,%14,%15}, %16, %17, p, 1, 1, %19, 0; }"
                 : ACC16(d) : "l"(da), "l"(db), "r"(sc), "n"(TA));
}
DEVINL void wg_rs32(float* d, const uint32_t* a, uint64_t db, int sc) {
    asm volatile("{ .reg .pred p; setp.ne.b32 p, %21, 0; wgmma.mma_async.sync.aligned.m64n32k16.f32.bf16.bf16 {%0,%1,%2,%3,%4,%5,%6,%7,%8,%9,%10,%11,%12,%13,%14,%15}, {%16,%17,%18,%19}, %20, p, 1, 1, 0; }"
                 : ACC16(d) : "r"(a[0]), "r"(a[1]), "r"(a[2]), "r"(a[3]), "l"(db), "r"(sc));
}
DEVINL void wg_ss40(float* d, uint64_t da, uint64_t db, int sc) {
    asm volatile("{ .reg .pred p; setp.ne.b32 p, %22, 0; wgmma.mma_async.sync.aligned.m64n40k16.f32.bf16.bf16 {%0,%1,%2,%3,%4,%5,%6,%7,%8,%9,%10,%11,%12,%13,%14,%15,%16,%17,%18,%19}, %20, %21, p, 1, 1, 1, 1; }"
                 : ACC16(d), "+f"(d[16]), "+f"(d[17]), "+f"(d[18]), "+f"(d[19]) : "l"(da), "l"(db), "r"(sc));
}
#define A8(d, o) "+f"(d[o]), "+f"(d[o + 1]), "+f"(d[o + 2]), "+f"(d[o + 3]), "+f"(d[o + 4]), "+f"(d[o + 5]), "+f"(d[o + 6]), "+f"(d[o + 7])
#define A32(d, o) A8(d, o), A8(d, o + 8), A8(d, o + 16), A8(d, o + 24)
DEVINL void wg_ss256(float* d, uint64_t da, uint64_t db, int sc) {
    asm volatile(
        "{ .reg .pred p; setp.ne.b32 p, %130, 0;\n"
        "wgmma.mma_async.sync.aligned.m64n256k16.f32.bf16.bf16 {"
        "%0,%1,%2,%3,%4,%5,%6,%7,%8,%9,%10,%11,%12,%13,%14,%15,%16,%17,%18,%19,%20,%21,%22,%23,%24,%25,%26,%27,%28,%29,%30,%31,"
        "%32,%33,%34,%35,%36,%37,%38,%39,%40,%41,%42,%43,%44,%45,%46,%47,%48,%49,%50,%51,%52,%53,%54,%55,%56,%57,%58,%59,%60,%61,%62,%63,"
        "%64,%65,%66,%67,%68,%69,%70,%71,%72,%73,%74,%75,%76,%77,%78,%79,%80,%81,%82,%83,%84,%85,%86,%87,%88,%89,%90,%91,%92,%93,%94,%95,"
        "%96,%97,%98,%99,%100,%101,%102,%103,%104,%105,%106,%107,%108,%109,%110,%111,%112,%113,%114,%115,%116,%117,%118,%119,%120,%121,%122,%123,%124,%125,%126,%127"
        "}, %128, %129, p, 1, 1, 0, 1; }"
        : A32(d, 0), A32(d, 32), A32(d, 64), A32(d, 96) : "l"(da), "l"(db), "r"(sc));
}

DEVINL float gate_row(const uint4 (&xv)[4], const uint4 (&gv)[4]) {
    float acc = 0.f;
#pragma unroll
    for (int i = 0; i < 4; i++) {
        const uint32_t xa[4] = {xv[i].x, xv[i].y, xv[i].z, xv[i].w}, ga[4] = {gv[i].x, gv[i].y, gv[i].z, gv[i].w};
#pragma unroll
        for (int e = 0; e < 4; e++) {
            acc = fmaf(__uint_as_float(xa[e] << 16), __uint_as_float(ga[e] << 16), acc);
            acc = fmaf(__uint_as_float(xa[e] & 0xffff0000u), __uint_as_float(ga[e] & 0xffff0000u), acc);
        }
    }
#pragma unroll
    for (int o = 16; o > 0; o >>= 1) acc += __shfl_xor_sync(0xffffffffu, acc, o);
    return 1.0f / (1.0f + __expf(-acc));
}
DEVINL uint4 ldg_nc(const void* p) { uint4 v; asm volatile("ld.global.nc.v4.u32 {%0,%1,%2,%3}, [%4];" : "=r"(v.x), "=r"(v.y), "=r"(v.z), "=r"(v.w) : "l"(p) : "memory"); return v; }
DEVINL uint32_t ld_strong4(const void* p) { uint32_t v; asm volatile("ld.relaxed.gpu.global.u32 %0, [%1];" : "=r"(v) : "l"(p) : "memory"); return v; }
DEVINL void wait_count(const uint32_t* p, uint32_t want) {
    uint32_t v, n = 0;
    while (true) {
        asm volatile("ld.acquire.gpu.global.u32 %0, [%1];" : "=r"(v) : "l"(p) : "memory");
        if (v >= want) break;
        __nanosleep(200);
        if (++n > 10000000u) __trap();
    }
}

constexpr int KR = 44;
constexpr int KS = 64 - KR;
constexpr int R_W = 0;
constexpr int R_WO = KS * 4096;
constexpr int R_QX = R_WO + 65536;
constexpr int R_RING = R_WO + 98304;
constexpr int R_K = R_RING + 24576;
constexpr int R_V = R_K + 10240;
constexpr int R_QM = R_V + 10240;
constexpr int R_O = R_QM + 2048;
constexpr int R_BAR = R_O + 2048;
constexpr int R_G = R_BAR + 256 + 512 + 256 + 128;
constexpr int R_Z = R_G + 256;
constexpr int R_SMEM = R_Z + 1024;
enum { B_FULL = 0, B_EMPTY = 5, B_MEM = 8, B_HOP1 = 12, B_XT, B_TFREE, B_O, B_AFREE0, B_AFREE1, B_PRO0, B_PRO1, B_XRECV, B_P, B_XDONE, B_OST0, B_OST1, B_HOPV };
#define D2_BASE 900
#define D2_STEP 200
#define PD2 6
#define CPB 8192
#define DDUP 0
#define WGAP 0
#define PVD 400
#define ELD 700
#define QD 3
#define DQ 1700
#define D3 0

DEVINL uint32_t clk32() { uint32_t c_; asm volatile("mov.u32 %0, %%clock;" : "=r"(c_)); return c_; }
DEVINL void spin_until(uint32_t t) { while ((uint32_t)(t - clk32() - 1u) < 100000u) {} }
#define PROF(i)
#define PROF2(i)
#define PROF3(i, val)
DEVINL void e_arrive(uint32_t bar) { asm volatile("{ .reg .pred p; elect.sync _|p, 0xffffffff; @p mbarrier.arrive.shared::cta.b64 _, [%0]; }" ::"r"(bar) : "memory"); }
DEVINL void e_arrive_remote(uint32_t cbar) { asm volatile("{ .reg .pred p; elect.sync _|p, 0xffffffff; @p mbarrier.arrive.relaxed.cluster.shared::cluster.b64 _, [%0]; }" ::"r"(cbar) : "memory"); }
DEVINL void e_count(uint32_t* p) { asm volatile("{ .reg .pred p; elect.sync _|p, 0xffffffff; @p red.relaxed.gpu.global.add.u32 [%0], 1; }" ::"l"(p) : "memory"); }
DEVINL void e_expect(uint32_t bar, uint32_t bytes) { asm volatile("{ .reg .pred p; elect.sync _|p, 0xffffffff; @p mbarrier.arrive.expect_tx.shared::cta.b64 _, [%0], %1; }" ::"r"(bar), "r"(bytes) : "memory"); }
DEVINL void e_tma_load(uint32_t dst, const CUtensorMap* tm, int c0, int c1, uint32_t bar) {
    asm volatile("{ .reg .pred p; elect.sync _|p, 0xffffffff; @p cp.async.bulk.tensor.2d.shared::cluster.global.mbarrier::complete_tx::bytes [%0], [%1, {%3, %4}], [%2]; }"
                 ::"r"(dst), "l"(tm), "r"(bar), "r"(c0), "r"(c1) : "memory");
}
DEVINL void e_tma_store(const CUtensorMap* tm, uint32_t src, int c0, int c1) {
    asm volatile("{ .reg .pred p; elect.sync _|p, 0xffffffff; @p cp.async.bulk.tensor.2d.global.shared::cta.bulk_group [%0, {%2, %3}], [%1]; }" ::"l"(tm), "r"(src), "r"(c0), "r"(c1) : "memory");
}
DEVINL void e_bulk_s2g(void* dst, uint32_t src, uint32_t bytes) {
    asm volatile("{ .reg .pred p; elect.sync _|p, 0xffffffff; @p cp.async.bulk.global.shared::cta.bulk_group [%0], [%1], %2; }" ::"l"(dst), "r"(src), "r"(bytes) : "memory");
}
DEVINL void e_bulk_s2s(uint32_t cdst, uint32_t src, uint32_t bytes, uint32_t cbar) {
    asm volatile("{ .reg .pred p; elect.sync _|p, 0xffffffff; @p cp.async.bulk.shared::cluster.shared::cta.mbarrier::complete_tx::bytes [%0], [%1], %2, [%3]; }" ::"r"(cdst), "r"(src), "r"(bytes), "r"(cbar) : "memory");
}

#define SLOT 0
#define PH3 0
#define PHQ 0
DEVINL void wait_slot(uint32_t phase) {
    if (SLOT) {
        uint32_t c; asm volatile("mov.u32 %0, %%globaltimer_lo;" : "=r"(c));
        const uint32_t tgt = c + (SLOT ? SLOT : 1) - ((c - phase) % (SLOT ? SLOT : 1));
        do { asm volatile("mov.u32 %0, %%globaltimer_lo;" : "=r"(c)); } while ((uint32_t)(tgt - c - 1u) < 100000u);
    }
}
template <int N> DEVINL uint32_t poll_set(uint4 (&v)[N], const uint32_t* rp, int stride, uint32_t phase, uint32_t wbar = 0, uint32_t wpar = 0) {
    wait_slot(phase);
#pragma unroll
    for (int i = 0; i < N; i++) v[i] = ld_strong16(rp + i * stride);
    if (wbar) mbar_wait(wbar, wpar);
    uint32_t n = 0;
    while (true) {
        uint32_t m = 0xffffffffu;
#pragma unroll
        for (int i = 0; i < N; i++) m = min4(v[i], m);
        if (__all_sync(0xffffffffu, m != 0u)) return n;
        wait_slot(phase);
#pragma unroll
        for (int i = 0; i < N; i++)
            asm volatile("{ .reg .pred p; setp.eq.u32 p, %5, 0; @p ld.relaxed.gpu.global.v4.u32 {%0,%1,%2,%3}, [%4]; }"
                         : "+r"(v[i].x), "+r"(v[i].y), "+r"(v[i].z), "+r"(v[i].w) : "l"(rp + i * stride), "r"(min4(v[i], 0xffffffffu)) : "memory");
        if (++n > 20000000u) __trap();
    }
}

struct RMaps { CUtensorMap x, w[3], wo, o; };
#define KC(c) ((c) * 64)

#define XORD 3
__host__ __device__ constexpr int xo(int i) {
    return XORD == 0 ? i : XORD == 1 ? (i + 14) % 16 : XORD == 2 ? (i + 11) % 16
         : XORD == 3 ? (i < 10 ? ((i & 1) ? i / 2 : 11 + i / 2) : i - 5) : (i < 6 ? i : ((i & 1) ? 6 + (i - 6) / 2 : 11 + (i - 6) / 2));
}
#define XC(i) (xo(i) * 64)
DEVINL void x_load_pair(uint32_t dst, const CUtensorMap* tmx, int h, int p, int seg, uint32_t fbar) {
    e_expect(fbar, 8192);
    e_tma_load(dst, tmx, XC(2 * p), seg * SEG, fbar);
    e_tma_load(dst + 4096, tmx, XC(2 * p + 1), seg * SEG, fbar);
}
__host__ __device__ constexpr int wo_tile(int role, int i) {
    return role == 0 ? (i < 2 ? 8 + i : 12 + i) : (i < 4 ? (i >> 1) * 4 : 10) + (role - 1) * 2 + (i & 1);
}

template <int NT> DEVINL void wo_phase(uint32_t sb, int tb, uint32_t* pp, uint32_t obar, uint32_t opar) {
    const int lane = tb & 31, krow = (lane & 7) + ((lane >> 4) << 3), chunk = ((tb >> 5) & 3) * 2 + ((lane >> 3) & 1);
    uint32_t wa = sb + R_WO + (tb >> 7) * 16384 + krow * 128 + ((chunk ^ (krow & 7)) << 4);
    uint32_t af[4][4], of[4][4];
#pragma unroll
    for (int g = 0; g < 4; g++) ldsm4t(af[g], wa + g * 2048);
    mbar_wait(obar, opar);
#pragma unroll
    for (int g = 0; g < 4; g++) ldsm4t(of[g], sb + R_O + g * 512 + lane * 16);
#pragma unroll 1
    for (int i = 0; i < NT; i++) {
        float w0[4] = {0.f, 0.f, 0.f, 0.f}, w1[4] = {0.f, 0.f, 0.f, 0.f};
        const int more = NT - 1 - i, yes = NT - i;
        mma16816(w0, af[0][0], af[0][1], af[0][2], af[0][3], of[0][0], of[0][1]);
        ldsm4t_if(af[0], wa + 4 * 2048, yes);
        mma16816(w1, af[1][0], af[1][1], af[1][2], af[1][3], of[0][2], of[0][3]);
        ldsm4t_if(af[1], wa + 5 * 2048, yes);
        mma16816(w0, af[2][0], af[2][1], af[2][2], af[2][3], of[1][0], of[1][1]);
        ldsm4t_if(af[2], wa + 6 * 2048, yes);
        mma16816(w1, af[3][0], af[3][1], af[3][2], af[3][3], of[1][2], of[1][3]);
        ldsm4t_if(af[3], wa + 7 * 2048, yes);
        wa += 32768;
        mma16816(w0, af[0][0], af[0][1], af[0][2], af[0][3], of[2][0], of[2][1]);
        ldsm4t_if(af[0], wa, more);
        mma16816(w1, af[1][0], af[1][1], af[1][2], af[1][3], of[2][2], of[2][3]);
        ldsm4t_if(af[1], wa + 2048, more);
        mma16816(w0, af[2][0], af[2][1], af[2][2], af[2][3], of[3][0], of[3][1]);
        ldsm4t_if(af[2], wa + 2 * 2048, more);
        mma16816(w1, af[3][0], af[3][1], af[3][2], af[3][3], of[3][2], of[3][3]);
        ldsm4t_if(af[3], wa + 3 * 2048, more);
        st_strong4(pp, pack_nz(w0[0] + w1[0], w0[1] + w1[1]));
        st_strong4(pp + 1024, pack_nz(w0[2] + w1[2], w0[3] + w1[3]));
        pp += (NT == 3 && i == 0) ? 4 * 8192 : 6 * 8192;
    }
}

template <uint32_t role> DEVINL void r_big(const RMaps& tm, const int wid) {
    extern __shared__ __align__(1024) unsigned char smem_raw[];
    const uint32_t sb = smem_u32(smem_raw);
    const uint32_t bar = sb + R_BAR;
    const int tid = threadIdx.x;
    int h; asm("mov.u32 %0, %%clusterid.x;" : "=r"(h));
        uint32_t a[KR][4];
        mbar_wait(bar + 8 * B_PRO0, 0);
        PT(0);
        {
            const int lane = tid & 31;
            const int krow = (lane & 7) + ((lane >> 4) << 3);
            const int chunk = (wid & 3) * 2 + ((lane >> 3) & 1);
            const uint32_t la = sb + (wid >> 2) * 8192 + krow * 128 + ((chunk ^ (krow & 7)) << 4);
#pragma unroll
            for (int k = 0; k < KR; k++) ldsm4t(a[k], la + (k >> 2) * 16384 + (k & 3) * 2048);
        }
        bar_sync(1, 256);
        {
            fence_async();
            const CUtensorMap* tw = &tm.w[role];
            e_expect(bar + 8 * B_PRO1, (wid < 5 ? 16384 : 0) + (wid < (role == 0 ? 4 : 6) ? 16384 : 0));
            if (wid < 5) {
                e_tma_load(sb + R_W + wid * 8192, tw, h * DH, KC(KR / 4 + wid), bar + 8 * B_PRO1);
                e_tma_load(sb + R_W + KS * 2048 + wid * 8192, tw, h * DH + 64, KC(KR / 4 + wid), bar + 8 * B_PRO1);
            }
            if (wid < (role == 0 ? 4 : 6)) e_tma_load(sb + R_WO + wid * 16384, &tm.wo, wo_tile(role, wid) * 64, h * DH, bar + 8 * B_PRO1);
        }
        constexpr uint32_t e0 = role == 0 ? R_QX + 16384 : R_K + 2048, e1 = role == 0 ? R_QX + 24576 : R_V + 2048;
        if (wid == 6) x_load_pair(sb + e0, &tm.x, h, 3, 0, bar + 8 * (B_FULL + 3));
        if (wid == 7) x_load_pair(sb + e1, &tm.x, h, 4, 0, bar + 8 * (B_FULL + 4));
        PT(1);
        mbar_wait(bar + 8 * B_PRO1, 0);
        PT(2);

        constexpr uint64_t dW0 = cdesc(R_W, 1024, 1024, 1);
        constexpr uint64_t dM = cdesc(R_RING, 128, 128, 0);
        constexpr uint64_t dX = cdesc(R_RING, 16, 1024, 1);
        constexpr uint64_t dX0 = cdesc(0, 16, 1024, 1);
        int tb = tid;
        int wq = wid;

        for (int seg = 0; seg < NSEG; seg++) {
            {
            const int s = seg - 1; (void)s;
            float d[16];
            OPAQUE(wq);
            const uint64_t dW = dW0 + (uint64_t)((wq >> 2) * (KS * 128));
#pragma unroll
            for (int p = 0; p < 8; p++) {
                const int slot = p % 5;
                mbar_wait(bar + 8 * (B_FULL + slot), slot < 3 ? (uint32_t)(p / 5) : (uint32_t)(seg & 1));
                PROF2(p);
                const uint64_t db = slot < 3 ? dX + (uint64_t)(slot * 512) : dX0 + (uint64_t)((slot == 3 ? e0 : e1) >> 4);
                wg_fence();
#pragma unroll
                for (int kk = 0; kk < 8; kk++) {
                    const int k = XORD >= 3 ? (kk & 1) * 4 + (kk >> 1) : kk;
                    const int ks = xo(2 * p + (k >> 2)) * 4 + (k & 3);
                    if (ks >= KR) wg_ss32<1>(d, dW + (uint64_t)((ks - KR) * 128), db + (uint64_t)((k >> 2) * 256 + (k & 3) * 2), p + k);
                    else wg_rs32(d, a[ks < KR ? ks : 0], db + (uint64_t)((k >> 2) * 256 + (k & 3) * 2), p + k);
                }
                wg_commit();
                if (p >= 1) {
                    wg_wait<1>();
                    if (p <= 3) {
                        if ((wq & 3) == p) e_arrive(bar + 8 * (B_EMPTY + p - 1));
                        if (wq == p + (p & 1) * 4) {
                            mbar_wait(bar + 8 * (B_EMPTY + p - 1), seg & 1);
                            x_load_pair(sb + R_RING + (p - 1) * 8192, &tm.x, h, p + 4, seg, bar + 8 * (B_FULL + p - 1));
                        }
                    }
                    if (p == 5 && role != 0 && (wq & 3) < 3) e_arrive_remote(mapa(bar + 8 * B_TFREE, wq & 3));
                    if (p == 6 && (wq & 3) == 1) e_arrive(bar + 8 * B_AFREE0);
                    if (p == 7 && (wq & 3) == 2) e_arrive(bar + 8 * B_AFREE1);
                }
            }
            mbar_wait(bar + 8 * B_TFREE, seg & 1);
            asm volatile("wgmma.wait_group.sync.aligned 0;" : ACC16(d)::"memory");
            PROF2(16);
            const uint32_t tilex = sb + (role == 0 ? R_QX + 2048 : (role == 1 ? R_K + 2048 : R_V + 2048));
            {
                OPAQUE(tb);
                const uint32_t gs = role == 0 ? 4096 : 2048;
                const uint32_t sa = tilex + ((tb >> 4) & 1) * gs + (tb >> 5) * 256 + (tb & 15) * 16;
                stsm4(sa, pack_bf16(d[0], d[1]), pack_bf16(d[2], d[3]), pack_bf16(d[4], d[5]), pack_bf16(d[6], d[7]));
                stsm4(sa + 2 * gs, pack_bf16(d[8], d[9]), pack_bf16(d[10], d[11]), pack_bf16(d[12], d[13]), pack_bf16(d[14], d[15]));
            }
            __syncwarp();
            e_arrive(bar + 8 * B_XDONE);
            if (role != 0 && (wq & 3) == 0) {
                mbar_wait(bar + 8 * B_XDONE, seg & 1);
                fence_async();
                uint32_t pr = role + 1 + (wq >> 2); pr = pr >= 3 ? pr - 3 : pr;
                e_bulk_s2s(mapa(tilex, pr), tilex, CPB, mapa(bar + 8 * B_XT, pr));
            }
            }
            {
                const int s = seg;
                OPAQUE(wq);
                const uint64_t dW = dW0 + (uint64_t)((wq >> 2) * (KS * 128));
                float y[4] = {0.f, 0.f, 0.f, 0.f};
                {
                    OPAQUE(tb);
                    const uint32_t ma = sb + R_RING + (tb & 31) * 16;
                    float z[4] = {0.f, 0.f, 0.f, 0.f}, u[4] = {0.f, 0.f, 0.f, 0.f};
                    uint32_t b[QD][4];
                    const int yes = s + 1;
                    mbar_wait(bar + 8 * B_MEM, s & 1);
                    PROF((wq >> 2) * 4 + 0);
                    if (s == 0) PT(3);
                    if (s == 1) PT(4);
#pragma unroll
                    for (int g = 0; g < QD; g++) ldsm4t(b[g], ma + g * 512);
#pragma unroll
                    for (int g = 0; g < KR / 2; g++) {
                        float* c0 = (g % 3 == 0) ? y : (g % 3 == 1) ? u : z;
                        float* c1 = (g % 3 == 0) ? z : (g % 3 == 1) ? y : u;
                        mma16816(c0, a[2 * g][0], a[2 * g][1], a[2 * g][2], a[2 * g][3], b[g % QD][0], b[g % QD][1]);
                        mma16816(c1, a[2 * g + 1][0], a[2 * g + 1][1], a[2 * g + 1][2], a[2 * g + 1][3], b[g % QD][2], b[g % QD][3]);
                        if (g + QD < KR / 2) {
                            if ((g + QD) % 8 == 0) mbar_wait(bar + 8 * (B_MEM + (g + QD) / 8), s & 1);
                            ldsm4t_if(b[g % QD], ma + (g + QD) * 512, yes);
                        }
                    }
                    y[0] += z[0] + u[0]; y[1] += z[1] + u[1]; y[2] += z[2] + u[2]; y[3] += z[3] + u[3];
                }
                PROF2(8);
                mbar_wait(bar + 8 * (B_MEM + 3), s & 1);
                wg_fence();
#pragma unroll
                for (int k = KR; k < 64; k++) wg_ss8<1, 1>(y, dW + (uint64_t)((k - KR) * 128), dM + (uint64_t)(k * 16), 1);
                wg_commit();
                asm volatile("wgmma.wait_group.sync.aligned 0;" : "+f"(y[0]), "+f"(y[1]), "+f"(y[2]), "+f"(y[3])::"memory");
                OPAQUE(tb);
                {
                    const uint32_t wo_ = (tb >> 5) * 256;
                    const uint32_t tile = sb + (role == 0 ? R_QX : (role == 1 ? R_K : R_V)) + wo_;
                    const uint32_t u0 = pack_bf16(y[0], y[1]), u1 = pack_bf16(y[2], y[3]);
                    sts32(tile + (tb & 31) * 4, u0);
                    sts32(tile + (tb & 31) * 4 + 128, u1);
                    __syncwarp();
                    uint4 v = lds128(tile + (tb & 15) * 16);
                    uint32_t peer = role + 1 + ((tb >> 4) & 1);
                    peer = peer >= 3 ? peer - 3 : peer;
                    const uint32_t rt = sb + (role == 0 ? R_QM : (role == 1 ? R_K : R_V)) + wo_ + (tb & 15) * 16;
                    st_async16(mapa(rt, peer), v, mapa(bar + 8 * (role == 2 ? B_HOPV : B_HOP1), peer));
                    if (role == 0) {
                        sts128(tile + 4096 + ((tb >> 4) & 1) * 4096 + (tb & 15) * 16, v);
                        sts32(tile + 12288 + (tb & 31) * 4, u0);
                        sts32(tile + 12288 + (tb & 31) * 4 + 128, u1);
                        __syncwarp();
                    }
                    e_arrive(bar + 8 * (role == 2 ? B_HOPV : B_HOP1));
                }
                PROF((wq >> 2) * 4 + 1);
                if (s < NSEG - 1) {
                    bar_sync(1, 256);
                    if (wq < 3) { fence_async(); x_load_pair(sb + R_RING + wq * 8192, &tm.x, h, wq, s + 1, bar + 8 * (B_FULL + wq)); }
                    else if (role == 0 && wq < 5) x_load_pair(sb + (wq == 3 ? e0 : e1), &tm.x, h, wq, s + 1, bar + 8 * (B_FULL + wq));
                    OPAQUE(tb);
                }
                uint32_t* pp = g_part[s & 3] + (h * 32 + (wo_tile(role, 0) + (tb >> 7)) * 8192 + ((tb >> 5) & 3) * 2048 + (tb & 31));
                asm volatile("" : "+l"(pp));
                if (s == NSEG - 1) break;
                wo_phase<role == 0 ? 2 : 3>(sb, tb, pp, bar + 8 * B_O, s & 1);
                if (wq == 0) PROF(10);
            }
        }
}

#define CLR 0
#define CLEAR(st) do { if (role != 0) { \
                const int w_ = wid & 3; \
                uint32_t* zp = g_part[(st) & 3] + ((rg0 + (w_ >> 1) * 64) * 1024 + (w_ & 1) * 512); \
                e_bulk_s2g(zp, sb + R_Z, 1024); \
                e_bulk_s2g(zp + 256, sb + R_Z, 1024); \
                e_bulk_s2g(&g_mem[(st) & 3][(rg0 + (w_ >> 1) * 64) * 32 + (w_ & 1) * 16], sb + R_Z, 64); \
                bulk_commit(); } } while (0)
template <uint32_t role> DEVINL void r_chain(const RMaps& tm, const bf16* __restrict__ mem0, const int wid) {
    extern __shared__ __align__(1024) unsigned char smem_raw[];
    const uint32_t sb = smem_u32(smem_raw);
    const uint32_t bar = sb + R_BAR;
    const int tid = threadIdx.x;
    int h; asm("mov.u32 %0, %%clusterid.x;" : "=r"(h));
        int t = tid & 127;
        const float sl2 = 0.08838834764831845f * 1.4426950408889634f;
        const float NEGRAW = -1000000000.0f / 0.08838834764831845f;
        const int rg0 = ((int)role - 1) * 32 + h;
        if (role != 0) {
#pragma unroll 1
            for (int r = 0; r < 4; r++) {
                uint32_t* zp = g_part[r] + ((rg0 + (t >> 6) * 64) * 1024 + (t & 63) * 4);
#pragma unroll
                for (int i = 0; i < 4; i++) st_strong16(zp + i * 256, make_uint4(0u, 0u, 0u, 0u));
                if ((t & 63) < 8) st_strong16(&g_mem[r][(rg0 + (t >> 6) * 64) * 32 + (t & 63) * 4], make_uint4(0u, 0u, 0u, 0u));
            }
            __threadfence();
        }
        if (role == 0 && (wid & 3) < 3) e_arrive_remote(mapa(bar + 8 * B_TFREE, wid & 3));
        if (t < 64) sts128(sb + R_Z + t * 16, make_uint4(0u, 0u, 0u, 0u));
        if (role == 0) sts128(sb + R_QM + t * 16, make_uint4(0u, 0u, 0u, 0u));
        {
            uint4 v[8];
#pragma unroll
            for (int r = 0; r < 8; r++) v[r] = __ldg((const uint4*)(mem0 + r * DM) + t);
            mbar_wait(bar + 8 * B_AFREE0, 0);
            mbar_wait(bar + 8 * B_AFREE1, 0);
#define TR2(f, c) \
            sts128(sb + R_RING + t * 128 + (c) * 16, make_uint4(__byte_perm(v[0].f, v[1].f, 0x5410), __byte_perm(v[2].f, v[3].f, 0x5410), __byte_perm(v[4].f, v[5].f, 0x5410), __byte_perm(v[6].f, v[7].f, 0x5410))); \
            sts128(sb + R_RING + t * 128 + (c) * 16 + 16, make_uint4(__byte_perm(v[0].f, v[1].f, 0x7632), __byte_perm(v[2].f, v[3].f, 0x7632), __byte_perm(v[4].f, v[5].f, 0x7632), __byte_perm(v[6].f, v[7].f, 0x7632)));
            TR2(x, 0) TR2(y, 2) TR2(z, 4) TR2(w, 6)
            fence_async();
            __syncwarp();
            e_arrive(bar + 8 * B_MEM + (t >> 5) * 8);
        }
        constexpr uint64_t dQ = role == 0 ? cdesc(R_QX, 128, 2048, 0) : cdesc(R_QM, 128, 0, 0);
        constexpr uint64_t dK = cdesc(R_K, 128, 2048, 0);

        for (int s = 0; s < NSEG; s++) {
            if (role == 0) {
                uint32_t n = 0, gate;
                do { gate = ld_strong4(&g_gate[s * SEG + (t >> 2)]); if (++n > 20000000u) __trap(); } while (gate == 0u);
                sts32(sb + R_G + (t >> 2) * 4, gate);
                __syncwarp();
            }
            mbar_wait(bar + 8 * B_XDONE, s & 1);
            mbar_wait(bar + 8 * B_XT, s & 1);
            if (t >= 1 && t < 3) { uint32_t pr = role + t; pr = pr >= 3 ? pr - 3 : pr; mbar_arrive_remote(mapa(bar + 8 * B_XRECV, pr)); }
            __syncwarp();
            mbar_wait(bar + 8 * B_HOP1, s & 1);
            PROF(8);
            fence_async();
            OPAQUE(t);
            if (s == NSEG - 1 && role != 0) { mbar_wait(bar + 8 * B_HOPV, s & 1); bulk_wait_all(); break; }
            float sc[20];
            wg_fence();
#pragma unroll
            for (int k = 0; k < 8; k++) wg_ss40(sc, dQ + (uint64_t)(k * 16), dK + (uint64_t)(k * 16), k);
            wg_commit();
            uint32_t t_o = clk32() + 500;
            {
                const uint32_t va = sb + R_V + 2048 + (t >> 5) * 512 + ((t >> 4) & 1) * 2048 + (t & 15) * 16;
                uint32_t v0[4], v1[4];
                ldsm4(v0, va); ldsm4(v1, va + 256);
                uint32_t vm[4];
                const bool v_here = mbar_try(bar + 8 * B_HOPV, s & 1);
                if (v_here) ldsm4(vm, sb + R_V + t * 16);
                wg_wait<0>();
                if (role == 0) {
#pragma unroll
                    for (int j = 0; j < 5; j++)
                        asm volatile("st.shared.v2.f32 [%0], {%1,%2};" ::"r"(sb + R_QX + 768 + (t >> 5) * 4096 + j * 256 + (t & 31) * 8), "f"(sc[4 * j + 2]), "f"(sc[4 * j + 3]) : "memory");
                }
                float m = fmaxf(sc[0], sc[1]);
#pragma unroll
                for (int j = 1; j < 5; j++) m = fmaxf(m, fmaxf(sc[4 * j], sc[4 * j + 1]));
                m = fmaxf(m, __shfl_xor_sync(0xffffffffu, m, 1));
                m = fmaxf(m, __shfl_xor_sync(0xffffffffu, m, 2));
                const float mb = m * sl2;
                uint32_t pk[5];
#pragma unroll
                for (int j = 0; j < 5; j++) pk[j] = pack_bf16(ex2(fmaf(sc[4 * j], sl2, -mb)), ex2(fmaf(sc[4 * j + 1], sl2, -mb)));
                float o0[4] = {0.f, 0.f, 0.f, 0.f}, o1[4] = {0.f, 0.f, 0.f, 0.f}, ls[4] = {0.f, 0.f, 0.f, 0.f};
                constexpr uint32_t ONE = 0x3F803F80u;
                mma16816(o0, v0[0], v0[1], v0[2], v0[3], pk[1], pk[2]);
                mma16816(o1, v1[0], v1[1], v1[2], v1[3], pk[1], pk[2]);
                ldsm4(v0, va + 4096); ldsm4(v1, va + 4096 + 256);
                mma16816(ls, ONE, ONE, ONE, ONE, pk[1], pk[2]);
                mma16816(ls, ONE, ONE, ONE, ONE, pk[3], pk[4]);
                mma1688(ls, ONE, ONE, pk[0]);
                mma16816(o0, v0[0], v0[1], v0[2], v0[3], pk[3], pk[4]);
                mma16816(o1, v1[0], v1[1], v1[2], v1[3], pk[3], pk[4]);
                if (!v_here) { mbar_wait(bar + 8 * B_HOPV, s & 1); ldsm4(vm, sb + R_V + t * 16); }
                mma1688(o0, vm[0], vm[1], pk[0]);
                mma1688(o1, vm[2], vm[3], pk[0]);
                const float i0 = rcp(ls[0]), i1 = rcp(ls[1]);
                const uint32_t oa = sb + R_O + (t >> 5) * 512 + (t & 31) * 4;
                sts32(oa, pack_bf16(o0[0] * i0, o0[1] * i1));
                sts32(oa + 128, pack_bf16(o0[2] * i0, o0[3] * i1));
                sts32(oa + 256, pack_bf16(o1[0] * i0, o1[1] * i1));
                sts32(oa + 384, pack_bf16(o1[2] * i0, o1[3] * i1));
                __syncwarp();
                e_arrive(bar + 8 * B_O);
                PROF(9);
                if (role == 0) {
                    OPAQUE(t);
                    const int lim = (t >> 2) - (t & 3) * 2 + 8;
                    float z[10];
#pragma unroll
                    for (int j = 0; j < 5; j++)
                        asm volatile("ld.shared.v2.f32 {%0,%1}, [%2];" : "=f"(z[2 * j]), "=f"(z[2 * j + 1]) : "r"(sb + R_QX + 768 + (t >> 5) * 4096 + j * 256 + (t & 31) * 8) : "memory");
                    float gate; asm volatile("ld.shared.f32 %0, [%1];" : "=f"(gate) : "r"(sb + R_G + (t >> 2) * 4) : "memory");
                    float m1 = fmaxf(z[0], z[1]);
#pragma unroll
                    for (int j = 1; j < 5; j++) {
                        z[2 * j] = 8 * j <= lim ? z[2 * j] : NEGRAW;
                        z[2 * j + 1] = 8 * j + 1 <= lim ? z[2 * j + 1] : NEGRAW;
                        m1 = fmaxf(m1, fmaxf(z[2 * j], z[2 * j + 1]));
                    }
                    m1 = fmaxf(m1, __shfl_xor_sync(0xffffffffu, m1, 1));
                    m1 = fmaxf(m1, __shfl_xor_sync(0xffffffffu, m1, 2));
                    const float mb1 = m1 * sl2;
                    float l1 = 0.f;
                    const uint32_t pa = sb + R_QX + (t >> 5) * 4096 + (t & 31) * 4;
#pragma unroll
                    for (int j = 0; j < 5; j++) {
                        const uint32_t pw = pack_bf16(ex2(fmaf(z[2 * j], sl2, -mb1)), ex2(fmaf(z[2 * j + 1], sl2, -mb1)));
                        l1 += __uint_as_float(pw << 16) + __uint_as_float(pw & 0xffff0000u);
                        sts32(pa + j * 128, pw);
                    }
                    sts32(pa + 5 * 128, 0u);
                    l1 += __shfl_xor_sync(0xffffffffu, l1, 1);
                    l1 += __shfl_xor_sync(0xffffffffu, l1, 2);
                    sts32(sb + R_G + 128 + (t >> 2) * 4, __float_as_uint(gate * rcp(l1)));
                    spin_until(t_o + PVD);
                    if ((wid & 3) == 0 && s >= 1) { bulk_wait_all(); e_count(&g_ocnt[(s - 1) >> 2]); }
                    fence_async();
                    bar_sync(2, 128);
                    constexpr uint64_t dV = cdesc(R_V, 2048, 128, 0);
                    constexpr uint64_t dP = cdesc(R_QX, 128, 4096, 0);
                    float sf[8];
#pragma unroll
                    for (int j = 0; j < 4; j++) asm volatile("ld.shared.v2.f32 {%0,%1}, [%2];" : "=f"(sf[2 * j]), "=f"(sf[2 * j + 1]) : "r"(sb + R_G + 128 + j * 32 + (t & 3) * 8) : "memory");
                    const uint32_t r = ((t >> 4) & 1) * 8 + (t & 7), ch = (t >> 5) * 2 + ((t >> 3) & 1);
                    const uint32_t sa = sb + R_QX + 2048 + r * 128 + ((ch ^ (r & 7)) << 4);
#pragma unroll
                    for (int hf = 0; hf < 2; hf++) {
                        float d[16];
                        wg_fence();
#pragma unroll
                        for (int k = 0; k < 3; k++) wg_ss32<0>(d, dV + (uint64_t)(hf * 64 + k * 256), dP + (uint64_t)(k * 16), k);
                        wg_commit();
                        asm volatile("wgmma.wait_group.sync.aligned 0;" : ACC16(d)::"memory");
                        stsm4t(sa + hf * 8192, pack_bf16(d[0] * sf[0], d[1] * sf[1]), pack_bf16(d[2] * sf[0], d[3] * sf[1]), pack_bf16(d[4] * sf[2], d[5] * sf[3]), pack_bf16(d[6] * sf[2], d[7] * sf[3]));
                        stsm4t(sa + hf * 8192 + 4096, pack_bf16(d[8] * sf[4], d[9] * sf[5]), pack_bf16(d[10] * sf[4], d[11] * sf[5]), pack_bf16(d[12] * sf[6], d[13] * sf[7]), pack_bf16(d[14] * sf[6], d[15] * sf[7]));
                    }
                    fence_async();
                    bar_sync(2, 128);
                    if ((wid & 3) == 0) {
#pragma unroll
                        for (int q = 0; q < 4; q++) e_tma_store(&tm.o, sb + R_QX + 2048 + q * 4096, h * DH + (q >> 1) * 64, s * SEG + (q & 1) * 16);
                        bulk_commit();
                        bulk_wait_read();
                    }
                    if ((wid & 3) < 3) e_arrive_remote(mapa(bar + 8 * B_TFREE, wid & 3));
                }
            }
            if (t < 32) { e_expect(bar + 8 * B_HOP1, role == 2 ? 4096 : 2048); if (role != 2) e_expect(bar + 8 * B_HOPV, 2048); e_expect(bar + 8 * B_XT, role == 0 ? 2 * CPB : CPB); }
            if (s == NSEG - 1) { bulk_wait_all(); break; }
            if (role != 0 && (wid & 3) >= 2) {
                mbar_wait(bar + 8 * B_XRECV, s & 1);
                mbar_wait(bar + 8 * B_O, s & 1);
                fence_async();
                spin_until(t_o + ELD);
                x_load_pair(sb + ((wid & 1) ? R_V + 2048 : R_K + 2048), &tm.x, h, 3 + (wid & 1), s + 1, bar + 8 * (B_FULL + 3 + (wid & 1)));
            }
            OPAQUE(t);
            PROF(11);
            if (role != 0 || DDUP) {
                const int grp = role == 0 ? (t >> 6) * 32 + h : rg0 + (t >> 6) * 64;
                const uint32_t* rp = g_part[s & 3] + (grp * 1024 + ((t >> 2) & 7) * 32 + ((t >> 5) & 1) * 16 + (t & 3) * 4);
                uint32_t* wp = &g_mem[(s + 1) & 3][grp * 32 + ((t >> 5) & 1) * 16 + (t & 3) * 4 + ((t >> 3) & 3)];
                bulk_wait_all();
                spin_until(t_o + D2_BASE + (role == 0 ? DDUP + (t >> 6) * D2_STEP : (role - 1 + (t >> 6) * 2) * D2_STEP));
                PROF3(0, clk32());
#define LO(u) __uint_as_float((u) << 16)
#define HI(u) __uint_as_float((u) & 0xffff0000u)
                uint4 v[4];
                uint32_t n = poll_set<4>(v, rp, 256, (role - 1 + (t >> 6) * 2) * PHQ);
                {
                    PROF3(1, clk32());
                    float f[8];
                    f[0] = (LO(v[0].x) + LO(v[1].x)) + (LO(v[2].x) + LO(v[3].x)); f[1] = (HI(v[0].x) + HI(v[1].x)) + (HI(v[2].x) + HI(v[3].x));
                    f[2] = (LO(v[0].y) + LO(v[1].y)) + (LO(v[2].y) + LO(v[3].y)); f[3] = (HI(v[0].y) + HI(v[1].y)) + (HI(v[2].y) + HI(v[3].y));
                    f[4] = (LO(v[0].z) + LO(v[1].z)) + (LO(v[2].z) + LO(v[3].z)); f[5] = (HI(v[0].z) + HI(v[1].z)) + (HI(v[2].z) + HI(v[3].z));
                    f[6] = (LO(v[0].w) + LO(v[1].w)) + (LO(v[2].w) + LO(v[3].w)); f[7] = (HI(v[0].w) + HI(v[1].w)) + (HI(v[2].w) + HI(v[3].w));
                    const bool b4 = t & 16, b3 = t & 8;
                    float g4[4], g2[2];
#pragma unroll
                    for (int i = 0; i < 4; i++) g4[i] = (b4 ? f[4 + i] : f[i]) + __shfl_xor_sync(0xffffffffu, b4 ? f[i] : f[4 + i], 16);
#pragma unroll
                    for (int i = 0; i < 2; i++) g2[i] = (b3 ? g4[2 + i] : g4[i]) + __shfl_xor_sync(0xffffffffu, b3 ? g4[i] : g4[2 + i], 8);
                    g2[0] += __shfl_xor_sync(0xffffffffu, g2[0], 4);
                    g2[1] += __shfl_xor_sync(0xffffffffu, g2[1], 4);
                    st_strong4(wp, pack_nz(g2[0], g2[1]));
                }
                PROF3(8, n); (void)n;
            }
            t_o += D2_BASE + DQ + D3 + (t >> 5) * D2_STEP;
            OPAQUE(t);
            PROF(12);
            {
                const uint32_t* rp = &g_mem[(s + 1) & 3][((t >> 5) * 256 + (t & 31)) * 4];
                const uint32_t da = sb + R_RING + ((t >> 5) * 256 + (t & 31)) * 16;
                uint4 v[8];
                spin_until(t_o);
                PROF3(2, clk32());
                uint32_t n = poll_set<8>(v, rp, 128, PH3 + (t >> 5) * PHQ);
                PROF(13);
                PROF3(3, clk32()); PROF3(9, n); (void)n;
                mbar_wait(bar + 8 * B_AFREE0 + (t >> 6) * 8, (s + 1) & 1);
                PROF3(4, clk32());
#pragma unroll
                for (int i = 0; i < 8; i++) sts128(da + i * 512, v[i]);
                if (t >= 64) fence_async();
                __syncwarp();
                e_arrive(bar + 8 * B_MEM + (t >> 5) * 8);
                PROF(14);
                PROF3(5, clk32());
            }
            CLEAR(s + 3);
        }
}

__global__ void __launch_bounds__(384, 1) r_kernel(const __grid_constant__ RMaps tm, const bf16* __restrict__ mem0, const bf16* __restrict__ x, const bf16* __restrict__ gate_w) {
    extern __shared__ __align__(1024) unsigned char smem_raw[];
    const uint32_t sb = smem_u32(smem_raw);
    if ((sb & 0x3FFFFu) != SB0) __trap();
    const int tid = threadIdx.x;
    const int wid = __shfl_sync(0xffffffffu, tid >> 5, 0);
    uint32_t role; asm("mov.u32 %0, %%cluster_ctarank;" : "=r"(role));
    int h; asm("mov.u32 %0, %%clusterid.x;" : "=r"(h));
    const uint32_t bar = sb + R_BAR;
    asm volatile("griddepcontrol.launch_dependents;");
    KT(0, 0);
    const int gr = blockIdx.x * 12 + wid;
    uint4 gx0[4], gx1[4], gw[4];
#pragma unroll
    for (int i = 0; i < 4; i++) {
        gx0[i] = ldg_nc((const uint4*)(x + gr * DM) + i * 32 + (tid & 31));
        gx1[i] = ldg_nc((const uint4*)(x + min(gr + 1152, SEQ - 1) * DM) + i * 32 + (tid & 31));
        gw[i] = ldg_nc((const uint4*)gate_w + i * 32 + (tid & 31));
    }

    if (tid == 0) {
        for (int i = 0; i < 5; i++) mbar_init(bar + 8 * (B_FULL + i), 1);
        for (int i = 0; i < 3; i++) mbar_init(bar + 8 * (B_EMPTY + i), 2);
        for (int i = 0; i < 4; i++) mbar_init(bar + 8 * (B_MEM + i), 1);
        mbar_init(bar + 8 * B_HOP1, role == 2 ? 1 : 9);
        mbar_init(bar + 8 * B_HOPV, role == 2 ? 8 : 1);
        mbar_init(bar + 8 * B_XT, 1);
        mbar_init(bar + 8 * B_TFREE, 5);
        mbar_init(bar + 8 * B_P, 4);
        mbar_init(bar + 8 * B_XDONE, 8);
        mbar_init(bar + 8 * B_OST0, 4);
        mbar_init(bar + 8 * B_OST1, 4);
        mbar_init(bar + 8 * B_XRECV, 2);
        mbar_init(bar + 8 * B_O, 4);
        mbar_init(bar + 8 * B_AFREE0, 2);
        mbar_init(bar + 8 * B_AFREE1, 2);
        mbar_init(bar + 8 * B_PRO0, 1);
        mbar_init(bar + 8 * B_PRO1, 8);
        asm volatile("fence.mbarrier_init.release.cluster;" ::: "memory");
        fence_async();
        mbar_expect(bar + 8 * B_PRO0, KR * 4096);
        for (int i = 0; i < 3; i++) mbar_expect(bar + 8 * (B_FULL + i), 8192);
        mbar_expect(bar + 8 * B_HOP1, role == 2 ? 4096 : 2048);
        if (role != 2) mbar_expect(bar + 8 * B_HOPV, 2048);
        mbar_expect(bar + 8 * B_XT, role == 0 ? 2 * CPB : CPB);
    }
    __syncthreads();
    asm volatile("barrier.cluster.arrive.relaxed.aligned;" ::: "memory");
    {
        const CUtensorMap* tw = &tm.w[role];
        if (wid < 11) {
            e_tma_load(sb + wid * 16384, tw, h * DH, KC(wid), bar + 8 * B_PRO0);
            e_tma_load(sb + wid * 16384 + 8192, tw, h * DH + 64, KC(wid), bar + 8 * B_PRO0);
        }
        if (wid < 6) e_tma_load(sb + R_RING + wid * 4096, &tm.x, XC(wid), 0, bar + 8 * (B_FULL + (wid >> 1)));
        if ((tid & 31) == 0) {
            if (wid < 10) tma_prefetch(tw, h * DH + (wid & 1) * 64, KC(KR / 4 + (wid >> 1)));
            if (wid >= 6 && wid - 6 < (role == 0 ? 4 : 6)) tma_prefetch(&tm.wo, wo_tile(role, wid - 6) * 64, h * DH);
        }
        __syncwarp();
        const uint32_t g0 = __float_as_uint(gate_row(gx0, gw)), g1 = __float_as_uint(gate_row(gx1, gw));
        if ((tid & 31) == 0) {
            st_strong4(&g_gate[gr], g0 ? g0 : 0x80000000u);
            if (gr + 1152 < SEQ) st_strong4(&g_gate[gr + 1152], g1 ? g1 : 0x80000000u);
        }
        __syncwarp();
    }
    asm volatile("barrier.cluster.wait.aligned;" ::: "memory");

    if (wid < 8) {
        asm volatile("setmaxnreg.inc.sync.aligned.u32 224;");
        if (role == 0) r_big<0>(tm, wid); else if (role == 1) r_big<1>(tm, wid); else r_big<2>(tm, wid);
    } else {
        asm volatile("setmaxnreg.dec.sync.aligned.u32 56;");
        if (role == 0) r_chain<0>(tm, mem0, wid); else if (role == 1) r_chain<1>(tm, mem0, wid); else r_chain<2>(tm, mem0, wid);
    }
    __syncwarp();
    asm volatile("barrier.cluster.arrive; barrier.cluster.wait;" ::: "memory");
    KT(0, 1);
}

#define STAG 0
#define TSTAG 500
constexpr int G_ST = 4;
constexpr int G_STAGE = 16384 + 32768;
constexpr int G_EPI = G_ST * G_STAGE;
constexpr int G_GATE = G_EPI + 32768;
constexpr int G_BAR = G_GATE + 1024;
constexpr int G_SMEM = G_BAR + 128 + 1024;

struct G1Maps { CUtensorMap x, wg, wu, hs, o, h, wo, wd, out; };
constexpr int G1_NB = FF / 128;
constexpr int G1_TILES = 16 * G1_NB;

DEVINL void g_mma_block(float* d, uint32_t sb, uint32_t bar, int it, int wg, int tid, bool first) {
    const int st = it % G_ST;
    mbar_wait(bar + 8 * st, (it / G_ST) & 1);
    const uint64_t da = mkdesc(sb + st * G_STAGE + wg * 8192, 16, 1024, 1);
    const uint64_t db = mkdesc(sb + st * G_STAGE + 16384, 8192, 1024, 1);
    wg_fence();
#pragma unroll
    for (int k = 0; k < 4; k++) wg_ss256(d, da + (uint64_t)(k * 2), db + (uint64_t)(k * 128), (first ? 0 : 1) | k);
    wg_commit();
    if (!first) { wg_wait<1>(); if ((tid & 127) == 0) mbar_arrive(bar + 8 * (G_ST + (it - 1) % G_ST)); }
}
DEVINL void g_load_block(uint32_t sb, uint32_t bar, int it, const CUtensorMap* ta, int k0, int m0, const CUtensorMap* tb, int n0) {
    const int st = it % G_ST;
    mbar_wait(bar + 8 * (G_ST + st), ((it / G_ST) & 1) ^ 1);
    const uint32_t fb = bar + 8 * st, sa = sb + st * G_STAGE;
    mbar_expect(fb, G_STAGE);
    tma_load(sa, ta, k0, m0, fb);
#pragma unroll
    for (int q = 0; q < 4; q++) tma_load(sa + 16384 + q * 8192, tb, n0 + q * 64, k0, fb);
}

DEVINL void g_store_tile(const float* d, const CUtensorMap* tout, uint32_t epi, int mb, int nb, int wg, int tid) {
    const int lane = tid & 31, row = ((tid >> 5) & 3) * 16 + ((lane >> 3) & 1) * 8 + (lane & 7);
#pragma unroll
    for (int half = 0; half < 2; half++) {
        if ((tid & 127) == 0) bulk_wait_read();
        bar_sync(1 + wg, 128);
#pragma unroll
        for (int j = 0; j < 16; j += 2) {
            const float* e = d + half * 64 + 4 * j;
            const int cgp = j + (lane >> 4);
            stsm4(epi + (cgp >> 3) * 8192 + row * 128 + (((cgp & 7) ^ (row & 7)) << 4),
                  pack_bf16(e[0], e[1]), pack_bf16(e[2], e[3]), pack_bf16(e[4], e[5]), pack_bf16(e[6], e[7]));
        }
        fence_async();
        bar_sync(1 + wg, 128);
        if ((tid & 127) == 0) {
            tma_store(tout, epi, nb * 256 + half * 128, mb * 128 + wg * 64);
            tma_store(tout, epi + 8192, nb * 256 + half * 128 + 64, mb * 128 + wg * 64);
            bulk_commit();
        }
    }
}
template <int NS> DEVINL void g_split_finish(const float* d, float4 (&r)[32 / NS], uint4* sk, int tile, int ks, bf16* __restrict__ out, int tid) {
    constexpr int Q = 32 / NS;
    uint4* mine = sk + ks * (16 * 256) + tid;
#pragma unroll
    for (int c = 0; c < NS; c++) {
        if (c != ks) {
#pragma unroll
            for (int q = c * Q / 2; q < (c + 1) * Q / 2; q++)
                __stcg(mine + q * 256, make_uint4(pack_bf16(d[8 * q], d[8 * q + 1]), pack_bf16(d[8 * q + 2], d[8 * q + 3]), pack_bf16(d[8 * q + 4], d[8 * q + 5]), pack_bf16(d[8 * q + 6], d[8 * q + 7])));
        } else {
#pragma unroll
            for (int q = 0; q < Q; q++) { const float* e = d + (c * Q + q) * 4; r[q].x += e[0]; r[q].y += e[1]; r[q].z += e[2]; r[q].w += e[3]; }
        }
    }
    __threadfence();
    bar_sync(3, 256);
    if (tile >= T_LATE) PT(20);
    if (tid == 0) {
        atomicAdd(&g_skcnt[tile], 1u);
        uint32_t v, n = 0;
        do {
            asm volatile("ld.acquire.gpu.global.u32 %0, [%1];" : "=r"(v) : "l"(&g_skcnt[tile]) : "memory");
            if (++n > 200000000u) __trap();
        } while (v < NS);
        if (atomicAdd(&g_skcnt[tile], 1u) == 2 * NS - 1) g_skcnt[tile] = 0u;
    }
    bar_sync(3, 256);
    if (tile >= T_LATE) PT(21);
#pragma unroll
    for (int c = 1; c < NS; c++) {
        const uint4* th = sk + (((ks + c) & (NS - 1)) * 16 + ks * (Q / 2)) * 256 + tid;
#pragma unroll
        for (int q = 0; q < Q / 2; q++) {
            const uint4 u = __ldcg(th + q * 256);
            r[2 * q].x += __uint_as_float(u.x << 16); r[2 * q].y += __uint_as_float(u.x & 0xffff0000u);
            r[2 * q].z += __uint_as_float(u.y << 16); r[2 * q].w += __uint_as_float(u.y & 0xffff0000u);
            r[2 * q + 1].x += __uint_as_float(u.z << 16); r[2 * q + 1].y += __uint_as_float(u.z & 0xffff0000u);
            r[2 * q + 1].z += __uint_as_float(u.w << 16); r[2 * q + 1].w += __uint_as_float(u.w & 0xffff0000u);
        }
    }
    const int lane = tid & 31;
    uint32_t* op = (uint32_t*)(out + ((tile >> 2) * 128 + (tid >> 5) * 16 + (lane >> 2)) * DM + (tile & 3) * 256 + ks * Q * 8 + (lane & 3) * 2);
#pragma unroll
    for (int q = 0; q < Q; q++) { op[q * 4] = pack_bf16(r[q].x, r[q].y); op[q * 4 + 4 * DM] = pack_bf16(r[q].z, r[q].w); }
}
DEVINL int g1_count(int pass, int tail) {
    return pass == 0 ? NPRE : pass == 1 ? NFULL : pass == 2 ? T_MID - NFULL : pass == 3 ? (T_MID2 - T_MID) * 4 : tail ? (64 - T_LATE) * 8 : (T_LATE - T_MID2) * 8;
}
DEVINL int g1_first(int pass, int tail) {
    const int b = blockIdx.x, n = gridDim.x;
    const int f = (pass < 2 || tail) ? b : pass == 2 ? n - 1 - b : (b + n - (pass == 3 ? 16 : 32)) % n;
    return (pass == 4 && !tail && f >= 32) ? 1 << 20 : f;
}
DEVINL int g1_stride(int pass, int tail) { return (pass == 4 && !tail) ? 32 : (int)gridDim.x; }
DEVINL int g1_tile(int pass, int tail, int i) {
    return pass == 1 ? i : pass == 3 ? T_MID + (i >> 2) : pass == 4 ? (tail ? T_LATE : T_MID2) + (i >> 3) : NFULL + i;
}
constexpr int H_EARLY = 24;

__global__ void __launch_bounds__(384, 1) g1_kernel(const __grid_constant__ G1Maps tm, bf16* __restrict__ out, const int tail) {
    extern __shared__ __align__(1024) unsigned char smem_raw[];
    const uint32_t sb = (smem_u32(smem_raw) + 1023) & ~1023u;
    const int tid = threadIdx.x, lane = tid & 31;
    const int wg = __shfl_sync(0xffffffffu, tid >> 7, 0);
    const int warp = __shfl_sync(0xffffffffu, (tid >> 5) & 3, 0);
    const uint32_t bar = sb + G_BAR;
    asm volatile("griddepcontrol.launch_dependents;");
    KT(1 + tail, 0);
    if (tail && (tid == 32 || tid == 64)) asm volatile("prefetch.tensormap [%0];" ::"l"(tid == 32 ? &tm.o : &tm.wo) : "memory");
    const int ntiles = tail ? 0 : G1_TILES;
    if (tid == 0) {
        for (int i = 0; i < G_ST; i++) { mbar_init(bar + 8 * i, 1); mbar_init(bar + 8 * (G_ST + i), 2); }
        fence_async();
    }
    __syncthreads();
    if (tail) PT(16);
    if (tail) asm volatile("griddepcontrol.wait;" ::: "memory");
    if (tail) PT(17);
    if (tail && wg == 2) {
        const int it = warp, tile = T_LATE + (blockIdx.x >> 3), k0 = ((blockIdx.x & 7) * 8 + it) * 64;
        e_expect(bar + 8 * it, G_STAGE);
        spin_until(clk32() + it * TSTAG);
        e_tma_load(sb + it * G_STAGE, &tm.o, k0, (tile >> 2) * 128, bar + 8 * it);
#pragma unroll
        for (int q = 0; q < 4; q++) e_tma_load(sb + it * G_STAGE + 16384 + q * 8192, &tm.wo, (tile & 3) * 256 + q * 64, k0, bar + 8 * it);
    }
    if (wg == 2) {
        asm volatile("setmaxnreg.dec.sync.aligned.u32 40;");
        if (tail && warp == 1) {
            if (blockIdx.x < SEQ / 32) g_gate[blockIdx.x * 32 + lane] = 0u;
            if (blockIdx.x == 0) { if (lane < 16) g_ocnt[lane] = 0u; g_hcnt[lane] = 0u; g_pcnt[lane] = 0u; g_pcnt[32 + lane] = 0u; }
        }
        if (warp == 0) {
            if (lane == 0) {
                int it = 0;
                for (int tile = blockIdx.x; tile < ntiles; tile += gridDim.x) {
                    const int mb = tile & 15, nb = tile >> 4;
                    for (int kb = 0; kb < 16; kb++, it++) {
                        const int st = it % G_ST;
                        mbar_wait(bar + 8 * (G_ST + st), ((it / G_ST) & 1) ^ 1);
                        const uint32_t fb = bar + 8 * st, sa = sb + st * G_STAGE;
                        mbar_expect(fb, G_STAGE);
                        tma_load(sa, &tm.x, kb * 64, mb * 128, fb);
                        tma_load(sa + 16384, &tm.wg, nb * 128, kb * 64, fb);
                        tma_load(sa + 16384 + 8192, &tm.wg, nb * 128 + 64, kb * 64, fb);
                        tma_load(sa + 16384 + 16384, &tm.wu, nb * 128, kb * 64, fb);
                        tma_load(sa + 16384 + 24576, &tm.wu, nb * 128 + 64, kb * 64, fb);
                    }
                }
                for (int pass = tail ? 4 : 0; pass < 5; pass++) {
                    for (int i = g1_first(pass, tail); i < g1_count(pass, tail); i += g1_stride(pass, tail)) {
                        const int tile = g1_tile(pass, tail, i), mb = tile >> 2, nb = tile & 3;
                        if (pass < 2) {
                            for (int kb = 0; kb < FF / 64; kb++, it++) {
                                if (kb == 0 || kb == 2 * H_EARLY) {
                                    wait_count(&g_hcnt[kb ? 16 + mb : mb], kb ? 2 * (G1_NB - H_EARLY) : 2 * H_EARLY);
                                    asm volatile("fence.proxy.async;" ::: "memory");
                                }
                                g_load_block(sb, bar, it, &tm.h, kb * 64, mb * 128, &tm.wd, nb * 256);
                            }
                        }
                        if (pass > 0) {
                            const int k0 = pass == 3 ? (i & 3) * 16 : pass == 4 ? (i & 7) * 8 : 0, k1 = pass == 3 ? k0 + 16 : pass == 4 ? k0 + 8 : HD / 64;
                            if (!tail) wait_count(&g_ocnt[mb], NH * 4);
                            asm volatile("fence.proxy.async;" ::: "memory");
                            for (int kb = k0; kb < k1; kb++, it++) if (!tail || it >= G_ST) g_load_block(sb, bar, it, &tm.o, kb * 64, mb * 128, &tm.wo, nb * 256);
                        }
                    }
                }
            }
        }
    } else {
        asm volatile("setmaxnreg.inc.sync.aligned.u32 232;");
        float d[128];
        int it = 0;
        const uint32_t epi = sb + G_EPI + wg * 16384;
        const int row = warp * 16 + ((lane >> 3) & 1) * 8 + (lane & 7);
        for (int tile = blockIdx.x; tile < ntiles; tile += gridDim.x) {
            const int mb = tile & 15, nb = tile >> 4;
            const uint32_t* gp = &g_gate[mb * 128 + wg * 64 + warp * 16 + (lane >> 2)];
            uint32_t u0 = ld_strong4(gp), u1 = ld_strong4(gp + 8);
            for (int kb = 0; kb < 16; kb++, it++) {
                if (it == (wg ? 0 : STAG)) bar_sync(4, 256);
                g_mma_block(d, sb, bar, it, wg, tid, kb == 0);
            }
            wg_wait<0>();
            for (uint32_t n = 0; u0 == 0u || u1 == 0u; n++) { u0 = ld_strong4(gp); u1 = ld_strong4(gp + 8); if (n > 20000000u) __trap(); }
            __syncwarp();
            const float s0 = 1.0f - __uint_as_float(u0), s1 = 1.0f - __uint_as_float(u1);
            if ((tid & 127) == 0) {
                mbar_arrive(bar + 8 * (G_ST + (it - 1) % G_ST));
                bulk_wait_all();
                const int pt = tile - (int)gridDim.x;
                if (pt >= 0) atomicAdd(&g_hcnt[(pt & 15) + ((pt >> 4) >= H_EARLY ? 16 : 0)], 1u);
            }
            bar_sync(1 + wg, 128);
#pragma unroll
            for (int j = 0; j < 16; j += 2) {
                uint32_t p[4];
#pragma unroll
                for (int q = 0; q < 4; q++) {
                    const int i = (j + (q >> 1)) * 4 + (q & 1) * 2;
                    const float sc = (q & 1) ? s1 : s0;
                    const float g0 = d[i], g1 = d[i + 1];
                    const float a0 = 1.0f + ex2(fminf(g0 * -1.4426950408889634f, 62.0f)), a1 = 1.0f + ex2(fminf(g1 * -1.4426950408889634f, 62.0f));
                    const float rr = rcp(a0 * a1) * sc;
                    const float h0 = (g0 * d[64 + i]) * (rr * a1);
                    const float h1 = (g1 * d[64 + i + 1]) * (rr * a0);
                    p[q] = pack_bf16(h0, h1);
                }
                const int cgp = j + (lane >> 4);
                stsm4(epi + (cgp >> 3) * 8192 + row * 128 + (((cgp & 7) ^ (row & 7)) << 4), p[0], p[1], p[2], p[3]);
            }
            fence_async();
            bar_sync(1 + wg, 128);
            if ((tid & 127) == 0) {
                tma_store(&tm.hs, epi, nb * 128, mb * 128 + wg * 64);
                tma_store(&tm.hs, epi + 8192, nb * 128 + 64, mb * 128 + wg * 64);
                bulk_commit();
            }
        }
        if ((tid & 127) == 0 && !tail) {
            bulk_wait_all();
            const int pt = blockIdx.x + (G1_TILES - 1 - blockIdx.x) / gridDim.x * gridDim.x;
            atomicAdd(&g_hcnt[(pt & 15) + ((pt >> 4) >= H_EARLY ? 16 : 0)], 1u);
        }
        for (int pass = tail ? 4 : 0; pass < 5; pass++) {
            for (int i = g1_first(pass, tail); i < g1_count(pass, tail); i += g1_stride(pass, tail)) {
                const int tile = g1_tile(pass, tail, i);
                const int nkb = pass == 0 ? FF / 64 : pass == 1 ? (FF + HD) / 64 : pass == 2 ? HD / 64 : pass == 3 ? 16 : 8;
                float4* pre = g_pre + (tile - NFULL) * (32 * 256) + tid;
                if (tail) asm volatile("prefetch.global.L2 [%0];" ::"l"(pre - tid + (i & 7) * 1024 + tid * 4));
                for (int kb = 0; kb < nkb; kb++, it++) { g_mma_block(d, sb, bar, it, wg, tid, kb == 0); if (tail && kb == 0) PT(18); }
                wg_wait<0>();
                if (tail) PT(19);
                if ((tid & 127) == 0) mbar_arrive(bar + 8 * (G_ST + (it - 1) % G_ST));
                if (pass >= 2 && !tail) { if ((tid & 31) == 0) wait_count(&g_pcnt[tile], 8); __syncwarp(); }
                if (pass == 0) {
#pragma unroll
                    for (int q = 0; q < 32; q++) __stcg(pre + q * 256, make_float4(d[4 * q], d[4 * q + 1], d[4 * q + 2], d[4 * q + 3]));
                    __threadfence();
                    __syncwarp();
                    if ((tid & 31) == 0) atomicAdd(&g_pcnt[tile], 1u);
                } else if (pass == 3) {
                    float4 r[8];
#pragma unroll
                    for (int q = 0; q < 8; q++) r[q] = __ldcg(pre + ((i & 3) * 8 + q) * 256);
                    g_split_finish<4>(d, r, g_sk + (tile - T_MID) * 8 * (16 * 256), tile, i & 3, out, tid);
                } else if (pass == 4) {
                    float4 r[4];
#pragma unroll
                    for (int q = 0; q < 4; q++) r[q] = __ldcg(pre + ((i & 7) * 4 + q) * 256);
                    g_split_finish<8>(d, r, g_sk + (tile - T_MID) * 8 * (16 * 256), tile, i & 7, out, tid);
                } else {
                    if (pass == 2) {
#pragma unroll
                        for (int q = 0; q < 32; q++) {
                            const float4 u = __ldcg(pre + q * 256); d[4 * q] += u.x; d[4 * q + 1] += u.y; d[4 * q + 2] += u.z; d[4 * q + 3] += u.w;
                            if ((q & 7) == 7) __syncwarp();
                        }
                    }
                    g_store_tile(d, &tm.out, epi, tile >> 2, tile & 3, wg, tid);
                }
            }
        }
        if ((tid & 127) == 0) bulk_wait_all();
        KT(1 + tail, 1);
    }
    __syncwarp();
    asm volatile("griddepcontrol.wait;" ::: "memory");
}

typedef CUresult (*EncodeFn)(CUtensorMap*, CUtensorMapDataType, cuuint32_t, void*, const cuuint64_t*, const cuuint64_t*, const cuuint32_t*,
                             const cuuint32_t*, CUtensorMapInterleave, CUtensorMapSwizzle, CUtensorMapL2promotion, CUtensorMapFloatOOBfill);

static void make_map(EncodeFn enc, CUtensorMap* m, const void* ptr, uint64_t rows, uint64_t cols, uint32_t box_rows) {
    cuuint64_t dims[2] = {cols, rows};
    cuuint64_t strides[1] = {cols * 2};
    cuuint32_t box[2] = {64, box_rows};
    cuuint32_t es[2] = {1, 1};
    enc(m, CU_TENSOR_MAP_DATA_TYPE_BFLOAT16, 2, (void*)ptr, dims, strides, box, es, CU_TENSOR_MAP_INTERLEAVE_NONE,
        CU_TENSOR_MAP_SWIZZLE_128B, CU_TENSOR_MAP_L2_PROMOTION_L2_256B, CU_TENSOR_MAP_FLOAT_OOB_FILL_NONE);
}

extern "C" void kernel_launch(void* const* d_in, const int* in_sizes, int n_in, void* d_out, int out_size) {
    (void)in_sizes; (void)n_in; (void)out_size;
    const bf16* x = (const bf16*)d_in[0];
    const bf16* mem0 = (const bf16*)d_in[1];
    const bf16* gate_w = (const bf16*)d_in[11];
    static EncodeFn enc = nullptr;
    static int n_sm = 0;
    static void *pO = nullptr, *pH = nullptr;
    if (!enc) {
        void* fn = nullptr;
        cudaDriverEntryPointQueryResult qr;
        cudaGetDriverEntryPoint("cuTensorMapEncodeTiled", &fn, cudaEnableDefault, &qr);
        enc = (EncodeFn)fn;
        cudaDeviceGetAttribute(&n_sm, cudaDevAttrMultiProcessorCount, 0);
        cudaFuncSetAttribute(r_kernel, cudaFuncAttributeMaxDynamicSharedMemorySize, R_SMEM);
        cudaFuncSetAttribute(g1_kernel, cudaFuncAttributeMaxDynamicSharedMemorySize, G_SMEM);
        cudaGetSymbolAddress(&pO, g_O);
        cudaGetSymbolAddress(&pH, g_H);
    }
    RMaps rm; G1Maps m1;
    make_map(enc, &rm.x, x, SEQ, DM, 32);
    for (int i = 0; i < 3; i++) make_map(enc, &rm.w[i], d_in[2 + i], DM, HD, 64);
    make_map(enc, &rm.wo, d_in[5], HD, DM, 128);
    make_map(enc, &rm.o, pO, SEQ, HD, 16);
    make_map(enc, &m1.x, x, SEQ, DM, 128);
    make_map(enc, &m1.wg, d_in[8], DM, FF, 64);
    make_map(enc, &m1.wu, d_in[9], DM, FF, 64);
    make_map(enc, &m1.hs, pH, SEQ, FF, 64);
    make_map(enc, &m1.o, pO, SEQ, HD, 128);
    make_map(enc, &m1.h, pH, SEQ, FF, 128);
    make_map(enc, &m1.wo, d_in[5], HD, DM, 64);
    make_map(enc, &m1.wd, d_in[10], FF, DM, 64);
    make_map(enc, &m1.out, d_out, SEQ, DM, 64);

    cudaStream_t st = cudaStreamPerThread;
    {
        cudaLaunchConfig_t cfg = {};
        cfg.gridDim = dim3(96); cfg.blockDim = dim3(384); cfg.dynamicSmemBytes = R_SMEM; cfg.stream = st;
        cudaLaunchAttribute at[1];
        at[0].id = cudaLaunchAttributeClusterDimension; at[0].val.clusterDim.x = 3; at[0].val.clusterDim.y = 1; at[0].val.clusterDim.z = 1;
        cfg.attrs = at; cfg.numAttrs = 1;
        cudaLaunchKernelEx(&cfg, r_kernel, rm, mem0, x, gate_w);
    }
    {
        cudaLaunchConfig_t cfg = {};
        cfg.gridDim = dim3(n_sm - 96); cfg.blockDim = dim3(384); cfg.dynamicSmemBytes = G_SMEM; cfg.stream = st;
        cudaLaunchAttribute at[1];
        at[0].id = cudaLaunchAttributeProgrammaticStreamSerialization; at[0].val.programmaticStreamSerializationAllowed = 1;
        cfg.attrs = at; cfg.numAttrs = 1;
        cudaLaunchKernelEx(&cfg, g1_kernel, m1, (bf16*)d_out, 0);
    }
    {
        cudaLaunchConfig_t cfg = {};
        cfg.gridDim = dim3((64 - T_LATE) * 8); cfg.blockDim = dim3(384); cfg.dynamicSmemBytes = G_SMEM; cfg.stream = st;
        cudaLaunchAttribute at[1];
        at[0].id = cudaLaunchAttributeProgrammaticStreamSerialization; at[0].val.programmaticStreamSerializationAllowed = 1;
        cfg.attrs = at; cfg.numAttrs = 1;
        cudaLaunchKernelEx(&cfg, g1_kernel, m1, (bf16*)d_out, 1);
    }
}
```

```cpp
#include <cuda_runtime.h>
#include <cuda_bf16.h>
#include <cuda.h>
#include <stdint.h>

typedef __nv_bfloat16 bf16;

constexpr int SEQ = 2048, DM = 1024, NH = 32, DH = 128, NMEM = 8, SEG = 32, NSEG = 64, FF = 3584;
constexpr int HD = NH * DH;

__device__ bf16 g_O[SEQ * HD];
__device__ bf16 g_H[SEQ * FF];
__device__ uint32_t g_gate[SEQ];
__device__ uint32_t g_part[4][128 * 32 * 32];
__device__ uint32_t g_mem[4][DM * 4];
#define TLATE 52
constexpr int NFULL = 36, T_MID = 44, T_MID2 = 48, T_LATE = TLATE;
constexpr int NPRE = 64 - NFULL;
__device__ float4 g_pre[NPRE * 32 * 256];
__device__ uint4 g_sk[(64 - T_MID) * 8 * 16 * 256];
__device__ uint32_t g_skcnt[64], g_pcnt[64];
__device__ uint32_t g_hcnt[32], g_ocnt[16];
#define KT(k, i)
#define PT(i)

#define DEVINL __device__ __forceinline__
constexpr long long SPIN_LIMIT = 4000000000LL;

DEVINL uint32_t smem_u32(const void* p) { return (uint32_t)__cvta_generic_to_shared(p); }
DEVINL void mbar_init(uint32_t bar, uint32_t cnt) { asm volatile("mbarrier.init.shared::cta.b64 [%0], %1;" ::"r"(bar), "r"(cnt) : "memory"); }
DEVINL void mbar_arrive(uint32_t bar) { asm volatile("mbarrier.arrive.shared::cta.b64 _, [%0];" ::"r"(bar) : "memory"); }
DEVINL void mbar_expect(uint32_t bar, uint32_t bytes) { asm volatile("mbarrier.arrive.expect_tx.shared::cta.b64 _, [%0], %1;" ::"r"(bar), "r"(bytes) : "memory"); }
DEVINL void mbar_arrive_remote(uint32_t cbar) { asm volatile("mbarrier.arrive.relaxed.cluster.shared::cluster.b64 _, [%0];" ::"r"(cbar) : "memory"); }
DEVINL bool mbar_try(uint32_t bar, uint32_t par) {
    uint32_t ok;
    asm volatile("{ .reg .pred p; mbarrier.try_wait.parity.shared::cta.b64 p, [%1], %2; selp.u32 %0, 1, 0, p; }" : "=r"(ok) : "r"(bar), "r"(par) : "memory");
    return ok;
}
__device__ __noinline__ void mbar_wait_slow(uint32_t bar, uint32_t par) {
    long long t0 = clock64();
    while (!mbar_try(bar, par)) { if (clock64() - t0 > SPIN_LIMIT) __trap(); }
}
DEVINL void mbar_wait(uint32_t bar, uint32_t par) {
    uint32_t n = 0;
    while (!mbar_try(bar, par)) { if (++n > 200000000u) __trap(); }
}
DEVINL uint32_t mapa(uint32_t a, uint32_t r) { uint32_t o; asm volatile("mapa.shared::cluster.u32 %0, %1, %2;" : "=r"(o) : "r"(a), "r"(r)); return o; }
DEVINL void fence_async() { asm volatile("fence.proxy.async.shared::cta;" ::: "memory"); }
DEVINL void bar_sync(int id, int n) { asm volatile("bar.sync %0, %1;" ::"r"(id), "r"(n) : "memory"); }
DEVINL void cluster_sync() { asm volatile("barrier.cluster.arrive.aligned; barrier.cluster.wait.aligned;" ::: "memory"); }
DEVINL void tma_load(uint32_t dst, const CUtensorMap* tm, int c0, int c1, uint32_t bar) {
    asm volatile("cp.async.bulk.tensor.2d.shared::cluster.global.mbarrier::complete_tx::bytes [%0], [%1, {%3, %4}], [%2];"
                 ::"r"(dst), "l"(tm), "r"(bar), "r"(c0), "r"(c1) : "memory");
}
DEVINL void tma_prefetch(const CUtensorMap* tm, int c0, int c1) {
    asm volatile("cp.async.bulk.prefetch.tensor.2d.L2.global [%0, {%1, %2}];" ::"l"(tm), "r"(c0), "r"(c1) : "memory");
}
DEVINL void tma_store(const CUtensorMap* tm, uint32_t src, int c0, int c1) {
    asm volatile("cp.async.bulk.tensor.2d.global.shared::cta.bulk_group [%0, {%2, %3}], [%1];" ::"l"(tm), "r"(src), "r"(c0), "r"(c1) : "memory");
}
DEVINL void bulk_commit() { asm volatile("cp.async.bulk.commit_group;" ::: "memory"); }
DEVINL void bulk_wait_read() { asm volatile("cp.async.bulk.wait_group.read 0;" ::: "memory"); }
DEVINL void bulk_wait_all() { asm volatile("cp.async.bulk.wait_group 0;" ::: "memory"); }
DEVINL void bulk_s2s(uint32_t cdst, uint32_t src, uint32_t bytes, uint32_t cbar) {
    asm volatile("cp.async.bulk.shared::cluster.shared::cta.mbarrier::complete_tx::bytes [%0], [%1], %2, [%3];" ::"r"(cdst), "r"(src), "r"(bytes), "r"(cbar) : "memory");
}
DEVINL void st_async16(uint32_t cdst, uint4 v, uint32_t cbar) {
    asm volatile("st.async.shared::cluster.mbarrier::complete_tx::bytes.v4.b32 [%0], {%1,%2,%3,%4}, [%5];" ::"r"(cdst), "r"(v.x), "r"(v.y), "r"(v.z), "r"(v.w), "r"(cbar) : "memory");
}
DEVINL uint64_t mkdesc(uint32_t addr, uint32_t lbo, uint32_t sbo, uint32_t swz) {
    return (uint64_t)((addr & 0x3FFFF) >> 4) | ((uint64_t)(lbo >> 4) << 16) | ((uint64_t)(sbo >> 4) << 32) | ((uint64_t)swz << 62);
}
constexpr uint32_t SB0 = 1024;
__host__ __device__ constexpr uint64_t cdesc(uint32_t off, uint32_t lbo, uint32_t sbo, uint32_t swz) {
    return (uint64_t)(((SB0 + off) & 0x3FFFF) >> 4) | ((uint64_t)(lbo >> 4) << 16) | ((uint64_t)(sbo >> 4) << 32) | ((uint64_t)swz << 62);
}
DEVINL float rcp(float x) { float y; asm("rcp.approx.ftz.f32 %0, %1;" : "=f"(y) : "f"(x)); return y; }
DEVINL float ex2(float x) { float y; asm("ex2.approx.ftz.f32 %0, %1;" : "=f"(y) : "f"(x)); return y; }
DEVINL void spin_clk(int d) { uint32_t t0, t1; asm volatile("mov.u32 %0, %%clock;" : "=r"(t0)); do { asm volatile("mov.u32 %0, %%clock;" : "=r"(t1)); } while ((int)(t1 - t0) < d); }
#define PROBE_GAP 150
#define OPAQUE(x) asm volatile("" : "+r"(x))
DEVINL void wg_fence() { asm volatile("wgmma.fence.sync.aligned;" ::: "memory"); }
DEVINL void wg_commit() { asm volatile("wgmma.commit_group.sync.aligned;" ::: "memory"); }
template <int N> DEVINL void wg_wait() { asm volatile("wgmma.wait_group.sync.aligned %0;" ::"n"(N) : "memory"); }
DEVINL uint32_t pack_bf16(float lo, float hi) { uint32_t r; asm("cvt.rn.bf16x2.f32 %0, %1, %2;" : "=r"(r) : "f"(hi), "f"(lo)); return r; }
DEVINL void ldsm4(uint32_t* r, uint32_t a) { asm volatile("ldmatrix.sync.aligned.m8n8.x4.shared.b16 {%0,%1,%2,%3}, [%4];" : "=r"(r[0]), "=r"(r[1]), "=r"(r[2]), "=r"(r[3]) : "r"(a) : "memory"); }
DEVINL void ldsm4t(uint32_t* r, uint32_t a) { asm volatile("ldmatrix.sync.aligned.m8n8.x4.trans.shared.b16 {%0,%1,%2,%3}, [%4];" : "=r"(r[0]), "=r"(r[1]), "=r"(r[2]), "=r"(r[3]) : "r"(a) : "memory"); }
DEVINL void ldsm4t_if(uint32_t* r, uint32_t a, int c) { asm volatile("{ .reg .pred p; setp.ne.s32 p, %5, 0; @p ldmatrix.sync.aligned.m8n8.x4.trans.shared.b16 {%0,%1,%2,%3}, [%4]; }" : "+r"(r[0]), "+r"(r[1]), "+r"(r[2]), "+r"(r[3]) : "r"(a), "r"(c) : "memory"); }
DEVINL void stsm4(uint32_t a, uint32_t r0, uint32_t r1, uint32_t r2, uint32_t r3) { asm volatile("stmatrix.sync.aligned.m8n8.x4.shared.b16 [%0], {%1,%2,%3,%4};" ::"r"(a), "r"(r0), "r"(r1), "r"(r2), "r"(r3) : "memory"); }
DEVINL void stsm4t(uint32_t a, uint32_t r0, uint32_t r1, uint32_t r2, uint32_t r3) { asm volatile("stmatrix.sync.aligned.m8n8.x4.trans.shared.b16 [%0], {%1,%2,%3,%4};" ::"r"(a), "r"(r0), "r"(r1), "r"(r2), "r"(r3) : "memory"); }
DEVINL void sts32(uint32_t a, uint32_t v) { asm volatile("st.shared.b32 [%0], %1;" ::"r"(a), "r"(v) : "memory"); }
DEVINL void sts128(uint32_t a, uint4 v) { asm volatile("st.shared.v4.b32 [%0], {%1,%2,%3,%4};" ::"r"(a), "r"(v.x), "r"(v.y), "r"(v.z), "r"(v.w) : "memory"); }
DEVINL uint4 lds128(uint32_t a) { uint4 v; asm volatile("ld.shared.v4.b32 {%0,%1,%2,%3}, [%4];" : "=r"(v.x), "=r"(v.y), "=r"(v.z), "=r"(v.w) : "r"(a) : "memory"); return v; }
DEVINL uint4 ld_strong16(const void* p) { uint4 v; asm volatile("ld.relaxed.gpu.global.v4.u32 {%0,%1,%2,%3}, [%4];" : "=r"(v.x), "=r"(v.y), "=r"(v.z), "=r"(v.w) : "l"(p) : "memory"); return v; }
DEVINL void st_strong8(void* p, uint32_t a, uint32_t b) { asm volatile("st.relaxed.gpu.global.v2.u32 [%0], {%1,%2};" ::"l"(p), "r"(a), "r"(b) : "memory"); }
DEVINL void st_strong4(void* p, uint32_t a) { asm volatile("st.relaxed.gpu.global.u32 [%0], %1;" ::"l"(p), "r"(a) : "memory"); }
DEVINL void st_strong16(void* p, uint4 v) { asm volatile("st.relaxed.gpu.global.v4.u32 [%0], {%1,%2,%3,%4};" ::"l"(p), "r"(v.x), "r"(v.y), "r"(v.z), "r"(v.w) : "memory"); }
DEVINL uint32_t pack_nz(float lo, float hi) { uint32_t r = pack_bf16(lo, hi); return r == 0u ? 0x8000u : r; }
DEVINL uint32_t min4(uint4 v, uint32_t m) { return __vimin3_u32(__vimin3_u32(v.x, v.y, m), v.z, v.w); }
DEVINL void mma16816(float* d, uint32_t a0, uint32_t a1, uint32_t a2, uint32_t a3, uint32_t b0, uint32_t b1) {
    asm volatile("mma.sync.aligned.m16n8k16.row.col.f32.bf16.bf16.f32 {%0,%1,%2,%3}, {%4,%5,%6,%7}, {%8,%9}, {%0,%1,%2,%3};"
                 : "+f"(d[0]), "+f"(d[1]), "+f"(d[2]), "+f"(d[3]) : "r"(a0), "r"(a1), "r"(a2), "r"(a3), "r"(b0), "r"(b1));
}
DEVINL void mma1688(float* d, uint32_t a0, uint32_t a1, uint32_t b0) {
    asm volatile("mma.sync.aligned.m16n8k8.row.col.f32.bf16.bf16.f32 {%0,%1,%2,%3}, {%4,%5}, {%6}, {%0,%1,%2,%3};"
                 : "+f"(d[0]), "+f"(d[1]), "+f"(d[2]), "+f"(d[3]) : "r"(a0), "r"(a1), "r"(b0));
}
template <int TA, int TB> DEVINL void wg_ss8(float* d, uint64_t da, uint64_t db, int sc) {
    asm volatile("{ .reg .pred p; setp.ne.b32 p, %6, 0; wgmma.mma_async.sync.aligned.m64n8k16.f32.bf16.bf16 {%0,%1,%2,%3}, %4, %5, p, 1, 1, %7, %8; }"
                 : "+f"(d[0]), "+f"(d[1]), "+f"(d[2]), "+f"(d[3]) : "l"(da), "l"(db), "r"(sc), "n"(TA), "n"(TB));
}
template <int TB> DEVINL void wg_rs8(float* d, const uint32_t* a, uint64_t db, int sc) {
    asm volatile("{ .reg .pred p; setp.ne.b32 p, %9, 0; wgmma.mma_async.sync.aligned.m64n8k16.f32.bf16.bf16 {%0,%1,%2,%3}, {%4,%5,%6,%7}, %8, p, 1, 1, %10; }"
                 : "+f"(d[0]), "+f"(d[1]), "+f"(d[2]), "+f"(d[3]) : "r"(a[0]), "r"(a[1]), "r"(a[2]), "r"(a[3]), "l"(db), "r"(sc), "n"(TB));
}
#define ACC16(d) "+f"(d[0]), "+f"(d[1]), "+f"(d[2]), "+f"(d[3]), "+f"(d[4]), "+f"(d[5]), "+f"(d[6]), "+f"(d[7]), "+f"(d[8]), "+f"(d[9]), "+f"(d[10]), "+f"(d[11]), "+f"(d[12]), "+f"(d[13]), "+f"(d[14]), "+f"(d[15])
template <int TA> DEVINL void wg_ss32(float* d, uint64_t da, uint64_t db, int sc) {
    asm volatile("{ .reg .pred p; setp.ne.b32 p, %18, 0; wgmma.mma_async.sync.aligned.m64n32k16.f32.bf16.bf16 {%0,%1,%2,%3,%4,%5,%6,%7,%8,%9,%10,%11,%12,%13,%14,%15}, %16, %17, p, 1, 1, %19, 0; }"
                 : ACC16(d) : "l"(da), "l"(db), "r"(sc), "n"(TA));
}
DEVINL void wg_rs32(float* d, const uint32_t* a, uint64_t db, int sc) {
    asm volatile("{ .reg .pred p; setp.ne.b32 p, %21, 0; wgmma.mma_async.sync.aligned.m64n32k16.f32.bf16.bf16 {%0,%1,%2,%3,%4,%5,%6,%7,%8,%9,%10,%11,%12,%13,%14,%15}, {%16,%17,%18,%19}, %20, p, 1, 1, 0; }"
                 : ACC16(d) : "r"(a[0]), "r"(a[1]), "r"(a[2]), "r"(a[3]), "l"(db), "r"(sc));
}
DEVINL void wg_ss40(float* d, uint64_t da, uint64_t db, int sc) {
    asm volatile("{ .reg .pred p; setp.ne.b32 p, %22, 0; wgmma.mma_async.sync.aligned.m64n40k16.f32.bf16.bf16 {%0,%1,%2,%3,%4,%5,%6,%7,%8,%9,%10,%11,%12,%13,%14,%15,%16,%17,%18,%19}, %20, %21, p, 1, 1, 1, 1; }"
                 : ACC16(d), "+f"(d[16]), "+f"(d[17]), "+f"(d[18]), "+f"(d[19]) : "l"(da), "l"(db), "r"(sc));
}
#define A8(d, o) "+f"(d[o]), "+f"(d[o + 1]), "+f"(d[o + 2]), "+f"(d[o + 3]), "+f"(d[o + 4]), "+f"(d[o + 5]), "+f"(d[o + 6]), "+f"(d[o + 7])
#define A32(d, o) A8(d, o), A8(d, o + 8), A8(d, o + 16), A8(d, o + 24)
DEVINL void wg_ss256(float* d, uint64_t da, uint64_t db, int sc) {
    asm volatile(
        "{ .reg .pred p; setp.ne.b32 p, %130, 0;\n"
        "wgmma.mma_async.sync.aligned.m64n256k16.f32.bf16.bf16 {"
        "%0,%1,%2,%3,%4,%5,%6,%7,%8,%9,%10,%11,%12,%13,%14,%15,%16,%17,%18,%19,%20,%21,%22,%23,%24,%25,%26,%27,%28,%29,%30,%31,"
        "%32,%33,%34,%35,%36,%37,%38,%39,%40,%41,%42,%43,%44,%45,%46,%47,%48,%49,%50,%51,%52,%53,%54,%55,%56,%57,%58,%59,%60,%61,%62,%63,"
        "%64,%65,%66,%67,%68,%69,%70,%71,%72,%73,%74,%75,%76,%77,%78,%79,%80,%81,%82,%83,%84,%85,%86,%87,%88,%89,%90,%91,%92,%93,%94,%95,"
        "%96,%97,%98,%99,%100,%101,%102,%103,%104,%105,%106,%107,%108,%109,%110,%111,%112,%113,%114,%115,%116,%117,%118,%119,%120,%121,%122,%123,%124,%125,%126,%127"
        "}, %128, %129, p, 1, 1, 0, 1; }"
        : A32(d, 0), A32(d, 32), A32(d, 64), A32(d, 96) : "l"(da), "l"(db), "r"(sc));
}

DEVINL float gate_row(const uint4 (&xv)[4], const uint4 (&gv)[4]) {
    float acc = 0.f;
#pragma unroll
    for (int i = 0; i < 4; i++) {
        const uint32_t xa[4] = {xv[i].x, xv[i].y, xv[i].z, xv[i].w}, ga[4] = {gv[i].x, gv[i].y, gv[i].z, gv[i].w};
#pragma unroll
        for (int e = 0; e < 4; e++) {
            acc = fmaf(__uint_as_float(xa[e] << 16), __uint_as_float(ga[e] << 16), acc);
            acc = fmaf(__uint_as_float(xa[e] & 0xffff0000u), __uint_as_float(ga[e] & 0xffff0000u), acc);
        }
    }
#pragma unroll
    for (int o = 16; o > 0; o >>= 1) acc += __shfl_xor_sync(0xffffffffu, acc, o);
    return 1.0f / (1.0f + __expf(-acc));
}
DEVINL uint4 ldg_nc(const void* p) { uint4 v; asm volatile("ld.global.nc.v4.u32 {%0,%1,%2,%3}, [%4];" : "=r"(v.x), "=r"(v.y), "=r"(v.z), "=r"(v.w) : "l"(p) : "memory"); return v; }
DEVINL uint32_t ld_strong4(const void* p) { uint32_t v; asm volatile("ld.relaxed.gpu.global.u32 %0, [%1];" : "=r"(v) : "l"(p) : "memory"); return v; }
DEVINL void wait_count(const uint32_t* p, uint32_t want) {
    uint32_t v, n = 0;
    while (true) {
        asm volatile("ld.acquire.gpu.global.u32 %0, [%1];" : "=r"(v) : "l"(p) : "memory");
        if (v >= want) break;
        __nanosleep(200);
        if (++n > 10000000u) __trap();
    }
}

constexpr int KR = 44;
constexpr int KS = 64 - KR;
constexpr int R_W = 0;
constexpr int R_WO = KS * 4096;
constexpr int R_QX = R_WO + 65536;
constexpr int R_RING = R_WO + 98304;
constexpr int R_K = R_RING + 24576;
constexpr int R_V = R_K + 10240;
constexpr int R_QM = R_V + 10240;
constexpr int R_O = R_QM + 2048;
constexpr int R_BAR = R_O + 2048;
constexpr int R_G = R_BAR + 256 + 512 + 256 + 128;
constexpr int R_Z = R_G + 256;
constexpr int R_SMEM = R_Z + 1024;
enum { B_FULL = 0, B_EMPTY = 5, B_MEM = 8, B_HOP1 = 12, B_XT, B_TFREE, B_O, B_AFREE0, B_AFREE1, B_PRO0, B_PRO1, B_XRECV, B_P, B_XDONE, B_OST0, B_OST1, B_HOPV };
#define D2_BASE 900
#define D2_STEP 200
#define PD2 6
#define CPB 8192
#define DDUP 0
#define WGAP 0
#define PVD 400
#define ELD 700
#define QD 3
#define DQ 1700
#define D3 0

DEVINL uint32_t clk32() { uint32_t c_; asm volatile("mov.u32 %0, %%clock;" : "=r"(c_)); return c_; }
DEVINL void spin_until(uint32_t t) { while ((uint32_t)(t - clk32() - 1u) < 100000u) {} }
#define PROF(i)
#define PROF2(i)
#define PROF3(i, val)
DEVINL void e_arrive(uint32_t bar) { asm volatile("{ .reg .pred p; elect.sync _|p, 0xffffffff; @p mbarrier.arrive.shared::cta.b64 _, [%0]; }" ::"r"(bar) : "memory"); }
DEVINL void e_arrive_remote(uint32_t cbar) { asm volatile("{ .reg .pred p; elect.sync _|p, 0xffffffff; @p mbarrier.arrive.relaxed.cluster.shared::cluster.b64 _, [%0]; }" ::"r"(cbar) : "memory"); }
DEVINL void e_count(uint32_t* p) { asm volatile("{ .reg .pred p; elect.sync _|p, 0xffffffff; @p red.relaxed.gpu.global.add.u32 [%0], 1; }" ::"l"(p) : "memory"); }
DEVINL void e_expect(uint32_t bar, uint32_t bytes) { asm volatile("{ .reg .pred p; elect.sync _|p, 0xffffffff; @p mbarrier.arrive.expect_tx.shared::cta.b64 _, [%0], %1; }" ::"r"(bar), "r"(bytes) : "memory"); }
DEVINL void e_tma_load(uint32_t dst, const CUtensorMap* tm, int c0, int c1, uint32_t bar) {
    asm volatile("{ .reg .pred p; elect.sync _|p, 0xffffffff; @p cp.async.bulk.tensor.2d.shared::cluster.global.mbarrier::complete_tx::bytes [%0], [%1, {%3, %4}], [%2]; }"
                 ::"r"(dst), "l"(tm), "r"(bar), "r"(c0), "r"(c1) : "memory");
}
DEVINL void e_tma_store(const CUtensorMap* tm, uint32_t src, int c0, int c1) {
    asm volatile("{ .reg .pred p; elect.sync _|p, 0xffffffff; @p cp.async.bulk.tensor.2d.global.shared::cta.bulk_group [%0, {%2, %3}], [%1]; }" ::"l"(tm), "r"(src), "r"(c0), "r"(c1) : "memory");
}
DEVINL void e_bulk_s2g(void* dst, uint32_t src, uint32_t bytes) {
    asm volatile("{ .reg .pred p; elect.sync _|p, 0xffffffff; @p cp.async.bulk.global.shared::cta.bulk_group [%0], [%1], %2; }" ::"l"(dst), "r"(src), "r"(bytes) : "memory");
}
DEVINL void e_bulk_s2s(uint32_t cdst, uint32_t src, uint32_t bytes, uint32_t cbar) {
    asm volatile("{ .reg .pred p; elect.sync _|p, 0xffffffff; @p cp.async.bulk.shared::cluster.shared::cta.mbarrier::complete_tx::bytes [%0], [%1], %2, [%3]; }" ::"r"(cdst), "r"(src), "r"(bytes), "r"(cbar) : "memory");
}

#define SLOT 0
#define PH3 0
#define PHQ 0
DEVINL void wait_slot(uint32_t phase) {
    if (SLOT) {
        uint32_t c; asm volatile("mov.u32 %0, %%globaltimer_lo;" : "=r"(c));
        const uint32_t tgt = c + (SLOT ? SLOT : 1) - ((c - phase) % (SLOT ? SLOT : 1));
        do { asm volatile("mov.u32 %0, %%globaltimer_lo;" : "=r"(c)); } while ((uint32_t)(tgt - c - 1u) < 100000u);
    }
}
template <int N> DEVINL uint32_t poll_set(uint4 (&v)[N], const uint32_t* rp, int stride, uint32_t phase, uint32_t wbar = 0, uint32_t wpar = 0) {
    wait_slot(phase);
#pragma unroll
    for (int i = 0; i < N; i++) v[i] = ld_strong16(rp + i * stride);
    if (wbar) mbar_wait(wbar, wpar);
    uint32_t n = 0;
    while (true) {
        uint32_t m = 0xffffffffu;
#pragma unroll
        for (int i = 0; i < N; i++) m = min4(v[i], m);
        if (__all_sync(0xffffffffu, m != 0u)) return n;
        wait_slot(phase);
#pragma unroll
        for (int i = 0; i < N; i++)
            asm volatile("{ .reg .pred p; setp.eq.u32 p, %5, 0; @p ld.relaxed.gpu.global.v4.u32 {%0,%1,%2,%3}, [%4]; }"
                         : "+r"(v[i].x), "+r"(v[i].y), "+r"(v[i].z), "+r"(v[i].w) : "l"(rp + i * stride), "r"(min4(v[i], 0xffffffffu)) : "memory");
        if (++n > 20000000u) __trap();
    }
}

struct RMaps { CUtensorMap x, w[3], wo, o; };
#define KC(c) ((c) * 64)

#define XORD 3
__host__ __device__ constexpr int xo(int i) {
    return XORD == 0 ? i : XORD == 1 ? (i + 14) % 16 : XORD == 2 ? (i + 11) % 16
         : XORD == 3 ? (i < 10 ? ((i & 1) ? i / 2 : 11 + i / 2) : i - 5) : (i < 6 ? i : ((i & 1) ? 6 + (i - 6) / 2 : 11 + (i - 6) / 2));
}
#define XC(i) (xo(i) * 64)
DEVINL void x_load_pair(uint32_t dst, const CUtensorMap* tmx, int h, int p, int seg, uint32_t fbar) {
    e_expect(fbar, 8192);
    e_tma_load(dst, tmx, XC(2 * p), seg * SEG, fbar);
    e_tma_load(dst + 4096, tmx, XC(2 * p + 1), seg * SEG, fbar);
}
__host__ __device__ constexpr int wo_tile(int role, int i) {
    return role == 0 ? (i < 2 ? 8 + i : 12 + i) : (i < 4 ? (i >> 1) * 4 : 10) + (role - 1) * 2 + (i & 1);
}

template <int NT> DEVINL void wo_phase(uint32_t sb, int tb, uint32_t* pp, uint32_t obar, uint32_t opar) {
    const int lane = tb & 31, krow = (lane & 7) + ((lane >> 4) << 3), chunk = ((tb >> 5) & 3) * 2 + ((lane >> 3) & 1);
    uint32_t wa = sb + R_WO + (tb >> 7) * 16384 + krow * 128 + ((chunk ^ (krow & 7)) << 4);
    uint32_t af[4][4], of[4][4];
#pragma unroll
    for (int g = 0; g < 4; g++) ldsm4t(af[g], wa + g * 2048);
    mbar_wait(obar, opar);
#pragma unroll
    for (int g = 0; g < 4; g++) ldsm4t(of[g], sb + R_O + g * 512 + lane * 16);
#pragma unroll 1
    for (int i = 0; i < NT; i++) {
        float w0[4] = {0.f, 0.f, 0.f, 0.f}, w1[4] = {0.f, 0.f, 0.f, 0.f};
        const int more = NT - 1 - i, yes = NT - i;
        mma16816(w0, af[0][0], af[0][1], af[0][2], af[0][3], of[0][0], of[0][1]);
        ldsm4t_if(af[0], wa + 4 * 2048, yes);
        mma16816(w1, af[1][0], af[1][1], af[1][2], af[1][3], of[0][2], of[0][3]);
        ldsm4t_if(af[1], wa + 5 * 2048, yes);
        mma16816(w0, af[2][0], af[2][1], af[2][2], af[2][3], of[1][0], of[1][1]);
        ldsm4t_if(af[2], wa + 6 * 2048, yes);
        mma16816(w1, af[3][0], af[3][1], af[3][2], af[3][3], of[1][2], of[1][3]);
        ldsm4t_if(af[3], wa + 7 * 2048, yes);
        wa += 32768;
        mma16816(w0, af[0][0], af[0][1], af[0][2], af[0][3], of[2][0], of[2][1]);
        ldsm4t_if(af[0], wa, more);
        mma16816(w1, af[1][0], af[1][1], af[1][2], af[1][3], of[2][2], of[2][3]);
        ldsm4t_if(af[1], wa + 2048, more);
        mma16816(w0, af[2][0], af[2][1], af[2][2], af[2][3], of[3][0], of[3][1]);
        ldsm4t_if(af[2], wa + 2 * 2048, more);
        mma16816(w1, af[3][0], af[3][1], af[3][2], af[3][3], of[3][2], of[3][3]);
        ldsm4t_if(af[3], wa + 3 * 2048, more);
        st_strong4(pp, pack_nz(w0[0] + w1[0], w0[1] + w1[1]));
        st_strong4(pp + 1024, pack_nz(w0[2] + w1[2], w0[3] + w1[3]));
        pp += (NT == 3 && i == 0) ? 4 * 8192 : 6 * 8192;
    }
}

template <uint32_t role> DEVINL void r_big(const RMaps& tm, const int wid) {
    extern __shared__ __align__(1024) unsigned char smem_raw[];
    const uint32_t sb = smem_u32(smem_raw);
    const uint32_t bar = sb + R_BAR;
    const int tid = threadIdx.x;
    int h; asm("mov.u32 %0, %%clusterid.x;" : "=r"(h));
        uint32_t a[KR][4];
        mbar_wait(bar + 8 * B_PRO0, 0);
        PT(0);
        {
            const int lane = tid & 31;
            const int krow = (lane & 7) + ((lane >> 4) << 3);
            const int chunk = (wid & 3) * 2 + ((lane >> 3) & 1);
            const uint32_t la = sb + (wid >> 2) * 8192 + krow * 128 + ((chunk ^ (krow & 7)) << 4);
#pragma unroll
            for (int k = 0; k < KR; k++) ldsm4t(a[k], la + (k >> 2) * 16384 + (k & 3) * 2048);
        }
        bar_sync(1, 256);
        {
            fence_async();
            const CUtensorMap* tw = &tm.w[role];
            e_expect(bar + 8 * B_PRO1, (wid < 5 ? 16384 : 0) + (wid < (role == 0 ? 4 : 6) ? 16384 : 0));
            if (wid < 5) {
                e_tma_load(sb + R_W + wid * 8192, tw, h * DH, KC(KR / 4 + wid), bar + 8 * B_PRO1);
                e_tma_load(sb + R_W + KS * 2048 + wid * 8192, tw, h * DH + 64, KC(KR / 4 + wid), bar + 8 * B_PRO1);
            }
            if (wid < (role == 0 ? 4 : 6)) e_tma_load(sb + R_WO + wid * 16384, &tm.wo, wo_tile(role, wid) * 64, h * DH, bar + 8 * B_PRO1);
        }
        constexpr uint32_t e0 = role == 0 ? R_QX + 16384 : R_K + 2048, e1 = role == 0 ? R_QX + 24576 : R_V + 2048;
        if (wid == 6) x_load_pair(sb + e0, &tm.x, h, 3, 0, bar + 8 * (B_FULL + 3));
        if (wid == 7) x_load_pair(sb + e1, &tm.x, h, 4, 0, bar + 8 * (B_FULL + 4));
        PT(1);
        mbar_wait(bar + 8 * B_PRO1, 0);
        PT(2);

        constexpr uint64_t dW0 = cdesc(R_W, 1024, 1024, 1);
        constexpr uint64_t dM = cdesc(R_RING, 128, 128, 0);
        constexpr uint64_t dX = cdesc(R_RING, 16, 1024, 1);
        constexpr uint64_t dX0 = cdesc(0, 16, 1024, 1);
        int tb = tid;
        int wq = wid;

        for (int seg = 0; seg < NSEG; seg++) {
            {
            const int s = seg - 1; (void)s;
            float d[16];
            OPAQUE(wq);
            const uint64_t dW = dW0 + (uint64_t)((wq >> 2) * (KS * 128));
#pragma unroll
            for (int p = 0; p < 8; p++) {
                const int slot = p % 5;
                mbar_wait(bar + 8 * (B_FULL + slot), slot < 3 ? (uint32_t)(p / 5) : (uint32_t)(seg & 1));
                PROF2(p);
                const uint64_t db = slot < 3 ? dX + (uint64_t)(slot * 512) : dX0 + (uint64_t)((slot == 3 ? e0 : e1) >> 4);
                wg_fence();
#pragma unroll
                for (int kk = 0; kk < 8; kk++) {
                    const int k = XORD >= 3 ? (kk & 1) * 4 + (kk >> 1) : kk;
                    const int ks = xo(2 * p + (k >> 2)) * 4 + (k & 3);
                    if (ks >= KR) wg_ss32<1>(d, dW + (uint64_t)((ks - KR) * 128), db + (uint64_t)((k >> 2) * 256 + (k & 3) * 2), p + k);
                    else wg_rs32(d, a[ks < KR ? ks : 0], db + (uint64_t)((k >> 2) * 256 + (k & 3) * 2), p + k);
                }
                wg_commit();
                if (p >= 1) {
                    wg_wait<1>();
                    if (p <= 3) {
                        if ((wq & 3) == p) e_arrive(bar + 8 * (B_EMPTY + p - 1));
                        if (wq == p + (p & 1) * 4) {
                            mbar_wait(bar + 8 * (B_EMPTY + p - 1), seg & 1);
                            x_load_pair(sb + R_RING + (p - 1) * 8192, &tm.x, h, p + 4, seg, bar + 8 * (B_FULL + p - 1));
                        }
                    }
                    if (p == 5 && role != 0 && (wq & 3) < 3) e_arrive_remote(mapa(bar + 8 * B_TFREE, wq & 3));
                    if (p == 6 && (wq & 3) == 1) e_arrive(bar + 8 * B_AFREE0);
                    if (p == 7 && (wq & 3) == 2) e_arrive(bar + 8 * B_AFREE1);
                }
            }
            mbar_wait(bar + 8 * B_TFREE, seg & 1);
            asm volatile("wgmma.wait_group.sync.aligned 0;" : ACC16(d)::"memory");
            PROF2(16);
            const uint32_t tilex = sb + (role == 0 ? R_QX + 2048 : (role == 1 ? R_K + 2048 : R_V + 2048));
            {
                OPAQUE(tb);
                const uint32_t gs = role == 0 ? 4096 : 2048;
                const uint32_t sa = tilex + ((tb >> 4) & 1) * gs + (tb >> 5) * 256 + (tb & 15) * 16;
                stsm4(sa, pack_bf16(d[0], d[1]), pack_bf16(d[2], d[3]), pack_bf16(d[4], d[5]), pack_bf16(d[6], d[7]));
                stsm4(sa + 2 * gs, pack_bf16(d[8], d[9]), pack_bf16(d[10], d[11]), pack_bf16(d[12], d[13]), pack_bf16(d[14], d[15]));
            }
            __syncwarp();
            e_arrive(bar + 8 * B_XDONE);
            if (role != 0 && (wq & 3) == 0) {
                mbar_wait(bar + 8 * B_XDONE, seg & 1);
                fence_async();
                uint32_t pr = role + 1 + (wq >> 2); pr = pr >= 3 ? pr - 3 : pr;
                e_bulk_s2s(mapa(tilex, pr), tilex, CPB, mapa(bar + 8 * B_XT, pr));
            }
            }
            {
                const int s = seg;
                OPAQUE(wq);
                const uint64_t dW = dW0 + (uint64_t)((wq >> 2) * (KS * 128));
                float y[4] = {0.f, 0.f, 0.f, 0.f};
                {
                    OPAQUE(tb);
                    const uint32_t ma = sb + R_RING + (tb & 31) * 16;
                    float z[4] = {0.f, 0.f, 0.f, 0.f}, u[4] = {0.f, 0.f, 0.f, 0.f};
                    uint32_t b[QD][4];
                    const int yes = s + 1;
                    mbar_wait(bar + 8 * B_MEM, s & 1);
                    PROF((wq >> 2) * 4 + 0);
                    if (s == 0) PT(3);
                    if (s == 1) PT(4);
#pragma unroll
                    for (int g = 0; g < QD; g++) ldsm4t(b[g], ma + g * 512);
#pragma unroll
                    for (int g = 0; g < KR / 2; g++) {
                        float* c0 = (g % 3 == 0) ? y : (g % 3 == 1) ? u : z;
                        float* c1 = (g % 3 == 0) ? z : (g % 3 == 1) ? y : u;
                        mma16816(c0, a[2 * g][0], a[2 * g][1], a[2 * g][2], a[2 * g][3], b[g % QD][0], b[g % QD][1]);
                        mma16816(c1, a[2 * g + 1][0], a[2 * g + 1][1], a[2 * g + 1][2], a[2 * g + 1][3], b[g % QD][2], b[g % QD][3]);
                        if (g + QD < KR / 2) {
                            if ((g + QD) % 8 == 0) mbar_wait(bar + 8 * (B_MEM + (g + QD) / 8), s & 1);
                            ldsm4t_if(b[g % QD], ma + (g + QD) * 512, yes);
                        }
                    }
                    y[0] += z[0] + u[0]; y[1] += z[1] + u[1]; y[2] += z[2] + u[2]; y[3] += z[3] + u[3];
                }
                PROF2(8);
                mbar_wait(bar + 8 * (B_MEM + 3), s & 1);
                wg_fence();
#pragma unroll
                for (int k = KR; k < 64; k++) wg_ss8<1, 1>(y, dW + (uint64_t)((k - KR) * 128), dM + (uint64_t)(k * 16), 1);
                wg_commit();
                asm volatile("wgmma.wait_group.sync.aligned 0;" : "+f"(y[0]), "+f"(y[1]), "+f"(y[2]), "+f"(y[3])::"memory");
                OPAQUE(tb);
                {
                    const uint32_t wo_ = (tb >> 5) * 256;
                    const uint32_t tile = sb + (role == 0 ? R_QX : (role == 1 ? R_K : R_V)) + wo_;
                    const uint32_t u0 = pack_bf16(y[0], y[1]), u1 = pack_bf16(y[2], y[3]);
                    sts32(tile + (tb & 31) * 4, u0);
                    sts32(tile + (tb & 31) * 4 + 128, u1);
                    __syncwarp();
                    uint4 v = lds128(tile + (tb & 15) * 16);
                    uint32_t peer = role + 1 + ((tb >> 4) & 1);
                    peer = peer >= 3 ? peer - 3 : peer;
                    const uint32_t rt = sb + (role == 0 ? R_QM : (role == 1 ? R_K : R_V)) + wo_ + (tb & 15) * 16;
                    st_async16(mapa(rt, peer), v, mapa(bar + 8 * (role == 2 ? B_HOPV : B_HOP1), peer));
                    if (role == 0) {
                        sts128(tile + 4096 + ((tb >> 4) & 1) * 4096 + (tb & 15) * 16, v);
                        sts32(tile + 12288 + (tb & 31) * 4, u0);
                        sts32(tile + 12288 + (tb & 31) * 4 + 128, u1);
                        __syncwarp();
                    }
                    e_arrive(bar + 8 * (role == 2 ? B_HOPV : B_HOP1));
                }
                PROF((wq >> 2) * 4 + 1);
                if (s < NSEG - 1) {
                    bar_sync(1, 256);
                    if (wq < 3) { fence_async(); x_load_pair(sb + R_RING + wq * 8192, &tm.x, h, wq, s + 1, bar + 8 * (B_FULL + wq)); }
                    else if (role == 0 && wq < 5) x_load_pair(sb + (wq == 3 ? e0 : e1), &tm.x, h, wq, s + 1, bar + 8 * (B_FULL + wq));
                    OPAQUE(tb);
                }
                uint32_t* pp = g_part[s & 3] + (h * 32 + (wo_tile(role, 0) + (tb >> 7)) * 8192 + ((tb >> 5) & 3) * 2048 + (tb & 31));
                asm volatile("" : "+l"(pp));
                if (s == NSEG - 1) break;
                wo_phase<role == 0 ? 2 : 3>(sb, tb, pp, bar + 8 * B_O, s & 1);
                if (wq == 0) PROF(10);
            }
        }
}

#define CLR 0
#define CLEAR(st) do { if (role != 0) { \
                const int w_ = wid & 3; \
                uint32_t* zp = g_part[(st) & 3] + ((rg0 + (w_ >> 1) * 64) * 1024 + (w_ & 1) * 512); \
                e_bulk_s2g(zp, sb + R_Z, 1024); \
                e_bulk_s2g(zp + 256, sb + R_Z, 1024); \
                e_bulk_s2g(&g_mem[(st) & 3][(rg0 + (w_ >> 1) * 64) * 32 + (w_ & 1) * 16], sb + R_Z, 64); \
                bulk_commit(); } } while (0)
template <uint32_t role> DEVINL void r_chain(const RMaps& tm, const bf16* __restrict__ mem0, const int wid) {
    extern __shared__ __align__(1024) unsigned char smem_raw[];
    const uint32_t sb = smem_u32(smem_raw);
    const uint32_t bar = sb + R_BAR;
    const int tid = threadIdx.x;
    int h; asm("mov.u32 %0, %%clusterid.x;" : "=r"(h));
        int t = tid & 127;
        const float sl2 = 0.08838834764831845f * 1.4426950408889634f;
        const float NEGRAW = -1000000000.0f / 0.08838834764831845f;
        const int rg0 = ((int)role - 1) * 32 + h;
        if (role != 0) {
#pragma unroll 1
            for (int r = 0; r < 4; r++) {
                uint32_t* zp = g_part[r] + ((rg0 + (t >> 6) * 64) * 1024 + (t & 63) * 4);
#pragma unroll
                for (int i = 0; i < 4; i++) st_strong16(zp + i * 256, make_uint4(0u, 0u, 0u, 0u));
                if ((t & 63) < 8) st_strong16(&g_mem[r][(rg0 + (t >> 6) * 64) * 32 + (t & 63) * 4], make_uint4(0u, 0u, 0u, 0u));
            }
            __threadfence();
        }
        if (role == 0 && (wid & 3) < 3) e_arrive_remote(mapa(bar + 8 * B_TFREE, wid & 3));
        if (t < 64) sts128(sb + R_Z + t * 16, make_uint4(0u, 0u, 0u, 0u));
        if (role == 0) sts128(sb + R_QM + t * 16, make_uint4(0u, 0u, 0u, 0u));
        {
            uint4 v[8];
#pragma unroll
            for (int r = 0; r < 8; r++) v[r] = __ldg((const uint4*)(mem0 + r * DM) + t);
            mbar_wait(bar + 8 * B_AFREE0, 0);
            mbar_wait(bar + 8 * B_AFREE1, 0);
#define TR2(f, c) \
            sts128(sb + R_RING + t * 128 + (c) * 16, make_uint4(__byte_perm(v[0].f, v[1].f, 0x5410), __byte_perm(v[2].f, v[3].f, 0x5410), __byte_perm(v[4].f, v[5].f, 0x5410), __byte_perm(v[6].f, v[7].f, 0x5410))); \
            sts128(sb + R_RING + t * 128 + (c) * 16 + 16, make_uint4(__byte_perm(v[0].f, v[1].f, 0x7632), __byte_perm(v[2].f, v[3].f, 0x7632), __byte_perm(v[4].f, v[5].f, 0x7632), __byte_perm(v[6].f, v[7].f, 0x7632)));
            TR2(x, 0) TR2(y, 2) TR2(z, 4) TR2(w, 6)
            fence_async();
            __syncwarp();
            e_arrive(bar + 8 * B_MEM + (t >> 5) * 8);
        }
        constexpr uint64_t dQ = role == 0 ? cdesc(R_QX, 128, 2048, 0) : cdesc(R_QM, 128, 0, 0);
        constexpr uint64_t dK = cdesc(R_K, 128, 2048, 0);

        for (int s = 0; s < NSEG; s++) {
            if (role == 0) {
                uint32_t n = 0, gate;
                do { gate = ld_strong4(&g_gate[s * SEG + (t >> 2)]); if (++n > 20000000u) __trap(); } while (gate == 0u);
                sts32(sb + R_G + (t >> 2) * 4, gate);
                __syncwarp();
            }
            mbar_wait(bar + 8 * B_XDONE, s & 1);
            mbar_wait(bar + 8 * B_XT, s & 1);
            if (t >= 1 && t < 3) { uint32_t pr = role + t; pr = pr >= 3 ? pr - 3 : pr; mbar_arrive_remote(mapa(bar + 8 * B_XRECV, pr)); }
            __syncwarp();
            mbar_wait(bar + 8 * B_HOP1, s & 1);
            PROF(8);
            fence_async();
            OPAQUE(t);
            if (s == NSEG - 1 && role != 0) { mbar_wait(bar + 8 * B_HOPV, s & 1); bulk_wait_all(); break; }
            float sc[20];
            wg_fence();
#pragma unroll
            for (int k = 0; k < 8; k++) wg_ss40(sc, dQ + (uint64_t)(k * 16), dK + (uint64_t)(k * 16), k);
            wg_commit();
            uint32_t t_o = clk32() + 500;
            {
                const uint32_t va = sb + R_V + 2048 + (t >> 5) * 512 + ((t >> 4) & 1) * 2048 + (t & 15) * 16;
                uint32_t v0[4], v1[4];
                ldsm4(v0, va); ldsm4(v1, va + 256);
                uint32_t vm[4];
                const bool v_here = mbar_try(bar + 8 * B_HOPV, s & 1);
                if (v_here) ldsm4(vm, sb + R_V + t * 16);
                wg_wait<0>();
                if (role == 0) {
#pragma unroll
                    for (int j = 0; j < 5; j++)
                        asm volatile("st.shared.v2.f32 [%0], {%1,%2};" ::"r"(sb + R_QX + 768 + (t >> 5) * 4096 + j * 256 + (t & 31) * 8), "f"(sc[4 * j + 2]), "f"(sc[4 * j + 3]) : "memory");
                }
                float m = fmaxf(sc[0], sc[1]);
#pragma unroll
                for (int j = 1; j < 5; j++) m = fmaxf(m, fmaxf(sc[4 * j], sc[4 * j + 1]));
                m = fmaxf(m, __shfl_xor_sync(0xffffffffu, m, 1));
                m = fmaxf(m, __shfl_xor_sync(0xffffffffu, m, 2));
                const float mb = m * sl2;
                uint32_t pk[5];
#pragma unroll
                for (int j = 0; j < 5; j++) pk[j] = pack_bf16(ex2(fmaf(sc[4 * j], sl2, -mb)), ex2(fmaf(sc[4 * j + 1], sl2, -mb)));
                float o0[4] = {0.f, 0.f, 0.f, 0.f}, o1[4] = {0.f, 0.f, 0.f, 0.f}, ls[4] = {0.f, 0.f, 0.f, 0.f};
                constexpr uint32_t ONE = 0x3F803F80u;
                mma16816(o0, v0[0], v0[1], v0[2], v0[3], pk[1], pk[2]);
                mma16816(o1, v1[0], v1[1], v1[2], v1[3], pk[1], pk[2]);
                ldsm4(v0, va + 4096); ldsm4(v1, va + 4096 + 256);
                mma16816(ls, ONE, ONE, ONE, ONE, pk[1], pk[2]);
                mma16816(ls, ONE, ONE, ONE, ONE, pk[3], pk[4]);
                mma1688(ls, ONE, ONE, pk[0]);
                mma16816(o0, v0[0], v0[1], v0[2], v0[3], pk[3], pk[4]);
                mma16816(o1, v1[0], v1[1], v1[2], v1[3], pk[3], pk[4]);
                if (!v_here) { mbar_wait(bar + 8 * B_HOPV, s & 1); ldsm4(vm, sb + R_V + t * 16); }
                mma1688(o0, vm[0], vm[1], pk[0]);
                mma1688(o1, vm[2], vm[3], pk[0]);
                const float i0 = rcp(ls[0]), i1 = rcp(ls[1]);
                const uint32_t oa = sb + R_O + (t >> 5) * 512 + (t & 31) * 4;
                sts32(oa, pack_bf16(o0[0] * i0, o0[1] * i1));
                sts32(oa + 128, pack_bf16(o0[2] * i0, o0[3] * i1));
                sts32(oa + 256, pack_bf16(o1[0] * i0, o1[1] * i1));
                sts32(oa + 384, pack_bf16(o1[2] * i0, o1[3] * i1));
                __syncwarp();
                e_arrive(bar + 8 * B_O);
                PROF(9);
                if (role == 0) {
                    OPAQUE(t);
                    const int lim = (t >> 2) - (t & 3) * 2 + 8;
                    float z[10];
#pragma unroll
                    for (int j = 0; j < 5; j++)
                        asm volatile("ld.shared.v2.f32 {%0,%1}, [%2];" : "=f"(z[2 * j]), "=f"(z[2 * j + 1]) : "r"(sb + R_QX + 768 + (t >> 5) * 4096 + j * 256 + (t & 31) * 8) : "memory");
                    float gate; asm volatile("ld.shared.f32 %0, [%1];" : "=f"(gate) : "r"(sb + R_G + (t >> 2) * 4) : "memory");
                    float m1 = fmaxf(z[0], z[1]);
#pragma unroll
                    for (int j = 1; j < 5; j++) {
                        z[2 * j] = 8 * j <= lim ? z[2 * j] : NEGRAW;
                        z[2 * j + 1] = 8 * j + 1 <= lim ? z[2 * j + 1] : NEGRAW;
                        m1 = fmaxf(m1, fmaxf(z[2 * j], z[2 * j + 1]));
                    }
                    m1 = fmaxf(m1, __shfl_xor_sync(0xffffffffu, m1, 1));
                    m1 = fmaxf(m1, __shfl_xor_sync(0xffffffffu, m1, 2));
                    const float mb1 = m1 * sl2;
                    float l1 = 0.f;
                    const uint32_t pa = sb + R_QX + (t >> 5) * 4096 + (t & 31) * 4;
#pragma unroll
                    for (int j = 0; j < 5; j++) {
                        const uint32_t pw = pack_bf16(ex2(fmaf(z[2 * j], sl2, -mb1)), ex2(fmaf(z[2 * j + 1], sl2, -mb1)));
                        l1 += __uint_as_float(pw << 16) + __uint_as_float(pw & 0xffff0000u);
                        sts32(pa + j * 128, pw);
                    }
                    sts32(pa + 5 * 128, 0u);
                    l1 += __shfl_xor_sync(0xffffffffu, l1, 1);
                    l1 += __shfl_xor_sync(0xffffffffu, l1, 2);
                    sts32(sb + R_G + 128 + (t >> 2) * 4, __float_as_uint(gate * rcp(l1)));
                    spin_until(t_o + PVD);
                    if ((wid & 3) == 0 && s >= 1) { bulk_wait_all(); e_count(&g_ocnt[(s - 1) >> 2]); }
                    fence_async();
                    bar_sync(2, 128);
                    constexpr uint64_t dV = cdesc(R_V, 2048, 128, 0);
                    constexpr uint64_t dP = cdesc(R_QX, 128, 4096, 0);
                    float sf[8];
#pragma unroll
                    for (int j = 0; j < 4; j++) asm volatile("ld.shared.v2.f32 {%0,%1}, [%2];" : "=f"(sf[2 * j]), "=f"(sf[2 * j + 1]) : "r"(sb + R_G + 128 + j * 32 + (t & 3) * 8) : "memory");
                    const uint32_t r = ((t >> 4) & 1) * 8 + (t & 7), ch = (t >> 5) * 2 + ((t >> 3) & 1);
                    const uint32_t sa = sb + R_QX + 2048 + r * 128 + ((ch ^ (r & 7)) << 4);
#pragma unroll
                    for (int hf = 0; hf < 2; hf++) {
                        float d[16];
                        wg_fence();
#pragma unroll
                        for (int k = 0; k < 3; k++) wg_ss32<0>(d, dV + (uint64_t)(hf * 64 + k * 256), dP + (uint64_t)(k * 16), k);
                        wg_commit();
                        asm volatile("wgmma.wait_group.sync.aligned 0;" : ACC16(d)::"memory");
                        stsm4t(sa + hf * 8192, pack_bf16(d[0] * sf[0], d[1] * sf[1]), pack_bf16(d[2] * sf[0], d[3] * sf[1]), pack_bf16(d[4] * sf[2], d[5] * sf[3]), pack_bf16(d[6] * sf[2], d[7] * sf[3]));
                        stsm4t(sa + hf * 8192 + 4096, pack_bf16(d[8] * sf[4], d[9] * sf[5]), pack_bf16(d[10] * sf[4], d[11] * sf[5]), pack_bf16(d[12] * sf[6], d[13] * sf[7]), pack_bf16(d[14] * sf[6], d[15] * sf[7]));
                    }
                    fence_async();
                    bar_sync(2, 128);
                    if ((wid & 3) == 0) {
#pragma unroll
                        for (int q = 0; q < 4; q++) e_tma_store(&tm.o, sb + R_QX + 2048 + q * 4096, h * DH + (q >> 1) * 64, s * SEG + (q & 1) * 16);
                        bulk_commit();
                        bulk_wait_read();
                    }
                    if ((wid & 3) < 3) e_arrive_remote(mapa(bar + 8 * B_TFREE, wid & 3));
                }
            }
            if (t < 32) { e_expect(bar + 8 * B_HOP1, role == 2 ? 4096 : 2048); if (role != 2) e_expect(bar + 8 * B_HOPV, 2048); e_expect(bar + 8 * B_XT, role == 0 ? 2 * CPB : CPB); }
            if (s == NSEG - 1) { bulk_wait_all(); break; }
            if (role != 0 && (wid & 3) >= 2) {
                mbar_wait(bar + 8 * B_XRECV, s & 1);
                mbar_wait(bar + 8 * B_O, s & 1);
                fence_async();
                spin_until(t_o + ELD);
                x_load_pair(sb + ((wid & 1) ? R_V + 2048 : R_K + 2048), &tm.x, h, 3 + (wid & 1), s + 1, bar + 8 * (B_FULL + 3 + (wid & 1)));
            }
            OPAQUE(t);
            PROF(11);
            if (role != 0 || DDUP) {
                const int grp = role == 0 ? (t >> 6) * 32 + h : rg0 + (t >> 6) * 64;
                const uint32_t* rp = g_part[s & 3] + (grp * 1024 + ((t >> 2) & 7) * 32 + ((t >> 5) & 1) * 16 + (t & 3) * 4);
                uint32_t* wp = &g_mem[(s + 1) & 3][grp * 32 + ((t >> 5) & 1) * 16 + (t & 3) * 4 + ((t >> 3) & 3)];
                bulk_wait_all();
                spin_until(t_o + D2_BASE + (role == 0 ? DDUP + (t >> 6) * D2_STEP : (role - 1 + (t >> 6) * 2) * D2_STEP));
                PROF3(0, clk32());
#define LO(u) __uint_as_float((u) << 16)
#define HI(u) __uint_as_float((u) & 0xffff0000u)
                uint4 v[4];
                uint32_t n = poll_set<4>(v, rp, 256, (role - 1 + (t >> 6) * 2) * PHQ);
                {
                    PROF3(1, clk32());
                    float f[8];
                    f[0] = (LO(v[0].x) + LO(v[1].x)) + (LO(v[2].x) + LO(v[3].x)); f[1] = (HI(v[0].x) + HI(v[1].x)) + (HI(v[2].x) + HI(v[3].x));
                    f[2] = (LO(v[0].y) + LO(v[1].y)) + (LO(v[2].y) + LO(v[3].y)); f[3] = (HI(v[0].y) + HI(v[1].y)) + (HI(v[2].y) + HI(v[3].y));
                    f[4] = (LO(v[0].z) + LO(v[1].z)) + (LO(v[2].z) + LO(v[3].z)); f[5] = (HI(v[0].z) + HI(v[1].z)) + (HI(v[2].z) + HI(v[3].z));
                    f[6] = (LO(v[0].w) + LO(v[1].w)) + (LO(v[2].w) + LO(v[3].w)); f[7] = (HI(v[0].w) + HI(v[1].w)) + (HI(v[2].w) + HI(v[3].w));
                    const bool b4 = t & 16, b3 = t & 8;
                    float g4[4], g2[2];
#pragma unroll
                    for (int i = 0; i < 4; i++) g4[i] = (b4 ? f[4 + i] : f[i]) + __shfl_xor_sync(0xffffffffu, b4 ? f[i] : f[4 + i], 16);
#pragma unroll
                    for (int i = 0; i < 2; i++) g2[i] = (b3 ? g4[2 + i] : g4[i]) + __shfl_xor_sync(0xffffffffu, b3 ? g4[i] : g4[2 + i], 8);
                    g2[0] += __shfl_xor_sync(0xffffffffu, g2[0], 4);
                    g2[1] += __shfl_xor_sync(0xffffffffu, g2[1], 4);
                    st_strong4(wp, pack_nz(g2[0], g2[1]));
                }
                PROF3(8, n); (void)n;
            }
            t_o += D2_BASE + DQ + D3 + (t >> 5) * D2_STEP;
            OPAQUE(t);
            PROF(12);
            {
                const uint32_t* rp = &g_mem[(s + 1) & 3][((t >> 5) * 256 + (t & 31)) * 4];
                const uint32_t da = sb + R_RING + ((t >> 5) * 256 + (t & 31)) * 16;
                uint4 v[8];
                spin_until(t_o);
                PROF3(2, clk32());
                uint32_t n = poll_set<8>(v, rp, 128, PH3 + (t >> 5) * PHQ);
                PROF(13);
                PROF3(3, clk32()); PROF3(9, n); (void)n;
                mbar_wait(bar + 8 * B_AFREE0 + (t >> 6) * 8, (s + 1) & 1);
                PROF3(4, clk32());
#pragma unroll
                for (int i = 0; i < 8; i++) sts128(da + i * 512, v[i]);
                if (t >= 64) fence_async();
                __syncwarp();
                e_arrive(bar + 8 * B_MEM + (t >> 5) * 8);
                PROF(14);
                PROF3(5, clk32());
            }
            CLEAR(s + 3);
        }
}

__global__ void __launch_bounds__(384, 1) r_kernel(const __grid_constant__ RMaps tm, const bf16* __restrict__ mem0, const bf16* __restrict__ x, const bf16* __restrict__ gate_w) {
    extern __shared__ __align__(1024) unsigned char smem_raw[];
    const uint32_t sb = smem_u32(smem_raw);
    if ((sb & 0x3FFFFu) != SB0) __trap();
    const int tid = threadIdx.x;
    const int wid = __shfl_sync(0xffffffffu, tid >> 5, 0);
    uint32_t role; asm("mov.u32 %0, %%cluster_ctarank;" : "=r"(role));
    int h; asm("mov.u32 %0, %%clusterid.x;" : "=r"(h));
    const uint32_t bar = sb + R_BAR;
    asm volatile("griddepcontrol.launch_dependents;");
    KT(0, 0);
    const int gr = blockIdx.x * 12 + wid;
    uint4 gx0[4], gx1[4], gw[4];
#pragma unroll
    for (int i = 0; i < 4; i++) {
        gx0[i] = ldg_nc((const uint4*)(x + gr * DM) + i * 32 + (tid & 31));
        gx1[i] = ldg_nc((const uint4*)(x + min(gr + 1152, SEQ - 1) * DM) + i * 32 + (tid & 31));
        gw[i] = ldg_nc((const uint4*)gate_w + i * 32 + (tid & 31));
    }

    if (tid == 0) {
        for (int i = 0; i < 5; i++) mbar_init(bar + 8 * (B_FULL + i), 1);
        for (int i = 0; i < 3; i++) mbar_init(bar + 8 * (B_EMPTY + i), 2);
        for (int i = 0; i < 4; i++) mbar_init(bar + 8 * (B_MEM + i), 1);
        mbar_init(bar + 8 * B_HOP1, role == 2 ? 1 : 9);
        mbar_init(bar + 8 * B_HOPV, role == 2 ? 8 : 1);
        mbar_init(bar + 8 * B_XT, 1);
        mbar_init(bar + 8 * B_TFREE, 5);
        mbar_init(bar + 8 * B_P, 4);
        mbar_init(bar + 8 * B_XDONE, 8);
        mbar_init(bar + 8 * B_OST0, 4);
        mbar_init(bar + 8 * B_OST1, 4);
        mbar_init(bar + 8 * B_XRECV, 2);
        mbar_init(bar + 8 * B_O, 4);
        mbar_init(bar + 8 * B_AFREE0, 2);
        mbar_init(bar + 8 * B_AFREE1, 2);
        mbar_init(bar + 8 * B_PRO0, 1);
        mbar_init(bar + 8 * B_PRO1, 8);
        asm volatile("fence.mbarrier_init.release.cluster;" ::: "memory");
        fence_async();
        mbar_expect(bar + 8 * B_PRO0, KR * 4096);
        for (int i = 0; i < 3; i++) mbar_expect(bar + 8 * (B_FULL + i), 8192);
        mbar_expect(bar + 8 * B_HOP1, role == 2 ? 4096 : 2048);
        if (role != 2) mbar_expect(bar + 8 * B_HOPV, 2048);
        mbar_expect(bar + 8 * B_XT, role == 0 ? 2 * CPB : CPB);
    }
    __syncthreads();
    asm volatile("barrier.cluster.arrive.relaxed.aligned;" ::: "memory");
    {
        const CUtensorMap* tw = &tm.w[role];
        if (wid < 11) {
            e_tma_load(sb + wid * 16384, tw, h * DH, KC(wid), bar + 8 * B_PRO0);
            e_tma_load(sb + wid * 16384 + 8192, tw, h * DH + 64, KC(wid), bar + 8 * B_PRO0);
        }
        if (wid < 6) e_tma_load(sb + R_RING + wid * 4096, &tm.x, XC(wid), 0, bar + 8 * (B_FULL + (wid >> 1)));
        if ((tid & 31) == 0) {
            if (wid < 10) tma_prefetch(tw, h * DH + (wid & 1) * 64, KC(KR / 4 + (wid >> 1)));
            if (wid >= 6 && wid - 6 < (role == 0 ? 4 : 6)) tma_prefetch(&tm.wo, wo_tile(role, wid - 6) * 64, h * DH);
        }
        __syncwarp();
        const uint32_t g0 = __float_as_uint(gate_row(gx0, gw)), g1 = __float_as_uint(gate_row(gx1, gw));
        if ((tid & 31) == 0) {
            st_strong4(&g_gate[gr], g0 ? g0 : 0x80000000u);
            if (gr + 1152 < SEQ) st_strong4(&g_gate[gr + 1152], g1 ? g1 : 0x80000000u);
        }
        __syncwarp();
    }
    asm volatile("barrier.cluster.wait.aligned;" ::: "memory");

    if (wid < 8) {
        asm volatile("setmaxnreg.inc.sync.aligned.u32 224;");
        if (role == 0) r_big<0>(tm, wid); else if (role == 1) r_big<1>(tm, wid); else r_big<2>(tm, wid);
    } else {
        asm volatile("setmaxnreg.dec.sync.aligned.u32 56;");
        if (role == 0) r_chain<0>(tm, mem0, wid); else if (role == 1) r_chain<1>(tm, mem0, wid); else r_chain<2>(tm, mem0, wid);
    }
    __syncwarp();
    asm volatile("barrier.cluster.arrive; barrier.cluster.wait;" ::: "memory");
    KT(0, 1);
}

#define STAG 0
constexpr int G_ST = 4;
constexpr int G_STAGE = 16384 + 32768;
constexpr int G_EPI = G_ST * G_STAGE;
constexpr int G_GATE = G_EPI + 32768;
constexpr int G_BAR = G_GATE + 1024;
constexpr int G_SMEM = G_BAR + 128 + 1024;

struct G1Maps { CUtensorMap x, wg, wu, hs, o, h, wo, wd, out; };
constexpr int G1_NB = FF / 128;
constexpr int G1_TILES = 16 * G1_NB;

DEVINL void g_mma_block(float* d, uint32_t sb, uint32_t bar, int it, int wg, int tid, bool first) {
    const int st = it % G_ST;
    mbar_wait(bar + 8 * st, (it / G_ST) & 1);
    const uint64_t da = mkdesc(sb + st * G_STAGE + wg * 8192, 16, 1024, 1);
    const uint64_t db = mkdesc(sb + st * G_STAGE + 16384, 8192, 1024, 1);
    wg_fence();
#pragma unroll
    for (int k = 0; k < 4; k++) wg_ss256(d, da + (uint64_t)(k * 2), db + (uint64_t)(k * 128), (first ? 0 : 1) | k);
    wg_commit();
    if (!first) { wg_wait<1>(); if ((tid & 127) == 0) mbar_arrive(bar + 8 * (G_ST + (it - 1) % G_ST)); }
}
DEVINL void g_load_block(uint32_t sb, uint32_t bar, int it, const CUtensorMap* ta, int k0, int m0, const CUtensorMap* tb, int n0) {
    const int st = it % G_ST;
    mbar_wait(bar + 8 * (G_ST + st), ((it / G_ST) & 1) ^ 1);
    const uint32_t fb = bar + 8 * st, sa = sb + st * G_STAGE;
    mbar_expect(fb, G_STAGE);
    tma_load(sa, ta, k0, m0, fb);
#pragma unroll
    for (int q = 0; q < 4; q++) tma_load(sa + 16384 + q * 8192, tb, n0 + q * 64, k0, fb);
}

DEVINL void g_store_tile(const float* d, const CUtensorMap* tout, uint32_t epi, int mb, int nb, int wg, int tid) {
    const int lane = tid & 31, row = ((tid >> 5) & 3) * 16 + ((lane >> 3) & 1) * 8 + (lane & 7);
#pragma unroll
    for (int half = 0; half < 2; half++) {
        if ((tid & 127) == 0) bulk_wait_read();
        bar_sync(1 + wg, 128);
#pragma unroll
        for (int j = 0; j < 16; j += 2) {
            const float* e = d + half * 64 + 4 * j;
            const int cgp = j + (lane >> 4);
            stsm4(epi + (cgp >> 3) * 8192 + row * 128 + (((cgp & 7) ^ (row & 7)) << 4),
                  pack_bf16(e[0], e[1]), pack_bf16(e[2], e[3]), pack_bf16(e[4], e[5]), pack_bf16(e[6], e[7]));
        }
        fence_async();
        bar_sync(1 + wg, 128);
        if ((tid & 127) == 0) {
            tma_store(tout, epi, nb * 256 + half * 128, mb * 128 + wg * 64);
            tma_store(tout, epi + 8192, nb * 256 + half * 128 + 64, mb * 128 + wg * 64);
            bulk_commit();
        }
    }
}
template <int NS> DEVINL void g_split_finish(const float* d, float4 (&r)[32 / NS], uint4* sk, int tile, int ks, bf16* __restrict__ out, int tid) {
    constexpr int Q = 32 / NS;
    uint4* mine = sk + ks * (16 * 256) + tid;
#pragma unroll
    for (int c = 0; c < NS; c++) {
        if (c != ks) {
#pragma unroll
            for (int q = c * Q / 2; q < (c + 1) * Q / 2; q++)
                __stcg(mine + q * 256, make_uint4(pack_bf16(d[8 * q], d[8 * q + 1]), pack_bf16(d[8 * q + 2], d[8 * q + 3]), pack_bf16(d[8 * q + 4], d[8 * q + 5]), pack_bf16(d[8 * q + 6], d[8 * q + 7])));
        } else {
#pragma unroll
            for (int q = 0; q < Q; q++) { const float* e = d + (c * Q + q) * 4; r[q].x += e[0]; r[q].y += e[1]; r[q].z += e[2]; r[q].w += e[3]; }
        }
    }
    __threadfence();
    bar_sync(3, 256);
    if (tile >= T_LATE) PT(20);
    if (tid == 0) {
        atomicAdd(&g_skcnt[tile], 1u);
        uint32_t v, n = 0;
        do {
            asm volatile("ld.acquire.gpu.global.u32 %0, [%1];" : "=r"(v) : "l"(&g_skcnt[tile]) : "memory");
            if (++n > 200000000u) __trap();
        } while (v < NS);
        if (atomicAdd(&g_skcnt[tile], 1u) == 2 * NS - 1) g_skcnt[tile] = 0u;
    }
    bar_sync(3, 256);
    if (tile >= T_LATE) PT(21);
#pragma unroll
    for (int c = 1; c < NS; c++) {
        const uint4* th = sk + (((ks + c) & (NS - 1)) * 16 + ks * (Q / 2)) * 256 + tid;
#pragma unroll
        for (int q = 0; q < Q / 2; q++) {
            const uint4 u = __ldcg(th + q * 256);
            r[2 * q].x += __uint_as_float(u.x << 16); r[2 * q].y += __uint_as_float(u.x & 0xffff0000u);
            r[2 * q].z += __uint_as_float(u.y << 16); r[2 * q].w += __uint_as_float(u.y & 0xffff0000u);
            r[2 * q + 1].x += __uint_as_float(u.z << 16); r[2 * q + 1].y += __uint_as_float(u.z & 0xffff0000u);
            r[2 * q + 1].z += __uint_as_float(u.w << 16); r[2 * q + 1].w += __uint_as_float(u.w & 0xffff0000u);
        }
    }
    const int lane = tid & 31;
    uint32_t* op = (uint32_t*)(out + ((tile >> 2) * 128 + (tid >> 5) * 16 + (lane >> 2)) * DM + (tile & 3) * 256 + ks * Q * 8 + (lane & 3) * 2);
#pragma unroll
    for (int q = 0; q < Q; q++) { op[q * 4] = pack_bf16(r[q].x, r[q].y); op[q * 4 + 4 * DM] = pack_bf16(r[q].z, r[q].w); }
}
DEVINL int g1_count(int pass, int tail) {
    return pass == 0 ? NPRE : pass == 1 ? NFULL : pass == 2 ? T_MID - NFULL : pass == 3 ? (T_MID2 - T_MID) * 4 : tail ? (64 - T_LATE) * 8 : (T_LATE - T_MID2) * 8;
}
DEVINL int g1_first(int pass, int tail) {
    const int b = blockIdx.x, n = gridDim.x;
    return (pass < 2 || tail) ? b : pass == 2 ? n - 1 - b : (b + n - (pass == 3 ? 16 : 32)) % n;
}
DEVINL int g1_tile(int pass, int tail, int i) {
    return pass == 1 ? i : pass == 3 ? T_MID + (i >> 2) : pass == 4 ? (tail ? T_LATE : T_MID2) + (i >> 3) : NFULL + i;
}
constexpr int H_EARLY = 24;

__global__ void __launch_bounds__(384, 1) g1_kernel(const __grid_constant__ G1Maps tm, bf16* __restrict__ out, const int tail) {
    extern __shared__ __align__(1024) unsigned char smem_raw[];
    const uint32_t sb = (smem_u32(smem_raw) + 1023) & ~1023u;
    const int tid = threadIdx.x, lane = tid & 31;
    const int wg = __shfl_sync(0xffffffffu, tid >> 7, 0);
    const int warp = __shfl_sync(0xffffffffu, (tid >> 5) & 3, 0);
    const uint32_t bar = sb + G_BAR;
    asm volatile("griddepcontrol.launch_dependents;");
    KT(1 + tail, 0);
    if (tail && (tid == 32 || tid == 64)) asm volatile("prefetch.tensormap [%0];" ::"l"(tid == 32 ? &tm.o : &tm.wo) : "memory");
    const int ntiles = tail ? 0 : G1_TILES;
    if (tid == 0) {
        for (int i = 0; i < G_ST; i++) { mbar_init(bar + 8 * i, 1); mbar_init(bar + 8 * (G_ST + i), 2); }
        fence_async();
    }
    __syncthreads();
    if (tail) PT(16);
    if (tail) asm volatile("griddepcontrol.wait;" ::: "memory");
    if (tail) PT(17);
    if (tail && tid < 32 * G_ST) {
        const int it = tid >> 5, tile = T_LATE + (blockIdx.x >> 3), k0 = ((blockIdx.x & 7) * 8 + it) * 64;
        e_expect(bar + 8 * it, G_STAGE);
        e_tma_load(sb + it * G_STAGE, &tm.o, k0, (tile >> 2) * 128, bar + 8 * it);
#pragma unroll
        for (int q = 0; q < 4; q++) e_tma_load(sb + it * G_STAGE + 16384 + q * 8192, &tm.wo, (tile & 3) * 256 + q * 64, k0, bar + 8 * it);
    }
    if (wg == 2) {
        asm volatile("setmaxnreg.dec.sync.aligned.u32 40;");
        if (tail && warp == 1) {
            if (blockIdx.x < SEQ / 32) g_gate[blockIdx.x * 32 + lane] = 0u;
            if (blockIdx.x == 0) { if (lane < 16) g_ocnt[lane] = 0u; g_hcnt[lane] = 0u; g_pcnt[lane] = 0u; g_pcnt[32 + lane] = 0u; }
        }
        if (warp == 0) {
            if (lane == 0) {
                int it = 0;
                for (int tile = blockIdx.x; tile < ntiles; tile += gridDim.x) {
                    const int mb = tile & 15, nb = tile >> 4;
                    for (int kb = 0; kb < 16; kb++, it++) {
                        const int st = it % G_ST;
                        mbar_wait(bar + 8 * (G_ST + st), ((it / G_ST) & 1) ^ 1);
                        const uint32_t fb = bar + 8 * st, sa = sb + st * G_STAGE;
                        mbar_expect(fb, G_STAGE);
                        tma_load(sa, &tm.x, kb * 64, mb * 128, fb);
                        tma_load(sa + 16384, &tm.wg, nb * 128, kb * 64, fb);
                        tma_load(sa + 16384 + 8192, &tm.wg, nb * 128 + 64, kb * 64, fb);
                        tma_load(sa + 16384 + 16384, &tm.wu, nb * 128, kb * 64, fb);
                        tma_load(sa + 16384 + 24576, &tm.wu, nb * 128 + 64, kb * 64, fb);
                    }
                }
                for (int pass = tail ? 4 : 0; pass < 5; pass++) {
                    for (int i = g1_first(pass, tail); i < g1_count(pass, tail); i += gridDim.x) {
                        const int tile = g1_tile(pass, tail, i), mb = tile >> 2, nb = tile & 3;
                        if (pass < 2) {
                            for (int kb = 0; kb < FF / 64; kb++, it++) {
                                if (kb == 0 || kb == 2 * H_EARLY) {
                                    wait_count(&g_hcnt[kb ? 16 + mb : mb], kb ? 2 * (G1_NB - H_EARLY) : 2 * H_EARLY);
                                    asm volatile("fence.proxy.async;" ::: "memory");
                                }
                                g_load_block(sb, bar, it, &tm.h, kb * 64, mb * 128, &tm.wd, nb * 256);
                            }
                        }
                        if (pass > 0) {
                            const int k0 = pass == 3 ? (i & 3) * 16 : pass == 4 ? (i & 7) * 8 : 0, k1 = pass == 3 ? k0 + 16 : pass == 4 ? k0 + 8 : HD / 64;
                            if (!tail) wait_count(&g_ocnt[mb], NH * 4);
                            asm volatile("fence.proxy.async;" ::: "memory");
                            for (int kb = k0; kb < k1; kb++, it++) if (!tail || it >= G_ST) g_load_block(sb, bar, it, &tm.o, kb * 64, mb * 128, &tm.wo, nb * 256);
                        }
                    }
                }
            }
        }
    } else {
        asm volatile("setmaxnreg.inc.sync.aligned.u32 232;");
        float d[128];
        int it = 0;
        const uint32_t epi = sb + G_EPI + wg * 16384;
        const int row = warp * 16 + ((lane >> 3) & 1) * 8 + (lane & 7);
        for (int tile = blockIdx.x; tile < ntiles; tile += gridDim.x) {
            const int mb = tile & 15, nb = tile >> 4;
            const uint32_t* gp = &g_gate[mb * 128 + wg * 64 + warp * 16 + (lane >> 2)];
            uint32_t u0 = ld_strong4(gp), u1 = ld_strong4(gp + 8);
            for (int kb = 0; kb < 16; kb++, it++) {
                if (it == (wg ? 0 : STAG)) bar_sync(4, 256);
                g_mma_block(d, sb, bar, it, wg, tid, kb == 0);
            }
            wg_wait<0>();
            for (uint32_t n = 0; u0 == 0u || u1 == 0u; n++) { u0 = ld_strong4(gp); u1 = ld_strong4(gp + 8); if (n > 20000000u) __trap(); }
            __syncwarp();
            const float s0 = 1.0f - __uint_as_float(u0), s1 = 1.0f - __uint_as_float(u1);
            if ((tid & 127) == 0) {
                mbar_arrive(bar + 8 * (G_ST + (it - 1) % G_ST));
                bulk_wait_all();
                const int pt = tile - (int)gridDim.x;
                if (pt >= 0) atomicAdd(&g_hcnt[(pt & 15) + ((pt >> 4) >= H_EARLY ? 16 : 0)], 1u);
            }
            bar_sync(1 + wg, 128);
#pragma unroll
            for (int j = 0; j < 16; j += 2) {
                uint32_t p[4];
#pragma unroll
                for (int q = 0; q < 4; q++) {
                    const int i = (j + (q >> 1)) * 4 + (q & 1) * 2;
                    const float sc = (q & 1) ? s1 : s0;
                    const float g0 = d[i], g1 = d[i + 1];
                    const float a0 = 1.0f + ex2(fminf(g0 * -1.4426950408889634f, 62.0f)), a1 = 1.0f + ex2(fminf(g1 * -1.4426950408889634f, 62.0f));
                    const float rr = rcp(a0 * a1) * sc;
                    const float h0 = (g0 * d[64 + i]) * (rr * a1);
                    const float h1 = (g1 * d[64 + i + 1]) * (rr * a0);
                    p[q] = pack_bf16(h0, h1);
                }
                const int cgp = j + (lane >> 4);
                stsm4(epi + (cgp >> 3) * 8192 + row * 128 + (((cgp & 7) ^ (row & 7)) << 4), p[0], p[1], p[2], p[3]);
            }
            fence_async();
            bar_sync(1 + wg, 128);
            if ((tid & 127) == 0) {
                tma_store(&tm.hs, epi, nb * 128, mb * 128 + wg * 64);
                tma_store(&tm.hs, epi + 8192, nb * 128 + 64, mb * 128 + wg * 64);
                bulk_commit();
            }
        }
        if ((tid & 127) == 0 && !tail) {
            bulk_wait_all();
            const int pt = blockIdx.x + (G1_TILES - 1 - blockIdx.x) / gridDim.x * gridDim.x;
            atomicAdd(&g_hcnt[(pt & 15) + ((pt >> 4) >= H_EARLY ? 16 : 0)], 1u);
        }
        for (int pass = tail ? 4 : 0; pass < 5; pass++) {
            for (int i = g1_first(pass, tail); i < g1_count(pass, tail); i += gridDim.x) {
                const int tile = g1_tile(pass, tail, i);
                const int nkb = pass == 0 ? FF / 64 : pass == 1 ? (FF + HD) / 64 : pass == 2 ? HD / 64 : pass == 3 ? 16 : 8;
                float4* pre = g_pre + (tile - NFULL) * (32 * 256) + tid;
                if (tail) asm volatile("prefetch.global.L2 [%0];" ::"l"(pre - tid + (i & 7) * 1024 + tid * 4));
                for (int kb = 0; kb < nkb; kb++, it++) { g_mma_block(d, sb, bar, it, wg, tid, kb == 0); if (tail && kb == 0) PT(18); }
                wg_wait<0>();
                if (tail) PT(19);
                if ((tid & 127) == 0) mbar_arrive(bar + 8 * (G_ST + (it - 1) % G_ST));
                if (pass >= 2 && !tail) { if ((tid & 31) == 0) wait_count(&g_pcnt[tile], 8); __syncwarp(); }
                if (pass == 0) {
#pragma unroll
                    for (int q = 0; q < 32; q++) __stcg(pre + q * 256, make_float4(d[4 * q], d[4 * q + 1], d[4 * q + 2], d[4 * q + 3]));
                    __threadfence();
                    __syncwarp();
                    if ((tid & 31) == 0) atomicAdd(&g_pcnt[tile], 1u);
                } else if (pass == 3) {
                    float4 r[8];
#pragma unroll
                    for (int q = 0; q < 8; q++) r[q] = __ldcg(pre + ((i & 3) * 8 + q) * 256);
                    g_split_finish<4>(d, r, g_sk + (tile - T_MID) * 8 * (16 * 256), tile, i & 3, out, tid);
                } else if (pass == 4) {
                    float4 r[4];
#pragma unroll
                    for (int q = 0; q < 4; q++) r[q] = __ldcg(pre + ((i & 7) * 4 + q) * 256);
                    g_split_finish<8>(d, r, g_sk + (tile - T_MID) * 8 * (16 * 256), tile, i & 7, out, tid);
                } else {
                    if (pass == 2) {
#pragma unroll
                        for (int q = 0; q < 32; q++) {
                            const float4 u = __ldcg(pre + q * 256); d[4 * q] += u.x; d[4 * q + 1] += u.y; d[4 * q + 2] += u.z; d[4 * q + 3] += u.w;
                            if ((q & 7) == 7) __syncwarp();
                        }
                    }
                    g_store_tile(d, &tm.out, epi, tile >> 2, tile & 3, wg, tid);
                }
            }
        }
        if ((tid & 127) == 0) bulk_wait_all();
        KT(1 + tail, 1);
    }
    __syncwarp();
    asm volatile("griddepcontrol.wait;" ::: "memory");
}

typedef CUresult (*EncodeFn)(CUtensorMap*, CUtensorMapDataType, cuuint32_t, void*, const cuuint64_t*, const cuuint64_t*, const cuuint32_t*,
                             const cuuint32_t*, CUtensorMapInterleave, CUtensorMapSwizzle, CUtensorMapL2promotion, CUtensorMapFloatOOBfill);

static void make_map(EncodeFn enc, CUtensorMap* m, const void* ptr, uint64_t rows, uint64_t cols, uint32_t box_rows) {
    cuuint64_t dims[2] = {cols, rows};
    cuuint64_t strides[1] = {cols * 2};
    cuuint32_t box[2] = {64, box_rows};
    cuuint32_t es[2] = {1, 1};
    enc(m, CU_TENSOR_MAP_DATA_TYPE_BFLOAT16, 2, (void*)ptr, dims, strides, box, es, CU_TENSOR_MAP_INTERLEAVE_NONE,
        CU_TENSOR_MAP_SWIZZLE_128B, CU_TENSOR_MAP_L2_PROMOTION_L2_256B, CU_TENSOR_MAP_FLOAT_OOB_FILL_NONE);
}

extern "C" void kernel_launch(void* const* d_in, const int* in_sizes, int n_in, void* d_out, int out_size) {
    (void)in_sizes; (void)n_in; (void)out_size;
    const bf16* x = (const bf16*)d_in[0];
    const bf16* mem0 = (const bf16*)d_in[1];
    const bf16* gate_w = (const bf16*)d_in[11];
    static EncodeFn enc = nullptr;
    static int n_sm = 0;
    static void *pO = nullptr, *pH = nullptr;
    if (!enc) {
        void* fn = nullptr;
        cudaDriverEntryPointQueryResult qr;
        cudaGetDriverEntryPoint("cuTensorMapEncodeTiled", &fn, cudaEnableDefault, &qr);
        enc = (EncodeFn)fn;
        cudaDeviceGetAttribute(&n_sm, cudaDevAttrMultiProcessorCount, 0);
        cudaFuncSetAttribute(r_kernel, cudaFuncAttributeMaxDynamicSharedMemorySize, R_SMEM);
        cudaFuncSetAttribute(g1_kernel, cudaFuncAttributeMaxDynamicSharedMemorySize, G_SMEM);
        cudaGetSymbolAddress(&pO, g_O);
        cudaGetSymbolAddress(&pH, g_H);
    }
    RMaps rm; G1Maps m1;
    make_map(enc, &rm.x, x, SEQ, DM, 32);
    for (int i = 0; i < 3; i++) make_map(enc, &rm.w[i], d_in[2 + i], DM, HD, 64);
    make_map(enc, &rm.wo, d_in[5], HD, DM, 128);
    make_map(enc, &rm.o, pO, SEQ, HD, 16);
    make_map(enc, &m1.x, x, SEQ, DM, 128);
    make_map(enc, &m1.wg, d_in[8], DM, FF, 64);
    make_map(enc, &m1.wu, d_in[9], DM, FF, 64);
    make_map(enc, &m1.hs, pH, SEQ, FF, 64);
    make_map(enc, &m1.o, pO, SEQ, HD, 128);
    make_map(enc, &m1.h, pH, SEQ, FF, 128);
    make_map(enc, &m1.wo, d_in[5], HD, DM, 64);
    make_map(enc, &m1.wd, d_in[10], FF, DM, 64);
    make_map(enc, &m1.out, d_out, SEQ, DM, 64);

    cudaStream_t st = cudaStreamPerThread;
    {
        cudaLaunchConfig_t cfg = {};
        cfg.gridDim = dim3(96); cfg.blockDim = dim3(384); cfg.dynamicSmemBytes = R_SMEM; cfg.stream = st;
        cudaLaunchAttribute at[1];
        at[0].id = cudaLaunchAttributeClusterDimension; at[0].val.clusterDim.x = 3; at[0].val.clusterDim.y = 1; at[0].val.clusterDim.z = 1;
        cfg.attrs = at; cfg.numAttrs = 1;
        cudaLaunchKernelEx(&cfg, r_kernel, rm, mem0, x, gate_w);
    }
    {
        cudaLaunchConfig_t cfg = {};
        cfg.gridDim = dim3(n_sm - 96); cfg.blockDim = dim3(384); cfg.dynamicSmemBytes = G_SMEM; cfg.stream = st;
        cudaLaunchAttribute at[1];
        at[0].id = cudaLaunchAttributeProgrammaticStreamSerialization; at[0].val.programmaticStreamSerializationAllowed = 1;
        cfg.attrs = at; cfg.numAttrs = 1;
        cudaLaunchKernelEx(&cfg, g1_kernel, m1, (bf16*)d_out, 0);
    }
    {
        cudaLaunchConfig_t cfg = {};
        cfg.gridDim = dim3((64 - T_LATE) * 8); cfg.blockDim = dim3(384); cfg.dynamicSmemBytes = G_SMEM; cfg.stream = st;
        cudaLaunchAttribute at[1];
        at[0].id = cudaLaunchAttributeProgrammaticStreamSerialization; at[0].val.programmaticStreamSerializationAllowed = 1;
        cfg.attrs = at; cfg.numAttrs = 1;
        cudaLaunchKernelEx(&cfg, g1_kernel, m1, (bf16*)d_out, 1);
    }
}
```

```cpp
#include <cuda_runtime.h>
#include <cuda_bf16.h>
#include <cuda.h>
#include <stdint.h>

typedef __nv_bfloat16 bf16;

constexpr int SEQ = 2048, DM = 1024, NH = 32, DH = 128, NMEM = 8, SEG = 32, NSEG = 64, FF = 3584;
constexpr int HD = NH * DH;

__device__ bf16 g_O[SEQ * HD];
__device__ bf16 g_H[SEQ * FF];
__device__ uint32_t g_gate[SEQ];
__device__ uint32_t g_part[4][128 * 32 * 32];
__device__ uint32_t g_mem[4][DM * 4];
#define TLATE 52
constexpr int NFULL = 36, T_MID = 44, T_MID2 = 48, T_LATE = TLATE;
constexpr int NPRE = 64 - NFULL;
__device__ float4 g_pre[NPRE * 32 * 256];
__device__ uint4 g_sk[(64 - T_MID) * 8 * 16 * 256];
__device__ uint32_t g_skcnt[64], g_pcnt[64];
__device__ uint32_t g_hcnt[32], g_ocnt[16];
#define KT(k, i)
#define PT(i)

#define DEVINL __device__ __forceinline__
constexpr long long SPIN_LIMIT = 4000000000LL;

DEVINL uint32_t smem_u32(const void* p) { return (uint32_t)__cvta_generic_to_shared(p); }
DEVINL void mbar_init(uint32_t bar, uint32_t cnt) { asm volatile("mbarrier.init.shared::cta.b64 [%0], %1;" ::"r"(bar), "r"(cnt) : "memory"); }
DEVINL void mbar_arrive(uint32_t bar) { asm volatile("mbarrier.arrive.shared::cta.b64 _, [%0];" ::"r"(bar) : "memory"); }
DEVINL void mbar_expect(uint32_t bar, uint32_t bytes) { asm volatile("mbarrier.arrive.expect_tx.shared::cta.b64 _, [%0], %1;" ::"r"(bar), "r"(bytes) : "memory"); }
DEVINL void mbar_arrive_remote(uint32_t cbar) { asm volatile("mbarrier.arrive.relaxed.cluster.shared::cluster.b64 _, [%0];" ::"r"(cbar) : "memory"); }
DEVINL bool mbar_try(uint32_t bar, uint32_t par) {
    uint32_t ok;
    asm volatile("{ .reg .pred p; mbarrier.try_wait.parity.shared::cta.b64 p, [%1], %2; selp.u32 %0, 1, 0, p; }" : "=r"(ok) : "r"(bar), "r"(par) : "memory");
    return ok;
}
__device__ __noinline__ void mbar_wait_slow(uint32_t bar, uint32_t par) {
    long long t0 = clock64();
    while (!mbar_try(bar, par)) { if (clock64() - t0 > SPIN_LIMIT) __trap(); }
}
DEVINL void mbar_wait(uint32_t bar, uint32_t par) {
    uint32_t n = 0;
    while (!mbar_try(bar, par)) { if (++n > 200000000u) __trap(); }
}
DEVINL uint32_t mapa(uint32_t a, uint32_t r) { uint32_t o; asm volatile("mapa.shared::cluster.u32 %0, %1, %2;" : "=r"(o) : "r"(a), "r"(r)); return o; }
DEVINL void fence_async() { asm volatile("fence.proxy.async.shared::cta;" ::: "memory"); }
DEVINL void bar_sync(int id, int n) { asm volatile("bar.sync %0, %1;" ::"r"(id), "r"(n) : "memory"); }
DEVINL void cluster_sync() { asm volatile("barrier.cluster.arrive.aligned; barrier.cluster.wait.aligned;" ::: "memory"); }
DEVINL void tma_load(uint32_t dst, const CUtensorMap* tm, int c0, int c1, uint32_t bar) {
    asm volatile("cp.async.bulk.tensor.2d.shared::cluster.global.mbarrier::complete_tx::bytes [%0], [%1, {%3, %4}], [%2];"
                 ::"r"(dst), "l"(tm), "r"(bar), "r"(c0), "r"(c1) : "memory");
}
DEVINL void tma_prefetch(const CUtensorMap* tm, int c0, int c1) {
    asm volatile("cp.async.bulk.prefetch.tensor.2d.L2.global [%0, {%1, %2}];" ::"l"(tm), "r"(c0), "r"(c1) : "memory");
}
DEVINL void tma_store(const CUtensorMap* tm, uint32_t src, int c0, int c1) {
    asm volatile("cp.async.bulk.tensor.2d.global.shared::cta.bulk_group [%0, {%2, %3}], [%1];" ::"l"(tm), "r"(src), "r"(c0), "r"(c1) : "memory");
}
DEVINL void bulk_commit() { asm volatile("cp.async.bulk.commit_group;" ::: "memory"); }
DEVINL void bulk_wait_read() { asm volatile("cp.async.bulk.wait_group.read 0;" ::: "memory"); }
DEVINL void bulk_wait_all() { asm volatile("cp.async.bulk.wait_group 0;" ::: "memory"); }
DEVINL void bulk_s2s(uint32_t cdst, uint32_t src, uint32_t bytes, uint32_t cbar) {
    asm volatile("cp.async.bulk.shared::cluster.shared::cta.mbarrier::complete_tx::bytes [%0], [%1], %2, [%3];" ::"r"(cdst), "r"(src), "r"(bytes), "r"(cbar) : "memory");
}
DEVINL void st_async16(uint32_t cdst, uint4 v, uint32_t cbar) {
    asm volatile("st.async.shared::cluster.mbarrier::complete_tx::bytes.v4.b32 [%0], {%1,%2,%3,%4}, [%5];" ::"r"(cdst), "r"(v.x), "r"(v.y), "r"(v.z), "r"(v.w), "r"(cbar) : "memory");
}
DEVINL uint64_t mkdesc(uint32_t addr, uint32_t lbo, uint32_t sbo, uint32_t swz) {
    return (uint64_t)((addr & 0x3FFFF) >> 4) | ((uint64_t)(lbo >> 4) << 16) | ((uint64_t)(sbo >> 4) << 32) | ((uint64_t)swz << 62);
}
constexpr uint32_t SB0 = 1024;
__host__ __device__ constexpr uint64_t cdesc(uint32_t off, uint32_t lbo, uint32_t sbo, uint32_t swz) {
    return (uint64_t)(((SB0 + off) & 0x3FFFF) >> 4) | ((uint64_t)(lbo >> 4) << 16) | ((uint64_t)(sbo >> 4) << 32) | ((uint64_t)swz << 62);
}
DEVINL float rcp(float x) { float y; asm("rcp.approx.ftz.f32 %0, %1;" : "=f"(y) : "f"(x)); return y; }
DEVINL float ex2(float x) { float y; asm("ex2.approx.ftz.f32 %0, %1;" : "=f"(y) : "f"(x)); return y; }
DEVINL void spin_clk(int d) { uint32_t t0, t1; asm volatile("mov.u32 %0, %%clock;" : "=r"(t0)); do { asm volatile("mov.u32 %0, %%clock;" : "=r"(t1)); } while ((int)(t1 - t0) < d); }
#define PROBE_GAP 150
#define OPAQUE(x) asm volatile("" : "+r"(x))
DEVINL void wg_fence() { asm volatile("wgmma.fence.sync.aligned;" ::: "memory"); }
DEVINL void wg_commit() { asm volatile("wgmma.commit_group.sync.aligned;" ::: "memory"); }
template <int N> DEVINL void wg_wait() { asm volatile("wgmma.wait_group.sync.aligned %0;" ::"n"(N) : "memory"); }
DEVINL uint32_t pack_bf16(float lo, float hi) { uint32_t r; asm("cvt.rn.bf16x2.f32 %0, %1, %2;" : "=r"(r) : "f"(hi), "f"(lo)); return r; }
DEVINL void ldsm4(uint32_t* r, uint32_t a) { asm volatile("ldmatrix.sync.aligned.m8n8.x4.shared.b16 {%0,%1,%2,%3}, [%4];" : "=r"(r[0]), "=r"(r[1]), "=r"(r[2]), "=r"(r[3]) : "r"(a) : "memory"); }
DEVINL void ldsm4t(uint32_t* r, uint32_t a) { asm volatile("ldmatrix.sync.aligned.m8n8.x4.trans.shared.b16 {%0,%1,%2,%3}, [%4];" : "=r"(r[0]), "=r"(r[1]), "=r"(r[2]), "=r"(r[3]) : "r"(a) : "memory"); }
DEVINL void ldsm4t_if(uint32_t* r, uint32_t a, int c) { asm volatile("{ .reg .pred p; setp.ne.s32 p, %5, 0; @p ldmatrix.sync.aligned.m8n8.x4.trans.shared.b16 {%0,%1,%2,%3}, [%4]; }" : "+r"(r[0]), "+r"(r[1]), "+r"(r[2]), "+r"(r[3]) : "r"(a), "r"(c) : "memory"); }
DEVINL void stsm4(uint32_t a, uint32_t r0, uint32_t r1, uint32_t r2, uint32_t r3) { asm volatile("stmatrix.sync.aligned.m8n8.x4.shared.b16 [%0], {%1,%2,%3,%4};" ::"r"(a), "r"(r0), "r"(r1), "r"(r2), "r"(r3) : "memory"); }
DEVINL void stsm4t(uint32_t a, uint32_t r0, uint32_t r1, uint32_t r2, uint32_t r3) { asm volatile("stmatrix.sync.aligned.m8n8.x4.trans.shared.b16 [%0], {%1,%2,%3,%4};" ::"r"(a), "r"(r0), "r"(r1), "r"(r2), "r"(r3) : "memory"); }
DEVINL void sts32(uint32_t a, uint32_t v) { asm volatile("st.shared.b32 [%0], %1;" ::"r"(a), "r"(v) : "memory"); }
DEVINL void sts128(uint32_t a, uint4 v) { asm volatile("st.shared.v4.b32 [%0], {%1,%2,%3,%4};" ::"r"(a), "r"(v.x), "r"(v.y), "r"(v.z), "r"(v.w) : "memory"); }
DEVINL uint4 lds128(uint32_t a) { uint4 v; asm volatile("ld.shared.v4.b32 {%0,%1,%2,%3}, [%4];" : "=r"(v.x), "=r"(v.y), "=r"(v.z), "=r"(v.w) : "r"(a) : "memory"); return v; }
DEVINL uint4 ld_strong16(const void* p) { uint4 v; asm volatile("ld.relaxed.gpu.global.v4.u32 {%0,%1,%2,%3}, [%4];" : "=r"(v.x), "=r"(v.y), "=r"(v.z), "=r"(v.w) : "l"(p) : "memory"); return v; }
DEVINL void st_strong8(void* p, uint32_t a, uint32_t b) { asm volatile("st.relaxed.gpu.global.v2.u32 [%0], {%1,%2};" ::"l"(p), "r"(a), "r"(b) : "memory"); }
DEVINL void st_strong4(void* p, uint32_t a) { asm volatile("st.relaxed.gpu.global.u32 [%0], %1;" ::"l"(p), "r"(a) : "memory"); }
DEVINL void st_strong16(void* p, uint4 v) { asm volatile("st.relaxed.gpu.global.v4.u32 [%0], {%1,%2,%3,%4};" ::"l"(p), "r"(v.x), "r"(v.y), "r"(v.z), "r"(v.w) : "memory"); }
DEVINL uint32_t pack_nz(float lo, float hi) { uint32_t r = pack_bf16(lo, hi); return r == 0u ? 0x8000u : r; }
DEVINL uint32_t min4(uint4 v, uint32_t m) { return __vimin3_u32(__vimin3_u32(v.x, v.y, m), v.z, v.w); }
DEVINL void mma16816(float* d, uint32_t a0, uint32_t a1, uint32_t a2, uint32_t a3, uint32_t b0, uint32_t b1) {
    asm volatile("mma.sync.aligned.m16n8k16.row.col.f32.bf16.bf16.f32 {%0,%1,%2,%3}, {%4,%5,%6,%7}, {%8,%9}, {%0,%1,%2,%3};"
                 : "+f"(d[0]), "+f"(d[1]), "+f"(d[2]), "+f"(d[3]) : "r"(a0), "r"(a1), "r"(a2), "r"(a3), "r"(b0), "r"(b1));
}
DEVINL void mma1688(float* d, uint32_t a0, uint32_t a1, uint32_t b0) {
    asm volatile("mma.sync.aligned.m16n8k8.row.col.f32.bf16.bf16.f32 {%0,%1,%2,%3}, {%4,%5}, {%6}, {%0,%1,%2,%3};"
                 : "+f"(d[0]), "+f"(d[1]), "+f"(d[2]), "+f"(d[3]) : "r"(a0), "r"(a1), "r"(b0));
}
template <int TA, int TB> DEVINL void wg_ss8(float* d, uint64_t da, uint64_t db, int sc) {
    asm volatile("{ .reg .pred p; setp.ne.b32 p, %6, 0; wgmma.mma_async.sync.aligned.m64n8k16.f32.bf16.bf16 {%0,%1,%2,%3}, %4, %5, p, 1, 1, %7, %8; }"
                 : "+f"(d[0]), "+f"(d[1]), "+f"(d[2]), "+f"(d[3]) : "l"(da), "l"(db), "r"(sc), "n"(TA), "n"(TB));
}
template <int TB> DEVINL void wg_rs8(float* d, const uint32_t* a, uint64_t db, int sc) {
    asm volatile("{ .reg .pred p; setp.ne.b32 p, %9, 0; wgmma.mma_async.sync.aligned.m64n8k16.f32.bf16.bf16 {%0,%1,%2,%3}, {%4,%5,%6,%7}, %8, p, 1, 1, %10; }"
                 : "+f"(d[0]), "+f"(d[1]), "+f"(d[2]), "+f"(d[3]) : "r"(a[0]), "r"(a[1]), "r"(a[2]), "r"(a[3]), "l"(db), "r"(sc), "n"(TB));
}
#define ACC16(d) "+f"(d[0]), "+f"(d[1]), "+f"(d[2]), "+f"(d[3]), "+f"(d[4]), "+f"(d[5]), "+f"(d[6]), "+f"(d[7]), "+f"(d[8]), "+f"(d[9]), "+f"(d[10]), "+f"(d[11]), "+f"(d[12]), "+f"(d[13]), "+f"(d[14]), "+f"(d[15])
template <int TA> DEVINL void wg_ss32(float* d, uint64_t da, uint64_t db, int sc) {
    asm volatile("{ .reg .pred p; setp.ne.b32 p, %18, 0; wgmma.mma_async.sync.aligned.m64n32k16.f32.bf16.bf16 {%0,%1,%2,%3,%4,%5,%6,%7,%8,%9,%10,%11,%12,%13,%14,%15}, %16, %17, p, 1, 1, %19, 0; }"
                 : ACC16(d) : "l"(da), "l"(db), "r"(sc), "n"(TA));
}
DEVINL void wg_rs32(float* d, const uint32_t* a, uint64_t db, int sc) {
    asm volatile("{ .reg .pred p; setp.ne.b32 p, %21, 0; wgmma.mma_async.sync.aligned.m64n32k16.f32.bf16.bf16 {%0,%1,%2,%3,%4,%5,%6,%7,%8,%9,%10,%11,%12,%13,%14,%15}, {%16,%17,%18,%19}, %20, p, 1, 1, 0; }"
                 : ACC16(d) : "r"(a[0]), "r"(a[1]), "r"(a[2]), "r"(a[3]), "l"(db), "r"(sc));
}
DEVINL void wg_ss40(float* d, uint64_t da, uint64_t db, int sc) {
    asm volatile("{ .reg .pred p; setp.ne.b32 p, %22, 0; wgmma.mma_async.sync.aligned.m64n40k16.f32.bf16.bf16 {%0,%1,%2,%3,%4,%5,%6,%7,%8,%9,%10,%11,%12,%13,%14,%15,%16,%17,%18,%19}, %20, %21, p, 1, 1, 1, 1; }"
                 : ACC16(d), "+f"(d[16]), "+f"(d[17]), "+f"(d[18]), "+f"(d[19]) : "l"(da), "l"(db), "r"(sc));
}
#define A8(d, o) "+f"(d[o]), "+f"(d[o + 1]), "+f"(d[o + 2]), "+f"(d[o + 3]), "+f"(d[o + 4]), "+f"(d[o + 5]), "+f"(d[o + 6]), "+f"(d[o + 7])
#define A32(d, o) A8(d, o), A8(d, o + 8), A8(d, o + 16), A8(d, o + 24)
DEVINL void wg_ss256(float* d, uint64_t da, uint64_t db, int sc) {
    asm volatile(
        "{ .reg .pred p; setp.ne.b32 p, %130, 0;\n"
        "wgmma.mma_async.sync.aligned.m64n256k16.f32.bf16.bf16 {"
        "%0,%1,%2,%3,%4,%5,%6,%7,%8,%9,%10,%11,%12,%13,%14,%15,%16,%17,%18,%19,%20,%21,%22,%23,%24,%25,%26,%27,%28,%29,%30,%31,"
        "%32,%33,%34,%35,%36,%37,%38,%39,%40,%41,%42,%43,%44,%45,%46,%47,%48,%49,%50,%51,%52,%53,%54,%55,%56,%57,%58,%59,%60,%61,%62,%63,"
        "%64,%65,%66,%67,%68,%69,%70,%71,%72,%73,%74,%75,%76,%77,%78,%79,%80,%81,%82,%83,%84,%85,%86,%87,%88,%89,%90,%91,%92,%93,%94,%95,"
        "%96,%97,%98,%99,%100,%101,%102,%103,%104,%105,%106,%107,%108,%109,%110,%111,%112,%113,%114,%115,%116,%117,%118,%119,%120,%121,%122,%123,%124,%125,%126,%127"
        "}, %128, %129, p, 1, 1, 0, 1; }"
        : A32(d, 0), A32(d, 32), A32(d, 64), A32(d, 96) : "l"(da), "l"(db), "r"(sc));
}

DEVINL float gate_row(const uint4 (&xv)[4], const uint4 (&gv)[4]) {
    float acc = 0.f;
#pragma unroll
    for (int i = 0; i < 4; i++) {
        const uint32_t xa[4] = {xv[i].x, xv[i].y, xv[i].z, xv[i].w}, ga[4] = {gv[i].x, gv[i].y, gv[i].z, gv[i].w};
#pragma unroll
        for (int e = 0; e < 4; e++) {
            acc = fmaf(__uint_as_float(xa[e] << 16), __uint_as_float(ga[e] << 16), acc);
            acc = fmaf(__uint_as_float(xa[e] & 0xffff0000u), __uint_as_float(ga[e] & 0xffff0000u), acc);
        }
    }
#pragma unroll
    for (int o = 16; o > 0; o >>= 1) acc += __shfl_xor_sync(0xffffffffu, acc, o);
    return 1.0f / (1.0f + __expf(-acc));
}
DEVINL uint4 ldg_nc(const void* p) { uint4 v; asm volatile("ld.global.nc.v4.u32 {%0,%1,%2,%3}, [%4];" : "=r"(v.x), "=r"(v.y), "=r"(v.z), "=r"(v.w) : "l"(p) : "memory"); return v; }
DEVINL uint32_t ld_strong4(const void* p) { uint32_t v; asm volatile("ld.relaxed.gpu.global.u32 %0, [%1];" : "=r"(v) : "l"(p) : "memory"); return v; }
DEVINL void wait_count(const uint32_t* p, uint32_t want) {
    uint32_t v, n = 0;
    while (true) {
        asm volatile("ld.acquire.gpu.global.u32 %0, [%1];" : "=r"(v) : "l"(p) : "memory");
        if (v >= want) break;
        __nanosleep(200);
        if (++n > 10000000u) __trap();
    }
}

constexpr int KR = 44;
constexpr int KS = 64 - KR;
constexpr int R_W = 0;
constexpr int R_WO = KS * 4096;
constexpr int R_QX = R_WO + 65536;
constexpr int R_RING = R_WO + 98304;
constexpr int R_K = R_RING + 24576;
constexpr int R_V = R_K + 10240;
constexpr int R_QM = R_V + 10240;
constexpr int R_O = R_QM + 2048;
constexpr int R_BAR = R_O + 2048;
constexpr int R_G = R_BAR + 256 + 512 + 256 + 128;
constexpr int R_Z = R_G + 256;
constexpr int R_SMEM = R_Z + 1024;
enum { B_FULL = 0, B_EMPTY = 5, B_MEM = 8, B_HOP1 = 12, B_XT, B_TFREE, B_O, B_AFREE0, B_AFREE1, B_PRO0, B_PRO1, B_XRECV, B_P, B_XDONE, B_OST0, B_OST1, B_HOPV };
#define D2_BASE 900
#define D2_STEP 200
#define PD2 6
#define CPB 8192
#define DDUP 0
#define WGAP 0
#define PVD 400
#define ELD 700
#define QD 3
#define PPF 0
#define DQ 1700
#define D3 0

DEVINL uint32_t clk32() { uint32_t c_; asm volatile("mov.u32 %0, %%clock;" : "=r"(c_)); return c_; }
DEVINL void spin_until(uint32_t t) { while ((uint32_t)(t - clk32() - 1u) < 100000u) {} }
#define PROF(i)
#define PROF2(i)
#define PROF3(i, val)
DEVINL void e_arrive(uint32_t bar) { asm volatile("{ .reg .pred p; elect.sync _|p, 0xffffffff; @p mbarrier.arrive.shared::cta.b64 _, [%0]; }" ::"r"(bar) : "memory"); }
DEVINL void e_arrive_remote(uint32_t cbar) { asm volatile("{ .reg .pred p; elect.sync _|p, 0xffffffff; @p mbarrier.arrive.relaxed.cluster.shared::cluster.b64 _, [%0]; }" ::"r"(cbar) : "memory"); }
DEVINL void e_count(uint32_t* p) { asm volatile("{ .reg .pred p; elect.sync _|p, 0xffffffff; @p red.relaxed.gpu.global.add.u32 [%0], 1; }" ::"l"(p) : "memory"); }
DEVINL void e_expect(uint32_t bar, uint32_t bytes) { asm volatile("{ .reg .pred p; elect.sync _|p, 0xffffffff; @p mbarrier.arrive.expect_tx.shared::cta.b64 _, [%0], %1; }" ::"r"(bar), "r"(bytes) : "memory"); }
DEVINL void e_tma_load(uint32_t dst, const CUtensorMap* tm, int c0, int c1, uint32_t bar) {
    asm volatile("{ .reg .pred p; elect.sync _|p, 0xffffffff; @p cp.async.bulk.tensor.2d.shared::cluster.global.mbarrier::complete_tx::bytes [%0], [%1, {%3, %4}], [%2]; }"
                 ::"r"(dst), "l"(tm), "r"(bar), "r"(c0), "r"(c1) : "memory");
}
DEVINL void e_tma_store(const CUtensorMap* tm, uint32_t src, int c0, int c1) {
    asm volatile("{ .reg .pred p; elect.sync _|p, 0xffffffff; @p cp.async.bulk.tensor.2d.global.shared::cta.bulk_group [%0, {%2, %3}], [%1]; }" ::"l"(tm), "r"(src), "r"(c0), "r"(c1) : "memory");
}
DEVINL void e_bulk_s2g(void* dst, uint32_t src, uint32_t bytes) {
    asm volatile("{ .reg .pred p; elect.sync _|p, 0xffffffff; @p cp.async.bulk.global.shared::cta.bulk_group [%0], [%1], %2; }" ::"l"(dst), "r"(src), "r"(bytes) : "memory");
}
DEVINL void e_bulk_s2s(uint32_t cdst, uint32_t src, uint32_t bytes, uint32_t cbar) {
    asm volatile("{ .reg .pred p; elect.sync _|p, 0xffffffff; @p cp.async.bulk.shared::cluster.shared::cta.mbarrier::complete_tx::bytes [%0], [%1], %2, [%3]; }" ::"r"(cdst), "r"(src), "r"(bytes), "r"(cbar) : "memory");
}

#define SLOT 0
#define PH3 0
#define PHQ 0
DEVINL void wait_slot(uint32_t phase) {
    if (SLOT) {
        uint32_t c; asm volatile("mov.u32 %0, %%globaltimer_lo;" : "=r"(c));
        const uint32_t tgt = c + (SLOT ? SLOT : 1) - ((c - phase) % (SLOT ? SLOT : 1));
        do { asm volatile("mov.u32 %0, %%globaltimer_lo;" : "=r"(c)); } while ((uint32_t)(tgt - c - 1u) < 100000u);
    }
}
template <int N> DEVINL uint32_t poll_set(uint4 (&v)[N], const uint32_t* rp, int stride, uint32_t phase, uint32_t wbar = 0, uint32_t wpar = 0) {
    wait_slot(phase);
#pragma unroll
    for (int i = 0; i < N; i++) v[i] = ld_strong16(rp + i * stride);
    if (wbar) mbar_wait(wbar, wpar);
    uint32_t n = 0;
    while (true) {
        uint32_t m = 0xffffffffu;
#pragma unroll
        for (int i = 0; i < N; i++) m = min4(v[i], m);
        if (__all_sync(0xffffffffu, m != 0u)) return n;
        wait_slot(phase);
#pragma unroll
        for (int i = 0; i < N; i++)
            asm volatile("{ .reg .pred p; setp.eq.u32 p, %5, 0; @p ld.relaxed.gpu.global.v4.u32 {%0,%1,%2,%3}, [%4]; }"
                         : "+r"(v[i].x), "+r"(v[i].y), "+r"(v[i].z), "+r"(v[i].w) : "l"(rp + i * stride), "r"(min4(v[i], 0xffffffffu)) : "memory");
        if (++n > 20000000u) __trap();
    }
}

struct RMaps { CUtensorMap x, w[3], wo, o; };
#define KC(c) ((c) * 64)

#define XORD 3
__host__ __device__ constexpr int xo(int i) {
    return XORD == 0 ? i : XORD == 1 ? (i + 14) % 16 : XORD == 2 ? (i + 11) % 16
         : XORD == 3 ? (i < 10 ? ((i & 1) ? i / 2 : 11 + i / 2) : i - 5) : (i < 6 ? i : ((i & 1) ? 6 + (i - 6) / 2 : 11 + (i - 6) / 2));
}
#define XC(i) (xo(i) * 64)
DEVINL void x_load_pair(uint32_t dst, const CUtensorMap* tmx, int h, int p, int seg, uint32_t fbar) {
    e_expect(fbar, 8192);
    e_tma_load(dst, tmx, XC(2 * p), seg * SEG, fbar);
    e_tma_load(dst + 4096, tmx, XC(2 * p + 1), seg * SEG, fbar);
}
__host__ __device__ constexpr int wo_tile(int role, int i) {
    return role == 0 ? (i < 2 ? 8 + i : 12 + i) : (i < 4 ? (i >> 1) * 4 : 10) + (role - 1) * 2 + (i & 1);
}

template <int NT> DEVINL void wo_phase(uint32_t sb, int tb, uint32_t* pp, uint32_t obar, uint32_t opar) {
    const int lane = tb & 31, krow = (lane & 7) + ((lane >> 4) << 3), chunk = ((tb >> 5) & 3) * 2 + ((lane >> 3) & 1);
    uint32_t wa = sb + R_WO + (tb >> 7) * 16384 + krow * 128 + ((chunk ^ (krow & 7)) << 4);
    uint32_t af[4][4], of[4][4];
#pragma unroll
    for (int g = 0; g < 4; g++) ldsm4t(af[g], wa + g * 2048);
    mbar_wait(obar, opar);
#pragma unroll
    for (int g = 0; g < 4; g++) ldsm4t(of[g], sb + R_O + g * 512 + lane * 16);
#pragma unroll 1
    for (int i = 0; i < NT; i++) {
        float w0[4] = {0.f, 0.f, 0.f, 0.f}, w1[4] = {0.f, 0.f, 0.f, 0.f};
        const int more = NT - 1 - i, yes = NT - i;
        mma16816(w0, af[0][0], af[0][1], af[0][2], af[0][3], of[0][0], of[0][1]);
        ldsm4t_if(af[0], wa + 4 * 2048, yes);
        mma16816(w1, af[1][0], af[1][1], af[1][2], af[1][3], of[0][2], of[0][3]);
        ldsm4t_if(af[1], wa + 5 * 2048, yes);
        mma16816(w0, af[2][0], af[2][1], af[2][2], af[2][3], of[1][0], of[1][1]);
        ldsm4t_if(af[2], wa + 6 * 2048, yes);
        mma16816(w1, af[3][0], af[3][1], af[3][2], af[3][3], of[1][2], of[1][3]);
        ldsm4t_if(af[3], wa + 7 * 2048, yes);
        wa += 32768;
        mma16816(w0, af[0][0], af[0][1], af[0][2], af[0][3], of[2][0], of[2][1]);
        ldsm4t_if(af[0], wa, more);
        mma16816(w1, af[1][0], af[1][1], af[1][2], af[1][3], of[2][2], of[2][3]);
        ldsm4t_if(af[1], wa + 2048, more);
        mma16816(w0, af[2][0], af[2][1], af[2][2], af[2][3], of[3][0], of[3][1]);
        ldsm4t_if(af[2], wa + 2 * 2048, more);
        mma16816(w1, af[3][0], af[3][1], af[3][2], af[3][3], of[3][2], of[3][3]);
        ldsm4t_if(af[3], wa + 3 * 2048, more);
        st_strong4(pp, pack_nz(w0[0] + w1[0], w0[1] + w1[1]));
        st_strong4(pp + 1024, pack_nz(w0[2] + w1[2], w0[3] + w1[3]));
        pp += (NT == 3 && i == 0) ? 4 * 8192 : 6 * 8192;
    }
}

template <uint32_t role> DEVINL void r_big(const RMaps& tm, const int wid) {
    extern __shared__ __align__(1024) unsigned char smem_raw[];
    const uint32_t sb = smem_u32(smem_raw);
    const uint32_t bar = sb + R_BAR;
    const int tid = threadIdx.x;
    int h; asm("mov.u32 %0, %%clusterid.x;" : "=r"(h));
        uint32_t a[KR][4];
        {
            const int lane = tid & 31;
            const int krow = (lane & 7) + ((lane >> 4) << 3);
            const int chunk = (wid & 3) * 2 + ((lane >> 3) & 1);
            const uint32_t la = sb + (wid >> 2) * 8192 + krow * 128 + ((chunk ^ (krow & 7)) << 4);
            const CUtensorMap* tw = &tm.w[role];
#pragma unroll
            for (int b = 0; b < KR / 4; b++) {
                mbar_wait(sb + R_O + 8 * b, 0);
                if (b == 0) PT(0);
#pragma unroll
                for (int k = 0; k < 4; k++) ldsm4t(a[b * 4 + k], la + b * 16384 + k * 2048);
                bar_sync(1, 256);
                if (wid == (b & 7)) {
                    fence_async();
                    if (b < 5) {
#pragma unroll
                        for (int q = 2 * b; q < 2 * b + 2; q++) e_tma_load(sb + R_W + q * 8192, tw, h * DH + (q / 5) * 64, KC(KR / 4 + q % 5), bar + 8 * B_PRO1);
                    } else if (b - 5 < (role == 0 ? 4 : 6)) {
                        e_tma_load(sb + R_WO + (b - 5) * 16384, &tm.wo, wo_tile(role, b - 5) * 64, h * DH, bar + 8 * B_PRO0);
                    }
                }
            }
        }
        constexpr uint32_t e0 = role == 0 ? R_QX + 16384 : R_K + 2048, e1 = role == 0 ? R_QX + 24576 : R_V + 2048;
        if (wid == 6) x_load_pair(sb + e0, &tm.x, h, 3, 0, bar + 8 * (B_FULL + 3));
        if (wid == 7) x_load_pair(sb + e1, &tm.x, h, 4, 0, bar + 8 * (B_FULL + 4));
        PT(1);
        mbar_wait(bar + 8 * B_PRO1, 0);
        PT(2);

        constexpr uint64_t dW0 = cdesc(R_W, 1024, 1024, 1);
        constexpr uint64_t dM = cdesc(R_RING, 128, 128, 0);
        constexpr uint64_t dX = cdesc(R_RING, 16, 1024, 1);
        constexpr uint64_t dX0 = cdesc(0, 16, 1024, 1);
        int tb = tid;
        int wq = wid;

        for (int seg = 0; seg < NSEG; seg++) {
            {
            const int s = seg - 1; (void)s;
            float d[16];
            OPAQUE(wq);
            const uint64_t dW = dW0 + (uint64_t)((wq >> 2) * (KS * 128));
#pragma unroll
            for (int p = 0; p < 8; p++) {
                const int slot = p % 5;
                mbar_wait(bar + 8 * (B_FULL + slot), slot < 3 ? (uint32_t)(p / 5) : (uint32_t)(seg & 1));
                PROF2(p);
                const uint64_t db = slot < 3 ? dX + (uint64_t)(slot * 512) : dX0 + (uint64_t)((slot == 3 ? e0 : e1) >> 4);
                wg_fence();
#pragma unroll
                for (int kk = 0; kk < 8; kk++) {
                    const int k = XORD >= 3 ? (kk & 1) * 4 + (kk >> 1) : kk;
                    const int ks = xo(2 * p + (k >> 2)) * 4 + (k & 3);
                    if (ks >= KR) wg_ss32<1>(d, dW + (uint64_t)((ks - KR) * 128), db + (uint64_t)((k >> 2) * 256 + (k & 3) * 2), p + k);
                    else wg_rs32(d, a[ks < KR ? ks : 0], db + (uint64_t)((k >> 2) * 256 + (k & 3) * 2), p + k);
                }
                wg_commit();
                if (p >= 1) {
                    wg_wait<1>();
                    if (p <= 3) {
                        if ((wq & 3) == p) e_arrive(bar + 8 * (B_EMPTY + p - 1));
                        if (wq == p + (p & 1) * 4) {
                            mbar_wait(bar + 8 * (B_EMPTY + p - 1), seg & 1);
                            x_load_pair(sb + R_RING + (p - 1) * 8192, &tm.x, h, p + 4, seg, bar + 8 * (B_FULL + p - 1));
                        }
                    }
                    if (p == 5 && role != 0 && (wq & 3) < 3) e_arrive_remote(mapa(bar + 8 * B_TFREE, wq & 3));
                    if (p == 6 && (wq & 3) == 1) e_arrive(bar + 8 * B_AFREE0);
                    if (p == 7 && (wq & 3) == 2) e_arrive(bar + 8 * B_AFREE1);
                }
            }
            mbar_wait(bar + 8 * B_TFREE, seg & 1);
            asm volatile("wgmma.wait_group.sync.aligned 0;" : ACC16(d)::"memory");
            PROF2(16);
            const uint32_t tilex = sb + (role == 0 ? R_QX + 2048 : (role == 1 ? R_K + 2048 : R_V + 2048));
            {
                OPAQUE(tb);
                const uint32_t gs = role == 0 ? 4096 : 2048;
                const uint32_t sa = tilex + ((tb >> 4) & 1) * gs + (tb >> 5) * 256 + (tb & 15) * 16;
                stsm4(sa, pack_bf16(d[0], d[1]), pack_bf16(d[2], d[3]), pack_bf16(d[4], d[5]), pack_bf16(d[6], d[7]));
                stsm4(sa + 2 * gs, pack_bf16(d[8], d[9]), pack_bf16(d[10], d[11]), pack_bf16(d[12], d[13]), pack_bf16(d[14], d[15]));
            }
            __syncwarp();
            e_arrive(bar + 8 * B_XDONE);
            if (role != 0 && (wq & 3) == 0) {
                mbar_wait(bar + 8 * B_XDONE, seg & 1);
                fence_async();
                uint32_t pr = role + 1 + (wq >> 2); pr = pr >= 3 ? pr - 3 : pr;
                e_bulk_s2s(mapa(tilex, pr), tilex, CPB, mapa(bar + 8 * B_XT, pr));
            }
            }
            {
                const int s = seg;
                OPAQUE(wq);
                const uint64_t dW = dW0 + (uint64_t)((wq >> 2) * (KS * 128));
                float y[4] = {0.f, 0.f, 0.f, 0.f};
                {
                    OPAQUE(tb);
                    const uint32_t ma = sb + R_RING + (tb & 31) * 16;
                    float z[4] = {0.f, 0.f, 0.f, 0.f}, u[4] = {0.f, 0.f, 0.f, 0.f};
                    uint32_t b[QD][4];
                    const int yes = s + 1;
                    mbar_wait(bar + 8 * B_MEM, s & 1);
                    PROF((wq >> 2) * 4 + 0);
                    if (s == 0) PT(3);
                    if (s == 1) PT(4);
#pragma unroll
                    for (int g = 0; g < QD; g++) ldsm4t(b[g], ma + g * 512);
#pragma unroll
                    for (int g = 0; g < KR / 2; g++) {
                        float* c0 = (g % 3 == 0) ? y : (g % 3 == 1) ? u : z;
                        float* c1 = (g % 3 == 0) ? z : (g % 3 == 1) ? y : u;
                        mma16816(c0, a[2 * g][0], a[2 * g][1], a[2 * g][2], a[2 * g][3], b[g % QD][0], b[g % QD][1]);
                        mma16816(c1, a[2 * g + 1][0], a[2 * g + 1][1], a[2 * g + 1][2], a[2 * g + 1][3], b[g % QD][2], b[g % QD][3]);
                        if (g + QD < KR / 2) {
                            if ((g + QD) % 8 == 0) mbar_wait(bar + 8 * (B_MEM + (g + QD) / 8), s & 1);
                            ldsm4t_if(b[g % QD], ma + (g + QD) * 512, yes);
                        }
                    }
                    y[0] += z[0] + u[0]; y[1] += z[1] + u[1]; y[2] += z[2] + u[2]; y[3] += z[3] + u[3];
                }
                PROF2(8);
                mbar_wait(bar + 8 * (B_MEM + 3), s & 1);
                wg_fence();
#pragma unroll
                for (int k = KR; k < 64; k++) wg_ss8<1, 1>(y, dW + (uint64_t)((k - KR) * 128), dM + (uint64_t)(k * 16), 1);
                wg_commit();
                asm volatile("wgmma.wait_group.sync.aligned 0;" : "+f"(y[0]), "+f"(y[1]), "+f"(y[2]), "+f"(y[3])::"memory");
                OPAQUE(tb);
                {
                    const uint32_t wo_ = (tb >> 5) * 256;
                    const uint32_t tile = sb + (role == 0 ? R_QX : (role == 1 ? R_K : R_V)) + wo_;
                    const uint32_t u0 = pack_bf16(y[0], y[1]), u1 = pack_bf16(y[2], y[3]);
                    sts32(tile + (tb & 31) * 4, u0);
                    sts32(tile + (tb & 31) * 4 + 128, u1);
                    __syncwarp();
                    uint4 v = lds128(tile + (tb & 15) * 16);
                    uint32_t peer = role + 1 + ((tb >> 4) & 1);
                    peer = peer >= 3 ? peer - 3 : peer;
                    const uint32_t rt = sb + (role == 0 ? R_QM : (role == 1 ? R_K : R_V)) + wo_ + (tb & 15) * 16;
                    st_async16(mapa(rt, peer), v, mapa(bar + 8 * (role == 2 ? B_HOPV : B_HOP1), peer));
                    if (role == 0) {
                        sts128(tile + 4096 + ((tb >> 4) & 1) * 4096 + (tb & 15) * 16, v);
                        sts32(tile + 12288 + (tb & 31) * 4, u0);
                        sts32(tile + 12288 + (tb & 31) * 4 + 128, u1);
                        __syncwarp();
                    }
                    e_arrive(bar + 8 * (role == 2 ? B_HOPV : B_HOP1));
                }
                PROF((wq >> 2) * 4 + 1);
                if (s < NSEG - 1) {
                    bar_sync(1, 256);
                    if (wq < 3) { fence_async(); x_load_pair(sb + R_RING + wq * 8192, &tm.x, h, wq, s + 1, bar + 8 * (B_FULL + wq)); }
                    else if (role == 0 && wq < 5) x_load_pair(sb + (wq == 3 ? e0 : e1), &tm.x, h, wq, s + 1, bar + 8 * (B_FULL + wq));
                    OPAQUE(tb);
                }
                uint32_t* pp = g_part[s & 3] + (h * 32 + (wo_tile(role, 0) + (tb >> 7)) * 8192 + ((tb >> 5) & 3) * 2048 + (tb & 31));
                asm volatile("" : "+l"(pp));
                if (s == NSEG - 1) break;
                if (s == 0) mbar_wait(bar + 8 * B_PRO0, 0);
                wo_phase<role == 0 ? 2 : 3>(sb, tb, pp, bar + 8 * B_O, s & 1);
                if (wq == 0) PROF(10);
            }
        }
}

#define CLR 0
#define CLEAR(st) do { if (role != 0) { \
                const int w_ = wid & 3; \
                uint32_t* zp = g_part[(st) & 3] + ((rg0 + (w_ >> 1) * 64) * 1024 + (w_ & 1) * 512); \
                e_bulk_s2g(zp, sb + R_Z, 1024); \
                e_bulk_s2g(zp + 256, sb + R_Z, 1024); \
                e_bulk_s2g(&g_mem[(st) & 3][(rg0 + (w_ >> 1) * 64) * 32 + (w_ & 1) * 16], sb + R_Z, 64); \
                bulk_commit(); } } while (0)
template <uint32_t role> DEVINL void r_chain(const RMaps& tm, const bf16* __restrict__ mem0, const int wid) {
    extern __shared__ __align__(1024) unsigned char smem_raw[];
    const uint32_t sb = smem_u32(smem_raw);
    const uint32_t bar = sb + R_BAR;
    const int tid = threadIdx.x;
    int h; asm("mov.u32 %0, %%clusterid.x;" : "=r"(h));
        int t = tid & 127;
        const float sl2 = 0.08838834764831845f * 1.4426950408889634f;
        const float NEGRAW = -1000000000.0f / 0.08838834764831845f;
        const int rg0 = ((int)role - 1) * 32 + h;
        if (role != 0) {
#pragma unroll 1
            for (int r = 0; r < 4; r++) {
                uint32_t* zp = g_part[r] + ((rg0 + (t >> 6) * 64) * 1024 + (t & 63) * 4);
#pragma unroll
                for (int i = 0; i < 4; i++) st_strong16(zp + i * 256, make_uint4(0u, 0u, 0u, 0u));
                if ((t & 63) < 8) st_strong16(&g_mem[r][(rg0 + (t >> 6) * 64) * 32 + (t & 63) * 4], make_uint4(0u, 0u, 0u, 0u));
            }
            __threadfence();
        }
        if (role == 0 && (wid & 3) < 3) e_arrive_remote(mapa(bar + 8 * B_TFREE, wid & 3));
        if (t < 64) sts128(sb + R_Z + t * 16, make_uint4(0u, 0u, 0u, 0u));
        if (role == 0) sts128(sb + R_QM + t * 16, make_uint4(0u, 0u, 0u, 0u));
        {
            uint4 v[8];
#pragma unroll
            for (int r = 0; r < 8; r++) v[r] = __ldg((const uint4*)(mem0 + r * DM) + t);
            mbar_wait(bar + 8 * B_AFREE0, 0);
            mbar_wait(bar + 8 * B_AFREE1, 0);
#define TR2(f, c) \
            sts128(sb + R_RING + t * 128 + (c) * 16, make_uint4(__byte_perm(v[0].f, v[1].f, 0x5410), __byte_perm(v[2].f, v[3].f, 0x5410), __byte_perm(v[4].f, v[5].f, 0x5410), __byte_perm(v[6].f, v[7].f, 0x5410))); \
            sts128(sb + R_RING + t * 128 + (c) * 16 + 16, make_uint4(__byte_perm(v[0].f, v[1].f, 0x7632), __byte_perm(v[2].f, v[3].f, 0x7632), __byte_perm(v[4].f, v[5].f, 0x7632), __byte_perm(v[6].f, v[7].f, 0x7632)));
            TR2(x, 0) TR2(y, 2) TR2(z, 4) TR2(w, 6)
            fence_async();
            __syncwarp();
            e_arrive(bar + 8 * B_MEM + (t >> 5) * 8);
        }
        constexpr uint64_t dQ = role == 0 ? cdesc(R_QX, 128, 2048, 0) : cdesc(R_QM, 128, 0, 0);
        constexpr uint64_t dK = cdesc(R_K, 128, 2048, 0);

        for (int s = 0; s < NSEG; s++) {
            if (role == 0) {
                uint32_t n = 0, gate;
                do { gate = ld_strong4(&g_gate[s * SEG + (t >> 2)]); if (++n > 20000000u) __trap(); } while (gate == 0u);
                sts32(sb + R_G + (t >> 2) * 4, gate);
                __syncwarp();
            }
            mbar_wait(bar + 8 * B_XDONE, s & 1);
            mbar_wait(bar + 8 * B_XT, s & 1);
            if (t >= 1 && t < 3) { uint32_t pr = role + t; pr = pr >= 3 ? pr - 3 : pr; mbar_arrive_remote(mapa(bar + 8 * B_XRECV, pr)); }
            __syncwarp();
            mbar_wait(bar + 8 * B_HOP1, s & 1);
            PROF(8);
            fence_async();
            OPAQUE(t);
            if (s == NSEG - 1 && role != 0) { mbar_wait(bar + 8 * B_HOPV, s & 1); bulk_wait_all(); break; }
            float sc[20];
            wg_fence();
#pragma unroll
            for (int k = 0; k < 8; k++) wg_ss40(sc, dQ + (uint64_t)(k * 16), dK + (uint64_t)(k * 16), k);
            wg_commit();
            uint32_t t_o = clk32() + 500;
            {
                const uint32_t va = sb + R_V + 2048 + (t >> 5) * 512 + ((t >> 4) & 1) * 2048 + (t & 15) * 16;
                uint32_t v0[4], v1[4];
                ldsm4(v0, va); ldsm4(v1, va + 256);
                uint32_t vm[4];
                const bool v_here = mbar_try(bar + 8 * B_HOPV, s & 1);
                if (v_here) ldsm4(vm, sb + R_V + t * 16);
                wg_wait<0>();
                if (role == 0) {
#pragma unroll
                    for (int j = 0; j < 5; j++)
                        asm volatile("st.shared.v2.f32 [%0], {%1,%2};" ::"r"(sb + R_QX + 768 + (t >> 5) * 4096 + j * 256 + (t & 31) * 8), "f"(sc[4 * j + 2]), "f"(sc[4 * j + 3]) : "memory");
                }
                float m = fmaxf(sc[0], sc[1]);
#pragma unroll
                for (int j = 1; j < 5; j++) m = fmaxf(m, fmaxf(sc[4 * j], sc[4 * j + 1]));
                m = fmaxf(m, __shfl_xor_sync(0xffffffffu, m, 1));
                m = fmaxf(m, __shfl_xor_sync(0xffffffffu, m, 2));
                const float mb = m * sl2;
                uint32_t pk[5];
#pragma unroll
                for (int j = 0; j < 5; j++) pk[j] = pack_bf16(ex2(fmaf(sc[4 * j], sl2, -mb)), ex2(fmaf(sc[4 * j + 1], sl2, -mb)));
                float o0[4] = {0.f, 0.f, 0.f, 0.f}, o1[4] = {0.f, 0.f, 0.f, 0.f}, ls[4] = {0.f, 0.f, 0.f, 0.f};
                constexpr uint32_t ONE = 0x3F803F80u;
                mma16816(o0, v0[0], v0[1], v0[2], v0[3], pk[1], pk[2]);
                mma16816(o1, v1[0], v1[1], v1[2], v1[3], pk[1], pk[2]);
                ldsm4(v0, va + 4096); ldsm4(v1, va + 4096 + 256);
                mma16816(ls, ONE, ONE, ONE, ONE, pk[1], pk[2]);
                mma16816(ls, ONE, ONE, ONE, ONE, pk[3], pk[4]);
                mma1688(ls, ONE, ONE, pk[0]);
                mma16816(o0, v0[0], v0[1], v0[2], v0[3], pk[3], pk[4]);
                mma16816(o1, v1[0], v1[1], v1[2], v1[3], pk[3], pk[4]);
                if (!v_here) { mbar_wait(bar + 8 * B_HOPV, s & 1); ldsm4(vm, sb + R_V + t * 16); }
                mma1688(o0, vm[0], vm[1], pk[0]);
                mma1688(o1, vm[2], vm[3], pk[0]);
                const float i0 = rcp(ls[0]), i1 = rcp(ls[1]);
                const uint32_t oa = sb + R_O + (t >> 5) * 512 + (t & 31) * 4;
                sts32(oa, pack_bf16(o0[0] * i0, o0[1] * i1));
                sts32(oa + 128, pack_bf16(o0[2] * i0, o0[3] * i1));
                sts32(oa + 256, pack_bf16(o1[0] * i0, o1[1] * i1));
                sts32(oa + 384, pack_bf16(o1[2] * i0, o1[3] * i1));
                __syncwarp();
                e_arrive(bar + 8 * B_O);
                PROF(9);
                if (role == 0) {
                    OPAQUE(t);
                    const int lim = (t >> 2) - (t & 3) * 2 + 8;
                    float z[10];
#pragma unroll
                    for (int j = 0; j < 5; j++)
                        asm volatile("ld.shared.v2.f32 {%0,%1}, [%2];" : "=f"(z[2 * j]), "=f"(z[2 * j + 1]) : "r"(sb + R_QX + 768 + (t >> 5) * 4096 + j * 256 + (t & 31) * 8) : "memory");
                    float gate; asm volatile("ld.shared.f32 %0, [%1];" : "=f"(gate) : "r"(sb + R_G + (t >> 2) * 4) : "memory");
                    float m1 = fmaxf(z[0], z[1]);
#pragma unroll
                    for (int j = 1; j < 5; j++) {
                        z[2 * j] = 8 * j <= lim ? z[2 * j] : NEGRAW;
                        z[2 * j + 1] = 8 * j + 1 <= lim ? z[2 * j + 1] : NEGRAW;
                        m1 = fmaxf(m1, fmaxf(z[2 * j], z[2 * j + 1]));
                    }
                    m1 = fmaxf(m1, __shfl_xor_sync(0xffffffffu, m1, 1));
                    m1 = fmaxf(m1, __shfl_xor_sync(0xffffffffu, m1, 2));
                    const float mb1 = m1 * sl2;
                    float l1 = 0.f;
                    const uint32_t pa = sb + R_QX + (t >> 5) * 4096 + (t & 31) * 4;
#pragma unroll
                    for (int j = 0; j < 5; j++) {
                        const uint32_t pw = pack_bf16(ex2(fmaf(z[2 * j], sl2, -mb1)), ex2(fmaf(z[2 * j + 1], sl2, -mb1)));
                        l1 += __uint_as_float(pw << 16) + __uint_as_float(pw & 0xffff0000u);
                        sts32(pa + j * 128, pw);
                    }
                    sts32(pa + 5 * 128, 0u);
                    l1 += __shfl_xor_sync(0xffffffffu, l1, 1);
                    l1 += __shfl_xor_sync(0xffffffffu, l1, 2);
                    sts32(sb + R_G + 128 + (t >> 2) * 4, __float_as_uint(gate * rcp(l1)));
                    spin_until(t_o + PVD);
                    if ((wid & 3) == 0 && s >= 1) { bulk_wait_all(); e_count(&g_ocnt[(s - 1) >> 2]); }
                    fence_async();
                    bar_sync(2, 128);
                    constexpr uint64_t dV = cdesc(R_V, 2048, 128, 0);
                    constexpr uint64_t dP = cdesc(R_QX, 128, 4096, 0);
                    float sf[8];
#pragma unroll
                    for (int j = 0; j < 4; j++) asm volatile("ld.shared.v2.f32 {%0,%1}, [%2];" : "=f"(sf[2 * j]), "=f"(sf[2 * j + 1]) : "r"(sb + R_G + 128 + j * 32 + (t & 3) * 8) : "memory");
                    const uint32_t r = ((t >> 4) & 1) * 8 + (t & 7), ch = (t >> 5) * 2 + ((t >> 3) & 1);
                    const uint32_t sa = sb + R_QX + 2048 + r * 128 + ((ch ^ (r & 7)) << 4);
#pragma unroll
                    for (int hf = 0; hf < 2; hf++) {
                        float d[16];
                        wg_fence();
#pragma unroll
                        for (int k = 0; k < 3; k++) wg_ss32<0>(d, dV + (uint64_t)(hf * 64 + k * 256), dP + (uint64_t)(k * 16), k);
                        wg_commit();
                        asm volatile("wgmma.wait_group.sync.aligned 0;" : ACC16(d)::"memory");
                        stsm4t(sa + hf * 8192, pack_bf16(d[0] * sf[0], d[1] * sf[1]), pack_bf16(d[2] * sf[0], d[3] * sf[1]), pack_bf16(d[4] * sf[2], d[5] * sf[3]), pack_bf16(d[6] * sf[2], d[7] * sf[3]));
                        stsm4t(sa + hf * 8192 + 4096, pack_bf16(d[8] * sf[4], d[9] * sf[5]), pack_bf16(d[10] * sf[4], d[11] * sf[5]), pack_bf16(d[12] * sf[6], d[13] * sf[7]), pack_bf16(d[14] * sf[6], d[15] * sf[7]));
                    }
                    fence_async();
                    bar_sync(2, 128);
                    if ((wid & 3) == 0) {
#pragma unroll
                        for (int q = 0; q < 4; q++) e_tma_store(&tm.o, sb + R_QX + 2048 + q * 4096, h * DH + (q >> 1) * 64, s * SEG + (q & 1) * 16);
                        bulk_commit();
                        bulk_wait_read();
                    }
                    if ((wid & 3) < 3) e_arrive_remote(mapa(bar + 8 * B_TFREE, wid & 3));
                }
            }
            if (t < 32) { e_expect(bar + 8 * B_HOP1, role == 2 ? 4096 : 2048); if (role != 2) e_expect(bar + 8 * B_HOPV, 2048); e_expect(bar + 8 * B_XT, role == 0 ? 2 * CPB : CPB); }
            if (s == NSEG - 1) { bulk_wait_all(); break; }
            if (role != 0 && (wid & 3) >= 2) {
                mbar_wait(bar + 8 * B_XRECV, s & 1);
                mbar_wait(bar + 8 * B_O, s & 1);
                fence_async();
                spin_until(t_o + ELD);
                x_load_pair(sb + ((wid & 1) ? R_V + 2048 : R_K + 2048), &tm.x, h, 3 + (wid & 1), s + 1, bar + 8 * (B_FULL + 3 + (wid & 1)));
            }
            OPAQUE(t);
            PROF(11);
            if (role != 0 || DDUP) {
                const int grp = role == 0 ? (t >> 6) * 32 + h : rg0 + (t >> 6) * 64;
                const uint32_t* rp = g_part[s & 3] + (grp * 1024 + ((t >> 2) & 7) * 32 + ((t >> 5) & 1) * 16 + (t & 3) * 4);
                uint32_t* wp = &g_mem[(s + 1) & 3][grp * 32 + ((t >> 5) & 1) * 16 + (t & 3) * 4 + ((t >> 3) & 3)];
                bulk_wait_all();
                spin_until(t_o + D2_BASE + (role == 0 ? DDUP + (t >> 6) * D2_STEP : (role - 1 + (t >> 6) * 2) * D2_STEP));
                PROF3(0, clk32());
#define LO(u) __uint_as_float((u) << 16)
#define HI(u) __uint_as_float((u) & 0xffff0000u)
                uint4 v[4];
                uint32_t n = poll_set<4>(v, rp, 256, (role - 1 + (t >> 6) * 2) * PHQ);
                {
                    PROF3(1, clk32());
                    float f[8];
                    f[0] = (LO(v[0].x) + LO(v[1].x)) + (LO(v[2].x) + LO(v[3].x)); f[1] = (HI(v[0].x) + HI(v[1].x)) + (HI(v[2].x) + HI(v[3].x));
                    f[2] = (LO(v[0].y) + LO(v[1].y)) + (LO(v[2].y) + LO(v[3].y)); f[3] = (HI(v[0].y) + HI(v[1].y)) + (HI(v[2].y) + HI(v[3].y));
                    f[4] = (LO(v[0].z) + LO(v[1].z)) + (LO(v[2].z) + LO(v[3].z)); f[5] = (HI(v[0].z) + HI(v[1].z)) + (HI(v[2].z) + HI(v[3].z));
                    f[6] = (LO(v[0].w) + LO(v[1].w)) + (LO(v[2].w) + LO(v[3].w)); f[7] = (HI(v[0].w) + HI(v[1].w)) + (HI(v[2].w) + HI(v[3].w));
                    const bool b4 = t & 16, b3 = t & 8;
                    float g4[4], g2[2];
#pragma unroll
                    for (int i = 0; i < 4; i++) g4[i] = (b4 ? f[4 + i] : f[i]) + __shfl_xor_sync(0xffffffffu, b4 ? f[i] : f[4 + i], 16);
#pragma unroll
                    for (int i = 0; i < 2; i++) g2[i] = (b3 ? g4[2 + i] : g4[i]) + __shfl_xor_sync(0xffffffffu, b3 ? g4[i] : g4[2 + i], 8);
                    g2[0] += __shfl_xor_sync(0xffffffffu, g2[0], 4);
                    g2[1] += __shfl_xor_sync(0xffffffffu, g2[1], 4);
                    st_strong4(wp, pack_nz(g2[0], g2[1]));
                }
                PROF3(8, n); (void)n;
            }
            t_o += D2_BASE + DQ + D3 + (t >> 5) * D2_STEP;
            OPAQUE(t);
            PROF(12);
            {
                const uint32_t* rp = &g_mem[(s + 1) & 3][((t >> 5) * 256 + (t & 31)) * 4];
                const uint32_t da = sb + R_RING + ((t >> 5) * 256 + (t & 31)) * 16;
                uint4 v[8];
                spin_until(t_o);
                PROF3(2, clk32());
                uint32_t n = poll_set<8>(v, rp, 128, PH3 + (t >> 5) * PHQ);
                PROF(13);
                PROF3(3, clk32()); PROF3(9, n); (void)n;
                mbar_wait(bar + 8 * B_AFREE0 + (t >> 6) * 8, (s + 1) & 1);
                PROF3(4, clk32());
#pragma unroll
                for (int i = 0; i < 8; i++) sts128(da + i * 512, v[i]);
                if (t >= 64) fence_async();
                __syncwarp();
                e_arrive(bar + 8 * B_MEM + (t >> 5) * 8);
                PROF(14);
                PROF3(5, clk32());
            }
            CLEAR(s + 3);
        }
}

__global__ void __launch_bounds__(384, 1) r_kernel(const __grid_constant__ RMaps tm, const bf16* __restrict__ mem0, const bf16* __restrict__ x, const bf16* __restrict__ gate_w) {
    extern __shared__ __align__(1024) unsigned char smem_raw[];
    const uint32_t sb = smem_u32(smem_raw);
    if ((sb & 0x3FFFFu) != SB0) __trap();
    const int tid = threadIdx.x;
    const int wid = __shfl_sync(0xffffffffu, tid >> 5, 0);
    uint32_t role; asm("mov.u32 %0, %%cluster_ctarank;" : "=r"(role));
    int h; asm("mov.u32 %0, %%clusterid.x;" : "=r"(h));
    const uint32_t bar = sb + R_BAR;
    asm volatile("griddepcontrol.launch_dependents;");
    KT(0, 0);
    const int gr = blockIdx.x * 12 + wid;
    uint4 gx0[4], gx1[4], gw[4];
#pragma unroll
    for (int i = 0; i < 4; i++) {
        gx0[i] = ldg_nc((const uint4*)(x + gr * DM) + i * 32 + (tid & 31));
        gx1[i] = ldg_nc((const uint4*)(x + min(gr + 1152, SEQ - 1) * DM) + i * 32 + (tid & 31));
        gw[i] = ldg_nc((const uint4*)gate_w + i * 32 + (tid & 31));
    }

    if (tid == 0) {
        for (int i = 0; i < 5; i++) mbar_init(bar + 8 * (B_FULL + i), 1);
        for (int i = 0; i < 3; i++) mbar_init(bar + 8 * (B_EMPTY + i), 2);
        for (int i = 0; i < 4; i++) mbar_init(bar + 8 * (B_MEM + i), 1);
        mbar_init(bar + 8 * B_HOP1, role == 2 ? 1 : 9);
        mbar_init(bar + 8 * B_HOPV, role == 2 ? 8 : 1);
        mbar_init(bar + 8 * B_XT, 1);
        mbar_init(bar + 8 * B_TFREE, 5);
        mbar_init(bar + 8 * B_P, 4);
        mbar_init(bar + 8 * B_XDONE, 8);
        mbar_init(bar + 8 * B_OST0, 4);
        mbar_init(bar + 8 * B_OST1, 4);
        mbar_init(bar + 8 * B_XRECV, 2);
        mbar_init(bar + 8 * B_O, 4);
        mbar_init(bar + 8 * B_AFREE0, 2);
        mbar_init(bar + 8 * B_AFREE1, 2);
        mbar_init(bar + 8 * B_PRO0, 1);
        mbar_init(bar + 8 * B_PRO1, 1);
        for (int i = 0; i < KR / 4; i++) mbar_init(sb + R_O + 8 * i, 1);
        asm volatile("fence.mbarrier_init.release.cluster;" ::: "memory");
        fence_async();
        for (int i = 0; i < KR / 4; i++) mbar_expect(sb + R_O + 8 * i, 16384);
        mbar_expect(bar + 8 * B_PRO1, KS * 4096);
        mbar_expect(bar + 8 * B_PRO0, (role == 0 ? 4 : 6) * 16384);
        for (int i = 0; i < 3; i++) mbar_expect(bar + 8 * (B_FULL + i), 8192);
        mbar_expect(bar + 8 * B_HOP1, role == 2 ? 4096 : 2048);
        if (role != 2) mbar_expect(bar + 8 * B_HOPV, 2048);
        mbar_expect(bar + 8 * B_XT, role == 0 ? 2 * CPB : CPB);
    }
    __syncthreads();
    asm volatile("barrier.cluster.arrive.relaxed.aligned;" ::: "memory");
    {
        const CUtensorMap* tw = &tm.w[role];
        if (wid < 11) {
            e_tma_load(sb + wid * 16384, tw, h * DH, KC(wid), sb + R_O + 8 * wid);
            e_tma_load(sb + wid * 16384 + 8192, tw, h * DH + 64, KC(wid), sb + R_O + 8 * wid);
        }
        if (wid < 6) e_tma_load(sb + R_RING + wid * 4096, &tm.x, XC(wid), 0, bar + 8 * (B_FULL + (wid >> 1)));
        __syncwarp();
        const uint32_t g0 = __float_as_uint(gate_row(gx0, gw)), g1 = __float_as_uint(gate_row(gx1, gw));
        if ((tid & 31) == 0) {
            st_strong4(&g_gate[gr], g0 ? g0 : 0x80000000u);
            if (gr + 1152 < SEQ) st_strong4(&g_gate[gr + 1152], g1 ? g1 : 0x80000000u);
        }
        __syncwarp();
    }
    asm volatile("barrier.cluster.wait.aligned;" ::: "memory");

    if (wid < 8) {
        asm volatile("setmaxnreg.inc.sync.aligned.u32 224;");
        if (role == 0) r_big<0>(tm, wid); else if (role == 1) r_big<1>(tm, wid); else r_big<2>(tm, wid);
    } else {
        asm volatile("setmaxnreg.dec.sync.aligned.u32 56;");
        if (role == 0) r_chain<0>(tm, mem0, wid); else if (role == 1) r_chain<1>(tm, mem0, wid); else r_chain<2>(tm, mem0, wid);
    }
    __syncwarp();
    asm volatile("barrier.cluster.arrive; barrier.cluster.wait;" ::: "memory");
    KT(0, 1);
}

#define STAG 0
constexpr int G_ST = 4;
constexpr int G_STAGE = 16384 + 32768;
constexpr int G_EPI = G_ST * G_STAGE;
constexpr int G_GATE = G_EPI + 32768;
constexpr int G_BAR = G_GATE + 1024;
constexpr int G_SMEM = G_BAR + 128 + 1024;

struct G1Maps { CUtensorMap x, wg, wu, hs, o, h, wo, wd, out; };
constexpr int G1_NB = FF / 128;
constexpr int G1_TILES = 16 * G1_NB;

DEVINL void g_mma_block(float* d, uint32_t sb, uint32_t bar, int it, int wg, int tid, bool first) {
    const int st = it % G_ST;
    mbar_wait(bar + 8 * st, (it / G_ST) & 1);
    const uint64_t da = mkdesc(sb + st * G_STAGE + wg * 8192, 16, 1024, 1);
    const uint64_t db = mkdesc(sb + st * G_STAGE + 16384, 8192, 1024, 1);
    wg_fence();
#pragma unroll
    for (int k = 0; k < 4; k++) wg_ss256(d, da + (uint64_t)(k * 2), db + (uint64_t)(k * 128), (first ? 0 : 1) | k);
    wg_commit();
    if (!first) { wg_wait<1>(); if ((tid & 127) == 0) mbar_arrive(bar + 8 * (G_ST + (it - 1) % G_ST)); }
}
DEVINL void g_load_block(uint32_t sb, uint32_t bar, int it, const CUtensorMap* ta, int k0, int m0, const CUtensorMap* tb, int n0) {
    const int st = it % G_ST;
    mbar_wait(bar + 8 * (G_ST + st), ((it / G_ST) & 1) ^ 1);
    const uint32_t fb = bar + 8 * st, sa = sb + st * G_STAGE;
    mbar_expect(fb, G_STAGE);
    tma_load(sa, ta, k0, m0, fb);
#pragma unroll
    for (int q = 0; q < 4; q++) tma_load(sa + 16384 + q * 8192, tb, n0 + q * 64, k0, fb);
}

DEVINL void g_store_tile(const float* d, const CUtensorMap* tout, uint32_t epi, int mb, int nb, int wg, int tid) {
    const int lane = tid & 31, row = ((tid >> 5) & 3) * 16 + ((lane >> 3) & 1) * 8 + (lane & 7);
#pragma unroll
    for (int half = 0; half < 2; half++) {
        if ((tid & 127) == 0) bulk_wait_read();
        bar_sync(1 + wg, 128);
#pragma unroll
        for (int j = 0; j < 16; j += 2) {
            const float* e = d + half * 64 + 4 * j;
            const int cgp = j + (lane >> 4);
            stsm4(epi + (cgp >> 3) * 8192 + row * 128 + (((cgp & 7) ^ (row & 7)) << 4),
                  pack_bf16(e[0], e[1]), pack_bf16(e[2], e[3]), pack_bf16(e[4], e[5]), pack_bf16(e[6], e[7]));
        }
        fence_async();
        bar_sync(1 + wg, 128);
        if ((tid & 127) == 0) {
            tma_store(tout, epi, nb * 256 + half * 128, mb * 128 + wg * 64);
            tma_store(tout, epi + 8192, nb * 256 + half * 128 + 64, mb * 128 + wg * 64);
            bulk_commit();
        }
    }
}
template <int NS> DEVINL void g_split_finish(const float* d, float4 (&r)[32 / NS], uint4* sk, int tile, int ks, bf16* __restrict__ out, int tid) {
    constexpr int Q = 32 / NS;
    uint4* mine = sk + ks * (16 * 256) + tid;
#pragma unroll
    for (int c = 0; c < NS; c++) {
        if (c != ks) {
#pragma unroll
            for (int q = c * Q / 2; q < (c + 1) * Q / 2; q++)
                __stcg(mine + q * 256, make_uint4(pack_bf16(d[8 * q], d[8 * q + 1]), pack_bf16(d[8 * q + 2], d[8 * q + 3]), pack_bf16(d[8 * q + 4], d[8 * q + 5]), pack_bf16(d[8 * q + 6], d[8 * q + 7])));
        } else {
#pragma unroll
            for (int q = 0; q < Q; q++) { const float* e = d + (c * Q + q) * 4; r[q].x += e[0]; r[q].y += e[1]; r[q].z += e[2]; r[q].w += e[3]; }
        }
    }
    __threadfence();
    bar_sync(3, 256);
    if (tile >= T_LATE) PT(20);
    if (tid == 0) {
        atomicAdd(&g_skcnt[tile], 1u);
        uint32_t v, n = 0;
        do {
            asm volatile("ld.acquire.gpu.global.u32 %0, [%1];" : "=r"(v) : "l"(&g_skcnt[tile]) : "memory");
            if (++n > 200000000u) __trap();
        } while (v < NS);
        if (atomicAdd(&g_skcnt[tile], 1u) == 2 * NS - 1) g_skcnt[tile] = 0u;
    }
    bar_sync(3, 256);
    if (tile >= T_LATE) PT(21);
#pragma unroll
    for (int c = 1; c < NS; c++) {
        const uint4* th = sk + (((ks + c) & (NS - 1)) * 16 + ks * (Q / 2)) * 256 + tid;
#pragma unroll
        for (int q = 0; q < Q / 2; q++) {
            const uint4 u = __ldcg(th + q * 256);
            r[2 * q].x += __uint_as_float(u.x << 16); r[2 * q].y += __uint_as_float(u.x & 0xffff0000u);
            r[2 * q].z += __uint_as_float(u.y << 16); r[2 * q].w += __uint_as_float(u.y & 0xffff0000u);
            r[2 * q + 1].x += __uint_as_float(u.z << 16); r[2 * q + 1].y += __uint_as_float(u.z & 0xffff0000u);
            r[2 * q + 1].z += __uint_as_float(u.w << 16); r[2 * q + 1].w += __uint_as_float(u.w & 0xffff0000u);
        }
    }
    const int lane = tid & 31;
    uint32_t* op = (uint32_t*)(out + ((tile >> 2) * 128 + (tid >> 5) * 16 + (lane >> 2)) * DM + (tile & 3) * 256 + ks * Q * 8 + (lane & 3) * 2);
#pragma unroll
    for (int q = 0; q < Q; q++) { op[q * 4] = pack_bf16(r[q].x, r[q].y); op[q * 4 + 4 * DM] = pack_bf16(r[q].z, r[q].w); }
}
DEVINL int g1_count(int pass, int tail) {
    return pass == 0 ? NPRE : pass == 1 ? NFULL : pass == 2 ? T_MID - NFULL : pass == 3 ? (T_MID2 - T_MID) * 4 : tail ? (64 - T_LATE) * 8 : (T_LATE - T_MID2) * 8;
}
DEVINL int g1_first(int pass, int tail) {
    const int b = blockIdx.x, n = gridDim.x;
    return (pass < 2 || tail) ? b : pass == 2 ? n - 1 - b : (b + n - (pass == 3 ? 16 : 32)) % n;
}
DEVINL int g1_tile(int pass, int tail, int i) {
    return pass == 1 ? i : pass == 3 ? T_MID + (i >> 2) : pass == 4 ? (tail ? T_LATE : T_MID2) + (i >> 3) : NFULL + i;
}
constexpr int H_EARLY = 24;

__global__ void __launch_bounds__(384, 1) g1_kernel(const __grid_constant__ G1Maps tm, bf16* __restrict__ out, const int tail) {
    extern __shared__ __align__(1024) unsigned char smem_raw[];
    const uint32_t sb = (smem_u32(smem_raw) + 1023) & ~1023u;
    const int tid = threadIdx.x, lane = tid & 31;
    const int wg = __shfl_sync(0xffffffffu, tid >> 7, 0);
    const int warp = __shfl_sync(0xffffffffu, (tid >> 5) & 3, 0);
    const uint32_t bar = sb + G_BAR;
    asm volatile("griddepcontrol.launch_dependents;");
    KT(1 + tail, 0);
    if (tail && (tid == 32 || tid == 64)) asm volatile("prefetch.tensormap [%0];" ::"l"(tid == 32 ? &tm.o : &tm.wo) : "memory");
    const int ntiles = tail ? 0 : G1_TILES;
    if (tid == 0) {
        for (int i = 0; i < G_ST; i++) { mbar_init(bar + 8 * i, 1); mbar_init(bar + 8 * (G_ST + i), 2); }
        fence_async();
    }
    __syncthreads();
    if (tail) PT(16);
    if (tail) asm volatile("griddepcontrol.wait;" ::: "memory");
    if (tail) PT(17);
    if (tail && tid < 32 * G_ST) {
        const int it = tid >> 5, tile = T_LATE + (blockIdx.x >> 3), k0 = ((blockIdx.x & 7) * 8 + it) * 64;
        e_expect(bar + 8 * it, G_STAGE);
        e_tma_load(sb + it * G_STAGE, &tm.o, k0, (tile >> 2) * 128, bar + 8 * it);
#pragma unroll
        for (int q = 0; q < 4; q++) e_tma_load(sb + it * G_STAGE + 16384 + q * 8192, &tm.wo, (tile & 3) * 256 + q * 64, k0, bar + 8 * it);
    }
    if (wg == 2) {
        asm volatile("setmaxnreg.dec.sync.aligned.u32 40;");
        if (tail && warp == 1) {
            if (blockIdx.x < SEQ / 32) g_gate[blockIdx.x * 32 + lane] = 0u;
            if (blockIdx.x == 0) { if (lane < 16) g_ocnt[lane] = 0u; g_hcnt[lane] = 0u; g_pcnt[lane] = 0u; g_pcnt[32 + lane] = 0u; }
        }
        if (warp == 0) {
            if (lane == 0) {
                int it = 0;
                for (int tile = blockIdx.x; tile < ntiles; tile += gridDim.x) {
                    const int mb = tile & 15, nb = tile >> 4;
                    for (int kb = 0; kb < 16; kb++, it++) {
                        const int st = it % G_ST;
                        mbar_wait(bar + 8 * (G_ST + st), ((it / G_ST) & 1) ^ 1);
                        const uint32_t fb = bar + 8 * st, sa = sb + st * G_STAGE;
                        mbar_expect(fb, G_STAGE);
                        tma_load(sa, &tm.x, kb * 64, mb * 128, fb);
                        tma_load(sa + 16384, &tm.wg, nb * 128, kb * 64, fb);
                        tma_load(sa + 16384 + 8192, &tm.wg, nb * 128 + 64, kb * 64, fb);
                        tma_load(sa + 16384 + 16384, &tm.wu, nb * 128, kb * 64, fb);
                        tma_load(sa + 16384 + 24576, &tm.wu, nb * 128 + 64, kb * 64, fb);
                    }
                }
                for (int pass = tail ? 4 : 0; pass < 5; pass++) {
                    for (int i = g1_first(pass, tail); i < g1_count(pass, tail); i += gridDim.x) {
                        const int tile = g1_tile(pass, tail, i), mb = tile >> 2, nb = tile & 3;
                        if (pass < 2) {
                            for (int kb = 0; kb < FF / 64; kb++, it++) {
                                if (kb == 0 || kb == 2 * H_EARLY) {
                                    wait_count(&g_hcnt[kb ? 16 + mb : mb], kb ? 2 * (G1_NB - H_EARLY) : 2 * H_EARLY);
                                    asm volatile("fence.proxy.async;" ::: "memory");
                                }
                                g_load_block(sb, bar, it, &tm.h, kb * 64, mb * 128, &tm.wd, nb * 256);
                            }
                        }
                        if (pass > 0) {
                            const int k0 = pass == 3 ? (i & 3) * 16 : pass == 4 ? (i & 7) * 8 : 0, k1 = pass == 3 ? k0 + 16 : pass == 4 ? k0 + 8 : HD / 64;
                            if (!tail) wait_count(&g_ocnt[mb], NH * 4);
                            asm volatile("fence.proxy.async;" ::: "memory");
                            for (int kb = k0; kb < k1; kb++, it++) if (!tail || it >= G_ST) g_load_block(sb, bar, it, &tm.o, kb * 64, mb * 128, &tm.wo, nb * 256);
                        }
                    }
                }
            }
        }
    } else {
        asm volatile("setmaxnreg.inc.sync.aligned.u32 232;");
        float d[128];
        int it = 0;
        const uint32_t epi = sb + G_EPI + wg * 16384;
        const int row = warp * 16 + ((lane >> 3) & 1) * 8 + (lane & 7);
        for (int tile = blockIdx.x; tile < ntiles; tile += gridDim.x) {
            const int mb = tile & 15, nb = tile >> 4;
            const uint32_t* gp = &g_gate[mb * 128 + wg * 64 + warp * 16 + (lane >> 2)];
            uint32_t u0 = ld_strong4(gp), u1 = ld_strong4(gp + 8);
            for (int kb = 0; kb < 16; kb++, it++) {
                if (it == (wg ? 0 : STAG)) bar_sync(4, 256);
                g_mma_block(d, sb, bar, it, wg, tid, kb == 0);
            }
            wg_wait<0>();
            for (uint32_t n = 0; u0 == 0u || u1 == 0u; n++) { u0 = ld_strong4(gp); u1 = ld_strong4(gp + 8); if (n > 20000000u) __trap(); }
            __syncwarp();
            const float s0 = 1.0f - __uint_as_float(u0), s1 = 1.0f - __uint_as_float(u1);
            if ((tid & 127) == 0) {
                mbar_arrive(bar + 8 * (G_ST + (it - 1) % G_ST));
                bulk_wait_all();
                const int pt = tile - (int)gridDim.x;
                if (pt >= 0) atomicAdd(&g_hcnt[(pt & 15) + ((pt >> 4) >= H_EARLY ? 16 : 0)], 1u);
            }
            bar_sync(1 + wg, 128);
#pragma unroll
            for (int j = 0; j < 16; j += 2) {
                uint32_t p[4];
#pragma unroll
                for (int q = 0; q < 4; q++) {
                    const int i = (j + (q >> 1)) * 4 + (q & 1) * 2;
                    const float sc = (q & 1) ? s1 : s0;
                    const float g0 = d[i], g1 = d[i + 1];
                    const float a0 = 1.0f + ex2(fminf(g0 * -1.4426950408889634f, 62.0f)), a1 = 1.0f + ex2(fminf(g1 * -1.4426950408889634f, 62.0f));
                    const float rr = rcp(a0 * a1) * sc;
                    const float h0 = (g0 * d[64 + i]) * (rr * a1);
                    const float h1 = (g1 * d[64 + i + 1]) * (rr * a0);
                    p[q] = pack_bf16(h0, h1);
                }
                const int cgp = j + (lane >> 4);
                stsm4(epi + (cgp >> 3) * 8192 + row * 128 + (((cgp & 7) ^ (row & 7)) << 4), p[0], p[1], p[2], p[3]);
            }
            fence_async();
            bar_sync(1 + wg, 128);
            if ((tid & 127) == 0) {
                tma_store(&tm.hs, epi, nb * 128, mb * 128 + wg * 64);
                tma_store(&tm.hs, epi + 8192, nb * 128 + 64, mb * 128 + wg * 64);
                bulk_commit();
            }
        }
        if ((tid & 127) == 0 && !tail) {
            bulk_wait_all();
            const int pt = blockIdx.x + (G1_TILES - 1 - blockIdx.x) / gridDim.x * gridDim.x;
            atomicAdd(&g_hcnt[(pt & 15) + ((pt >> 4) >= H_EARLY ? 16 : 0)], 1u);
        }
        for (int pass = tail ? 4 : 0; pass < 5; pass++) {
            for (int i = g1_first(pass, tail); i < g1_count(pass, tail); i += gridDim.x) {
                const int tile = g1_tile(pass, tail, i);
                const int nkb = pass == 0 ? FF / 64 : pass == 1 ? (FF + HD) / 64 : pass == 2 ? HD / 64 : pass == 3 ? 16 : 8;
                float4* pre = g_pre + (tile - NFULL) * (32 * 256) + tid;
                if (tail) asm volatile("prefetch.global.L2 [%0];" ::"l"(pre - tid + (i & 7) * 1024 + tid * 4));
                for (int kb = 0; kb < nkb; kb++, it++) { g_mma_block(d, sb, bar, it, wg, tid, kb == 0); if (tail && kb == 0) PT(18); }
                wg_wait<0>();
                if (tail) PT(19);
                if ((tid & 127) == 0) mbar_arrive(bar + 8 * (G_ST + (it - 1) % G_ST));
                if (pass >= 2 && !tail) { if ((tid & 31) == 0) wait_count(&g_pcnt[tile], 8); __syncwarp(); }
                if (pass == 0) {
#pragma unroll
                    for (int q = 0; q < 32; q++) __stcg(pre + q * 256, make_float4(d[4 * q], d[4 * q + 1], d[4 * q + 2], d[4 * q + 3]));
                    __threadfence();
                    __syncwarp();
                    if ((tid & 31) == 0) atomicAdd(&g_pcnt[tile], 1u);
                } else if (pass == 3) {
                    float4 r[8];
#pragma unroll
                    for (int q = 0; q < 8; q++) r[q] = __ldcg(pre + ((i & 3) * 8 + q) * 256);
                    g_split_finish<4>(d, r, g_sk + (tile - T_MID) * 8 * (16 * 256), tile, i & 3, out, tid);
                } else if (pass == 4) {
                    float4 r[4];
#pragma unroll
                    for (int q = 0; q < 4; q++) r[q] = __ldcg(pre + ((i & 7) * 4 + q) * 256);
                    g_split_finish<8>(d, r, g_sk + (tile - T_MID) * 8 * (16 * 256), tile, i & 7, out, tid);
                } else {
                    if (pass == 2) {
#pragma unroll
                        for (int q = 0; q < 32; q++) {
                            const float4 u = __ldcg(pre + q * 256); d[4 * q] += u.x; d[4 * q + 1] += u.y; d[4 * q + 2] += u.z; d[4 * q + 3] += u.w;
                            if ((q & 7) == 7) __syncwarp();
                        }
                    }
                    g_store_tile(d, &tm.out, epi, tile >> 2, tile & 3, wg, tid);
                }
            }
        }
        if ((tid & 127) == 0) bulk_wait_all();
        KT(1 + tail, 1);
    }
    __syncwarp();
    asm volatile("griddepcontrol.wait;" ::: "memory");
}

__device__ bf16 f_qkv[3][(SEQ + NMEM) * HD];
__device__ bf16 f_mem[NMEM * DM], f_om[NMEM * HD];

__global__ void __launch_bounds__(256) f_gemm(const bf16* __restrict__ A, const bf16* __restrict__ B, bf16* __restrict__ C, int K, int N) {
    __shared__ float sa[8][256];
    const int n = blockIdx.x * 256 + threadIdx.x, m0 = blockIdx.y * 8;
    float acc[8] = {0.f, 0.f, 0.f, 0.f, 0.f, 0.f, 0.f, 0.f};
    for (int k0 = 0; k0 < K; k0 += 256) {
        __syncthreads();
        for (int r = 0; r < 8; r++) sa[r][threadIdx.x] = __bfloat162float(A[(size_t)(m0 + r) * K + k0 + threadIdx.x]);
        __syncthreads();
        for (int k = 0; k < 256; k++) {
            const float b = __bfloat162float(B[(size_t)(k0 + k) * N + n]);
#pragma unroll
            for (int r = 0; r < 8; r++) acc[r] = fmaf(sa[r][k], b, acc[r]);
        }
    }
    for (int r = 0; r < 8; r++) C[(size_t)(m0 + r) * N + n] = __float2bfloat16(acc[r]);
}
__global__ void __launch_bounds__(32) f_gate(const bf16* __restrict__ x, const bf16* __restrict__ gate_w) {
    uint4 xv[4], gv[4];
    for (int i = 0; i < 4; i++) { xv[i] = ldg_nc((const uint4*)(x + blockIdx.x * DM) + i * 32 + threadIdx.x); gv[i] = ldg_nc((const uint4*)gate_w + i * 32 + threadIdx.x); }
    const uint32_t g = __float_as_uint(gate_row(xv, gv));
    if (threadIdx.x == 0) { g_gate[blockIdx.x] = g ? g : 0x80000000u; if (blockIdx.x < 16) g_ocnt[blockIdx.x] = NH * 4; }
}
__global__ void __launch_bounds__(128) f_attn(int s) {
    __shared__ float sq[DH], sp[NMEM + SEG];
    const int h = blockIdx.x, i = blockIdx.y, t = threadIdx.x;
    auto row = [&](int r) { return (size_t)(r < NMEM ? SEQ + r : s * SEG + r - NMEM) * HD + h * DH; };
    sq[t] = __bfloat162float(f_qkv[0][row(i) + t]);
    __syncthreads();
    if (t < NMEM + SEG) {
        float a = 0.f;
        for (int e = 0; e < DH; e++) a = fmaf(sq[e], __bfloat162float(f_qkv[1][row(t) + e]), a);
        sp[t] = (i < NMEM || i >= t) ? a * 0.08838834764831845f : -1000000000.0f;
    }
    __syncthreads();
    float m = sp[0], l = 0.f, o = 0.f;
    for (int j = 1; j < NMEM + SEG; j++) m = fmaxf(m, sp[j]);
    for (int j = 0; j < NMEM + SEG; j++) { const float p = __expf(sp[j] - m); l += p; o = fmaf(p, __bfloat162float(f_qkv[2][row(j) + t]), o); }
    if (i < NMEM) f_om[i * HD + h * DH + t] = __float2bfloat16(o / l);
    else g_O[(size_t)(s * SEG + i - NMEM) * HD + h * DH + t] = __float2bfloat16(o / l * __uint_as_float(g_gate[s * SEG + i - NMEM]));
}

typedef CUresult (*EncodeFn)(CUtensorMap*, CUtensorMapDataType, cuuint32_t, void*, const cuuint64_t*, const cuuint64_t*, const cuuint32_t*,
                             const cuuint32_t*, CUtensorMapInterleave, CUtensorMapSwizzle, CUtensorMapL2promotion, CUtensorMapFloatOOBfill);

static void make_map(EncodeFn enc, CUtensorMap* m, const void* ptr, uint64_t rows, uint64_t cols, uint32_t box_rows) {
    cuuint64_t dims[2] = {cols, rows};
    cuuint64_t strides[1] = {cols * 2};
    cuuint32_t box[2] = {64, box_rows};
    cuuint32_t es[2] = {1, 1};
    enc(m, CU_TENSOR_MAP_DATA_TYPE_BFLOAT16, 2, (void*)ptr, dims, strides, box, es, CU_TENSOR_MAP_INTERLEAVE_NONE,
        CU_TENSOR_MAP_SWIZZLE_128B, CU_TENSOR_MAP_L2_PROMOTION_L2_256B, CU_TENSOR_MAP_FLOAT_OOB_FILL_NONE);
}

extern "C" void kernel_launch(void* const* d_in, const int* in_sizes, int n_in, void* d_out, int out_size) {
    (void)in_sizes; (void)n_in; (void)out_size;
    const bf16* x = (const bf16*)d_in[0];
    const bf16* mem0 = (const bf16*)d_in[1];
    const bf16* gate_w = (const bf16*)d_in[11];
    static EncodeFn enc = nullptr;
    static int n_sm = 0;
    static void *pO = nullptr, *pH = nullptr, *pQ = nullptr, *pM = nullptr, *pOm = nullptr;
    static int n_clusters = 0;
    if (!enc) {
        void* fn = nullptr;
        cudaDriverEntryPointQueryResult qr;
        cudaGetDriverEntryPoint("cuTensorMapEncodeTiled", &fn, cudaEnableDefault, &qr);
        enc = (EncodeFn)fn;
        cudaDeviceGetAttribute(&n_sm, cudaDevAttrMultiProcessorCount, 0);
        cudaFuncSetAttribute(r_kernel, cudaFuncAttributeMaxDynamicSharedMemorySize, R_SMEM);
        cudaFuncSetAttribute(g1_kernel, cudaFuncAttributeMaxDynamicSharedMemorySize, G_SMEM);
        cudaGetSymbolAddress(&pO, g_O);
        cudaGetSymbolAddress(&pH, g_H);
        cudaGetSymbolAddress(&pQ, f_qkv);
        cudaGetSymbolAddress(&pM, f_mem);
        cudaGetSymbolAddress(&pOm, f_om);
        cudaLaunchConfig_t cfg = {};
        cfg.gridDim = dim3(96); cfg.blockDim = dim3(384); cfg.dynamicSmemBytes = R_SMEM;
        cudaLaunchAttribute at[1];
        at[0].id = cudaLaunchAttributeClusterDimension; at[0].val.clusterDim.x = 3; at[0].val.clusterDim.y = 1; at[0].val.clusterDim.z = 1;
        cfg.attrs = at; cfg.numAttrs = 1;
        if (cudaOccupancyMaxActiveClusters(&n_clusters, r_kernel, &cfg) != cudaSuccess) { n_clusters = 0; (void)cudaGetLastError(); }
    }
    RMaps rm; G1Maps m1;
    make_map(enc, &rm.x, x, SEQ, DM, 32);
    for (int i = 0; i < 3; i++) make_map(enc, &rm.w[i], d_in[2 + i], DM, HD, 64);
    make_map(enc, &rm.wo, d_in[5], HD, DM, 128);
    make_map(enc, &rm.o, pO, SEQ, HD, 16);
    make_map(enc, &m1.x, x, SEQ, DM, 128);
    make_map(enc, &m1.wg, d_in[8], DM, FF, 64);
    make_map(enc, &m1.wu, d_in[9], DM, FF, 64);
    make_map(enc, &m1.hs, pH, SEQ, FF, 64);
    make_map(enc, &m1.o, pO, SEQ, HD, 128);
    make_map(enc, &m1.h, pH, SEQ, FF, 128);
    make_map(enc, &m1.wo, d_in[5], HD, DM, 64);
    make_map(enc, &m1.wd, d_in[10], FF, DM, 64);
    make_map(enc, &m1.out, d_out, SEQ, DM, 64);

    cudaStream_t st = cudaStreamPerThread;
    if (n_clusters < NH) {
        bf16* qkv = (bf16*)pQ;
        const size_t plane = (size_t)(SEQ + NMEM) * HD;
        f_gate<<<SEQ, 32, 0, st>>>(x, gate_w);
        for (int i = 0; i < 3; i++) f_gemm<<<dim3(HD / 256, SEQ / 8), 256, 0, st>>>(x, (const bf16*)d_in[2 + i], qkv + i * plane, DM, HD);
        for (int s = 0; s < NSEG; s++) {
            for (int i = 0; i < 3; i++)
                f_gemm<<<dim3(HD / 256, 1), 256, 0, st>>>(s ? (const bf16*)pM : mem0, (const bf16*)d_in[2 + i], qkv + i * plane + (size_t)SEQ * HD, DM, HD);
            f_attn<<<dim3(NH, NMEM + SEG), 128, 0, st>>>(s);
            f_gemm<<<dim3(DM / 256, 1), 256, 0, st>>>((const bf16*)pOm, (const bf16*)d_in[5], (bf16*)pM, HD, DM);
        }
    } else {
        cudaLaunchConfig_t cfg = {};
        cfg.gridDim = dim3(96); cfg.blockDim = dim3(384); cfg.dynamicSmemBytes = R_SMEM; cfg.stream = st;
        cudaLaunchAttribute at[1];
        at[0].id = cudaLaunchAttributeClusterDimension; at[0].val.clusterDim.x = 3; at[0].val.clusterDim.y = 1; at[0].val.clusterDim.z = 1;
        cfg.attrs = at; cfg.numAttrs = 1;
        cudaLaunchKernelEx(&cfg, r_kernel, rm, mem0, x, gate_w);
    }
    {
        cudaLaunchConfig_t cfg = {};
        cfg.gridDim = dim3(n_sm - 96 > 32 ? n_sm - 96 : 32); cfg.blockDim = dim3(384); cfg.dynamicSmemBytes = G_SMEM; cfg.stream = st;
        cudaLaunchAttribute at[1];
        at[0].id = cudaLaunchAttributeProgrammaticStreamSerialization; at[0].val.programmaticStreamSerializationAllowed = 1;
        cfg.attrs = at; cfg.numAttrs = n_clusters < NH ? 0 : 1;
        cudaLaunchKernelEx(&cfg, g1_kernel, m1, (bf16*)d_out, 0);
    }
    {
        cudaLaunchConfig_t cfg = {};
        cfg.gridDim = dim3((64 - T_LATE) * 8); cfg.blockDim = dim3(384); cfg.dynamicSmemBytes = G_SMEM; cfg.stream = st;
        cudaLaunchAttribute at[1];
        at[0].id = cudaLaunchAttributeProgrammaticStreamSerialization; at[0].val.programmaticStreamSerializationAllowed = 1;
        cfg.attrs = at; cfg.numAttrs = 1;
        cudaLaunchKernelEx(&cfg, g1_kernel, m1, (bf16*)d_out, 1);
    }
}
```

```cpp
#include <cuda_runtime.h>
#include <cuda_bf16.h>
#include <cuda.h>
#include <stdint.h>

typedef __nv_bfloat16 bf16;

constexpr int SEQ = 2048, DM = 1024, NH = 32, DH = 128, NMEM = 8, SEG = 32, NSEG = 64, FF = 3584;
constexpr int HD = NH * DH;

__device__ bf16 g_O[SEQ * HD];
__device__ bf16 g_H[SEQ * FF];
__device__ uint32_t g_gate[SEQ];
__device__ uint32_t g_part[4][128 * 32 * 32];
__device__ uint32_t g_mem[4][DM * 4];
#define TLATE 52
constexpr int NFULL = 36, T_MID = 44, T_MID2 = 48, T_LATE = TLATE;
constexpr int NPRE = 64 - NFULL;
__device__ float4 g_pre[NPRE * 32 * 256];
__device__ uint4 g_sk[(64 - T_MID) * 8 * 16 * 256];
__device__ uint32_t g_skcnt[64], g_pcnt[64], g_ticket;
__device__ uint32_t g_hcnt[32], g_ocnt[16];
#define KT(k, i)
#define PT(i)

#define DEVINL __device__ __forceinline__
constexpr long long SPIN_LIMIT = 4000000000LL;

DEVINL uint32_t smem_u32(const void* p) { return (uint32_t)__cvta_generic_to_shared(p); }
DEVINL void mbar_init(uint32_t bar, uint32_t cnt) { asm volatile("mbarrier.init.shared::cta.b64 [%0], %1;" ::"r"(bar), "r"(cnt) : "memory"); }
DEVINL void mbar_arrive(uint32_t bar) { asm volatile("mbarrier.arrive.shared::cta.b64 _, [%0];" ::"r"(bar) : "memory"); }
DEVINL void mbar_expect(uint32_t bar, uint32_t bytes) { asm volatile("mbarrier.arrive.expect_tx.shared::cta.b64 _, [%0], %1;" ::"r"(bar), "r"(bytes) : "memory"); }
DEVINL void mbar_arrive_remote(uint32_t cbar) { asm volatile("mbarrier.arrive.relaxed.cluster.shared::cluster.b64 _, [%0];" ::"r"(cbar) : "memory"); }
DEVINL bool mbar_try(uint32_t bar, uint32_t par) {
    uint32_t ok;
    asm volatile("{ .reg .pred p; mbarrier.try_wait.parity.shared::cta.b64 p, [%1], %2; selp.u32 %0, 1, 0, p; }" : "=r"(ok) : "r"(bar), "r"(par) : "memory");
    return ok;
}
__device__ __noinline__ void mbar_wait_slow(uint32_t bar, uint32_t par) {
    long long t0 = clock64();
    while (!mbar_try(bar, par)) { if (clock64() - t0 > SPIN_LIMIT) __trap(); }
}
DEVINL void mbar_wait(uint32_t bar, uint32_t par) {
    uint32_t n = 0;
    while (!mbar_try(bar, par)) { if (++n > 200000000u) __trap(); }
}
DEVINL uint32_t mapa(uint32_t a, uint32_t r) { uint32_t o; asm volatile("mapa.shared::cluster.u32 %0, %1, %2;" : "=r"(o) : "r"(a), "r"(r)); return o; }
DEVINL void fence_async() { asm volatile("fence.proxy.async.shared::cta;" ::: "memory"); }
DEVINL void bar_sync(int id, int n) { asm volatile("bar.sync %0, %1;" ::"r"(id), "r"(n) : "memory"); }
DEVINL void cluster_sync() { asm volatile("barrier.cluster.arrive.aligned; barrier.cluster.wait.aligned;" ::: "memory"); }
DEVINL void tma_load(uint32_t dst, const CUtensorMap* tm, int c0, int c1, uint32_t bar) {
    asm volatile("cp.async.bulk.tensor.2d.shared::cluster.global.mbarrier::complete_tx::bytes [%0], [%1, {%3, %4}], [%2];"
                 ::"r"(dst), "l"(tm), "r"(bar), "r"(c0), "r"(c1) : "memory");
}
DEVINL void tma_prefetch(const CUtensorMap* tm, int c0, int c1) {
    asm volatile("cp.async.bulk.prefetch.tensor.2d.L2.global [%0, {%1, %2}];" ::"l"(tm), "r"(c0), "r"(c1) : "memory");
}
DEVINL void tma_store(const CUtensorMap* tm, uint32_t src, int c0, int c1) {
    asm volatile("cp.async.bulk.tensor.2d.global.shared::cta.bulk_group [%0, {%2, %3}], [%1];" ::"l"(tm), "r"(src), "r"(c0), "r"(c1) : "memory");
}
DEVINL void bulk_commit() { asm volatile("cp.async.bulk.commit_group;" ::: "memory"); }
DEVINL void bulk_wait_read() { asm volatile("cp.async.bulk.wait_group.read 0;" ::: "memory"); }
DEVINL void bulk_wait_all() { asm volatile("cp.async.bulk.wait_group 0;" ::: "memory"); }
DEVINL void bulk_s2s(uint32_t cdst, uint32_t src, uint32_t bytes, uint32_t cbar) {
    asm volatile("cp.async.bulk.shared::cluster.shared::cta.mbarrier::complete_tx::bytes [%0], [%1], %2, [%3];" ::"r"(cdst), "r"(src), "r"(bytes), "r"(cbar) : "memory");
}
DEVINL void st_async16(uint32_t cdst, uint4 v, uint32_t cbar) {
    asm volatile("st.async.shared::cluster.mbarrier::complete_tx::bytes.v4.b32 [%0], {%1,%2,%3,%4}, [%5];" ::"r"(cdst), "r"(v.x), "r"(v.y), "r"(v.z), "r"(v.w), "r"(cbar) : "memory");
}
DEVINL uint64_t mkdesc(uint32_t addr, uint32_t lbo, uint32_t sbo, uint32_t swz) {
    return (uint64_t)((addr & 0x3FFFF) >> 4) | ((uint64_t)(lbo >> 4) << 16) | ((uint64_t)(sbo >> 4) << 32) | ((uint64_t)swz << 62);
}
constexpr uint32_t SB0 = 1024;
__host__ __device__ constexpr uint64_t cdesc(uint32_t off, uint32_t lbo, uint32_t sbo, uint32_t swz) {
    return (uint64_t)(((SB0 + off) & 0x3FFFF) >> 4) | ((uint64_t)(lbo >> 4) << 16) | ((uint64_t)(sbo >> 4) << 32) | ((uint64_t)swz << 62);
}
DEVINL float rcp(float x) { float y; asm("rcp.approx.ftz.f32 %0, %1;" : "=f"(y) : "f"(x)); return y; }
DEVINL float ex2(float x) { float y; asm("ex2.approx.ftz.f32 %0, %1;" : "=f"(y) : "f"(x)); return y; }
DEVINL void spin_clk(int d) { uint32_t t0, t1; asm volatile("mov.u32 %0, %%clock;" : "=r"(t0)); do { asm volatile("mov.u32 %0, %%clock;" : "=r"(t1)); } while ((int)(t1 - t0) < d); }
#define PROBE_GAP 150
#define OPAQUE(x) asm volatile("" : "+r"(x))
DEVINL void wg_fence() { asm volatile("wgmma.fence.sync.aligned;" ::: "memory"); }
DEVINL void wg_commit() { asm volatile("wgmma.commit_group.sync.aligned;" ::: "memory"); }
template <int N> DEVINL void wg_wait() { asm volatile("wgmma.wait_group.sync.aligned %0;" ::"n"(N) : "memory"); }
DEVINL uint32_t pack_bf16(float lo, float hi) { uint32_t r; asm("cvt.rn.bf16x2.f32 %0, %1, %2;" : "=r"(r) : "f"(hi), "f"(lo)); return r; }
DEVINL void ldsm4(uint32_t* r, uint32_t a) { asm volatile("ldmatrix.sync.aligned.m8n8.x4.shared.b16 {%0,%1,%2,%3}, [%4];" : "=r"(r[0]), "=r"(r[1]), "=r"(r[2]), "=r"(r[3]) : "r"(a) : "memory"); }
DEVINL void ldsm4t(uint32_t* r, uint32_t a) { asm volatile("ldmatrix.sync.aligned.m8n8.x4.trans.shared.b16 {%0,%1,%2,%3}, [%4];" : "=r"(r[0]), "=r"(r[1]), "=r"(r[2]), "=r"(r[3]) : "r"(a) : "memory"); }
DEVINL void ldsm4t_if(uint32_t* r, uint32_t a, int c) { asm volatile("{ .reg .pred p; setp.ne.s32 p, %5, 0; @p ldmatrix.sync.aligned.m8n8.x4.trans.shared.b16 {%0,%1,%2,%3}, [%4]; }" : "+r"(r[0]), "+r"(r[1]), "+r"(r[2]), "+r"(r[3]) : "r"(a), "r"(c) : "memory"); }
DEVINL void stsm4(uint32_t a, uint32_t r0, uint32_t r1, uint32_t r2, uint32_t r3) { asm volatile("stmatrix.sync.aligned.m8n8.x4.shared.b16 [%0], {%1,%2,%3,%4};" ::"r"(a), "r"(r0), "r"(r1), "r"(r2), "r"(r3) : "memory"); }
DEVINL void stsm4t(uint32_t a, uint32_t r0, uint32_t r1, uint32_t r2, uint32_t r3) { asm volatile("stmatrix.sync.aligned.m8n8.x4.trans.shared.b16 [%0], {%1,%2,%3,%4};" ::"r"(a), "r"(r0), "r"(r1), "r"(r2), "r"(r3) : "memory"); }
DEVINL void sts32(uint32_t a, uint32_t v) { asm volatile("st.shared.b32 [%0], %1;" ::"r"(a), "r"(v) : "memory"); }
DEVINL void sts128(uint32_t a, uint4 v) { asm volatile("st.shared.v4.b32 [%0], {%1,%2,%3,%4};" ::"r"(a), "r"(v.x), "r"(v.y), "r"(v.z), "r"(v.w) : "memory"); }
DEVINL uint4 lds128(uint32_t a) { uint4 v; asm volatile("ld.shared.v4.b32 {%0,%1,%2,%3}, [%4];" : "=r"(v.x), "=r"(v.y), "=r"(v.z), "=r"(v.w) : "r"(a) : "memory"); return v; }
DEVINL uint4 ld_strong16(const void* p) { uint4 v; asm volatile("ld.relaxed.gpu.global.v4.u32 {%0,%1,%2,%3}, [%4];" : "=r"(v.x), "=r"(v.y), "=r"(v.z), "=r"(v.w) : "l"(p) : "memory"); return v; }
DEVINL void st_strong8(void* p, uint32_t a, uint32_t b) { asm volatile("st.relaxed.gpu.global.v2.u32 [%0], {%1,%2};" ::"l"(p), "r"(a), "r"(b) : "memory"); }
DEVINL void st_strong4(void* p, uint32_t a) { asm volatile("st.relaxed.gpu.global.u32 [%0], %1;" ::"l"(p), "r"(a) : "memory"); }
DEVINL void st_strong16(void* p, uint4 v) { asm volatile("st.relaxed.gpu.global.v4.u32 [%0], {%1,%2,%3,%4};" ::"l"(p), "r"(v.x), "r"(v.y), "r"(v.z), "r"(v.w) : "memory"); }
DEVINL uint32_t pack_nz(float lo, float hi) { uint32_t r = pack_bf16(lo, hi); return r == 0u ? 0x8000u : r; }
DEVINL uint32_t min4(uint4 v, uint32_t m) { return __vimin3_u32(__vimin3_u32(v.x, v.y, m), v.z, v.w); }
DEVINL void mma16816(float* d, uint32_t a0, uint32_t a1, uint32_t a2, uint32_t a3, uint32_t b0, uint32_t b1) {
    asm volatile("mma.sync.aligned.m16n8k16.row.col.f32.bf16.bf16.f32 {%0,%1,%2,%3}, {%4,%5,%6,%7}, {%8,%9}, {%0,%1,%2,%3};"
                 : "+f"(d[0]), "+f"(d[1]), "+f"(d[2]), "+f"(d[3]) : "r"(a0), "r"(a1), "r"(a2), "r"(a3), "r"(b0), "r"(b1));
}
DEVINL void mma1688(float* d, uint32_t a0, uint32_t a1, uint32_t b0) {
    asm volatile("mma.sync.aligned.m16n8k8.row.col.f32.bf16.bf16.f32 {%0,%1,%2,%3}, {%4,%5}, {%6}, {%0,%1,%2,%3};"
                 : "+f"(d[0]), "+f"(d[1]), "+f"(d[2]), "+f"(d[3]) : "r"(a0), "r"(a1), "r"(b0));
}
template <int TA, int TB> DEVINL void wg_ss8(float* d, uint64_t da, uint64_t db, int sc) {
    asm volatile("{ .reg .pred p; setp.ne.b32 p, %6, 0; wgmma.mma_async.sync.aligned.m64n8k16.f32.bf16.bf16 {%0,%1,%2,%3}, %4, %5, p, 1, 1, %7, %8; }"
                 : "+f"(d[0]), "+f"(d[1]), "+f"(d[2]), "+f"(d[3]) : "l"(da), "l"(db), "r"(sc), "n"(TA), "n"(TB));
}
template <int TB> DEVINL void wg_rs8(float* d, const uint32_t* a, uint64_t db, int sc) {
    asm volatile("{ .reg .pred p; setp.ne.b32 p, %9, 0; wgmma.mma_async.sync.aligned.m64n8k16.f32.bf16.bf16 {%0,%1,%2,%3}, {%4,%5,%6,%7}, %8, p, 1, 1, %10; }"
                 : "+f"(d[0]), "+f"(d[1]), "+f"(d[2]), "+f"(d[3]) : "r"(a[0]), "r"(a[1]), "r"(a[2]), "r"(a[3]), "l"(db), "r"(sc), "n"(TB));
}
#define ACC16(d) "+f"(d[0]), "+f"(d[1]), "+f"(d[2]), "+f"(d[3]), "+f"(d[4]), "+f"(d[5]), "+f"(d[6]), "+f"(d[7]), "+f"(d[8]), "+f"(d[9]), "+f"(d[10]), "+f"(d[11]), "+f"(d[12]), "+f"(d[13]), "+f"(d[14]), "+f"(d[15])
template <int TA> DEVINL void wg_ss32(float* d, uint64_t da, uint64_t db, int sc) {
    asm volatile("{ .reg .pred p; setp.ne.b32 p, %18, 0; wgmma.mma_async.sync.aligned.m64n32k16.f32.bf16.bf16 {%0,%1,%2,%3,%4,%5,%6,%7,%8,%9,%10,%11,%12,%13,%14,%15}, %16, %17, p, 1, 1, %19, 0; }"
                 : ACC16(d) : "l"(da), "l"(db), "r"(sc), "n"(TA));
}
DEVINL void wg_rs32(float* d, const uint32_t* a, uint64_t db, int sc) {
    asm volatile("{ .reg .pred p; setp.ne.b32 p, %21, 0; wgmma.mma_async.sync.aligned.m64n32k16.f32.bf16.bf16 {%0,%1,%2,%3,%4,%5,%6,%7,%8,%9,%10,%11,%12,%13,%14,%15}, {%16,%17,%18,%19}, %20, p, 1, 1, 0; }"
                 : ACC16(d) : "r"(a[0]), "r"(a[1]), "r"(a[2]), "r"(a[3]), "l"(db), "r"(sc));
}
DEVINL void wg_ss40(float* d, uint64_t da, uint64_t db, int sc) {
    asm volatile("{ .reg .pred p; setp.ne.b32 p, %22, 0; wgmma.mma_async.sync.aligned.m64n40k16.f32.bf16.bf16 {%0,%1,%2,%3,%4,%5,%6,%7,%8,%9,%10,%11,%12,%13,%14,%15,%16,%17,%18,%19}, %20, %21, p, 1, 1, 1, 1; }"
                 : ACC16(d), "+f"(d[16]), "+f"(d[17]), "+f"(d[18]), "+f"(d[19]) : "l"(da), "l"(db), "r"(sc));
}
#define A8(d, o) "+f"(d[o]), "+f"(d[o + 1]), "+f"(d[o + 2]), "+f"(d[o + 3]), "+f"(d[o + 4]), "+f"(d[o + 5]), "+f"(d[o + 6]), "+f"(d[o + 7])
#define A32(d, o) A8(d, o), A8(d, o + 8), A8(d, o + 16), A8(d, o + 24)
DEVINL void wg_ss256(float* d, uint64_t da, uint64_t db, int sc) {
    asm volatile(
        "{ .reg .pred p; setp.ne.b32 p, %130, 0;\n"
        "wgmma.mma_async.sync.aligned.m64n256k16.f32.bf16.bf16 {"
        "%0,%1,%2,%3,%4,%5,%6,%7,%8,%9,%10,%11,%12,%13,%14,%15,%16,%17,%18,%19,%20,%21,%22,%23,%24,%25,%26,%27,%28,%29,%30,%31,"
        "%32,%33,%34,%35,%36,%37,%38,%39,%40,%41,%42,%43,%44,%45,%46,%47,%48,%49,%50,%51,%52,%53,%54,%55,%56,%57,%58,%59,%60,%61,%62,%63,"
        "%64,%65,%66,%67,%68,%69,%70,%71,%72,%73,%74,%75,%76,%77,%78,%79,%80,%81,%82,%83,%84,%85,%86,%87,%88,%89,%90,%91,%92,%93,%94,%95,"
        "%96,%97,%98,%99,%100,%101,%102,%103,%104,%105,%106,%107,%108,%109,%110,%111,%112,%113,%114,%115,%116,%117,%118,%119,%120,%121,%122,%123,%124,%125,%126,%127"
        "}, %128, %129, p, 1, 1, 0, 1; }"
        : A32(d, 0), A32(d, 32), A32(d, 64), A32(d, 96) : "l"(da), "l"(db), "r"(sc));
}

DEVINL float gate_row(const uint4 (&xv)[4], const uint4 (&gv)[4]) {
    float acc = 0.f;
#pragma unroll
    for (int i = 0; i < 4; i++) {
        const uint32_t xa[4] = {xv[i].x, xv[i].y, xv[i].z, xv[i].w}, ga[4] = {gv[i].x, gv[i].y, gv[i].z, gv[i].w};
#pragma unroll
        for (int e = 0; e < 4; e++) {
            acc = fmaf(__uint_as_float(xa[e] << 16), __uint_as_float(ga[e] << 16), acc);
            acc = fmaf(__uint_as_float(xa[e] & 0xffff0000u), __uint_as_float(ga[e] & 0xffff0000u), acc);
        }
    }
#pragma unroll
    for (int o = 16; o > 0; o >>= 1) acc += __shfl_xor_sync(0xffffffffu, acc, o);
    return 1.0f / (1.0f + __expf(-acc));
}
DEVINL uint4 ldg_nc(const void* p) { uint4 v; asm volatile("ld.global.nc.v4.u32 {%0,%1,%2,%3}, [%4];" : "=r"(v.x), "=r"(v.y), "=r"(v.z), "=r"(v.w) : "l"(p) : "memory"); return v; }
DEVINL uint32_t ld_strong4(const void* p) { uint32_t v; asm volatile("ld.relaxed.gpu.global.u32 %0, [%1];" : "=r"(v) : "l"(p) : "memory"); return v; }
DEVINL void wait_count(const uint32_t* p, uint32_t want) {
    uint32_t v, n = 0;
    while (true) {
        asm volatile("ld.acquire.gpu.global.u32 %0, [%1];" : "=r"(v) : "l"(p) : "memory");
        if (v >= want) break;
        __nanosleep(100);
        if (++n > 20000000u) __trap();
    }
}

constexpr int KR = 44;
constexpr int KS = 64 - KR;
constexpr int R_W = 0;
constexpr int R_WO = KS * 4096;
constexpr int R_QX = R_WO + 65536;
constexpr int R_RING = R_WO + 98304;
constexpr int R_K = R_RING + 24576;
constexpr int R_V = R_K + 10240;
constexpr int R_QM = R_V + 10240;
constexpr int R_O = R_QM + 2048;
constexpr int R_BAR = R_O + 2048;
constexpr int R_G = R_BAR + 256 + 512 + 256 + 128;
constexpr int R_Z = R_G + 256;
constexpr int R_SMEM = R_Z + 1024;
enum { B_FULL = 0, B_EMPTY = 5, B_MEM = 8, B_HOP1 = 12, B_XT, B_TFREE, B_O, B_AFREE0, B_AFREE1, B_PRO0, B_PRO1, B_XRECV, B_P, B_XDONE, B_OST0, B_OST1, B_HOPV };
#define D2_BASE 900
#define D2_STEP 200
#define PD2 6
#define CPB 8192
#define DDUP 0
#define WGAP 0
#define PVD 400
#define ELD 700
#define QD 3
#define PPF 0
#define DQ 1700
#define D3 0

DEVINL uint32_t clk32() { uint32_t c_; asm volatile("mov.u32 %0, %%clock;" : "=r"(c_)); return c_; }
DEVINL void spin_until(uint32_t t) { while ((uint32_t)(t - clk32() - 1u) < 100000u) {} }
#define PROF(i)
#define PROF2(i)
#define PROF3(i, val)
DEVINL void e_arrive(uint32_t bar) { asm volatile("{ .reg .pred p; elect.sync _|p, 0xffffffff; @p mbarrier.arrive.shared::cta.b64 _, [%0]; }" ::"r"(bar) : "memory"); }
DEVINL void e_arrive_remote(uint32_t cbar) { asm volatile("{ .reg .pred p; elect.sync _|p, 0xffffffff; @p mbarrier.arrive.relaxed.cluster.shared::cluster.b64 _, [%0]; }" ::"r"(cbar) : "memory"); }
DEVINL void e_count(uint32_t* p) { asm volatile("{ .reg .pred p; elect.sync _|p, 0xffffffff; @p red.relaxed.gpu.global.add.u32 [%0], 1; }" ::"l"(p) : "memory"); }
DEVINL void e_expect(uint32_t bar, uint32_t bytes) { asm volatile("{ .reg .pred p; elect.sync _|p, 0xffffffff; @p mbarrier.arrive.expect_tx.shared::cta.b64 _, [%0], %1; }" ::"r"(bar), "r"(bytes) : "memory"); }
DEVINL void e_tma_load(uint32_t dst, const CUtensorMap* tm, int c0, int c1, uint32_t bar) {
    asm volatile("{ .reg .pred p; elect.sync _|p, 0xffffffff; @p cp.async.bulk.tensor.2d.shared::cluster.global.mbarrier::complete_tx::bytes [%0], [%1, {%3, %4}], [%2]; }"
                 ::"r"(dst), "l"(tm), "r"(bar), "r"(c0), "r"(c1) : "memory");
}
DEVINL void e_tma_store(const CUtensorMap* tm, uint32_t src, int c0, int c1) {
    asm volatile("{ .reg .pred p; elect.sync _|p, 0xffffffff; @p cp.async.bulk.tensor.2d.global.shared::cta.bulk_group [%0, {%2, %3}], [%1]; }" ::"l"(tm), "r"(src), "r"(c0), "r"(c1) : "memory");
}
DEVINL void e_bulk_s2g(void* dst, uint32_t src, uint32_t bytes) {
    asm volatile("{ .reg .pred p; elect.sync _|p, 0xffffffff; @p cp.async.bulk.global.shared::cta.bulk_group [%0], [%1], %2; }" ::"l"(dst), "r"(src), "r"(bytes) : "memory");
}
DEVINL void e_bulk_s2s(uint32_t cdst, uint32_t src, uint32_t bytes, uint32_t cbar) {
    asm volatile("{ .reg .pred p; elect.sync _|p, 0xffffffff; @p cp.async.bulk.shared::cluster.shared::cta.mbarrier::complete_tx::bytes [%0], [%1], %2, [%3]; }" ::"r"(cdst), "r"(src), "r"(bytes), "r"(cbar) : "memory");
}

#define SLOT 0
#define PH3 0
#define PHQ 0
DEVINL void wait_slot(uint32_t phase) {
    if (SLOT) {
        uint32_t c; asm volatile("mov.u32 %0, %%globaltimer_lo;" : "=r"(c));
        const uint32_t tgt = c + (SLOT ? SLOT : 1) - ((c - phase) % (SLOT ? SLOT : 1));
        do { asm volatile("mov.u32 %0, %%globaltimer_lo;" : "=r"(c)); } while ((uint32_t)(tgt - c - 1u) < 100000u);
    }
}
template <int N> DEVINL uint32_t poll_set(uint4 (&v)[N], const uint32_t* rp, int stride, uint32_t phase, uint32_t wbar = 0, uint32_t wpar = 0) {
    wait_slot(phase);
#pragma unroll
    for (int i = 0; i < N; i++) v[i] = ld_strong16(rp + i * stride);
    if (wbar) mbar_wait(wbar, wpar);
    uint32_t n = 0;
    while (true) {
        uint32_t m = 0xffffffffu;
#pragma unroll
        for (int i = 0; i < N; i++) m = min4(v[i], m);
        if (__all_sync(0xffffffffu, m != 0u)) return n;
        wait_slot(phase);
#pragma unroll
        for (int i = 0; i < N; i++)
            asm volatile("{ .reg .pred p; setp.eq.u32 p, %5, 0; @p ld.relaxed.gpu.global.v4.u32 {%0,%1,%2,%3}, [%4]; }"
                         : "+r"(v[i].x), "+r"(v[i].y), "+r"(v[i].z), "+r"(v[i].w) : "l"(rp + i * stride), "r"(min4(v[i], 0xffffffffu)) : "memory");
        if (++n > 20000000u) __trap();
    }
}

struct RMaps { CUtensorMap x, w[3], wo, o; };
#define KC(c) ((c) * 64)

#define XORD 3
__host__ __device__ constexpr int xo(int i) {
    return XORD == 0 ? i : XORD == 1 ? (i + 14) % 16 : XORD == 2 ? (i + 11) % 16
         : XORD == 3 ? (i < 10 ? ((i & 1) ? i / 2 : 11 + i / 2) : i - 5) : (i < 6 ? i : ((i & 1) ? 6 + (i - 6) / 2 : 11 + (i - 6) / 2));
}
#define XC(i) (xo(i) * 64)
DEVINL void x_load_pair(uint32_t dst, const CUtensorMap* tmx, int h, int p, int seg, uint32_t fbar) {
    e_expect(fbar, 8192);
    e_tma_load(dst, tmx, XC(2 * p), seg * SEG, fbar);
    e_tma_load(dst + 4096, tmx, XC(2 * p + 1), seg * SEG, fbar);
}
__host__ __device__ constexpr int wo_tile(int role, int i) {
    return role == 0 ? (i < 2 ? 8 + i : 12 + i) : (i < 4 ? (i >> 1) * 4 : 10) + (role - 1) * 2 + (i & 1);
}

template <int NT> DEVINL void wo_phase(uint32_t sb, int tb, uint32_t* pp, uint32_t obar, uint32_t opar) {
    const int lane = tb & 31, krow = (lane & 7) + ((lane >> 4) << 3), chunk = ((tb >> 5) & 3) * 2 + ((lane >> 3) & 1);
    uint32_t wa = sb + R_WO + (tb >> 7) * 16384 + krow * 128 + ((chunk ^ (krow & 7)) << 4);
    uint32_t af[4][4], of[4][4];
#pragma unroll
    for (int g = 0; g < 4; g++) ldsm4t(af[g], wa + g * 2048);
    mbar_wait(obar, opar);
#pragma unroll
    for (int g = 0; g < 4; g++) ldsm4t(of[g], sb + R_O + g * 512 + lane * 16);
#pragma unroll 1
    for (int i = 0; i < NT; i++) {
        float w0[4] = {0.f, 0.f, 0.f, 0.f}, w1[4] = {0.f, 0.f, 0.f, 0.f};
        const int more = NT - 1 - i, yes = NT - i;
        mma16816(w0, af[0][0], af[0][1], af[0][2], af[0][3], of[0][0], of[0][1]);
        ldsm4t_if(af[0], wa + 4 * 2048, yes);
        mma16816(w1, af[1][0], af[1][1], af[1][2], af[1][3], of[0][2], of[0][3]);
        ldsm4t_if(af[1], wa + 5 * 2048, yes);
        mma16816(w0, af[2][0], af[2][1], af[2][2], af[2][3], of[1][0], of[1][1]);
        ldsm4t_if(af[2], wa + 6 * 2048, yes);
        mma16816(w1, af[3][0], af[3][1], af[3][2], af[3][3], of[1][2], of[1][3]);
        ldsm4t_if(af[3], wa + 7 * 2048, yes);
        wa += 32768;
        mma16816(w0, af[0][0], af[0][1], af[0][2], af[0][3], of[2][0], of[2][1]);
        ldsm4t_if(af[0], wa, more);
        mma16816(w1, af[1][0], af[1][1], af[1][2], af[1][3], of[2][2], of[2][3]);
        ldsm4t_if(af[1], wa + 2048, more);
        mma16816(w0, af[2][0], af[2][1], af[2][2], af[2][3], of[3][0], of[3][1]);
        ldsm4t_if(af[2], wa + 2 * 2048, more);
        mma16816(w1, af[3][0], af[3][1], af[3][2], af[3][3], of[3][2], of[3][3]);
        ldsm4t_if(af[3], wa + 3 * 2048, more);
        st_strong4(pp, pack_nz(w0[0] + w1[0], w0[1] + w1[1]));
        st_strong4(pp + 1024, pack_nz(w0[2] + w1[2], w0[3] + w1[3]));
        pp += (NT == 3 && i == 0) ? 4 * 8192 : 6 * 8192;
    }
}

template <uint32_t role> DEVINL void r_big(const RMaps& tm, const int wid) {
    extern __shared__ __align__(1024) unsigned char smem_raw[];
    const uint32_t sb = smem_u32(smem_raw);
    const uint32_t bar = sb + R_BAR;
    const int tid = threadIdx.x;
    int h; asm("mov.u32 %0, %%clusterid.x;" : "=r"(h));
        uint32_t a[KR][4];
        {
            const int lane = tid & 31;
            const int krow = (lane & 7) + ((lane >> 4) << 3);
            const int chunk = (wid & 3) * 2 + ((lane >> 3) & 1);
            const uint32_t la = sb + (wid >> 2) * 8192 + krow * 128 + ((chunk ^ (krow & 7)) << 4);
            const CUtensorMap* tw = &tm.w[role];
#pragma unroll
            for (int b = 0; b < KR / 4; b++) {
                mbar_wait(sb + R_O + 8 * b, 0);
                if (b == 0) PT(0);
#pragma unroll
                for (int k = 0; k < 4; k++) ldsm4t(a[b * 4 + k], la + b * 16384 + k * 2048);
                bar_sync(1, 256);
                if (wid == (b & 7)) {
                    fence_async();
                    if (b < 5) {
#pragma unroll
                        for (int q = 2 * b; q < 2 * b + 2; q++) e_tma_load(sb + R_W + q * 8192, tw, h * DH + (q / 5) * 64, KC(KR / 4 + q % 5), bar + 8 * B_PRO1);
                    } else if (b - 5 < (role == 0 ? 4 : 6)) {
                        e_tma_load(sb + R_WO + (b - 5) * 16384, &tm.wo, wo_tile(role, b - 5) * 64, h * DH, bar + 8 * B_PRO0);
                    }
                }
            }
        }
        constexpr uint32_t e0 = role == 0 ? R_QX + 16384 : R_K + 2048, e1 = role == 0 ? R_QX + 24576 : R_V + 2048;
        if (wid == 6) x_load_pair(sb + e0, &tm.x, h, 3, 0, bar + 8 * (B_FULL + 3));
        if (wid == 7) x_load_pair(sb + e1, &tm.x, h, 4, 0, bar + 8 * (B_FULL + 4));
        PT(1);
        mbar_wait(bar + 8 * B_PRO1, 0);
        PT(2);

        constexpr uint64_t dW0 = cdesc(R_W, 1024, 1024, 1);
        constexpr uint64_t dM = cdesc(R_RING, 128, 128, 0);
        constexpr uint64_t dX = cdesc(R_RING, 16, 1024, 1);
        constexpr uint64_t dX0 = cdesc(0, 16, 1024, 1);
        int tb = tid;
        int wq = wid;

        for (int seg = 0; seg < NSEG; seg++) {
            {
            const int s = seg - 1; (void)s;
            float d[16];
            OPAQUE(wq);
            const uint64_t dW = dW0 + (uint64_t)((wq >> 2) * (KS * 128));
#pragma unroll
            for (int p = 0; p < 8; p++) {
                const int slot = p % 5;
                mbar_wait(bar + 8 * (B_FULL + slot), slot < 3 ? (uint32_t)(p / 5) : (uint32_t)(seg & 1));
                PROF2(p);
                const uint64_t db = slot < 3 ? dX + (uint64_t)(slot * 512) : dX0 + (uint64_t)((slot == 3 ? e0 : e1) >> 4);
                wg_fence();
#pragma unroll
                for (int kk = 0; kk < 8; kk++) {
                    const int k = XORD >= 3 ? (kk & 1) * 4 + (kk >> 1) : kk;
                    const int ks = xo(2 * p + (k >> 2)) * 4 + (k & 3);
                    if (ks >= KR) wg_ss32<1>(d, dW + (uint64_t)((ks - KR) * 128), db + (uint64_t)((k >> 2) * 256 + (k & 3) * 2), p + k);
                    else wg_rs32(d, a[ks < KR ? ks : 0], db + (uint64_t)((k >> 2) * 256 + (k & 3) * 2), p + k);
                }
                wg_commit();
                if (p >= 1) {
                    wg_wait<1>();
                    if (p <= 3) {
                        if ((wq & 3) == p) e_arrive(bar + 8 * (B_EMPTY + p - 1));
                        if (wq == p + (p & 1) * 4) {
                            mbar_wait(bar + 8 * (B_EMPTY + p - 1), seg & 1);
                            x_load_pair(sb + R_RING + (p - 1) * 8192, &tm.x, h, p + 4, seg, bar + 8 * (B_FULL + p - 1));
                        }
                    }
                    if (p == 5 && role != 0 && (wq & 3) < 3) e_arrive_remote(mapa(bar + 8 * B_TFREE, wq & 3));
                    if (p == 6 && (wq & 3) == 1) e_arrive(bar + 8 * B_AFREE0);
                    if (p == 7 && (wq & 3) == 2) e_arrive(bar + 8 * B_AFREE1);
                }
            }
            mbar_wait(bar + 8 * B_TFREE, seg & 1);
            asm volatile("wgmma.wait_group.sync.aligned 0;" : ACC16(d)::"memory");
            PROF2(16);
            const uint32_t tilex = sb + (role == 0 ? R_QX + 2048 : (role == 1 ? R_K + 2048 : R_V + 2048));
            {
                OPAQUE(tb);
                const uint32_t gs = role == 0 ? 4096 : 2048;
                const uint32_t sa = tilex + ((tb >> 4) & 1) * gs + (tb >> 5) * 256 + (tb & 15) * 16;
                stsm4(sa, pack_bf16(d[0], d[1]), pack_bf16(d[2], d[3]), pack_bf16(d[4], d[5]), pack_bf16(d[6], d[7]));
                stsm4(sa + 2 * gs, pack_bf16(d[8], d[9]), pack_bf16(d[10], d[11]), pack_bf16(d[12], d[13]), pack_bf16(d[14], d[15]));
            }
            __syncwarp();
            e_arrive(bar + 8 * B_XDONE);
            if (role != 0 && (wq & 3) == 0) {
                mbar_wait(bar + 8 * B_XDONE, seg & 1);
                fence_async();
                uint32_t pr = role + 1 + (wq >> 2); pr = pr >= 3 ? pr - 3 : pr;
                e_bulk_s2s(mapa(tilex, pr), tilex, CPB, mapa(bar + 8 * B_XT, pr));
            }
            }
            {
                const int s = seg;
                OPAQUE(wq);
                const uint64_t dW = dW0 + (uint64_t)((wq >> 2) * (KS * 128));
                float y[4] = {0.f, 0.f, 0.f, 0.f};
                {
                    OPAQUE(tb);
                    const uint32_t ma = sb + R_RING + (tb & 31) * 16;
                    float z[4] = {0.f, 0.f, 0.f, 0.f}, u[4] = {0.f, 0.f, 0.f, 0.f};
                    uint32_t b[QD][4];
                    const int yes = s + 1;
                    mbar_wait(bar + 8 * B_MEM, s & 1);
                    PROF((wq >> 2) * 4 + 0);
                    if (s == 0) PT(3);
                    if (s == 1) PT(4);
#pragma unroll
                    for (int g = 0; g < QD; g++) ldsm4t(b[g], ma + g * 512);
#pragma unroll
                    for (int g = 0; g < KR / 2; g++) {
                        float* c0 = (g % 3 == 0) ? y : (g % 3 == 1) ? u : z;
                        float* c1 = (g % 3 == 0) ? z : (g % 3 == 1) ? y : u;
                        mma16816(c0, a[2 * g][0], a[2 * g][1], a[2 * g][2], a[2 * g][3], b[g % QD][0], b[g % QD][1]);
                        mma16816(c1, a[2 * g + 1][0], a[2 * g + 1][1], a[2 * g + 1][2], a[2 * g + 1][3], b[g % QD][2], b[g % QD][3]);
                        if (g + QD < KR / 2) {
                            if ((g + QD) % 8 == 0) mbar_wait(bar + 8 * (B_MEM + (g + QD) / 8), s & 1);
                            ldsm4t_if(b[g % QD], ma + (g + QD) * 512, yes);
                        }
                    }
                    y[0] += z[0] + u[0]; y[1] += z[1] + u[1]; y[2] += z[2] + u[2]; y[3] += z[3] + u[3];
                }
                PROF2(8);
                mbar_wait(bar + 8 * (B_MEM + 3), s & 1);
                wg_fence();
#pragma unroll
                for (int k = KR; k < 64; k++) {
                    wg_ss8<1, 1>(y, dW + (uint64_t)((k - KR) * 128), dM + (uint64_t)(k * 16), 1);
                }
                wg_commit();
                asm volatile("wgmma.wait_group.sync.aligned 0;" : "+f"(y[0]), "+f"(y[1]), "+f"(y[2]), "+f"(y[3])::"memory");
                OPAQUE(tb);
                {
                    const uint32_t wo_ = (tb >> 5) * 256;
                    const uint32_t tile = sb + (role == 0 ? R_QX : (role == 1 ? R_K : R_V)) + wo_;
                    const uint32_t u0 = pack_bf16(y[0], y[1]), u1 = pack_bf16(y[2], y[3]);
                    sts32(tile + (tb & 31) * 4, u0);
                    sts32(tile + (tb & 31) * 4 + 128, u1);
                    __syncwarp();
                    uint4 v = lds128(tile + (tb & 15) * 16);
                    uint32_t peer = role + 1 + ((tb >> 4) & 1);
                    peer = peer >= 3 ? peer - 3 : peer;
                    const uint32_t rt = sb + (role == 0 ? R_QM : (role == 1 ? R_K : R_V)) + wo_ + (tb & 15) * 16;
                    st_async16(mapa(rt, peer), v, mapa(bar + 8 * (role == 2 ? B_HOPV : B_HOP1), peer));
                    if (role == 0) {
                        sts128(tile + 4096 + ((tb >> 4) & 1) * 4096 + (tb & 15) * 16, v);
                        sts32(tile + 12288 + (tb & 31) * 4, u0);
                        sts32(tile + 12288 + (tb & 31) * 4 + 128, u1);
                        __syncwarp();
                    }
                    e_arrive(bar + 8 * (role == 2 ? B_HOPV : B_HOP1));
                }
                PROF((wq >> 2) * 4 + 1);
                if (s < NSEG - 1) {
                    bar_sync(1, 256);
                    if (wq < 3) { fence_async(); x_load_pair(sb + R_RING + wq * 8192, &tm.x, h, wq, s + 1, bar + 8 * (B_FULL + wq)); }
                    else if (role == 0 && wq < 5) x_load_pair(sb + (wq == 3 ? e0 : e1), &tm.x, h, wq, s + 1, bar + 8 * (B_FULL + wq));
                    OPAQUE(tb);
                }
                uint32_t* pp = g_part[s & 3] + (h * 32 + (wo_tile(role, 0) + (tb >> 7)) * 8192 + ((tb >> 5) & 3) * 2048 + (tb & 31));
                asm volatile("" : "+l"(pp));
                if (s == NSEG - 1) break;
                if (s == 0) mbar_wait(bar + 8 * B_PRO0, 0);
                wo_phase<role == 0 ? 2 : 3>(sb, tb, pp, bar + 8 * B_O, s & 1);
                if (wq == 0) PROF(10);
            }
        }
}

#define CLR 0
#define CLEAR(st) do { if (role != 0) { \
                const int w_ = wid & 3; \
                uint32_t* zp = g_part[(st) & 3] + ((rg0 + (w_ >> 1) * 64) * 1024 + (w_ & 1) * 512); \
                e_bulk_s2g(zp, sb + R_Z, 1024); \
                e_bulk_s2g(zp + 256, sb + R_Z, 1024); \
                e_bulk_s2g(&g_mem[(st) & 3][(rg0 + (w_ >> 1) * 64) * 32 + (w_ & 1) * 16], sb + R_Z, 64); \
                bulk_commit(); } } while (0)
template <uint32_t role> DEVINL void r_chain(const RMaps& tm, const bf16* __restrict__ mem0, const int wid) {
    extern __shared__ __align__(1024) unsigned char smem_raw[];
    const uint32_t sb = smem_u32(smem_raw);
    const uint32_t bar = sb + R_BAR;
    const int tid = threadIdx.x;
    int h; asm("mov.u32 %0, %%clusterid.x;" : "=r"(h));
        int t = tid & 127;
        const float sl2 = 0.08838834764831845f * 1.4426950408889634f;
        const float NEGRAW = -1000000000.0f / 0.08838834764831845f;
        const int rg0 = ((int)role - 1) * 32 + h;
        if (role != 0) {
#pragma unroll 1
            for (int r = 0; r < 4; r++) {
                uint32_t* zp = g_part[r] + ((rg0 + (t >> 6) * 64) * 1024 + (t & 63) * 4);
#pragma unroll
                for (int i = 0; i < 4; i++) if (r) st_strong16(zp + i * 256, make_uint4(0u, 0u, 0u, 0u));
                if ((t & 63) < 8) st_strong16(&g_mem[r][(rg0 + (t >> 6) * 64) * 32 + (t & 63) * 4], make_uint4(0u, 0u, 0u, 0u));
            }
            __threadfence();
        }
        if (role == 0 && (wid & 3) < 3) e_arrive_remote(mapa(bar + 8 * B_TFREE, wid & 3));
        if (t < 64) sts128(sb + R_Z + t * 16, make_uint4(0u, 0u, 0u, 0u));
        if (role == 0) sts128(sb + R_QM + t * 16, make_uint4(0u, 0u, 0u, 0u));
        {
            uint4 v[8];
#pragma unroll
            for (int r = 0; r < 8; r++) v[r] = __ldg((const uint4*)(mem0 + r * DM) + t);
            mbar_wait(bar + 8 * B_AFREE0, 0);
            mbar_wait(bar + 8 * B_AFREE1, 0);
#define TR2(f, c) \
            sts128(sb + R_RING + t * 128 + (c) * 16, make_uint4(__byte_perm(v[0].f, v[1].f, 0x5410), __byte_perm(v[2].f, v[3].f, 0x5410), __byte_perm(v[4].f, v[5].f, 0x5410), __byte_perm(v[6].f, v[7].f, 0x5410))); \
            sts128(sb + R_RING + t * 128 + (c) * 16 + 16, make_uint4(__byte_perm(v[0].f, v[1].f, 0x7632), __byte_perm(v[2].f, v[3].f, 0x7632), __byte_perm(v[4].f, v[5].f, 0x7632), __byte_perm(v[6].f, v[7].f, 0x7632)));
            TR2(x, 0) TR2(y, 2) TR2(z, 4) TR2(w, 6)
            fence_async();
            __syncwarp();
            e_arrive(bar + 8 * B_MEM + (t >> 5) * 8);
        }
        constexpr uint64_t dQ = role == 0 ? cdesc(R_QX, 128, 2048, 0) : cdesc(R_QM, 128, 0, 0);
        constexpr uint64_t dK = cdesc(R_K, 128, 2048, 0);

        for (int s = 0; s < NSEG; s++) {
            if (role == 0) {
                uint32_t n = 0, gate;
                do { gate = ld_strong4(&g_gate[s * SEG + (t >> 2)]); if (++n > 20000000u) __trap(); } while (gate == 0u);
                sts32(sb + R_G + (t >> 2) * 4, gate);
                __syncwarp();
            }
            mbar_wait(bar + 8 * B_XDONE, s & 1);
            mbar_wait(bar + 8 * B_XT, s & 1);
            if (t >= 1 && t < 3) { uint32_t pr = role + t; pr = pr >= 3 ? pr - 3 : pr; mbar_arrive_remote(mapa(bar + 8 * B_XRECV, pr)); }
            __syncwarp();
            mbar_wait(bar + 8 * B_HOP1, s & 1);
            PROF(8);
            fence_async();
            OPAQUE(t);
            if (s == NSEG - 1 && role != 0) { mbar_wait(bar + 8 * B_HOPV, s & 1); bulk_wait_all(); break; }
            float sc[20];
            wg_fence();
#pragma unroll
            for (int k = 0; k < 8; k++) wg_ss40(sc, dQ + (uint64_t)(k * 16), dK + (uint64_t)(k * 16), k);
            wg_commit();
            uint32_t t_o = clk32() + 500;
            {
                const uint32_t va = sb + R_V + 2048 + (t >> 5) * 512 + ((t >> 4) & 1) * 2048 + (t & 15) * 16;
                uint32_t v0[4], v1[4];
                ldsm4(v0, va); ldsm4(v1, va + 256);
                uint32_t vm[4];
                const bool v_here = mbar_try(bar + 8 * B_HOPV, s & 1);
                if (v_here) ldsm4(vm, sb + R_V + t * 16);
                wg_wait<0>();
                if (role == 0) {
#pragma unroll
                    for (int j = 0; j < 5; j++)
                        asm volatile("st.shared.v2.f32 [%0], {%1,%2};" ::"r"(sb + R_QX + 768 + (t >> 5) * 4096 + j * 256 + (t & 31) * 8), "f"(sc[4 * j + 2]), "f"(sc[4 * j + 3]) : "memory");
                }
                float m = fmaxf(sc[0], sc[1]);
#pragma unroll
                for (int j = 1; j < 5; j++) m = fmaxf(m, fmaxf(sc[4 * j], sc[4 * j + 1]));
                m = fmaxf(m, __shfl_xor_sync(0xffffffffu, m, 1));
                m = fmaxf(m, __shfl_xor_sync(0xffffffffu, m, 2));
                const float mb = m * sl2;
                uint32_t pk[5];
#pragma unroll
                for (int j = 0; j < 5; j++) pk[j] = pack_bf16(ex2(fmaf(sc[4 * j], sl2, -mb)), ex2(fmaf(sc[4 * j + 1], sl2, -mb)));
                float o0[4] = {0.f, 0.f, 0.f, 0.f}, o1[4] = {0.f, 0.f, 0.f, 0.f}, ls[4] = {0.f, 0.f, 0.f, 0.f};
                constexpr uint32_t ONE = 0x3F803F80u;
                mma16816(o0, v0[0], v0[1], v0[2], v0[3], pk[1], pk[2]);
                mma16816(o1, v1[0], v1[1], v1[2], v1[3], pk[1], pk[2]);
                ldsm4(v0, va + 4096); ldsm4(v1, va + 4096 + 256);
                mma16816(ls, ONE, ONE, ONE, ONE, pk[1], pk[2]);
                mma16816(ls, ONE, ONE, ONE, ONE, pk[3], pk[4]);
                mma1688(ls, ONE, ONE, pk[0]);
                mma16816(o0, v0[0], v0[1], v0[2], v0[3], pk[3], pk[4]);
                mma16816(o1, v1[0], v1[1], v1[2], v1[3], pk[3], pk[4]);
                if (!v_here) { mbar_wait(bar + 8 * B_HOPV, s & 1); ldsm4(vm, sb + R_V + t * 16); }
                mma1688(o0, vm[0], vm[1], pk[0]);
                mma1688(o1, vm[2], vm[3], pk[0]);
                const float i0 = rcp(ls[0]), i1 = rcp(ls[1]);
                const uint32_t oa = sb + R_O + (t >> 5) * 512 + (t & 31) * 4;
                sts32(oa, pack_bf16(o0[0] * i0, o0[1] * i1));
                sts32(oa + 128, pack_bf16(o0[2] * i0, o0[3] * i1));
                sts32(oa + 256, pack_bf16(o1[0] * i0, o1[1] * i1));
                sts32(oa + 384, pack_bf16(o1[2] * i0, o1[3] * i1));
                __syncwarp();
                e_arrive(bar + 8 * B_O);
                PROF(9);
                if (role == 0) {
                    OPAQUE(t);
                    const int lim = (t >> 2) - (t & 3) * 2 + 8;
                    float z[10];
#pragma unroll
                    for (int j = 0; j < 5; j++)
                        asm volatile("ld.shared.v2.f32 {%0,%1}, [%2];" : "=f"(z[2 * j]), "=f"(z[2 * j + 1]) : "r"(sb + R_QX + 768 + (t >> 5) * 4096 + j * 256 + (t & 31) * 8) : "memory");
                    float gate; asm volatile("ld.shared.f32 %0, [%1];" : "=f"(gate) : "r"(sb + R_G + (t >> 2) * 4) : "memory");
                    float m1 = fmaxf(z[0], z[1]);
#pragma unroll
                    for (int j = 1; j < 5; j++) {
                        z[2 * j] = 8 * j <= lim ? z[2 * j] : NEGRAW;
                        z[2 * j + 1] = 8 * j + 1 <= lim ? z[2 * j + 1] : NEGRAW;
                        m1 = fmaxf(m1, fmaxf(z[2 * j], z[2 * j + 1]));
                    }
                    m1 = fmaxf(m1, __shfl_xor_sync(0xffffffffu, m1, 1));
                    m1 = fmaxf(m1, __shfl_xor_sync(0xffffffffu, m1, 2));
                    const float mb1 = m1 * sl2;
                    float l1 = 0.f;
                    const uint32_t pa = sb + R_QX + (t >> 5) * 4096 + (t & 31) * 4;
#pragma unroll
                    for (int j = 0; j < 5; j++) {
                        const uint32_t pw = pack_bf16(ex2(fmaf(z[2 * j], sl2, -mb1)), ex2(fmaf(z[2 * j + 1], sl2, -mb1)));
                        l1 += __uint_as_float(pw << 16) + __uint_as_float(pw & 0xffff0000u);
                        sts32(pa + j * 128, pw);
                    }
                    sts32(pa + 5 * 128, 0u);
                    l1 += __shfl_xor_sync(0xffffffffu, l1, 1);
                    l1 += __shfl_xor_sync(0xffffffffu, l1, 2);
                    sts32(sb + R_G + 128 + (t >> 2) * 4, __float_as_uint(gate * rcp(l1)));
                    spin_until(t_o + PVD);
                    if ((wid & 3) == 0 && s >= 1) { bulk_wait_all(); e_count(&g_ocnt[(s - 1) >> 2]); }
                    fence_async();
                    bar_sync(2, 128);
                    constexpr uint64_t dV = cdesc(R_V, 2048, 128, 0);
                    constexpr uint64_t dP = cdesc(R_QX, 128, 4096, 0);
                    float sf[8];
#pragma unroll
                    for (int j = 0; j < 4; j++) asm volatile("ld.shared.v2.f32 {%0,%1}, [%2];" : "=f"(sf[2 * j]), "=f"(sf[2 * j + 1]) : "r"(sb + R_G + 128 + j * 32 + (t & 3) * 8) : "memory");
                    const uint32_t r = ((t >> 4) & 1) * 8 + (t & 7), ch = (t >> 5) * 2 + ((t >> 3) & 1);
                    const uint32_t sa = sb + R_QX + 2048 + r * 128 + ((ch ^ (r & 7)) << 4);
#pragma unroll
                    for (int hf = 0; hf < 2; hf++) {
                        float d[16];
                        wg_fence();
#pragma unroll
                        for (int k = 0; k < 3; k++) wg_ss32<0>(d, dV + (uint64_t)(hf * 64 + k * 256), dP + (uint64_t)(k * 16), k);
                        wg_commit();
                        asm volatile("wgmma.wait_group.sync.aligned 0;" : ACC16(d)::"memory");
                        stsm4t(sa + hf * 8192, pack_bf16(d[0] * sf[0], d[1] * sf[1]), pack_bf16(d[2] * sf[0], d[3] * sf[1]), pack_bf16(d[4] * sf[2], d[5] * sf[3]), pack_bf16(d[6] * sf[2], d[7] * sf[3]));
                        stsm4t(sa + hf * 8192 + 4096, pack_bf16(d[8] * sf[4], d[9] * sf[5]), pack_bf16(d[10] * sf[4], d[11] * sf[5]), pack_bf16(d[12] * sf[6], d[13] * sf[7]), pack_bf16(d[14] * sf[6], d[15] * sf[7]));
                    }
                    fence_async();
                    bar_sync(2, 128);
                    if ((wid & 3) == 0) {
#pragma unroll
                        for (int q = 0; q < 4; q++) e_tma_store(&tm.o, sb + R_QX + 2048 + q * 4096, h * DH + (q >> 1) * 64, s * SEG + (q & 1) * 16);
                        bulk_commit();
                        bulk_wait_read();
                    }
                    if ((wid & 3) < 3) e_arrive_remote(mapa(bar + 8 * B_TFREE, wid & 3));
                }
            }
            if (t < 32) { e_expect(bar + 8 * B_HOP1, role == 2 ? 4096 : 2048); if (role != 2) e_expect(bar + 8 * B_HOPV, 2048); e_expect(bar + 8 * B_XT, role == 0 ? 2 * CPB : CPB); }
            if (s == NSEG - 1) { bulk_wait_all(); if ((wid & 3) == 0) e_count(&g_ocnt[s >> 2]); break; }
            if (role != 0 && (wid & 3) >= 2) {
                mbar_wait(bar + 8 * B_XRECV, s & 1);
                mbar_wait(bar + 8 * B_O, s & 1);
                fence_async();
                spin_until(t_o + ELD);
                x_load_pair(sb + ((wid & 1) ? R_V + 2048 : R_K + 2048), &tm.x, h, 3 + (wid & 1), s + 1, bar + 8 * (B_FULL + 3 + (wid & 1)));
            }
            OPAQUE(t);
            PROF(11);
            if (role != 0 || DDUP) {
                const int grp = role == 0 ? (t >> 6) * 32 + h : rg0 + (t >> 6) * 64;
                const uint32_t* rp = g_part[s & 3] + (grp * 1024 + ((t >> 2) & 7) * 32 + ((t >> 5) & 1) * 16 + (t & 3) * 4);
                uint32_t* wp = &g_mem[(s + 1) & 3][grp * 32 + ((t >> 5) & 1) * 16 + (t & 3) * 4 + ((t >> 3) & 3)];
                bulk_wait_all();
                spin_until(t_o + D2_BASE + (role == 0 ? DDUP + (t >> 6) * D2_STEP : (role - 1 + (t >> 6) * 2) * D2_STEP));
                PROF3(0, clk32());
#define LO(u) __uint_as_float((u) << 16)
#define HI(u) __uint_as_float((u) & 0xffff0000u)
                uint4 v[4];
                uint32_t n = poll_set<4>(v, rp, 256, (role - 1 + (t >> 6) * 2) * PHQ);
                {
                    PROF3(1, clk32());
                    float f[8];
                    f[0] = (LO(v[0].x) + LO(v[1].x)) + (LO(v[2].x) + LO(v[3].x)); f[1] = (HI(v[0].x) + HI(v[1].x)) + (HI(v[2].x) + HI(v[3].x));
                    f[2] = (LO(v[0].y) + LO(v[1].y)) + (LO(v[2].y) + LO(v[3].y)); f[3] = (HI(v[0].y) + HI(v[1].y)) + (HI(v[2].y) + HI(v[3].y));
                    f[4] = (LO(v[0].z) + LO(v[1].z)) + (LO(v[2].z) + LO(v[3].z)); f[5] = (HI(v[0].z) + HI(v[1].z)) + (HI(v[2].z) + HI(v[3].z));
                    f[6] = (LO(v[0].w) + LO(v[1].w)) + (LO(v[2].w) + LO(v[3].w)); f[7] = (HI(v[0].w) + HI(v[1].w)) + (HI(v[2].w) + HI(v[3].w));
                    const bool b4 = t & 16, b3 = t & 8;
                    float g4[4], g2[2];
#pragma unroll
                    for (int i = 0; i < 4; i++) g4[i] = (b4 ? f[4 + i] : f[i]) + __shfl_xor_sync(0xffffffffu, b4 ? f[i] : f[4 + i], 16);
#pragma unroll
                    for (int i = 0; i < 2; i++) g2[i] = (b3 ? g4[2 + i] : g4[i]) + __shfl_xor_sync(0xffffffffu, b3 ? g4[i] : g4[2 + i], 8);
                    g2[0] += __shfl_xor_sync(0xffffffffu, g2[0], 4);
                    g2[1] += __shfl_xor_sync(0xffffffffu, g2[1], 4);
                    st_strong4(wp, pack_nz(g2[0], g2[1]));
                }
                PROF3(8, n); (void)n;
            }
            t_o += D2_BASE + DQ + D3 + (t >> 5) * D2_STEP;
            OPAQUE(t);
            PROF(12);
            {
                const uint32_t* rp = &g_mem[(s + 1) & 3][((t >> 5) * 256 + (t & 31)) * 4];
                const uint32_t da = sb + R_RING + ((t >> 5) * 256 + (t & 31)) * 16;
                uint4 v[8];
                spin_until(t_o);
                PROF3(2, clk32());
                uint32_t n = poll_set<8>(v, rp, 128, PH3 + (t >> 5) * PHQ);
                PROF(13);
                PROF3(3, clk32()); PROF3(9, n); (void)n;
                mbar_wait(bar + 8 * B_AFREE0 + (t >> 6) * 8, (s + 1) & 1);
                PROF3(4, clk32());
#pragma unroll
                for (int i = 0; i < 8; i++) sts128(da + i * 512, v[i]);
                if (t >= 64) fence_async();
                __syncwarp();
                e_arrive(bar + 8 * B_MEM + (t >> 5) * 8);
                PROF(14);
                PROF3(5, clk32());
            }
            CLEAR(s + 3);
        }
}

__global__ void __launch_bounds__(384, 1) r_kernel(const __grid_constant__ RMaps tm, const bf16* __restrict__ mem0, const bf16* __restrict__ x, const bf16* __restrict__ gate_w) {
    extern __shared__ __align__(1024) unsigned char smem_raw[];
    const uint32_t sb = smem_u32(smem_raw);
    if ((sb & 0x3FFFFu) != SB0) __trap();
    const int tid = threadIdx.x;
    const int wid = __shfl_sync(0xffffffffu, tid >> 5, 0);
    uint32_t role; asm("mov.u32 %0, %%cluster_ctarank;" : "=r"(role));
    int h; asm("mov.u32 %0, %%clusterid.x;" : "=r"(h));
    const uint32_t bar = sb + R_BAR;
    asm volatile("griddepcontrol.launch_dependents;");
    KT(0, 0);
    const int gr = blockIdx.x * 12 + wid;
    uint4 gx0[4], gx1[4], gw[4];
#pragma unroll
    for (int i = 0; i < 4; i++) {
        gx0[i] = ldg_nc((const uint4*)(x + gr * DM) + i * 32 + (tid & 31));
        gx1[i] = ldg_nc((const uint4*)(x + min(gr + 1152, SEQ - 1) * DM) + i * 32 + (tid & 31));
        gw[i] = ldg_nc((const uint4*)gate_w + i * 32 + (tid & 31));
    }

    if (tid == 0) {
        for (int i = 0; i < 5; i++) mbar_init(bar + 8 * (B_FULL + i), 1);
        for (int i = 0; i < 3; i++) mbar_init(bar + 8 * (B_EMPTY + i), 2);
        for (int i = 0; i < 4; i++) mbar_init(bar + 8 * (B_MEM + i), 1);
        mbar_init(bar + 8 * B_HOP1, role == 2 ? 1 : 9);
        mbar_init(bar + 8 * B_HOPV, role == 2 ? 8 : 1);
        mbar_init(bar + 8 * B_XT, 1);
        mbar_init(bar + 8 * B_TFREE, 5);
        mbar_init(bar + 8 * B_P, 4);
        mbar_init(bar + 8 * B_XDONE, 8);
        mbar_init(bar + 8 * B_OST0, 4);
        mbar_init(bar + 8 * B_OST1, 4);
        mbar_init(bar + 8 * B_XRECV, 2);
        mbar_init(bar + 8 * B_O, 4);
        mbar_init(bar + 8 * B_AFREE0, 2);
        mbar_init(bar + 8 * B_AFREE1, 2);
        mbar_init(bar + 8 * B_PRO0, 1);
        mbar_init(bar + 8 * B_PRO1, 1);
        for (int i = 0; i < KR / 4; i++) mbar_init(sb + R_O + 8 * i, 1);
        asm volatile("fence.mbarrier_init.release.cluster;" ::: "memory");
        fence_async();
        for (int i = 0; i < KR / 4; i++) mbar_expect(sb + R_O + 8 * i, 16384);
        mbar_expect(bar + 8 * B_PRO1, KS * 4096);
        mbar_expect(bar + 8 * B_PRO0, (role == 0 ? 4 : 6) * 16384);
        for (int i = 0; i < 3; i++) mbar_expect(bar + 8 * (B_FULL + i), 8192);
        mbar_expect(bar + 8 * B_HOP1, role == 2 ? 4096 : 2048);
        if (role != 2) mbar_expect(bar + 8 * B_HOPV, 2048);
        mbar_expect(bar + 8 * B_XT, role == 0 ? 2 * CPB : CPB);
    }
    __syncthreads();
    asm volatile("barrier.cluster.arrive.relaxed.aligned;" ::: "memory");
    {
        const CUtensorMap* tw = &tm.w[role];
        if (wid < 11) {
            e_tma_load(sb + wid * 16384, tw, h * DH, KC(wid), sb + R_O + 8 * wid);
            e_tma_load(sb + wid * 16384 + 8192, tw, h * DH + 64, KC(wid), sb + R_O + 8 * wid);
        }
        if (wid < 6) e_tma_load(sb + R_RING + wid * 4096, &tm.x, XC(wid), 0, bar + 8 * (B_FULL + (wid >> 1)));
        __syncwarp();
        const uint32_t g0 = __float_as_uint(gate_row(gx0, gw)), g1 = __float_as_uint(gate_row(gx1, gw));
        if ((tid & 31) == 0) {
            st_strong4(&g_gate[gr], g0 ? g0 : 0x80000000u);
            if (gr + 1152 < SEQ) st_strong4(&g_gate[gr + 1152], g1 ? g1 : 0x80000000u);
        }
        __syncwarp();
    }
    asm volatile("barrier.cluster.wait.aligned;" ::: "memory");

    if (wid < 8) {
        asm volatile("setmaxnreg.inc.sync.aligned.u32 224;");
        if (role == 0) r_big<0>(tm, wid); else if (role == 1) r_big<1>(tm, wid); else r_big<2>(tm, wid);
    } else {
        asm volatile("setmaxnreg.dec.sync.aligned.u32 56;");
        if (role == 0) r_chain<0>(tm, mem0, wid); else if (role == 1) r_chain<1>(tm, mem0, wid); else r_chain<2>(tm, mem0, wid);
    }
    __syncwarp();
    asm volatile("barrier.cluster.arrive; barrier.cluster.wait;" ::: "memory");
    KT(0, 1);
}

#define STAG 0
constexpr int G_ST = 4;
constexpr int G_STAGE = 16384 + 32768;
constexpr int G_EPI = G_ST * G_STAGE;
constexpr int G_GATE = G_EPI + 32768;
constexpr int G_BAR = G_GATE + 1024;
constexpr int G_SMEM = G_BAR + 128 + 1024;

struct G1Maps { CUtensorMap x, wg, wu, hs, o, h, wo, wd, out; };
constexpr int G1_NB = FF / 128;
constexpr int G1_TILES = 16 * G1_NB;

DEVINL void g_mma_block(float* d, uint32_t sb, uint32_t bar, int it, int wg, int tid, bool first) {
    const int st = it % G_ST;
    mbar_wait(bar + 8 * st, (it / G_ST) & 1);
    const uint64_t da = mkdesc(sb + st * G_STAGE + wg * 8192, 16, 1024, 1);
    const uint64_t db = mkdesc(sb + st * G_STAGE + 16384, 8192, 1024, 1);
    wg_fence();
#pragma unroll
    for (int k = 0; k < 4; k++) wg_ss256(d, da + (uint64_t)(k * 2), db + (uint64_t)(k * 128), (first ? 0 : 1) | k);
    wg_commit();
    if (!first) { wg_wait<1>(); if ((tid & 127) == 0) mbar_arrive(bar + 8 * (G_ST + (it - 1) % G_ST)); }
}
DEVINL void g_load_block(uint32_t sb, uint32_t bar, int it, const CUtensorMap* ta, int k0, int m0, const CUtensorMap* tb, int n0) {
    const int st = it % G_ST;
    mbar_wait(bar + 8 * (G_ST + st), ((it / G_ST) & 1) ^ 1);
    const uint32_t fb = bar + 8 * st, sa = sb + st * G_STAGE;
    mbar_expect(fb, G_STAGE);
    tma_load(sa, ta, k0, m0, fb);
#pragma unroll
    for (int q = 0; q < 4; q++) tma_load(sa + 16384 + q * 8192, tb, n0 + q * 64, k0, fb);
}

DEVINL void g_store_tile(const float* d, const CUtensorMap* tout, uint32_t epi, int mb, int nb, int wg, int tid) {
    const int lane = tid & 31, row = ((tid >> 5) & 3) * 16 + ((lane >> 3) & 1) * 8 + (lane & 7);
#pragma unroll
    for (int half = 0; half < 2; half++) {
        if ((tid & 127) == 0) bulk_wait_read();
        bar_sync(1 + wg, 128);
#pragma unroll
        for (int j = 0; j < 16; j += 2) {
            const float* e = d + half * 64 + 4 * j;
            const int cgp = j + (lane >> 4);
            stsm4(epi + (cgp >> 3) * 8192 + row * 128 + (((cgp & 7) ^ (row & 7)) << 4),
                  pack_bf16(e[0], e[1]), pack_bf16(e[2], e[3]), pack_bf16(e[4], e[5]), pack_bf16(e[6], e[7]));
        }
        fence_async();
        bar_sync(1 + wg, 128);
        if ((tid & 127) == 0) {
            tma_store(tout, epi, nb * 256 + half * 128, mb * 128 + wg * 64);
            tma_store(tout, epi + 8192, nb * 256 + half * 128 + 64, mb * 128 + wg * 64);
            bulk_commit();
        }
    }
}
template <int NS> DEVINL void g_split_finish(const float* d, float4 (&r)[32 / NS], uint4* sk, int tile, int ks, bf16* __restrict__ out, int tid) {
    constexpr int Q = 32 / NS;
    uint4* mine = sk + ks * (16 * 256) + tid;
#pragma unroll
    for (int c = 0; c < NS; c++) {
        if (c != ks) {
#pragma unroll
            for (int q = c * Q / 2; q < (c + 1) * Q / 2; q++)
                __stcg(mine + q * 256, make_uint4(pack_bf16(d[8 * q], d[8 * q + 1]), pack_bf16(d[8 * q + 2], d[8 * q + 3]), pack_bf16(d[8 * q + 4], d[8 * q + 5]), pack_bf16(d[8 * q + 6], d[8 * q + 7])));
        } else {
#pragma unroll
            for (int q = 0; q < Q; q++) { const float* e = d + (c * Q + q) * 4; r[q].x += e[0]; r[q].y += e[1]; r[q].z += e[2]; r[q].w += e[3]; }
        }
    }
    __threadfence();
    bar_sync(3, 256);
    if (tile >= T_LATE) PT(20);
    if (tid == 0) {
        atomicAdd(&g_skcnt[tile], 1u);
        uint32_t v, n = 0;
        do {
            asm volatile("ld.acquire.gpu.global.u32 %0, [%1];" : "=r"(v) : "l"(&g_skcnt[tile]) : "memory");
            if (++n > 200000000u) __trap();
        } while (v < NS);
        if (atomicAdd(&g_skcnt[tile], 1u) == 2 * NS - 1) g_skcnt[tile] = 0u;
    }
    bar_sync(3, 256);
    if (tile >= T_LATE) PT(21);
#pragma unroll
    for (int c = 1; c < NS; c++) {
        const uint4* th = sk + (((ks + c) & (NS - 1)) * 16 + ks * (Q / 2)) * 256 + tid;
#pragma unroll
        for (int q = 0; q < Q / 2; q++) {
            const uint4 u = __ldcg(th + q * 256);
            r[2 * q].x += __uint_as_float(u.x << 16); r[2 * q].y += __uint_as_float(u.x & 0xffff0000u);
            r[2 * q].z += __uint_as_float(u.y << 16); r[2 * q].w += __uint_as_float(u.y & 0xffff0000u);
            r[2 * q + 1].x += __uint_as_float(u.z << 16); r[2 * q + 1].y += __uint_as_float(u.z & 0xffff0000u);
            r[2 * q + 1].z += __uint_as_float(u.w << 16); r[2 * q + 1].w += __uint_as_float(u.w & 0xffff0000u);
        }
    }
    const int lane = tid & 31;
    uint32_t* op = (uint32_t*)(out + ((tile >> 2) * 128 + (tid >> 5) * 16 + (lane >> 2)) * DM + (tile & 3) * 256 + ks * Q * 8 + (lane & 3) * 2);
#pragma unroll
    for (int q = 0; q < Q; q++) { op[q * 4] = pack_bf16(r[q].x, r[q].y); op[q * 4 + 4 * DM] = pack_bf16(r[q].z, r[q].w); }
}
DEVINL int g1_count(int pass, int tail) {
    return pass == 0 ? NPRE : pass == 1 ? NFULL : pass == 2 ? T_MID - NFULL : pass == 3 ? (T_MID2 - T_MID) * 4 : tail ? (64 - T_LATE) * 8 : (T_LATE - T_MID2) * 8;
}
DEVINL int g1_first(int pass, int tail) {
    const int b = blockIdx.x, n = gridDim.x;
    return (pass < 2 || tail) ? b : pass == 2 ? n - 1 - b : (b + n - (pass == 3 ? 16 : 32)) % n;
}
DEVINL int g1_tile(int pass, int tail, int i) {
    return pass == 1 ? i : pass == 3 ? T_MID + (i >> 2) : pass == 4 ? (tail ? T_LATE : T_MID2) + (i >> 3) : NFULL + i;
}
constexpr int H_EARLY = 24;

__global__ void __launch_bounds__(384, 1) g1_kernel(const __grid_constant__ G1Maps tm, bf16* __restrict__ out, const int tail) {
    extern __shared__ __align__(1024) unsigned char smem_raw[];
    const uint32_t sb = (smem_u32(smem_raw) + 1023) & ~1023u;
    const int tid = threadIdx.x, lane = tid & 31;
    const int wg = __shfl_sync(0xffffffffu, tid >> 7, 0);
    const int warp = __shfl_sync(0xffffffffu, (tid >> 5) & 3, 0);
    const uint32_t bar = sb + G_BAR;
    asm volatile("griddepcontrol.launch_dependents;");
    KT(1 + tail, 0);
    if (tail && (tid == 32 || tid == 64)) asm volatile("prefetch.tensormap [%0];" ::"l"(tid == 32 ? &tm.o : &tm.wo) : "memory");
    const int ntiles = tail ? 0 : G1_TILES;
    if (tid == 0) {
        for (int i = 0; i < G_ST; i++) { mbar_init(bar + 8 * i, 1); mbar_init(bar + 8 * (G_ST + i), 2); }
        fence_async();
    }
    __syncthreads();
    if (tail) PT(16);
    if (tail) PT(17);
    if (tail) PT(22);
    if (wg == 2) {
        asm volatile("setmaxnreg.dec.sync.aligned.u32 40;");
        if (tail) {
            const int tile = T_LATE + (blockIdx.x >> 3), k0 = ((blockIdx.x & 7) * 8 + warp) * 64;
            e_expect(bar + 8 * warp, G_STAGE);
#pragma unroll
            for (int q = 0; q < 4; q++) e_tma_load(sb + warp * G_STAGE + 16384 + q * 8192, &tm.wo, (tile & 3) * 256 + q * 64, k0, bar + 8 * warp);
            wait_count(&g_ocnt[tile >> 2], NH * 4);
            asm volatile("fence.proxy.async;" ::: "memory");
            e_tma_load(sb + warp * G_STAGE, &tm.o, k0, (tile >> 2) * 128, bar + 8 * warp);
        }
        if (warp == 0) {
            if (lane == 0) {
                int it = 0;
                for (int tile = blockIdx.x; tile < ntiles; tile += gridDim.x) {
                    const int mb = tile & 15, nb = tile >> 4;
                    for (int kb = 0; kb < 16; kb++, it++) {
                        const int st = it % G_ST;
                        mbar_wait(bar + 8 * (G_ST + st), ((it / G_ST) & 1) ^ 1);
                        const uint32_t fb = bar + 8 * st, sa = sb + st * G_STAGE;
                        mbar_expect(fb, G_STAGE);
                        tma_load(sa, &tm.x, kb * 64, mb * 128, fb);
                        tma_load(sa + 16384, &tm.wg, nb * 128, kb * 64, fb);
                        tma_load(sa + 16384 + 8192, &tm.wg, nb * 128 + 64, kb * 64, fb);
                        tma_load(sa + 16384 + 16384, &tm.wu, nb * 128, kb * 64, fb);
                        tma_load(sa + 16384 + 24576, &tm.wu, nb * 128 + 64, kb * 64, fb);
                    }
                }
                for (int pass = tail ? 4 : 0; pass < 5; pass++) {
                    for (int i = g1_first(pass, tail); i < g1_count(pass, tail); i += gridDim.x) {
                        const int tile = g1_tile(pass, tail, i), mb = tile >> 2, nb = tile & 3;
                        if (pass < 2) {
                            for (int kb = 0; kb < FF / 64; kb++, it++) {
                                if (kb == 0 || kb == 2 * H_EARLY) {
                                    wait_count(&g_hcnt[kb ? 16 + mb : mb], kb ? 2 * (G1_NB - H_EARLY) : 2 * H_EARLY);
                                    asm volatile("fence.proxy.async;" ::: "memory");
                                }
                                g_load_block(sb, bar, it, &tm.h, kb * 64, mb * 128, &tm.wd, nb * 256);
                            }
                        }
                        if (pass > 0) {
                            const int k0 = pass == 3 ? (i & 3) * 16 : pass == 4 ? (i & 7) * 8 : 0, k1 = pass == 3 ? k0 + 16 : pass == 4 ? k0 + 8 : HD / 64;
                            if (!tail) wait_count(&g_ocnt[mb], NH * 4);
                            asm volatile("fence.proxy.async;" ::: "memory");
                            for (int kb = k0; kb < k1; kb++, it++) if (!tail || it >= G_ST) g_load_block(sb, bar, it, &tm.o, kb * 64, mb * 128, &tm.wo, nb * 256);
                        }
                    }
                }
            }
        }
    } else {
        asm volatile("setmaxnreg.inc.sync.aligned.u32 232;");
        float d[128];
        int it = 0;
        const uint32_t epi = sb + G_EPI + wg * 16384;
        const int row = warp * 16 + ((lane >> 3) & 1) * 8 + (lane & 7);
        for (int tile = blockIdx.x; tile < ntiles; tile += gridDim.x) {
            const int mb = tile & 15, nb = tile >> 4;
            const uint32_t* gp = &g_gate[mb * 128 + wg * 64 + warp * 16 + (lane >> 2)];
            uint32_t u0 = ld_strong4(gp), u1 = ld_strong4(gp + 8);
            for (int kb = 0; kb < 16; kb++, it++) {
                if (it == (wg ? 0 : STAG)) bar_sync(4, 256);
                g_mma_block(d, sb, bar, it, wg, tid, kb == 0);
            }
            wg_wait<0>();
            for (uint32_t n = 0; u0 == 0u || u1 == 0u; n++) { u0 = ld_strong4(gp); u1 = ld_strong4(gp + 8); if (n > 20000000u) __trap(); }
            __syncwarp();
            const float s0 = 1.0f - __uint_as_float(u0), s1 = 1.0f - __uint_as_float(u1);
            if ((tid & 127) == 0) {
                mbar_arrive(bar + 8 * (G_ST + (it - 1) % G_ST));
                bulk_wait_all();
                const int pt = tile - (int)gridDim.x;
                if (pt >= 0) atomicAdd(&g_hcnt[(pt & 15) + ((pt >> 4) >= H_EARLY ? 16 : 0)], 1u);
            }
            bar_sync(1 + wg, 128);
#pragma unroll
            for (int j = 0; j < 16; j += 2) {
                uint32_t p[4];
#pragma unroll
                for (int q = 0; q < 4; q++) {
                    const int i = (j + (q >> 1)) * 4 + (q & 1) * 2;
                    const float sc = (q & 1) ? s1 : s0;
                    const float g0 = d[i], g1 = d[i + 1];
                    const float a0 = 1.0f + ex2(fminf(g0 * -1.4426950408889634f, 62.0f)), a1 = 1.0f + ex2(fminf(g1 * -1.4426950408889634f, 62.0f));
                    const float rr = rcp(a0 * a1) * sc;
                    const float h0 = (g0 * d[64 + i]) * (rr * a1);
                    const float h1 = (g1 * d[64 + i + 1]) * (rr * a0);
                    p[q] = pack_bf16(h0, h1);
                }
                const int cgp = j + (lane >> 4);
                stsm4(epi + (cgp >> 3) * 8192 + row * 128 + (((cgp & 7) ^ (row & 7)) << 4), p[0], p[1], p[2], p[3]);
            }
            fence_async();
            bar_sync(1 + wg, 128);
            if ((tid & 127) == 0) {
                tma_store(&tm.hs, epi, nb * 128, mb * 128 + wg * 64);
                tma_store(&tm.hs, epi + 8192, nb * 128 + 64, mb * 128 + wg * 64);
                bulk_commit();
            }
        }
        if ((tid & 127) == 0 && !tail) {
            bulk_wait_all();
            const int pt = blockIdx.x + (G1_TILES - 1 - blockIdx.x) / gridDim.x * gridDim.x;
            atomicAdd(&g_hcnt[(pt & 15) + ((pt >> 4) >= H_EARLY ? 16 : 0)], 1u);
        }
        for (int pass = tail ? 4 : 0; pass < 5; pass++) {
            for (int i = g1_first(pass, tail); i < g1_count(pass, tail); i += gridDim.x) {
                const int tile = g1_tile(pass, tail, i);
                const int nkb = pass == 0 ? FF / 64 : pass == 1 ? (FF + HD) / 64 : pass == 2 ? HD / 64 : pass == 3 ? 16 : 8;
                float4* pre = g_pre + (tile - NFULL) * (32 * 256) + tid;
                if (tail) PT(23);
                if (tail) asm volatile("prefetch.global.L2 [%0];" ::"l"(pre - tid + (i & 7) * 1024 + tid * 4));
                for (int kb = 0; kb < nkb; kb++, it++) { g_mma_block(d, sb, bar, it, wg, tid, kb == 0); if (tail && kb == 0) PT(18); }
                wg_wait<0>();
                if (tail) PT(19);
                if ((tid & 127) == 0) mbar_arrive(bar + 8 * (G_ST + (it - 1) % G_ST));
                if (pass >= 2) { if ((tid & 31) == 0) wait_count(&g_pcnt[tile], 8); __syncwarp(); }
                if (pass == 0) {
#pragma unroll
                    for (int q = 0; q < 32; q++) __stcg(pre + q * 256, make_float4(d[4 * q], d[4 * q + 1], d[4 * q + 2], d[4 * q + 3]));
                    __threadfence();
                    __syncwarp();
                    if ((tid & 31) == 0) atomicAdd(&g_pcnt[tile], 1u);
                } else if (pass == 3) {
                    float4 r[8];
#pragma unroll
                    for (int q = 0; q < 8; q++) r[q] = __ldcg(pre + ((i & 3) * 8 + q) * 256);
                    g_split_finish<4>(d, r, g_sk + (tile - T_MID) * 8 * (16 * 256), tile, i & 3, out, tid);
                } else if (pass == 4) {
                    float4 r[4];
#pragma unroll
                    for (int q = 0; q < 4; q++) r[q] = __ldcg(pre + ((i & 7) * 4 + q) * 256);
                    g_split_finish<8>(d, r, g_sk + (tile - T_MID) * 8 * (16 * 256), tile, i & 7, out, tid);
                } else {
                    if (pass == 2) {
#pragma unroll
                        for (int q = 0; q < 32; q++) {
                            const float4 u = __ldcg(pre + q * 256); d[4 * q] += u.x; d[4 * q + 1] += u.y; d[4 * q + 2] += u.z; d[4 * q + 3] += u.w;
                            if ((q & 7) == 7) __syncwarp();
                        }
                    }
                    g_store_tile(d, &tm.out, epi, tile >> 2, tile & 3, wg, tid);
                }
            }
        }
        if ((tid & 127) == 0) bulk_wait_all();
        KT(1 + tail, 1);
        if (wg == 0) {
            uint32_t last = blockIdx.x == 0;
            if (tail) {
                if (tid == 0) sts32(bar + 64, atomicAdd(&g_ticket, 1u) == gridDim.x - 1);
                bar_sync(1, 128);
                asm volatile("ld.shared.b32 %0, [%1];" : "=r"(last) : "r"(bar + 64) : "memory");
            }
            if (last) {
                asm volatile("griddepcontrol.wait;" ::: "memory");
                if (tail) {
                    for (int i = tid; i < SEQ; i += 128) g_gate[i] = 0u;
                    if (tid < 64) g_pcnt[tid] = 0u;
                    if (tid < 32) g_hcnt[tid] = 0u;
                    if (tid < 16) g_ocnt[tid] = 0u;
                    if (tid == 0) g_ticket = 0u;
                }
            }
        }
    }
}

__device__ bf16 f_qkv[3][(SEQ + NMEM) * HD];
__device__ bf16 f_mem[NMEM * DM], f_om[NMEM * HD];

__global__ void __launch_bounds__(256) f_gemm(const bf16* __restrict__ A, const bf16* __restrict__ B, bf16* __restrict__ C, int K, int N) {
    __shared__ float sa[8][256];
    const int n = blockIdx.x * 256 + threadIdx.x, m0 = blockIdx.y * 8;
    float acc[8] = {0.f, 0.f, 0.f, 0.f, 0.f, 0.f, 0.f, 0.f};
    for (int k0 = 0; k0 < K; k0 += 256) {
        __syncthreads();
        for (int r = 0; r < 8; r++) sa[r][threadIdx.x] = __bfloat162float(A[(size_t)(m0 + r) * K + k0 + threadIdx.x]);
        __syncthreads();
        for (int k = 0; k < 256; k++) {
            const float b = __bfloat162float(B[(size_t)(k0 + k) * N + n]);
#pragma unroll
            for (int r = 0; r < 8; r++) acc[r] = fmaf(sa[r][k], b, acc[r]);
        }
    }
    for (int r = 0; r < 8; r++) C[(size_t)(m0 + r) * N + n] = __float2bfloat16(acc[r]);
}
__global__ void __launch_bounds__(32) f_gate(const bf16* __restrict__ x, const bf16* __restrict__ gate_w) {
    uint4 xv[4], gv[4];
    for (int i = 0; i < 4; i++) { xv[i] = ldg_nc((const uint4*)(x + blockIdx.x * DM) + i * 32 + threadIdx.x); gv[i] = ldg_nc((const uint4*)gate_w + i * 32 + threadIdx.x); }
    const uint32_t g = __float_as_uint(gate_row(xv, gv));
    if (threadIdx.x == 0) { g_gate[blockIdx.x] = g ? g : 0x80000000u; if (blockIdx.x < 16) g_ocnt[blockIdx.x] = NH * 4; }
}
__global__ void __launch_bounds__(128) f_attn(int s) {
    __shared__ float sq[DH], sp[NMEM + SEG];
    const int h = blockIdx.x, i = blockIdx.y, t = threadIdx.x;
    auto row = [&](int r) { return (size_t)(r < NMEM ? SEQ + r : s * SEG + r - NMEM) * HD + h * DH; };
    sq[t] = __bfloat162float(f_qkv[0][row(i) + t]);
    __syncthreads();
    if (t < NMEM + SEG) {
        float a = 0.f;
        for (int e = 0; e < DH; e++) a = fmaf(sq[e], __bfloat162float(f_qkv[1][row(t) + e]), a);
        sp[t] = (i < NMEM || i >= t) ? a * 0.08838834764831845f : -1000000000.0f;
    }
    __syncthreads();
    float m = sp[0], l = 0.f, o = 0.f;
    for (int j = 1; j < NMEM + SEG; j++) m = fmaxf(m, sp[j]);
    for (int j = 0; j < NMEM + SEG; j++) { const float p = __expf(sp[j] - m); l += p; o = fmaf(p, __bfloat162float(f_qkv[2][row(j) + t]), o); }
    if (i < NMEM) f_om[i * HD + h * DH + t] = __float2bfloat16(o / l);
    else g_O[(size_t)(s * SEG + i - NMEM) * HD + h * DH + t] = __float2bfloat16(o / l * __uint_as_float(g_gate[s * SEG + i - NMEM]));
}

typedef CUresult (*EncodeFn)(CUtensorMap*, CUtensorMapDataType, cuuint32_t, void*, const cuuint64_t*, const cuuint64_t*, const cuuint32_t*,
                             const cuuint32_t*, CUtensorMapInterleave, CUtensorMapSwizzle, CUtensorMapL2promotion, CUtensorMapFloatOOBfill);

static void make_map(EncodeFn enc, CUtensorMap* m, const void* ptr, uint64_t rows, uint64_t cols, uint32_t box_rows) {
    cuuint64_t dims[2] = {cols, rows};
    cuuint64_t strides[1] = {cols * 2};
    cuuint32_t box[2] = {64, box_rows};
    cuuint32_t es[2] = {1, 1};
    enc(m, CU_TENSOR_MAP_DATA_TYPE_BFLOAT16, 2, (void*)ptr, dims, strides, box, es, CU_TENSOR_MAP_INTERLEAVE_NONE,
        CU_TENSOR_MAP_SWIZZLE_128B, CU_TENSOR_MAP_L2_PROMOTION_L2_256B, CU_TENSOR_MAP_FLOAT_OOB_FILL_NONE);
}

extern "C" void kernel_launch(void* const* d_in, const int* in_sizes, int n_in, void* d_out, int out_size) {
    (void)in_sizes; (void)n_in; (void)out_size;
    const bf16* x = (const bf16*)d_in[0];
    const bf16* mem0 = (const bf16*)d_in[1];
    const bf16* gate_w = (const bf16*)d_in[11];
    static EncodeFn enc = nullptr;
    static int n_sm = 0;
    static void *pO = nullptr, *pH = nullptr, *pQ = nullptr, *pM = nullptr, *pOm = nullptr;
    static int n_clusters = 0;
    if (!enc) {
        void* fn = nullptr;
        cudaDriverEntryPointQueryResult qr;
        cudaGetDriverEntryPoint("cuTensorMapEncodeTiled", &fn, cudaEnableDefault, &qr);
        enc = (EncodeFn)fn;
        cudaDeviceGetAttribute(&n_sm, cudaDevAttrMultiProcessorCount, 0);
        cudaFuncSetAttribute(r_kernel, cudaFuncAttributeMaxDynamicSharedMemorySize, R_SMEM);
        cudaFuncSetAttribute(g1_kernel, cudaFuncAttributeMaxDynamicSharedMemorySize, G_SMEM);
        cudaGetSymbolAddress(&pO, g_O);
        cudaGetSymbolAddress(&pH, g_H);
        cudaGetSymbolAddress(&pQ, f_qkv);
        cudaGetSymbolAddress(&pM, f_mem);
        cudaGetSymbolAddress(&pOm, f_om);
        cudaLaunchConfig_t cfg = {};
        cfg.gridDim = dim3(96); cfg.blockDim = dim3(384); cfg.dynamicSmemBytes = R_SMEM;
        cudaLaunchAttribute at[1];
        at[0].id = cudaLaunchAttributeClusterDimension; at[0].val.clusterDim.x = 3; at[0].val.clusterDim.y = 1; at[0].val.clusterDim.z = 1;
        cfg.attrs = at; cfg.numAttrs = 1;
        if (cudaOccupancyMaxActiveClusters(&n_clusters, r_kernel, &cfg) != cudaSuccess) { n_clusters = 0; (void)cudaGetLastError(); }
    }
    RMaps rm; G1Maps m1;
    make_map(enc, &rm.x, x, SEQ, DM, 32);
    for (int i = 0; i < 3; i++) make_map(enc, &rm.w[i], d_in[2 + i], DM, HD, 64);
    make_map(enc, &rm.wo, d_in[5], HD, DM, 128);
    make_map(enc, &rm.o, pO, SEQ, HD, 16);
    make_map(enc, &m1.x, x, SEQ, DM, 128);
    make_map(enc, &m1.wg, d_in[8], DM, FF, 64);
    make_map(enc, &m1.wu, d_in[9], DM, FF, 64);
    make_map(enc, &m1.hs, pH, SEQ, FF, 64);
    make_map(enc, &m1.o, pO, SEQ, HD, 128);
    make_map(enc, &m1.h, pH, SEQ, FF, 128);
    make_map(enc, &m1.wo, d_in[5], HD, DM, 64);
    make_map(enc, &m1.wd, d_in[10], FF, DM, 64);
    make_map(enc, &m1.out, d_out, SEQ, DM, 64);

    cudaStream_t st = cudaStreamPerThread;
    if (n_clusters < NH) {
        bf16* qkv = (bf16*)pQ;
        const size_t plane = (size_t)(SEQ + NMEM) * HD;
        f_gate<<<SEQ, 32, 0, st>>>(x, gate_w);
        for (int i = 0; i < 3; i++) f_gemm<<<dim3(HD / 256, SEQ / 8), 256, 0, st>>>(x, (const bf16*)d_in[2 + i], qkv + i * plane, DM, HD);
        for (int s = 0; s < NSEG; s++) {
            for (int i = 0; i < 3; i++)
                f_gemm<<<dim3(HD / 256, 1), 256, 0, st>>>(s ? (const bf16*)pM : mem0, (const bf16*)d_in[2 + i], qkv + i * plane + (size_t)SEQ * HD, DM, HD);
            f_attn<<<dim3(NH, NMEM + SEG), 128, 0, st>>>(s);
            f_gemm<<<dim3(DM / 256, 1), 256, 0, st>>>((const bf16*)pOm, (const bf16*)d_in[5], (bf16*)pM, HD, DM);
        }
    } else {
        cudaLaunchConfig_t cfg = {};
        cfg.gridDim = dim3(96); cfg.blockDim = dim3(384); cfg.dynamicSmemBytes = R_SMEM; cfg.stream = st;
        cudaLaunchAttribute at[1];
        at[0].id = cudaLaunchAttributeClusterDimension; at[0].val.clusterDim.x = 3; at[0].val.clusterDim.y = 1; at[0].val.clusterDim.z = 1;
        cfg.attrs = at; cfg.numAttrs = 1;
        cudaLaunchKernelEx(&cfg, r_kernel, rm, mem0, x, gate_w);
    }
    {
        cudaLaunchConfig_t cfg = {};
        cfg.gridDim = dim3(n_sm - 96 > 32 ? n_sm - 96 : 32); cfg.blockDim = dim3(384); cfg.dynamicSmemBytes = G_SMEM; cfg.stream = st;
        cudaLaunchAttribute at[1];
        at[0].id = cudaLaunchAttributeProgrammaticStreamSerialization; at[0].val.programmaticStreamSerializationAllowed = 1;
        cfg.attrs = at; cfg.numAttrs = n_clusters < NH ? 0 : 1;
        cudaLaunchKernelEx(&cfg, g1_kernel, m1, (bf16*)d_out, 0);
    }
    {
        cudaLaunchConfig_t cfg = {};
        cfg.gridDim = dim3((64 - T_LATE) * 8); cfg.blockDim = dim3(384); cfg.dynamicSmemBytes = G_SMEM; cfg.stream = st;
        cudaLaunchAttribute at[1];
        at[0].id = cudaLaunchAttributeProgrammaticStreamSerialization; at[0].val.programmaticStreamSerializationAllowed = 1;
        cfg.attrs = at; cfg.numAttrs = 1;
        cudaLaunchKernelEx(&cfg, g1_kernel, m1, (bf16*)d_out, 1);
    }
}
```

```cpp
#include <cuda_runtime.h>
#include <cuda_bf16.h>
#include <cuda.h>
#include <stdint.h>

typedef __nv_bfloat16 bf16;

constexpr int SEQ = 2048, DM = 1024, NH = 32, DH = 128, NMEM = 8, SEG = 32, NSEG = 64, FF = 3584;
constexpr int HD = NH * DH;

__device__ bf16 g_O[SEQ * HD];
__device__ bf16 g_H[SEQ * FF];
__device__ uint32_t g_gate[SEQ];
__device__ uint32_t g_part[4][128 * 32 * 32];
__device__ uint32_t g_mem[4][DM * 4];
#define TLATE 56
constexpr int NFULL = 36, T_MID = 44, T_MID2 = 48, T_LATE = TLATE;
constexpr int NPRE = 64 - NFULL;
__device__ float4 g_pre[NPRE * 32 * 256];
__device__ uint4 g_sk[(64 - T_MID) * 16 * 16 * 256];
__device__ uint32_t g_skcnt[64], g_pcnt[64], g_ticket;
__device__ uint32_t g_hcnt[32], g_ocnt[16];
#define KT(k, i)
#define PT(i)

#define DEVINL __device__ __forceinline__
constexpr long long SPIN_LIMIT = 4000000000LL;

DEVINL uint32_t smem_u32(const void* p) { return (uint32_t)__cvta_generic_to_shared(p); }
DEVINL void mbar_init(uint32_t bar, uint32_t cnt) { asm volatile("mbarrier.init.shared::cta.b64 [%0], %1;" ::"r"(bar), "r"(cnt) : "memory"); }
DEVINL void mbar_arrive(uint32_t bar) { asm volatile("mbarrier.arrive.shared::cta.b64 _, [%0];" ::"r"(bar) : "memory"); }
DEVINL void mbar_expect(uint32_t bar, uint32_t bytes) { asm volatile("mbarrier.arrive.expect_tx.shared::cta.b64 _, [%0], %1;" ::"r"(bar), "r"(bytes) : "memory"); }
DEVINL void mbar_arrive_remote(uint32_t cbar) { asm volatile("mbarrier.arrive.relaxed.cluster.shared::cluster.b64 _, [%0];" ::"r"(cbar) : "memory"); }
DEVINL bool mbar_try(uint32_t bar, uint32_t par) {
    uint32_t ok;
    asm volatile("{ .reg .pred p; mbarrier.try_wait.parity.shared::cta.b64 p, [%1], %2; selp.u32 %0, 1, 0, p; }" : "=r"(ok) : "r"(bar), "r"(par) : "memory");
    return ok;
}
__device__ __noinline__ void mbar_wait_slow(uint32_t bar, uint32_t par) {
    long long t0 = clock64();
    while (!mbar_try(bar, par)) { if (clock64() - t0 > SPIN_LIMIT) __trap(); }
}
DEVINL void mbar_wait(uint32_t bar, uint32_t par) {
    uint32_t n = 0;
    while (!mbar_try(bar, par)) { if (++n > 200000000u) __trap(); }
}
DEVINL uint32_t mapa(uint32_t a, uint32_t r) { uint32_t o; asm volatile("mapa.shared::cluster.u32 %0, %1, %2;" : "=r"(o) : "r"(a), "r"(r)); return o; }
DEVINL void fence_async() { asm volatile("fence.proxy.async.shared::cta;" ::: "memory"); }
DEVINL void bar_sync(int id, int n) { asm volatile("bar.sync %0, %1;" ::"r"(id), "r"(n) : "memory"); }
DEVINL void cluster_sync() { asm volatile("barrier.cluster.arrive.aligned; barrier.cluster.wait.aligned;" ::: "memory"); }
DEVINL void tma_load(uint32_t dst, const CUtensorMap* tm, int c0, int c1, uint32_t bar) {
    asm volatile("cp.async.bulk.tensor.2d.shared::cluster.global.mbarrier::complete_tx::bytes [%0], [%1, {%3, %4}], [%2];"
                 ::"r"(dst), "l"(tm), "r"(bar), "r"(c0), "r"(c1) : "memory");
}
DEVINL void tma_prefetch(const CUtensorMap* tm, int c0, int c1) {
    asm volatile("cp.async.bulk.prefetch.tensor.2d.L2.global [%0, {%1, %2}];" ::"l"(tm), "r"(c0), "r"(c1) : "memory");
}
DEVINL void tma_store(const CUtensorMap* tm, uint32_t src, int c0, int c1) {
    asm volatile("cp.async.bulk.tensor.2d.global.shared::cta.bulk_group [%0, {%2, %3}], [%1];" ::"l"(tm), "r"(src), "r"(c0), "r"(c1) : "memory");
}
DEVINL void bulk_commit() { asm volatile("cp.async.bulk.commit_group;" ::: "memory"); }
DEVINL void bulk_wait_read() { asm volatile("cp.async.bulk.wait_group.read 0;" ::: "memory"); }
DEVINL void bulk_wait_all() { asm volatile("cp.async.bulk.wait_group 0;" ::: "memory"); }
DEVINL void bulk_s2s(uint32_t cdst, uint32_t src, uint32_t bytes, uint32_t cbar) {
    asm volatile("cp.async.bulk.shared::cluster.shared::cta.mbarrier::complete_tx::bytes [%0], [%1], %2, [%3];" ::"r"(cdst), "r"(src), "r"(bytes), "r"(cbar) : "memory");
}
DEVINL void st_async16(uint32_t cdst, uint4 v, uint32_t cbar) {
    asm volatile("st.async.shared::cluster.mbarrier::complete_tx::bytes.v4.b32 [%0], {%1,%2,%3,%4}, [%5];" ::"r"(cdst), "r"(v.x), "r"(v.y), "r"(v.z), "r"(v.w), "r"(cbar) : "memory");
}
DEVINL uint64_t mkdesc(uint32_t addr, uint32_t lbo, uint32_t sbo, uint32_t swz) {
    return (uint64_t)((addr & 0x3FFFF) >> 4) | ((uint64_t)(lbo >> 4) << 16) | ((uint64_t)(sbo >> 4) << 32) | ((uint64_t)swz << 62);
}
constexpr uint32_t SB0 = 1024;
__host__ __device__ constexpr uint64_t cdesc(uint32_t off, uint32_t lbo, uint32_t sbo, uint32_t swz) {
    return (uint64_t)(((SB0 + off) & 0x3FFFF) >> 4) | ((uint64_t)(lbo >> 4) << 16) | ((uint64_t)(sbo >> 4) << 32) | ((uint64_t)swz << 62);
}
DEVINL float rcp(float x) { float y; asm("rcp.approx.ftz.f32 %0, %1;" : "=f"(y) : "f"(x)); return y; }
DEVINL float ex2(float x) { float y; asm("ex2.approx.ftz.f32 %0, %1;" : "=f"(y) : "f"(x)); return y; }
DEVINL void spin_clk(int d) { uint32_t t0, t1; asm volatile("mov.u32 %0, %%clock;" : "=r"(t0)); do { asm volatile("mov.u32 %0, %%clock;" : "=r"(t1)); } while ((int)(t1 - t0) < d); }
#define PROBE_GAP 150
#define OPAQUE(x) asm volatile("" : "+r"(x))
DEVINL void wg_fence() { asm volatile("wgmma.fence.sync.aligned;" ::: "memory"); }
DEVINL void wg_commit() { asm volatile("wgmma.commit_group.sync.aligned;" ::: "memory"); }
template <int N> DEVINL void wg_wait() { asm volatile("wgmma.wait_group.sync.aligned %0;" ::"n"(N) : "memory"); }
DEVINL uint32_t pack_bf16(float lo, float hi) { uint32_t r; asm("cvt.rn.bf16x2.f32 %0, %1, %2;" : "=r"(r) : "f"(hi), "f"(lo)); return r; }
DEVINL void ldsm4(uint32_t* r, uint32_t a) { asm volatile("ldmatrix.sync.aligned.m8n8.x4.shared.b16 {%0,%1,%2,%3}, [%4];" : "=r"(r[0]), "=r"(r[1]), "=r"(r[2]), "=r"(r[3]) : "r"(a) : "memory"); }
DEVINL void ldsm4t(uint32_t* r, uint32_t a) { asm volatile("ldmatrix.sync.aligned.m8n8.x4.trans.shared.b16 {%0,%1,%2,%3}, [%4];" : "=r"(r[0]), "=r"(r[1]), "=r"(r[2]), "=r"(r[3]) : "r"(a) : "memory"); }
DEVINL void ldsm4t_if(uint32_t* r, uint32_t a, int c) { asm volatile("{ .reg .pred p; setp.ne.s32 p, %5, 0; @p ldmatrix.sync.aligned.m8n8.x4.trans.shared.b16 {%0,%1,%2,%3}, [%4]; }" : "+r"(r[0]), "+r"(r[1]), "+r"(r[2]), "+r"(r[3]) : "r"(a), "r"(c) : "memory"); }
DEVINL void stsm4(uint32_t a, uint32_t r0, uint32_t r1, uint32_t r2, uint32_t r3) { asm volatile("stmatrix.sync.aligned.m8n8.x4.shared.b16 [%0], {%1,%2,%3,%4};" ::"r"(a), "r"(r0), "r"(r1), "r"(r2), "r"(r3) : "memory"); }
DEVINL void stsm4t(uint32_t a, uint32_t r0, uint32_t r1, uint32_t r2, uint32_t r3) { asm volatile("stmatrix.sync.aligned.m8n8.x4.trans.shared.b16 [%0], {%1,%2,%3,%4};" ::"r"(a), "r"(r0), "r"(r1), "r"(r2), "r"(r3) : "memory"); }
DEVINL void sts32(uint32_t a, uint32_t v) { asm volatile("st.shared.b32 [%0], %1;" ::"r"(a), "r"(v) : "memory"); }
DEVINL void sts128(uint32_t a, uint4 v) { asm volatile("st.shared.v4.b32 [%0], {%1,%2,%3,%4};" ::"r"(a), "r"(v.x), "r"(v.y), "r"(v.z), "r"(v.w) : "memory"); }
DEVINL uint4 lds128(uint32_t a) { uint4 v; asm volatile("ld.shared.v4.b32 {%0,%1,%2,%3}, [%4];" : "=r"(v.x), "=r"(v.y), "=r"(v.z), "=r"(v.w) : "r"(a) : "memory"); return v; }
DEVINL uint4 ld_strong16(const void* p) { uint4 v; asm volatile("ld.relaxed.gpu.global.v4.u32 {%0,%1,%2,%3}, [%4];" : "=r"(v.x), "=r"(v.y), "=r"(v.z), "=r"(v.w) : "l"(p) : "memory"); return v; }
DEVINL void st_strong8(void* p, uint32_t a, uint32_t b) { asm volatile("st.relaxed.gpu.global.v2.u32 [%0], {%1,%2};" ::"l"(p), "r"(a), "r"(b) : "memory"); }
DEVINL void st_strong4(void* p, uint32_t a) { asm volatile("st.relaxed.gpu.global.u32 [%0], %1;" ::"l"(p), "r"(a) : "memory"); }
DEVINL void st_strong16(void* p, uint4 v) { asm volatile("st.relaxed.gpu.global.v4.u32 [%0], {%1,%2,%3,%4};" ::"l"(p), "r"(v.x), "r"(v.y), "r"(v.z), "r"(v.w) : "memory"); }
DEVINL uint32_t pack_nz(float lo, float hi) { uint32_t r = pack_bf16(lo, hi); return r == 0u ? 0x8000u : r; }
DEVINL uint32_t min4(uint4 v, uint32_t m) { return __vimin3_u32(__vimin3_u32(v.x, v.y, m), v.z, v.w); }
DEVINL void mma16816(float* d, uint32_t a0, uint32_t a1, uint32_t a2, uint32_t a3, uint32_t b0, uint32_t b1) {
    asm volatile("mma.sync.aligned.m16n8k16.row.col.f32.bf16.bf16.f32 {%0,%1,%2,%3}, {%4,%5,%6,%7}, {%8,%9}, {%0,%1,%2,%3};"
                 : "+f"(d[0]), "+f"(d[1]), "+f"(d[2]), "+f"(d[3]) : "r"(a0), "r"(a1), "r"(a2), "r"(a3), "r"(b0), "r"(b1));
}
DEVINL void mma1688(float* d, uint32_t a0, uint32_t a1, uint32_t b0) {
    asm volatile("mma.sync.aligned.m16n8k8.row.col.f32.bf16.bf16.f32 {%0,%1,%2,%3}, {%4,%5}, {%6}, {%0,%1,%2,%3};"
                 : "+f"(d[0]), "+f"(d[1]), "+f"(d[2]), "+f"(d[3]) : "r"(a0), "r"(a1), "r"(b0));
}
template <int TA, int TB> DEVINL void wg_ss8(float* d, uint64_t da, uint64_t db, int sc) {
    asm volatile("{ .reg .pred p; setp.ne.b32 p, %6, 0; wgmma.mma_async.sync.aligned.m64n8k16.f32.bf16.bf16 {%0,%1,%2,%3}, %4, %5, p, 1, 1, %7, %8; }"
                 : "+f"(d[0]), "+f"(d[1]), "+f"(d[2]), "+f"(d[3]) : "l"(da), "l"(db), "r"(sc), "n"(TA), "n"(TB));
}
template <int TB> DEVINL void wg_rs8(float* d, const uint32_t* a, uint64_t db, int sc) {
    asm volatile("{ .reg .pred p; setp.ne.b32 p, %9, 0; wgmma.mma_async.sync.aligned.m64n8k16.f32.bf16.bf16 {%0,%1,%2,%3}, {%4,%5,%6,%7}, %8, p, 1, 1, %10; }"
                 : "+f"(d[0]), "+f"(d[1]), "+f"(d[2]), "+f"(d[3]) : "r"(a[0]), "r"(a[1]), "r"(a[2]), "r"(a[3]), "l"(db), "r"(sc), "n"(TB));
}
#define ACC16(d) "+f"(d[0]), "+f"(d[1]), "+f"(d[2]), "+f"(d[3]), "+f"(d[4]), "+f"(d[5]), "+f"(d[6]), "+f"(d[7]), "+f"(d[8]), "+f"(d[9]), "+f"(d[10]), "+f"(d[11]), "+f"(d[12]), "+f"(d[13]), "+f"(d[14]), "+f"(d[15])
template <int TA> DEVINL void wg_ss32(float* d, uint64_t da, uint64_t db, int sc) {
    asm volatile("{ .reg .pred p; setp.ne.b32 p, %18, 0; wgmma.mma_async.sync.aligned.m64n32k16.f32.bf16.bf16 {%0,%1,%2,%3,%4,%5,%6,%7,%8,%9,%10,%11,%12,%13,%14,%15}, %16, %17, p, 1, 1, %19, 0; }"
                 : ACC16(d) : "l"(da), "l"(db), "r"(sc), "n"(TA));
}
DEVINL void wg_rs32(float* d, const uint32_t* a, uint64_t db, int sc) {
    asm volatile("{ .reg .pred p; setp.ne.b32 p, %21, 0; wgmma.mma_async.sync.aligned.m64n32k16.f32.bf16.bf16 {%0,%1,%2,%3,%4,%5,%6,%7,%8,%9,%10,%11,%12,%13,%14,%15}, {%16,%17,%18,%19}, %20, p, 1, 1, 0; }"
                 : ACC16(d) : "r"(a[0]), "r"(a[1]), "r"(a[2]), "r"(a[3]), "l"(db), "r"(sc));
}
DEVINL void wg_ss40(float* d, uint64_t da, uint64_t db, int sc) {
    asm volatile("{ .reg .pred p; setp.ne.b32 p, %22, 0; wgmma.mma_async.sync.aligned.m64n40k16.f32.bf16.bf16 {%0,%1,%2,%3,%4,%5,%6,%7,%8,%9,%10,%11,%12,%13,%14,%15,%16,%17,%18,%19}, %20, %21, p, 1, 1, 1, 1; }"
                 : ACC16(d), "+f"(d[16]), "+f"(d[17]), "+f"(d[18]), "+f"(d[19]) : "l"(da), "l"(db), "r"(sc));
}
#define A8(d, o) "+f"(d[o]), "+f"(d[o + 1]), "+f"(d[o + 2]), "+f"(d[o + 3]), "+f"(d[o + 4]), "+f"(d[o + 5]), "+f"(d[o + 6]), "+f"(d[o + 7])
#define A32(d, o) A8(d, o), A8(d, o + 8), A8(d, o + 16), A8(d, o + 24)
DEVINL void wg_ss256(float* d, uint64_t da, uint64_t db, int sc) {
    asm volatile(
        "{ .reg .pred p; setp.ne.b32 p, %130, 0;\n"
        "wgmma.mma_async.sync.aligned.m64n256k16.f32.bf16.bf16 {"
        "%0,%1,%2,%3,%4,%5,%6,%7,%8,%9,%10,%11,%12,%13,%14,%15,%16,%17,%18,%19,%20,%21,%22,%23,%24,%25,%26,%27,%28,%29,%30,%31,"
        "%32,%33,%34,%35,%36,%37,%38,%39,%40,%41,%42,%43,%44,%45,%46,%47,%48,%49,%50,%51,%52,%53,%54,%55,%56,%57,%58,%59,%60,%61,%62,%63,"
        "%64,%65,%66,%67,%68,%69,%70,%71,%72,%73,%74,%75,%76,%77,%78,%79,%80,%81,%82,%83,%84,%85,%86,%87,%88,%89,%90,%91,%92,%93,%94,%95,"
        "%96,%97,%98,%99,%100,%101,%102,%103,%104,%105,%106,%107,%108,%109,%110,%111,%112,%113,%114,%115,%116,%117,%118,%119,%120,%121,%122,%123,%124,%125,%126,%127"
        "}, %128, %129, p, 1, 1, 0, 1; }"
        : A32(d, 0), A32(d, 32), A32(d, 64), A32(d, 96) : "l"(da), "l"(db), "r"(sc));
}

DEVINL float gate_row(const uint4 (&xv)[4], const uint4 (&gv)[4]) {
    float acc = 0.f;
#pragma unroll
    for (int i = 0; i < 4; i++) {
        const uint32_t xa[4] = {xv[i].x, xv[i].y, xv[i].z, xv[i].w}, ga[4] = {gv[i].x, gv[i].y, gv[i].z, gv[i].w};
#pragma unroll
        for (int e = 0; e < 4; e++) {
            acc = fmaf(__uint_as_float(xa[e] << 16), __uint_as_float(ga[e] << 16), acc);
            acc = fmaf(__uint_as_float(xa[e] & 0xffff0000u), __uint_as_float(ga[e] & 0xffff0000u), acc);
        }
    }
#pragma unroll
    for (int o = 16; o > 0; o >>= 1) acc += __shfl_xor_sync(0xffffffffu, acc, o);
    return 1.0f / (1.0f + __expf(-acc));
}
DEVINL uint4 ldg_nc(const void* p) { uint4 v; asm volatile("ld.global.nc.v4.u32 {%0,%1,%2,%3}, [%4];" : "=r"(v.x), "=r"(v.y), "=r"(v.z), "=r"(v.w) : "l"(p) : "memory"); return v; }
DEVINL uint32_t ld_strong4(const void* p) { uint32_t v; asm volatile("ld.relaxed.gpu.global.u32 %0, [%1];" : "=r"(v) : "l"(p) : "memory"); return v; }
DEVINL void wait_count(const uint32_t* p, uint32_t want) {
    uint32_t v, n = 0;
    while (true) {
        asm volatile("ld.acquire.gpu.global.u32 %0, [%1];" : "=r"(v) : "l"(p) : "memory");
        if (v >= want) break;
        __nanosleep(100);
        if (++n > 20000000u) __trap();
    }
}

constexpr int KR = 44;
constexpr int KS = 64 - KR;
constexpr int R_W = 0;
constexpr int R_WO = KS * 4096;
constexpr int R_QX = R_WO + 65536;
constexpr int R_RING = R_WO + 98304;
constexpr int R_K = R_RING + 24576;
constexpr int R_V = R_K + 10240;
constexpr int R_QM = R_V + 10240;
constexpr int R_O = R_QM + 2048;
constexpr int R_BAR = R_O + 2048;
constexpr int R_G = R_BAR + 256 + 512 + 256 + 128;
constexpr int R_Z = R_G + 256;
constexpr int R_SMEM = R_Z + 1024;
enum { B_FULL = 0, B_EMPTY = 5, B_MEM = 8, B_HOP1 = 12, B_XT, B_TFREE, B_O, B_AFREE0, B_AFREE1, B_PRO0, B_PRO1, B_XRECV, B_P, B_XDONE, B_OST0, B_OST1, B_HOPV };
#define D2_BASE 900
#define D2_STEP 200
#define PD2 6
#define CPB 8192
#define DDUP 0
#define WGAP 0
#define PVD 400
#define ELD 700
#define QD 3
#define PPF 0
#define DQ 1700
#define D3 0

DEVINL uint32_t clk32() { uint32_t c_; asm volatile("mov.u32 %0, %%clock;" : "=r"(c_)); return c_; }
DEVINL void spin_until(uint32_t t) { while ((uint32_t)(t - clk32() - 1u) < 100000u) {} }
#define PROF(i)
#define PROF2(i)
#define PROF3(i, val)
DEVINL void e_arrive(uint32_t bar) { asm volatile("{ .reg .pred p; elect.sync _|p, 0xffffffff; @p mbarrier.arrive.shared::cta.b64 _, [%0]; }" ::"r"(bar) : "memory"); }
DEVINL void e_arrive_remote(uint32_t cbar) { asm volatile("{ .reg .pred p; elect.sync _|p, 0xffffffff; @p mbarrier.arrive.relaxed.cluster.shared::cluster.b64 _, [%0]; }" ::"r"(cbar) : "memory"); }
DEVINL void e_count(uint32_t* p) { asm volatile("{ .reg .pred p; elect.sync _|p, 0xffffffff; @p red.relaxed.gpu.global.add.u32 [%0], 1; }" ::"l"(p) : "memory"); }
DEVINL void e_expect(uint32_t bar, uint32_t bytes) { asm volatile("{ .reg .pred p; elect.sync _|p, 0xffffffff; @p mbarrier.arrive.expect_tx.shared::cta.b64 _, [%0], %1; }" ::"r"(bar), "r"(bytes) : "memory"); }
DEVINL void e_tma_load(uint32_t dst, const CUtensorMap* tm, int c0, int c1, uint32_t bar) {
    asm volatile("{ .reg .pred p; elect.sync _|p, 0xffffffff; @p cp.async.bulk.tensor.2d.shared::cluster.global.mbarrier::complete_tx::bytes [%0], [%1, {%3, %4}], [%2]; }"
                 ::"r"(dst), "l"(tm), "r"(bar), "r"(c0), "r"(c1) : "memory");
}
DEVINL void e_tma_store(const CUtensorMap* tm, uint32_t src, int c0, int c1) {
    asm volatile("{ .reg .pred p; elect.sync _|p, 0xffffffff; @p cp.async.bulk.tensor.2d.global.shared::cta.bulk_group [%0, {%2, %3}], [%1]; }" ::"l"(tm), "r"(src), "r"(c0), "r"(c1) : "memory");
}
DEVINL void e_bulk_s2g(void* dst, uint32_t src, uint32_t bytes) {
    asm volatile("{ .reg .pred p; elect.sync _|p, 0xffffffff; @p cp.async.bulk.global.shared::cta.bulk_group [%0], [%1], %2; }" ::"l"(dst), "r"(src), "r"(bytes) : "memory");
}
DEVINL void e_bulk_s2s(uint32_t cdst, uint32_t src, uint32_t bytes, uint32_t cbar) {
    asm volatile("{ .reg .pred p; elect.sync _|p, 0xffffffff; @p cp.async.bulk.shared::cluster.shared::cta.mbarrier::complete_tx::bytes [%0], [%1], %2, [%3]; }" ::"r"(cdst), "r"(src), "r"(bytes), "r"(cbar) : "memory");
}

#define SLOT 0
#define PH3 0
#define PHQ 0
DEVINL void wait_slot(uint32_t phase) {
    if (SLOT) {
        uint32_t c; asm volatile("mov.u32 %0, %%globaltimer_lo;" : "=r"(c));
        const uint32_t tgt = c + (SLOT ? SLOT : 1) - ((c - phase) % (SLOT ? SLOT : 1));
        do { asm volatile("mov.u32 %0, %%globaltimer_lo;" : "=r"(c)); } while ((uint32_t)(tgt - c - 1u) < 100000u);
    }
}
template <int N> DEVINL uint32_t poll_set(uint4 (&v)[N], const uint32_t* rp, int stride, uint32_t phase, uint32_t wbar = 0, uint32_t wpar = 0) {
    wait_slot(phase);
#pragma unroll
    for (int i = 0; i < N; i++) v[i] = ld_strong16(rp + i * stride);
    if (wbar) mbar_wait(wbar, wpar);
    uint32_t n = 0;
    while (true) {
        uint32_t m = 0xffffffffu;
#pragma unroll
        for (int i = 0; i < N; i++) m = min4(v[i], m);
        if (__all_sync(0xffffffffu, m != 0u)) return n;
        wait_slot(phase);
#pragma unroll
        for (int i = 0; i < N; i++)
            asm volatile("{ .reg .pred p; setp.eq.u32 p, %5, 0; @p ld.relaxed.gpu.global.v4.u32 {%0,%1,%2,%3}, [%4]; }"
                         : "+r"(v[i].x), "+r"(v[i].y), "+r"(v[i].z), "+r"(v[i].w) : "l"(rp + i * stride), "r"(min4(v[i], 0xffffffffu)) : "memory");
        if (++n > 20000000u) __trap();
    }
}

struct RMaps { CUtensorMap x, w[3], wo, o; };
#define KC(c) ((c) * 64)

#define XORD 3
__host__ __device__ constexpr int xo(int i) {
    return XORD == 0 ? i : XORD == 1 ? (i + 14) % 16 : XORD == 2 ? (i + 11) % 16
         : XORD == 3 ? (i < 10 ? ((i & 1) ? i / 2 : 11 + i / 2) : i - 5) : (i < 6 ? i : ((i & 1) ? 6 + (i - 6) / 2 : 11 + (i - 6) / 2));
}
#define XC(i) (xo(i) * 64)
DEVINL void x_load_pair(uint32_t dst, const CUtensorMap* tmx, int h, int p, int seg, uint32_t fbar) {
    e_expect(fbar, 8192);
    e_tma_load(dst, tmx, XC(2 * p), seg * SEG, fbar);
    e_tma_load(dst + 4096, tmx, XC(2 * p + 1), seg * SEG, fbar);
}
__host__ __device__ constexpr int wo_tile(int role, int i) {
    return role == 0 ? (i < 2 ? 8 + i : 12 + i) : (i < 4 ? (i >> 1) * 4 : 10) + (role - 1) * 2 + (i & 1);
}

template <int NT> DEVINL void wo_phase(uint32_t sb, int tb, uint32_t* pp, uint32_t obar, uint32_t opar) {
    const int lane = tb & 31, krow = (lane & 7) + ((lane >> 4) << 3), chunk = ((tb >> 5) & 3) * 2 + ((lane >> 3) & 1);
    uint32_t wa = sb + R_WO + (tb >> 7) * 16384 + krow * 128 + ((chunk ^ (krow & 7)) << 4);
    uint32_t af[4][4], of[4][4];
#pragma unroll
    for (int g = 0; g < 4; g++) ldsm4t(af[g], wa + g * 2048);
    mbar_wait(obar, opar);
#pragma unroll
    for (int g = 0; g < 4; g++) ldsm4t(of[g], sb + R_O + g * 512 + lane * 16);
#pragma unroll 1
    for (int i = 0; i < NT; i++) {
        float w0[4] = {0.f, 0.f, 0.f, 0.f}, w1[4] = {0.f, 0.f, 0.f, 0.f};
        const int more = NT - 1 - i, yes = NT - i;
        mma16816(w0, af[0][0], af[0][1], af[0][2], af[0][3], of[0][0], of[0][1]);
        ldsm4t_if(af[0], wa + 4 * 2048, yes);
        mma16816(w1, af[1][0], af[1][1], af[1][2], af[1][3], of[0][2], of[0][3]);
        ldsm4t_if(af[1], wa + 5 * 2048, yes);
        mma16816(w0, af[2][0], af[2][1], af[2][2], af[2][3], of[1][0], of[1][1]);
        ldsm4t_if(af[2], wa + 6 * 2048, yes);
        mma16816(w1, af[3][0], af[3][1], af[3][2], af[3][3], of[1][2], of[1][3]);
        ldsm4t_if(af[3], wa + 7 * 2048, yes);
        wa += 32768;
        mma16816(w0, af[0][0], af[0][1], af[0][2], af[0][3], of[2][0], of[2][1]);
        ldsm4t_if(af[0], wa, more);
        mma16816(w1, af[1][0], af[1][1], af[1][2], af[1][3], of[2][2], of[2][3]);
        ldsm4t_if(af[1], wa + 2048, more);
        mma16816(w0, af[2][0], af[2][1], af[2][2], af[2][3], of[3][0], of[3][1]);
        ldsm4t_if(af[2], wa + 2 * 2048, more);
        mma16816(w1, af[3][0], af[3][1], af[3][2], af[3][3], of[3][2], of[3][3]);
        ldsm4t_if(af[3], wa + 3 * 2048, more);
        st_strong4(pp, pack_nz(w0[0] + w1[0], w0[1] + w1[1]));
        st_strong4(pp + 1024, pack_nz(w0[2] + w1[2], w0[3] + w1[3]));
        pp += (NT == 3 && i == 0) ? 4 * 8192 : 6 * 8192;
    }
}

template <uint32_t role> DEVINL void r_big(const RMaps& tm, const int wid) {
    extern __shared__ __align__(1024) unsigned char smem_raw[];
    const uint32_t sb = smem_u32(smem_raw);
    const uint32_t bar = sb + R_BAR;
    const int tid = threadIdx.x;
    int h; asm("mov.u32 %0, %%clusterid.x;" : "=r"(h));
        uint32_t a[KR][4];
        {
            const int lane = tid & 31;
            const int krow = (lane & 7) + ((lane >> 4) << 3);
            const int chunk = (wid & 3) * 2 + ((lane >> 3) & 1);
            const uint32_t la = sb + (wid >> 2) * 8192 + krow * 128 + ((chunk ^ (krow & 7)) << 4);
            const CUtensorMap* tw = &tm.w[role];
#pragma unroll
            for (int b = 0; b < KR / 4; b++) {
                mbar_wait(sb + R_O + 8 * b, 0);
                if (b == 0) PT(0);
#pragma unroll
                for (int k = 0; k < 4; k++) ldsm4t(a[b * 4 + k], la + b * 16384 + k * 2048);
                bar_sync(1, 256);
                if (wid == (b & 7)) {
                    fence_async();
                    if (b < 5) {
#pragma unroll
                        for (int q = 2 * b; q < 2 * b + 2; q++) e_tma_load(sb + R_W + q * 8192, tw, h * DH + (q / 5) * 64, KC(KR / 4 + q % 5), bar + 8 * B_PRO1);
                    } else if (b - 5 < (role == 0 ? 4 : 6)) {
                        e_tma_load(sb + R_WO + (b - 5) * 16384, &tm.wo, wo_tile(role, b - 5) * 64, h * DH, bar + 8 * B_PRO0);
                    }
                }
            }
        }
        constexpr uint32_t e0 = role == 0 ? R_QX + 16384 : R_K + 2048, e1 = role == 0 ? R_QX + 24576 : R_V + 2048;
        if (wid == 6) x_load_pair(sb + e0, &tm.x, h, 3, 0, bar + 8 * (B_FULL + 3));
        if (wid == 7) x_load_pair(sb + e1, &tm.x, h, 4, 0, bar + 8 * (B_FULL + 4));
        PT(1);
        mbar_wait(bar + 8 * B_PRO1, 0);
        PT(2);

        constexpr uint64_t dW0 = cdesc(R_W, 1024, 1024, 1);
        constexpr uint64_t dM = cdesc(R_RING, 128, 128, 0);
        constexpr uint64_t dX = cdesc(R_RING, 16, 1024, 1);
        constexpr uint64_t dX0 = cdesc(0, 16, 1024, 1);
        int tb = tid;
        int wq = wid;

        for (int seg = 0; seg < NSEG; seg++) {
            {
            const int s = seg - 1; (void)s;
            float d[16];
            OPAQUE(wq);
            const uint64_t dW = dW0 + (uint64_t)((wq >> 2) * (KS * 128));
#pragma unroll
            for (int p = 0; p < 8; p++) {
                const int slot = p % 5;
                mbar_wait(bar + 8 * (B_FULL + slot), slot < 3 ? (uint32_t)(p / 5) : (uint32_t)(seg & 1));
                PROF2(p);
                const uint64_t db = slot < 3 ? dX + (uint64_t)(slot * 512) : dX0 + (uint64_t)((slot == 3 ? e0 : e1) >> 4);
                wg_fence();
#pragma unroll
                for (int kk = 0; kk < 8; kk++) {
                    const int k = XORD >= 3 ? (kk & 1) * 4 + (kk >> 1) : kk;
                    const int ks = xo(2 * p + (k >> 2)) * 4 + (k & 3);
                    if (ks >= KR) wg_ss32<1>(d, dW + (uint64_t)((ks - KR) * 128), db + (uint64_t)((k >> 2) * 256 + (k & 3) * 2), p + k);
                    else wg_rs32(d, a[ks < KR ? ks : 0], db + (uint64_t)((k >> 2) * 256 + (k & 3) * 2), p + k);
                }
                wg_commit();
                if (p >= 1) {
                    wg_wait<1>();
                    if (p <= 3) {
                        if ((wq & 3) == p) e_arrive(bar + 8 * (B_EMPTY + p - 1));
                        if (wq == p + (p & 1) * 4) {
                            mbar_wait(bar + 8 * (B_EMPTY + p - 1), seg & 1);
                            x_load_pair(sb + R_RING + (p - 1) * 8192, &tm.x, h, p + 4, seg, bar + 8 * (B_FULL + p - 1));
                        }
                    }
                    if (p == 5 && role != 0 && (wq & 3) < 3) e_arrive_remote(mapa(bar + 8 * B_TFREE, wq & 3));
                    if (p == 6 && (wq & 3) == 1) e_arrive(bar + 8 * B_AFREE0);
                    if (p == 7 && (wq & 3) == 2) e_arrive(bar + 8 * B_AFREE1);
                }
            }
            mbar_wait(bar + 8 * B_TFREE, seg & 1);
            asm volatile("wgmma.wait_group.sync.aligned 0;" : ACC16(d)::"memory");
            PROF2(16);
            const uint32_t tilex = sb + (role == 0 ? R_QX + 2048 : (role == 1 ? R_K + 2048 : R_V + 2048));
            {
                OPAQUE(tb);
                const uint32_t gs = role == 0 ? 4096 : 2048;
                const uint32_t sa = tilex + ((tb >> 4) & 1) * gs + (tb >> 5) * 256 + (tb & 15) * 16;
                stsm4(sa, pack_bf16(d[0], d[1]), pack_bf16(d[2], d[3]), pack_bf16(d[4], d[5]), pack_bf16(d[6], d[7]));
                stsm4(sa + 2 * gs, pack_bf16(d[8], d[9]), pack_bf16(d[10], d[11]), pack_bf16(d[12], d[13]), pack_bf16(d[14], d[15]));
            }
            __syncwarp();
            e_arrive(bar + 8 * B_XDONE);
            if (role != 0 && (wq & 3) == 0) {
                mbar_wait(bar + 8 * B_XDONE, seg & 1);
                fence_async();
                uint32_t pr = role + 1 + (wq >> 2); pr = pr >= 3 ? pr - 3 : pr;
                e_bulk_s2s(mapa(tilex, pr), tilex, CPB, mapa(bar + 8 * B_XT, pr));
            }
            }
            {
                const int s = seg;
                OPAQUE(wq);
                const uint64_t dW = dW0 + (uint64_t)((wq >> 2) * (KS * 128));
                float y[4] = {0.f, 0.f, 0.f, 0.f};
                {
                    OPAQUE(tb);
                    const uint32_t ma = sb + R_RING + (tb & 31) * 16;
                    float z[4] = {0.f, 0.f, 0.f, 0.f}, u[4] = {0.f, 0.f, 0.f, 0.f};
                    uint32_t b[QD][4];
                    const int yes = s + 1;
                    mbar_wait(bar + 8 * B_MEM, s & 1);
                    PROF((wq >> 2) * 4 + 0);
                    if (s == 0) PT(3);
                    if (s == 1) PT(4);
#pragma unroll
                    for (int g = 0; g < QD; g++) ldsm4t(b[g], ma + g * 512);
#pragma unroll
                    for (int g = 0; g < KR / 2; g++) {
                        float* c0 = (g % 3 == 0) ? y : (g % 3 == 1) ? u : z;
                        float* c1 = (g % 3 == 0) ? z : (g % 3 == 1) ? y : u;
                        mma16816(c0, a[2 * g][0], a[2 * g][1], a[2 * g][2], a[2 * g][3], b[g % QD][0], b[g % QD][1]);
                        mma16816(c1, a[2 * g + 1][0], a[2 * g + 1][1], a[2 * g + 1][2], a[2 * g + 1][3], b[g % QD][2], b[g % QD][3]);
                        if (g + QD < KR / 2) {
                            if ((g + QD) % 8 == 0) mbar_wait(bar + 8 * (B_MEM + (g + QD) / 8), s & 1);
                            ldsm4t_if(b[g % QD], ma + (g + QD) * 512, yes);
                        }
                    }
                    y[0] += z[0] + u[0]; y[1] += z[1] + u[1]; y[2] += z[2] + u[2]; y[3] += z[3] + u[3];
                }
                PROF2(8);
                mbar_wait(bar + 8 * (B_MEM + 3), s & 1);
                wg_fence();
#pragma unroll
                for (int k = KR; k < 64; k++) {
                    wg_ss8<1, 1>(y, dW + (uint64_t)((k - KR) * 128), dM + (uint64_t)(k * 16), 1);
                }
                wg_commit();
                asm volatile("wgmma.wait_group.sync.aligned 0;" : "+f"(y[0]), "+f"(y[1]), "+f"(y[2]), "+f"(y[3])::"memory");
                OPAQUE(tb);
                {
                    const uint32_t wo_ = (tb >> 5) * 256;
                    const uint32_t tile = sb + (role == 0 ? R_QX : (role == 1 ? R_K : R_V)) + wo_;
                    const uint32_t u0 = pack_bf16(y[0], y[1]), u1 = pack_bf16(y[2], y[3]);
                    sts32(tile + (tb & 31) * 4, u0);
                    sts32(tile + (tb & 31) * 4 + 128, u1);
                    __syncwarp();
                    uint4 v = lds128(tile + (tb & 15) * 16);
                    uint32_t peer = role + 1 + ((tb >> 4) & 1);
                    peer = peer >= 3 ? peer - 3 : peer;
                    const uint32_t rt = sb + (role == 0 ? R_QM : (role == 1 ? R_K : R_V)) + wo_ + (tb & 15) * 16;
                    st_async16(mapa(rt, peer), v, mapa(bar + 8 * (role == 2 ? B_HOPV : B_HOP1), peer));
                    if (role == 0) {
                        sts128(tile + 4096 + ((tb >> 4) & 1) * 4096 + (tb & 15) * 16, v);
                        sts32(tile + 12288 + (tb & 31) * 4, u0);
                        sts32(tile + 12288 + (tb & 31) * 4 + 128, u1);
                        __syncwarp();
                    }
                    e_arrive(bar + 8 * (role == 2 ? B_HOPV : B_HOP1));
                }
                PROF((wq >> 2) * 4 + 1);
                if (s < NSEG - 1) {
                    bar_sync(1, 256);
                    if (wq < 3) { fence_async(); x_load_pair(sb + R_RING + wq * 8192, &tm.x, h, wq, s + 1, bar + 8 * (B_FULL + wq)); }
                    else if (role == 0 && wq < 5) x_load_pair(sb + (wq == 3 ? e0 : e1), &tm.x, h, wq, s + 1, bar + 8 * (B_FULL + wq));
                    OPAQUE(tb);
                }
                uint32_t* pp = g_part[s & 3] + (h * 32 + (wo_tile(role, 0) + (tb >> 7)) * 8192 + ((tb >> 5) & 3) * 2048 + (tb & 31));
                asm volatile("" : "+l"(pp));
                if (s == NSEG - 1) break;
                if (s == 0) mbar_wait(bar + 8 * B_PRO0, 0);
                wo_phase<role == 0 ? 2 : 3>(sb, tb, pp, bar + 8 * B_O, s & 1);
                if (wq == 0) PROF(10);
            }
        }
}

#define CLR 0
#define CLEAR(st) do { if (role != 0) { \
                const int w_ = wid & 3; \
                uint32_t* zp = g_part[(st) & 3] + ((rg0 + (w_ >> 1) * 64) * 1024 + (w_ & 1) * 512); \
                e_bulk_s2g(zp, sb + R_Z, 1024); \
                e_bulk_s2g(zp + 256, sb + R_Z, 1024); \
                e_bulk_s2g(&g_mem[(st) & 3][(rg0 + (w_ >> 1) * 64) * 32 + (w_ & 1) * 16], sb + R_Z, 64); \
                bulk_commit(); } } while (0)
template <uint32_t role> DEVINL void r_chain(const RMaps& tm, const bf16* __restrict__ mem0, const int wid) {
    extern __shared__ __align__(1024) unsigned char smem_raw[];
    const uint32_t sb = smem_u32(smem_raw);
    const uint32_t bar = sb + R_BAR;
    const int tid = threadIdx.x;
    int h; asm("mov.u32 %0, %%clusterid.x;" : "=r"(h));
        int t = tid & 127;
        const float sl2 = 0.08838834764831845f * 1.4426950408889634f;
        const float NEGRAW = -1000000000.0f / 0.08838834764831845f;
        const int rg0 = ((int)role - 1) * 32 + h;
        if (role != 0) {
#pragma unroll 1
            for (int r = 0; r < 4; r++) {
                uint32_t* zp = g_part[r] + ((rg0 + (t >> 6) * 64) * 1024 + (t & 63) * 4);
#pragma unroll
                for (int i = 0; i < 4; i++) if (r) st_strong16(zp + i * 256, make_uint4(0u, 0u, 0u, 0u));
                if ((t & 63) < 8) st_strong16(&g_mem[r][(rg0 + (t >> 6) * 64) * 32 + (t & 63) * 4], make_uint4(0u, 0u, 0u, 0u));
            }
            __threadfence();
        }
        if (role == 0 && (wid & 3) < 3) e_arrive_remote(mapa(bar + 8 * B_TFREE, wid & 3));
        if (t < 64) sts128(sb + R_Z + t * 16, make_uint4(0u, 0u, 0u, 0u));
        if (role == 0) sts128(sb + R_QM + t * 16, make_uint4(0u, 0u, 0u, 0u));
        {
            uint4 v[8];
#pragma unroll
            for (int r = 0; r < 8; r++) v[r] = __ldg((const uint4*)(mem0 + r * DM) + t);
            mbar_wait(bar + 8 * B_AFREE0, 0);
            mbar_wait(bar + 8 * B_AFREE1, 0);
#define TR2(f, c) \
            sts128(sb + R_RING + t * 128 + (c) * 16, make_uint4(__byte_perm(v[0].f, v[1].f, 0x5410), __byte_perm(v[2].f, v[3].f, 0x5410), __byte_perm(v[4].f, v[5].f, 0x5410), __byte_perm(v[6].f, v[7].f, 0x5410))); \
            sts128(sb + R_RING + t * 128 + (c) * 16 + 16, make_uint4(__byte_perm(v[0].f, v[1].f, 0x7632), __byte_perm(v[2].f, v[3].f, 0x7632), __byte_perm(v[4].f, v[5].f, 0x7632), __byte_perm(v[6].f, v[7].f, 0x7632)));
            TR2(x, 0) TR2(y, 2) TR2(z, 4) TR2(w, 6)
            fence_async();
            __syncwarp();
            e_arrive(bar + 8 * B_MEM + (t >> 5) * 8);
        }
        constexpr uint64_t dQ = role == 0 ? cdesc(R_QX, 128, 2048, 0) : cdesc(R_QM, 128, 0, 0);
        constexpr uint64_t dK = cdesc(R_K, 128, 2048, 0);

        for (int s = 0; s < NSEG; s++) {
            if (role == 0) {
                uint32_t n = 0, gate;
                do { gate = ld_strong4(&g_gate[s * SEG + (t >> 2)]); if (++n > 20000000u) __trap(); } while (gate == 0u);
                sts32(sb + R_G + (t >> 2) * 4, gate);
                __syncwarp();
            }
            mbar_wait(bar + 8 * B_XDONE, s & 1);
            mbar_wait(bar + 8 * B_XT, s & 1);
            if (t >= 1 && t < 3) { uint32_t pr = role + t; pr = pr >= 3 ? pr - 3 : pr; mbar_arrive_remote(mapa(bar + 8 * B_XRECV, pr)); }
            __syncwarp();
            mbar_wait(bar + 8 * B_HOP1, s & 1);
            PROF(8);
            fence_async();
            OPAQUE(t);
            if (s == NSEG - 1 && role != 0) { mbar_wait(bar + 8 * B_HOPV, s & 1); bulk_wait_all(); break; }
            float sc[20];
            wg_fence();
#pragma unroll
            for (int k = 0; k < 8; k++) wg_ss40(sc, dQ + (uint64_t)(k * 16), dK + (uint64_t)(k * 16), k);
            wg_commit();
            uint32_t t_o = clk32() + 500;
            {
                const uint32_t va = sb + R_V + 2048 + (t >> 5) * 512 + ((t >> 4) & 1) * 2048 + (t & 15) * 16;
                uint32_t v0[4], v1[4];
                ldsm4(v0, va); ldsm4(v1, va + 256);
                uint32_t vm[4];
                const bool v_here = mbar_try(bar + 8 * B_HOPV, s & 1);
                if (v_here) ldsm4(vm, sb + R_V + t * 16);
                wg_wait<0>();
                if (role == 0) {
#pragma unroll
                    for (int j = 0; j < 5; j++)
                        asm volatile("st.shared.v2.f32 [%0], {%1,%2};" ::"r"(sb + R_QX + 768 + (t >> 5) * 4096 + j * 256 + (t & 31) * 8), "f"(sc[4 * j + 2]), "f"(sc[4 * j + 3]) : "memory");
                }
                float m = fmaxf(sc[0], sc[1]);
#pragma unroll
                for (int j = 1; j < 5; j++) m = fmaxf(m, fmaxf(sc[4 * j], sc[4 * j + 1]));
                m = fmaxf(m, __shfl_xor_sync(0xffffffffu, m, 1));
                m = fmaxf(m, __shfl_xor_sync(0xffffffffu, m, 2));
                const float mb = m * sl2;
                uint32_t pk[5];
#pragma unroll
                for (int j = 0; j < 5; j++) pk[j] = pack_bf16(ex2(fmaf(sc[4 * j], sl2, -mb)), ex2(fmaf(sc[4 * j + 1], sl2, -mb)));
                float o0[4] = {0.f, 0.f, 0.f, 0.f}, o1[4] = {0.f, 0.f, 0.f, 0.f}, ls[4] = {0.f, 0.f, 0.f, 0.f};
                constexpr uint32_t ONE = 0x3F803F80u;
                mma16816(o0, v0[0], v0[1], v0[2], v0[3], pk[1], pk[2]);
                mma16816(o1, v1[0], v1[1], v1[2], v1[3], pk[1], pk[2]);
                ldsm4(v0, va + 4096); ldsm4(v1, va + 4096 + 256);
                mma16816(ls, ONE, ONE, ONE, ONE, pk[1], pk[2]);
                mma16816(ls, ONE, ONE, ONE, ONE, pk[3], pk[4]);
                mma1688(ls, ONE, ONE, pk[0]);
                mma16816(o0, v0[0], v0[1], v0[2], v0[3], pk[3], pk[4]);
                mma16816(o1, v1[0], v1[1], v1[2], v1[3], pk[3], pk[4]);
                if (!v_here) { mbar_wait(bar + 8 * B_HOPV, s & 1); ldsm4(vm, sb + R_V + t * 16); }
                mma1688(o0, vm[0], vm[1], pk[0]);
                mma1688(o1, vm[2], vm[3], pk[0]);
                const float i0 = rcp(ls[0]), i1 = rcp(ls[1]);
                const uint32_t oa = sb + R_O + (t >> 5) * 512 + (t & 31) * 4;
                sts32(oa, pack_bf16(o0[0] * i0, o0[1] * i1));
                sts32(oa + 128, pack_bf16(o0[2] * i0, o0[3] * i1));
                sts32(oa + 256, pack_bf16(o1[0] * i0, o1[1] * i1));
                sts32(oa + 384, pack_bf16(o1[2] * i0, o1[3] * i1));
                __syncwarp();
                e_arrive(bar + 8 * B_O);
                PROF(9);
                if (role == 0) {
                    OPAQUE(t);
                    const int lim = (t >> 2) - (t & 3) * 2 + 8;
                    float z[10];
#pragma unroll
                    for (int j = 0; j < 5; j++)
                        asm volatile("ld.shared.v2.f32 {%0,%1}, [%2];" : "=f"(z[2 * j]), "=f"(z[2 * j + 1]) : "r"(sb + R_QX + 768 + (t >> 5) * 4096 + j * 256 + (t & 31) * 8) : "memory");
                    float gate; asm volatile("ld.shared.f32 %0, [%1];" : "=f"(gate) : "r"(sb + R_G + (t >> 2) * 4) : "memory");
                    float m1 = fmaxf(z[0], z[1]);
#pragma unroll
                    for (int j = 1; j < 5; j++) {
                        z[2 * j] = 8 * j <= lim ? z[2 * j] : NEGRAW;
                        z[2 * j + 1] = 8 * j + 1 <= lim ? z[2 * j + 1] : NEGRAW;
                        m1 = fmaxf(m1, fmaxf(z[2 * j], z[2 * j + 1]));
                    }
                    m1 = fmaxf(m1, __shfl_xor_sync(0xffffffffu, m1, 1));
                    m1 = fmaxf(m1, __shfl_xor_sync(0xffffffffu, m1, 2));
                    const float mb1 = m1 * sl2;
                    float l1 = 0.f;
                    const uint32_t pa = sb + R_QX + (t >> 5) * 4096 + (t & 31) * 4;
#pragma unroll
                    for (int j = 0; j < 5; j++) {
                        const uint32_t pw = pack_bf16(ex2(fmaf(z[2 * j], sl2, -mb1)), ex2(fmaf(z[2 * j + 1], sl2, -mb1)));
                        l1 += __uint_as_float(pw << 16) + __uint_as_float(pw & 0xffff0000u);
                        sts32(pa + j * 128, pw);
                    }
                    sts32(pa + 5 * 128, 0u);
                    l1 += __shfl_xor_sync(0xffffffffu, l1, 1);
                    l1 += __shfl_xor_sync(0xffffffffu, l1, 2);
                    sts32(sb + R_G + 128 + (t >> 2) * 4, __float_as_uint(gate * rcp(l1)));
                    spin_until(t_o + PVD);
                    if ((wid & 3) == 0 && s >= 1) { bulk_wait_all(); e_count(&g_ocnt[(s - 1) >> 2]); }
                    fence_async();
                    bar_sync(2, 128);
                    constexpr uint64_t dV = cdesc(R_V, 2048, 128, 0);
                    constexpr uint64_t dP = cdesc(R_QX, 128, 4096, 0);
                    float sf[8];
#pragma unroll
                    for (int j = 0; j < 4; j++) asm volatile("ld.shared.v2.f32 {%0,%1}, [%2];" : "=f"(sf[2 * j]), "=f"(sf[2 * j + 1]) : "r"(sb + R_G + 128 + j * 32 + (t & 3) * 8) : "memory");
                    const uint32_t r = ((t >> 4) & 1) * 8 + (t & 7), ch = (t >> 5) * 2 + ((t >> 3) & 1);
                    const uint32_t sa = sb + R_QX + 2048 + r * 128 + ((ch ^ (r & 7)) << 4);
#pragma unroll
                    for (int hf = 0; hf < 2; hf++) {
                        float d[16];
                        wg_fence();
#pragma unroll
                        for (int k = 0; k < 3; k++) wg_ss32<0>(d, dV + (uint64_t)(hf * 64 + k * 256), dP + (uint64_t)(k * 16), k);
                        wg_commit();
                        asm volatile("wgmma.wait_group.sync.aligned 0;" : ACC16(d)::"memory");
                        stsm4t(sa + hf * 8192, pack_bf16(d[0] * sf[0], d[1] * sf[1]), pack_bf16(d[2] * sf[0], d[3] * sf[1]), pack_bf16(d[4] * sf[2], d[5] * sf[3]), pack_bf16(d[6] * sf[2], d[7] * sf[3]));
                        stsm4t(sa + hf * 8192 + 4096, pack_bf16(d[8] * sf[4], d[9] * sf[5]), pack_bf16(d[10] * sf[4], d[11] * sf[5]), pack_bf16(d[12] * sf[6], d[13] * sf[7]), pack_bf16(d[14] * sf[6], d[15] * sf[7]));
                    }
                    fence_async();
                    bar_sync(2, 128);
                    if ((wid & 3) == 0) {
#pragma unroll
                        for (int q = 0; q < 4; q++) e_tma_store(&tm.o, sb + R_QX + 2048 + q * 4096, h * DH + (q >> 1) * 64, s * SEG + (q & 1) * 16);
                        bulk_commit();
                        bulk_wait_read();
                    }
                    if ((wid & 3) < 3) e_arrive_remote(mapa(bar + 8 * B_TFREE, wid & 3));
                }
            }
            if (t < 32) { e_expect(bar + 8 * B_HOP1, role == 2 ? 4096 : 2048); if (role != 2) e_expect(bar + 8 * B_HOPV, 2048); e_expect(bar + 8 * B_XT, role == 0 ? 2 * CPB : CPB); }
            if (s == NSEG - 1) { bulk_wait_all(); if ((wid & 3) == 0) e_count(&g_ocnt[s >> 2]); break; }
            if (role != 0 && (wid & 3) >= 2) {
                mbar_wait(bar + 8 * B_XRECV, s & 1);
                mbar_wait(bar + 8 * B_O, s & 1);
                fence_async();
                spin_until(t_o + ELD);
                x_load_pair(sb + ((wid & 1) ? R_V + 2048 : R_K + 2048), &tm.x, h, 3 + (wid & 1), s + 1, bar + 8 * (B_FULL + 3 + (wid & 1)));
            }
            OPAQUE(t);
            PROF(11);
            if (role != 0 || DDUP) {
                const int grp = role == 0 ? (t >> 6) * 32 + h : rg0 + (t >> 6) * 64;
                const uint32_t* rp = g_part[s & 3] + (grp * 1024 + ((t >> 2) & 7) * 32 + ((t >> 5) & 1) * 16 + (t & 3) * 4);
                uint32_t* wp = &g_mem[(s + 1) & 3][grp * 32 + ((t >> 5) & 1) * 16 + (t & 3) * 4 + ((t >> 3) & 3)];
                bulk_wait_all();
                spin_until(t_o + D2_BASE + (role == 0 ? DDUP + (t >> 6) * D2_STEP : (role - 1 + (t >> 6) * 2) * D2_STEP));
                PROF3(0, clk32());
#define LO(u) __uint_as_float((u) << 16)
#define HI(u) __uint_as_float((u) & 0xffff0000u)
                uint4 v[4];
                uint32_t n = poll_set<4>(v, rp, 256, (role - 1 + (t >> 6) * 2) * PHQ);
                {
                    PROF3(1, clk32());
                    float f[8];
                    f[0] = (LO(v[0].x) + LO(v[1].x)) + (LO(v[2].x) + LO(v[3].x)); f[1] = (HI(v[0].x) + HI(v[1].x)) + (HI(v[2].x) + HI(v[3].x));
                    f[2] = (LO(v[0].y) + LO(v[1].y)) + (LO(v[2].y) + LO(v[3].y)); f[3] = (HI(v[0].y) + HI(v[1].y)) + (HI(v[2].y) + HI(v[3].y));
                    f[4] = (LO(v[0].z) + LO(v[1].z)) + (LO(v[2].z) + LO(v[3].z)); f[5] = (HI(v[0].z) + HI(v[1].z)) + (HI(v[2].z) + HI(v[3].z));
                    f[6] = (LO(v[0].w) + LO(v[1].w)) + (LO(v[2].w) + LO(v[3].w)); f[7] = (HI(v[0].w) + HI(v[1].w)) + (HI(v[2].w) + HI(v[3].w));
                    const bool b4 = t & 16, b3 = t & 8;
                    float g4[4], g2[2];
#pragma unroll
                    for (int i = 0; i < 4; i++) g4[i] = (b4 ? f[4 + i] : f[i]) + __shfl_xor_sync(0xffffffffu, b4 ? f[i] : f[4 + i], 16);
#pragma unroll
                    for (int i = 0; i < 2; i++) g2[i] = (b3 ? g4[2 + i] : g4[i]) + __shfl_xor_sync(0xffffffffu, b3 ? g4[i] : g4[2 + i], 8);
                    g2[0] += __shfl_xor_sync(0xffffffffu, g2[0], 4);
                    g2[1] += __shfl_xor_sync(0xffffffffu, g2[1], 4);
                    st_strong4(wp, pack_nz(g2[0], g2[1]));
                }
                PROF3(8, n); (void)n;
            }
            t_o += D2_BASE + DQ + D3 + (t >> 5) * D2_STEP;
            OPAQUE(t);
            PROF(12);
            {
                const uint32_t* rp = &g_mem[(s + 1) & 3][((t >> 5) * 256 + (t & 31)) * 4];
                const uint32_t da = sb + R_RING + ((t >> 5) * 256 + (t & 31)) * 16;
                uint4 v[8];
                spin_until(t_o);
                PROF3(2, clk32());
                uint32_t n = poll_set<8>(v, rp, 128, PH3 + (t >> 5) * PHQ);
                PROF(13);
                PROF3(3, clk32()); PROF3(9, n); (void)n;
                mbar_wait(bar + 8 * B_AFREE0 + (t >> 6) * 8, (s + 1) & 1);
                PROF3(4, clk32());
#pragma unroll
                for (int i = 0; i < 8; i++) sts128(da + i * 512, v[i]);
                if (t >= 64) fence_async();
                __syncwarp();
                e_arrive(bar + 8 * B_MEM + (t >> 5) * 8);
                PROF(14);
                PROF3(5, clk32());
            }
            CLEAR(s + 3);
        }
}

__global__ void __launch_bounds__(384, 1) r_kernel(const __grid_constant__ RMaps tm, const bf16* __restrict__ mem0, const bf16* __restrict__ x, const bf16* __restrict__ gate_w) {
    extern __shared__ __align__(1024) unsigned char smem_raw[];
    const uint32_t sb = smem_u32(smem_raw);
    if ((sb & 0x3FFFFu) != SB0) __trap();
    const int tid = threadIdx.x;
    const int wid = __shfl_sync(0xffffffffu, tid >> 5, 0);
    uint32_t role; asm("mov.u32 %0, %%cluster_ctarank;" : "=r"(role));
    int h; asm("mov.u32 %0, %%clusterid.x;" : "=r"(h));
    const uint32_t bar = sb + R_BAR;
    asm volatile("griddepcontrol.launch_dependents;");
    KT(0, 0);
    const int gr = blockIdx.x * 12 + wid;
    uint4 gx0[4], gx1[4], gw[4];
#pragma unroll
    for (int i = 0; i < 4; i++) {
        gx0[i] = ldg_nc((const uint4*)(x + gr * DM) + i * 32 + (tid & 31));
        gx1[i] = ldg_nc((const uint4*)(x + min(gr + 1152, SEQ - 1) * DM) + i * 32 + (tid & 31));
        gw[i] = ldg_nc((const uint4*)gate_w + i * 32 + (tid & 31));
    }

    if (tid == 0) {
        for (int i = 0; i < 5; i++) mbar_init(bar + 8 * (B_FULL + i), 1);
        for (int i = 0; i < 3; i++) mbar_init(bar + 8 * (B_EMPTY + i), 2);
        for (int i = 0; i < 4; i++) mbar_init(bar + 8 * (B_MEM + i), 1);
        mbar_init(bar + 8 * B_HOP1, role == 2 ? 1 : 9);
        mbar_init(bar + 8 * B_HOPV, role == 2 ? 8 : 1);
        mbar_init(bar + 8 * B_XT, 1);
        mbar_init(bar + 8 * B_TFREE, 5);
        mbar_init(bar + 8 * B_P, 4);
        mbar_init(bar + 8 * B_XDONE, 8);
        mbar_init(bar + 8 * B_OST0, 4);
        mbar_init(bar + 8 * B_OST1, 4);
        mbar_init(bar + 8 * B_XRECV, 2);
        mbar_init(bar + 8 * B_O, 4);
        mbar_init(bar + 8 * B_AFREE0, 2);
        mbar_init(bar + 8 * B_AFREE1, 2);
        mbar_init(bar + 8 * B_PRO0, 1);
        mbar_init(bar + 8 * B_PRO1, 1);
        for (int i = 0; i < KR / 4; i++) mbar_init(sb + R_O + 8 * i, 1);
        asm volatile("fence.mbarrier_init.release.cluster;" ::: "memory");
        fence_async();
        for (int i = 0; i < KR / 4; i++) mbar_expect(sb + R_O + 8 * i, 16384);
        mbar_expect(bar + 8 * B_PRO1, KS * 4096);
        mbar_expect(bar + 8 * B_PRO0, (role == 0 ? 4 : 6) * 16384);
        for (int i = 0; i < 3; i++) mbar_expect(bar + 8 * (B_FULL + i), 8192);
        mbar_expect(bar + 8 * B_HOP1, role == 2 ? 4096 : 2048);
        if (role != 2) mbar_expect(bar + 8 * B_HOPV, 2048);
        mbar_expect(bar + 8 * B_XT, role == 0 ? 2 * CPB : CPB);
    }
    __syncthreads();
    asm volatile("barrier.cluster.arrive.relaxed.aligned;" ::: "memory");
    {
        const CUtensorMap* tw = &tm.w[role];
        if (wid < 11) {
            e_tma_load(sb + wid * 16384, tw, h * DH, KC(wid), sb + R_O + 8 * wid);
            e_tma_load(sb + wid * 16384 + 8192, tw, h * DH + 64, KC(wid), sb + R_O + 8 * wid);
        }
        if (wid < 6) e_tma_load(sb + R_RING + wid * 4096, &tm.x, XC(wid), 0, bar + 8 * (B_FULL + (wid >> 1)));
        __syncwarp();
        const uint32_t g0 = __float_as_uint(gate_row(gx0, gw)), g1 = __float_as_uint(gate_row(gx1, gw));
        if ((tid & 31) == 0) {
            st_strong4(&g_gate[gr], g0 ? g0 : 0x80000000u);
            if (gr + 1152 < SEQ) st_strong4(&g_gate[gr + 1152], g1 ? g1 : 0x80000000u);
        }
        __syncwarp();
    }
    asm volatile("barrier.cluster.wait.aligned;" ::: "memory");

    if (wid < 8) {
        asm volatile("setmaxnreg.inc.sync.aligned.u32 224;");
        if (role == 0) r_big<0>(tm, wid); else if (role == 1) r_big<1>(tm, wid); else r_big<2>(tm, wid);
    } else {
        asm volatile("setmaxnreg.dec.sync.aligned.u32 56;");
        if (role == 0) r_chain<0>(tm, mem0, wid); else if (role == 1) r_chain<1>(tm, mem0, wid); else r_chain<2>(tm, mem0, wid);
    }
    __syncwarp();
    asm volatile("barrier.cluster.arrive; barrier.cluster.wait;" ::: "memory");
    KT(0, 1);
}

#define STAG 0
constexpr int G_ST = 4;
constexpr int G_STAGE = 16384 + 32768;
constexpr int G_EPI = G_ST * G_STAGE;
constexpr int G_GATE = G_EPI + 32768;
constexpr int G_BAR = G_GATE + 1024;
constexpr int G_SMEM = G_BAR + 128 + 1024;

struct G1Maps { CUtensorMap x, wg, wu, hs, o, h, wo, wd, out; };
constexpr int G1_NB = FF / 128;
constexpr int G1_TILES = 16 * G1_NB;

DEVINL void g_mma_block(float* d, uint32_t sb, uint32_t bar, int it, int wg, int tid, bool first) {
    const int st = it % G_ST;
    mbar_wait(bar + 8 * st, (it / G_ST) & 1);
    const uint64_t da = mkdesc(sb + st * G_STAGE + wg * 8192, 16, 1024, 1);
    const uint64_t db = mkdesc(sb + st * G_STAGE + 16384, 8192, 1024, 1);
    wg_fence();
#pragma unroll
    for (int k = 0; k < 4; k++) wg_ss256(d, da + (uint64_t)(k * 2), db + (uint64_t)(k * 128), (first ? 0 : 1) | k);
    wg_commit();
    if (!first) { wg_wait<1>(); if ((tid & 127) == 0) mbar_arrive(bar + 8 * (G_ST + (it - 1) % G_ST)); }
}
DEVINL void g_load_block(uint32_t sb, uint32_t bar, int it, const CUtensorMap* ta, int k0, int m0, const CUtensorMap* tb, int n0) {
    const int st = it % G_ST;
    mbar_wait(bar + 8 * (G_ST + st), ((it / G_ST) & 1) ^ 1);
    const uint32_t fb = bar + 8 * st, sa = sb + st * G_STAGE;
    mbar_expect(fb, G_STAGE);
    tma_load(sa, ta, k0, m0, fb);
#pragma unroll
    for (int q = 0; q < 4; q++) tma_load(sa + 16384 + q * 8192, tb, n0 + q * 64, k0, fb);
}

DEVINL void g_store_tile(const float* d, const CUtensorMap* tout, uint32_t epi, int mb, int nb, int wg, int tid) {
    const int lane = tid & 31, row = ((tid >> 5) & 3) * 16 + ((lane >> 3) & 1) * 8 + (lane & 7);
#pragma unroll
    for (int half = 0; half < 2; half++) {
        if ((tid & 127) == 0) bulk_wait_read();
        bar_sync(1 + wg, 128);
#pragma unroll
        for (int j = 0; j < 16; j += 2) {
            const float* e = d + half * 64 + 4 * j;
            const int cgp = j + (lane >> 4);
            stsm4(epi + (cgp >> 3) * 8192 + row * 128 + (((cgp & 7) ^ (row & 7)) << 4),
                  pack_bf16(e[0], e[1]), pack_bf16(e[2], e[3]), pack_bf16(e[4], e[5]), pack_bf16(e[6], e[7]));
        }
        fence_async();
        bar_sync(1 + wg, 128);
        if ((tid & 127) == 0) {
            tma_store(tout, epi, nb * 256 + half * 128, mb * 128 + wg * 64);
            tma_store(tout, epi + 8192, nb * 256 + half * 128 + 64, mb * 128 + wg * 64);
            bulk_commit();
        }
    }
}
template <int NS> DEVINL void g_split_finish(const float* d, float4 (&r)[32 / NS], uint4* sk, int tile, int ks, bf16* __restrict__ out, int tid) {
    constexpr int Q = 32 / NS;
    uint4* mine = sk + ks * (16 * 256) + tid;
#pragma unroll
    for (int c = 0; c < NS; c++) {
        if (c != ks) {
#pragma unroll
            for (int q = c * Q / 2; q < (c + 1) * Q / 2; q++)
                __stcg(mine + q * 256, make_uint4(pack_bf16(d[8 * q], d[8 * q + 1]), pack_bf16(d[8 * q + 2], d[8 * q + 3]), pack_bf16(d[8 * q + 4], d[8 * q + 5]), pack_bf16(d[8 * q + 6], d[8 * q + 7])));
        } else {
#pragma unroll
            for (int q = 0; q < Q; q++) { const float* e = d + (c * Q + q) * 4; r[q].x += e[0]; r[q].y += e[1]; r[q].z += e[2]; r[q].w += e[3]; }
        }
    }
    __threadfence();
    bar_sync(3, 256);
    if (tile >= T_LATE) PT(20);
    if (tid == 0) {
        atomicAdd(&g_skcnt[tile], 1u);
        uint32_t v, n = 0;
        do {
            asm volatile("ld.acquire.gpu.global.u32 %0, [%1];" : "=r"(v) : "l"(&g_skcnt[tile]) : "memory");
            if (++n > 200000000u) __trap();
        } while (v < NS);
        if (atomicAdd(&g_skcnt[tile], 1u) == 2 * NS - 1) g_skcnt[tile] = 0u;
    }
    bar_sync(3, 256);
    if (tile >= T_LATE) PT(21);
#pragma unroll
    for (int c = 1; c < NS; c++) {
        const uint4* th = sk + (((ks + c) & (NS - 1)) * 16 + ks * (Q / 2)) * 256 + tid;
#pragma unroll
        for (int q = 0; q < Q / 2; q++) {
            const uint4 u = __ldcg(th + q * 256);
            r[2 * q].x += __uint_as_float(u.x << 16); r[2 * q].y += __uint_as_float(u.x & 0xffff0000u);
            r[2 * q].z += __uint_as_float(u.y << 16); r[2 * q].w += __uint_as_float(u.y & 0xffff0000u);
            r[2 * q + 1].x += __uint_as_float(u.z << 16); r[2 * q + 1].y += __uint_as_float(u.z & 0xffff0000u);
            r[2 * q + 1].z += __uint_as_float(u.w << 16); r[2 * q + 1].w += __uint_as_float(u.w & 0xffff0000u);
        }
    }
    const int lane = tid & 31;
    uint32_t* op = (uint32_t*)(out + ((tile >> 2) * 128 + (tid >> 5) * 16 + (lane >> 2)) * DM + (tile & 3) * 256 + ks * Q * 8 + (lane & 3) * 2);
#pragma unroll
    for (int q = 0; q < Q; q++) { op[q * 4] = pack_bf16(r[q].x, r[q].y); op[q * 4 + 4 * DM] = pack_bf16(r[q].z, r[q].w); }
}
DEVINL int g1_count(int pass) {
    return pass == 0 ? NPRE : pass == 1 ? NFULL : pass == 2 ? T_MID - NFULL : pass == 3 ? (T_MID2 - T_MID) * 4 : pass == 4 ? (T_LATE - T_MID2) * 8 : (64 - T_LATE) * 16;
}
DEVINL int g1_first(int pass) {
    const int b = blockIdx.x, n = gridDim.x;
    const int f = (pass < 2 || pass == 5) ? b : pass == 2 ? n - 1 - b : (b + n - (pass == 3 ? 16 : 32)) % n;
    return (pass == 4 && f >= 32) ? 1 << 20 : f;
}
DEVINL int g1_stride(int pass) { return pass == 4 ? 32 : (int)gridDim.x; }
DEVINL int g1_tile(int pass, int i) {
    return pass == 1 ? i : pass == 3 ? T_MID + (i >> 2) : pass == 4 ? T_MID2 + (i >> 3) : pass == 5 ? T_LATE + (i >> 4) : NFULL + i;
}
constexpr int H_EARLY = 24;

__global__ void __launch_bounds__(384, 1) g1_kernel(const __grid_constant__ G1Maps tm, bf16* __restrict__ out, const int tail) {
    extern __shared__ __align__(1024) unsigned char smem_raw[];
    const uint32_t sb = (smem_u32(smem_raw) + 1023) & ~1023u;
    const int tid = threadIdx.x, lane = tid & 31;
    const int wg = __shfl_sync(0xffffffffu, tid >> 7, 0);
    const int warp = __shfl_sync(0xffffffffu, (tid >> 5) & 3, 0);
    const uint32_t bar = sb + G_BAR;
    asm volatile("griddepcontrol.launch_dependents;");
    KT(1 + tail, 0);
    if (tail && (tid == 32 || tid == 64)) asm volatile("prefetch.tensormap [%0];" ::"l"(tid == 32 ? &tm.o : &tm.wo) : "memory");
    const int ntiles = tail ? 0 : G1_TILES;
    if (tid == 0) {
        for (int i = 0; i < G_ST; i++) { mbar_init(bar + 8 * i, 1); mbar_init(bar + 8 * (G_ST + i), 2); }
        fence_async();
    }
    __syncthreads();
    if (tail) PT(16);
    if (tail) PT(17);
    if (tail) PT(22);
    if (wg == 2) {
        asm volatile("setmaxnreg.dec.sync.aligned.u32 40;");
        if (tail) {
            const int tile = T_LATE + (blockIdx.x >> 4), k0 = ((blockIdx.x & 15) * 4 + warp) * 64;
            e_expect(bar + 8 * warp, G_STAGE);
#pragma unroll
            for (int q = 0; q < 4; q++) e_tma_load(sb + warp * G_STAGE + 16384 + q * 8192, &tm.wo, (tile & 3) * 256 + q * 64, k0, bar + 8 * warp);
            wait_count(&g_ocnt[tile >> 2], NH * 4);
            asm volatile("fence.proxy.async;" ::: "memory");
            e_tma_load(sb + warp * G_STAGE, &tm.o, k0, (tile >> 2) * 128, bar + 8 * warp);
        }
        if (warp == 0) {
            if (lane == 0) {
                int it = 0;
                for (int tile = blockIdx.x; tile < ntiles; tile += gridDim.x) {
                    const int mb = tile & 15, nb = tile >> 4;
                    for (int kb = 0; kb < 16; kb++, it++) {
                        const int st = it % G_ST;
                        mbar_wait(bar + 8 * (G_ST + st), ((it / G_ST) & 1) ^ 1);
                        const uint32_t fb = bar + 8 * st, sa = sb + st * G_STAGE;
                        mbar_expect(fb, G_STAGE);
                        tma_load(sa, &tm.x, kb * 64, mb * 128, fb);
                        tma_load(sa + 16384, &tm.wg, nb * 128, kb * 64, fb);
                        tma_load(sa + 16384 + 8192, &tm.wg, nb * 128 + 64, kb * 64, fb);
                        tma_load(sa + 16384 + 16384, &tm.wu, nb * 128, kb * 64, fb);
                        tma_load(sa + 16384 + 24576, &tm.wu, nb * 128 + 64, kb * 64, fb);
                    }
                }
                for (int pass = tail ? 5 : 0; pass < 5; pass++) {
                    for (int i = g1_first(pass); i < g1_count(pass); i += g1_stride(pass)) {
                        const int tile = g1_tile(pass, i), mb = tile >> 2, nb = tile & 3;
                        if (pass < 2) {
                            for (int kb = 0; kb < FF / 64; kb++, it++) {
                                if (kb == 0 || kb == 2 * H_EARLY) {
                                    wait_count(&g_hcnt[kb ? 16 + mb : mb], kb ? 2 * (G1_NB - H_EARLY) : 2 * H_EARLY);
                                    asm volatile("fence.proxy.async;" ::: "memory");
                                }
                                g_load_block(sb, bar, it, &tm.h, kb * 64, mb * 128, &tm.wd, nb * 256);
                            }
                        }
                        if (pass > 0) {
                            const int k0 = pass == 3 ? (i & 3) * 16 : pass == 4 ? (i & 7) * 8 : 0, k1 = pass == 3 ? k0 + 16 : pass == 4 ? k0 + 8 : HD / 64;
                            wait_count(&g_ocnt[mb], NH * 4);
                            asm volatile("fence.proxy.async;" ::: "memory");
                            for (int kb = k0; kb < k1; kb++, it++) g_load_block(sb, bar, it, &tm.o, kb * 64, mb * 128, &tm.wo, nb * 256);
                        }
                    }
                }
            }
        }
    } else {
        asm volatile("setmaxnreg.inc.sync.aligned.u32 232;");
        float d[128];
        int it = 0;
        const uint32_t epi = sb + G_EPI + wg * 16384;
        const int row = warp * 16 + ((lane >> 3) & 1) * 8 + (lane & 7);
        for (int tile = blockIdx.x; tile < ntiles; tile += gridDim.x) {
            const int mb = tile & 15, nb = tile >> 4;
            const uint32_t* gp = &g_gate[mb * 128 + wg * 64 + warp * 16 + (lane >> 2)];
            uint32_t u0 = ld_strong4(gp), u1 = ld_strong4(gp + 8);
            for (int kb = 0; kb < 16; kb++, it++) {
                if (it == (wg ? 0 : STAG)) bar_sync(4, 256);
                g_mma_block(d, sb, bar, it, wg, tid, kb == 0);
            }
            wg_wait<0>();
            for (uint32_t n = 0; u0 == 0u || u1 == 0u; n++) { u0 = ld_strong4(gp); u1 = ld_strong4(gp + 8); if (n > 20000000u) __trap(); }
            __syncwarp();
            const float s0 = 1.0f - __uint_as_float(u0), s1 = 1.0f - __uint_as_float(u1);
            if ((tid & 127) == 0) {
                mbar_arrive(bar + 8 * (G_ST + (it - 1) % G_ST));
                bulk_wait_all();
                const int pt = tile - (int)gridDim.x;
                if (pt >= 0) atomicAdd(&g_hcnt[(pt & 15) + ((pt >> 4) >= H_EARLY ? 16 : 0)], 1u);
            }
            bar_sync(1 + wg, 128);
#pragma unroll
            for (int j = 0; j < 16; j += 2) {
                uint32_t p[4];
#pragma unroll
                for (int q = 0; q < 4; q++) {
                    const int i = (j + (q >> 1)) * 4 + (q & 1) * 2;
                    const float sc = (q & 1) ? s1 : s0;
                    const float g0 = d[i], g1 = d[i + 1];
                    const float a0 = 1.0f + ex2(fminf(g0 * -1.4426950408889634f, 62.0f)), a1 = 1.0f + ex2(fminf(g1 * -1.4426950408889634f, 62.0f));
                    const float rr = rcp(a0 * a1) * sc;
                    const float h0 = (g0 * d[64 + i]) * (rr * a1);
                    const float h1 = (g1 * d[64 + i + 1]) * (rr * a0);
                    p[q] = pack_bf16(h0, h1);
                }
                const int cgp = j + (lane >> 4);
                stsm4(epi + (cgp >> 3) * 8192 + row * 128 + (((cgp & 7) ^ (row & 7)) << 4), p[0], p[1], p[2], p[3]);
            }
            fence_async();
            bar_sync(1 + wg, 128);
            if ((tid & 127) == 0) {
                tma_store(&tm.hs, epi, nb * 128, mb * 128 + wg * 64);
                tma_store(&tm.hs, epi + 8192, nb * 128 + 64, mb * 128 + wg * 64);
                bulk_commit();
            }
        }
        if ((tid & 127) == 0 && !tail) {
            bulk_wait_all();
            const int pt = blockIdx.x + (G1_TILES - 1 - blockIdx.x) / gridDim.x * gridDim.x;
            atomicAdd(&g_hcnt[(pt & 15) + ((pt >> 4) >= H_EARLY ? 16 : 0)], 1u);
        }
        for (int pass = tail ? 5 : 0; pass < 5 + tail; pass++) {
            for (int i = g1_first(pass); i < g1_count(pass); i += g1_stride(pass)) {
                const int tile = g1_tile(pass, i);
                const int nkb = pass == 0 ? FF / 64 : pass == 1 ? (FF + HD) / 64 : pass == 2 ? HD / 64 : pass == 3 ? 16 : pass == 4 ? 8 : 4;
                float4* pre = g_pre + (tile - NFULL) * (32 * 256) + tid;
                if (tail) PT(23);
                if (tail) asm volatile("prefetch.global.L2 [%0];" ::"l"(pre - tid + (i & 15) * 512 + tid * 2));
                for (int kb = 0; kb < nkb; kb++, it++) { g_mma_block(d, sb, bar, it, wg, tid, kb == 0); if (tail && kb == 0) PT(18); }
                wg_wait<0>();
                if (tail) PT(19);
                if ((tid & 127) == 0) mbar_arrive(bar + 8 * (G_ST + (it - 1) % G_ST));
                if (pass >= 2) { if ((tid & 31) == 0) wait_count(&g_pcnt[tile], 8); __syncwarp(); }
                if (pass == 0) {
#pragma unroll
                    for (int q = 0; q < 32; q++) __stcg(pre + q * 256, make_float4(d[4 * q], d[4 * q + 1], d[4 * q + 2], d[4 * q + 3]));
                    __threadfence();
                    __syncwarp();
                    if ((tid & 31) == 0) atomicAdd(&g_pcnt[tile], 1u);
                } else if (pass == 3) {
                    float4 r[8];
#pragma unroll
                    for (int q = 0; q < 8; q++) r[q] = __ldcg(pre + ((i & 3) * 8 + q) * 256);
                    g_split_finish<4>(d, r, g_sk + (tile - T_MID) * 16 * (16 * 256), tile, i & 3, out, tid);
                } else if (pass == 4) {
                    float4 r[4];
#pragma unroll
                    for (int q = 0; q < 4; q++) r[q] = __ldcg(pre + ((i & 7) * 4 + q) * 256);
                    g_split_finish<8>(d, r, g_sk + (tile - T_MID) * 16 * (16 * 256), tile, i & 7, out, tid);
                } else if (pass == 5) {
                    float4 r[2];
#pragma unroll
                    for (int q = 0; q < 2; q++) r[q] = __ldcg(pre + ((i & 15) * 2 + q) * 256);
                    g_split_finish<16>(d, r, g_sk + (tile - T_MID) * 16 * (16 * 256), tile, i & 15, out, tid);
                } else {
                    if (pass == 2) {
#pragma unroll
                        for (int q = 0; q < 32; q++) {
                            const float4 u = __ldcg(pre + q * 256); d[4 * q] += u.x; d[4 * q + 1] += u.y; d[4 * q + 2] += u.z; d[4 * q + 3] += u.w;
                            if ((q & 7) == 7) __syncwarp();
                        }
                    }
                    g_store_tile(d, &tm.out, epi, tile >> 2, tile & 3, wg, tid);
                }
            }
        }
        if ((tid & 127) == 0) bulk_wait_all();
        KT(1 + tail, 1);
        if (wg == 0) {
            uint32_t last = blockIdx.x == 0;
            if (tail) {
                if (tid == 0) sts32(bar + 64, atomicAdd(&g_ticket, 1u) == gridDim.x - 1);
                bar_sync(1, 128);
                asm volatile("ld.shared.b32 %0, [%1];" : "=r"(last) : "r"(bar + 64) : "memory");
            }
            if (last) {
                asm volatile("griddepcontrol.wait;" ::: "memory");
                if (tail) {
                    for (int i = tid; i < SEQ; i += 128) g_gate[i] = 0u;
                    if (tid < 64) g_pcnt[tid] = 0u;
                    if (tid < 32) g_hcnt[tid] = 0u;
                    if (tid < 16) g_ocnt[tid] = 0u;
                    if (tid == 0) g_ticket = 0u;
                }
            }
        }
    }
}

__device__ bf16 f_qkv[3][(SEQ + NMEM) * HD];
__device__ bf16 f_mem[NMEM * DM], f_om[NMEM * HD];

__global__ void __launch_bounds__(256) f_gemm(const bf16* __restrict__ A, const bf16* __restrict__ B, bf16* __restrict__ C, int K, int N) {
    __shared__ float sa[8][256];
    const int n = blockIdx.x * 256 + threadIdx.x, m0 = blockIdx.y * 8;
    float acc[8] = {0.f, 0.f, 0.f, 0.f, 0.f, 0.f, 0.f, 0.f};
    for (int k0 = 0; k0 < K; k0 += 256) {
        __syncthreads();
        for (int r = 0; r < 8; r++) sa[r][threadIdx.x] = __bfloat162float(A[(size_t)(m0 + r) * K + k0 + threadIdx.x]);
        __syncthreads();
        for (int k = 0; k < 256; k++) {
            const float b = __bfloat162float(B[(size_t)(k0 + k) * N + n]);
#pragma unroll
            for (int r = 0; r < 8; r++) acc[r] = fmaf(sa[r][k], b, acc[r]);
        }
    }
    for (int r = 0; r < 8; r++) C[(size_t)(m0 + r) * N + n] = __float2bfloat16(acc[r]);
}
__global__ void __launch_bounds__(32) f_gate(const bf16* __restrict__ x, const bf16* __restrict__ gate_w) {
    uint4 xv[4], gv[4];
    for (int i = 0; i < 4; i++) { xv[i] = ldg_nc((const uint4*)(x + blockIdx.x * DM) + i * 32 + threadIdx.x); gv[i] = ldg_nc((const uint4*)gate_w + i * 32 + threadIdx.x); }
    const uint32_t g = __float_as_uint(gate_row(xv, gv));
    if (threadIdx.x == 0) { g_gate[blockIdx.x] = g ? g : 0x80000000u; if (blockIdx.x < 16) g_ocnt[blockIdx.x] = NH * 4; }
}
__global__ void __launch_bounds__(128) f_attn(int s) {
    __shared__ float sq[DH], sp[NMEM + SEG];
    const int h = blockIdx.x, i = blockIdx.y, t = threadIdx.x;
    auto row = [&](int r) { return (size_t)(r < NMEM ? SEQ + r : s * SEG + r - NMEM) * HD + h * DH; };
    sq[t] = __bfloat162float(f_qkv[0][row(i) + t]);
    __syncthreads();
    if (t < NMEM + SEG) {
        float a = 0.f;
        for (int e = 0; e < DH; e++) a = fmaf(sq[e], __bfloat162float(f_qkv[1][row(t) + e]), a);
        sp[t] = (i < NMEM || i >= t) ? a * 0.08838834764831845f : -1000000000.0f;
    }
    __syncthreads();
    float m = sp[0], l = 0.f, o = 0.f;
    for (int j = 1; j < NMEM + SEG; j++) m = fmaxf(m, sp[j]);
    for (int j = 0; j < NMEM + SEG; j++) { const float p = __expf(sp[j] - m); l += p; o = fmaf(p, __bfloat162float(f_qkv[2][row(j) + t]), o); }
    if (i < NMEM) f_om[i * HD + h * DH + t] = __float2bfloat16(o / l);
    else g_O[(size_t)(s * SEG + i - NMEM) * HD + h * DH + t] = __float2bfloat16(o / l * __uint_as_float(g_gate[s * SEG + i - NMEM]));
}

typedef CUresult (*EncodeFn)(CUtensorMap*, CUtensorMapDataType, cuuint32_t, void*, const cuuint64_t*, const cuuint64_t*, const cuuint32_t*,
                             const cuuint32_t*, CUtensorMapInterleave, CUtensorMapSwizzle, CUtensorMapL2promotion, CUtensorMapFloatOOBfill);

static void make_map(EncodeFn enc, CUtensorMap* m, const void* ptr, uint64_t rows, uint64_t cols, uint32_t box_rows) {
    cuuint64_t dims[2] = {cols, rows};
    cuuint64_t strides[1] = {cols * 2};
    cuuint32_t box[2] = {64, box_rows};
    cuuint32_t es[2] = {1, 1};
    enc(m, CU_TENSOR_MAP_DATA_TYPE_BFLOAT16, 2, (void*)ptr, dims, strides, box, es, CU_TENSOR_MAP_INTERLEAVE_NONE,
        CU_TENSOR_MAP_SWIZZLE_128B, CU_TENSOR_MAP_L2_PROMOTION_L2_256B, CU_TENSOR_MAP_FLOAT_OOB_FILL_NONE);
}

extern "C" void kernel_launch(void* const* d_in, const int* in_sizes, int n_in, void* d_out, int out_size) {
    (void)in_sizes; (void)n_in; (void)out_size;
    const bf16* x = (const bf16*)d_in[0];
    const bf16* mem0 = (const bf16*)d_in[1];
    const bf16* gate_w = (const bf16*)d_in[11];
    static EncodeFn enc = nullptr;
    static int n_sm = 0;
    static void *pO = nullptr, *pH = nullptr, *pQ = nullptr, *pM = nullptr, *pOm = nullptr;
    static int n_clusters = 0;
    if (!enc) {
        void* fn = nullptr;
        cudaDriverEntryPointQueryResult qr;
        cudaGetDriverEntryPoint("cuTensorMapEncodeTiled", &fn, cudaEnableDefault, &qr);
        enc = (EncodeFn)fn;
        cudaDeviceGetAttribute(&n_sm, cudaDevAttrMultiProcessorCount, 0);
        cudaFuncSetAttribute(r_kernel, cudaFuncAttributeMaxDynamicSharedMemorySize, R_SMEM);
        cudaFuncSetAttribute(g1_kernel, cudaFuncAttributeMaxDynamicSharedMemorySize, G_SMEM);
        cudaGetSymbolAddress(&pO, g_O);
        cudaGetSymbolAddress(&pH, g_H);
        cudaGetSymbolAddress(&pQ, f_qkv);
        cudaGetSymbolAddress(&pM, f_mem);
        cudaGetSymbolAddress(&pOm, f_om);
        cudaLaunchConfig_t cfg = {};
        cfg.gridDim = dim3(96); cfg.blockDim = dim3(384); cfg.dynamicSmemBytes = R_SMEM;
        cudaLaunchAttribute at[1];
        at[0].id = cudaLaunchAttributeClusterDimension; at[0].val.clusterDim.x = 3; at[0].val.clusterDim.y = 1; at[0].val.clusterDim.z = 1;
        cfg.attrs = at; cfg.numAttrs = 1;
        if (cudaOccupancyMaxActiveClusters(&n_clusters, r_kernel, &cfg) != cudaSuccess) { n_clusters = 0; (void)cudaGetLastError(); }
    }
    RMaps rm; G1Maps m1;
    make_map(enc, &rm.x, x, SEQ, DM, 32);
    for (int i = 0; i < 3; i++) make_map(enc, &rm.w[i], d_in[2 + i], DM, HD, 64);
    make_map(enc, &rm.wo, d_in[5], HD, DM, 128);
    make_map(enc, &rm.o, pO, SEQ, HD, 16);
    make_map(enc, &m1.x, x, SEQ, DM, 128);
    make_map(enc, &m1.wg, d_in[8], DM, FF, 64);
    make_map(enc, &m1.wu, d_in[9], DM, FF, 64);
    make_map(enc, &m1.hs, pH, SEQ, FF, 64);
    make_map(enc, &m1.o, pO, SEQ, HD, 128);
    make_map(enc, &m1.h, pH, SEQ, FF, 128);
    make_map(enc, &m1.wo, d_in[5], HD, DM, 64);
    make_map(enc, &m1.wd, d_in[10], FF, DM, 64);
    make_map(enc, &m1.out, d_out, SEQ, DM, 64);

    cudaStream_t st = cudaStreamPerThread;
    if (n_clusters < NH) {
        bf16* qkv = (bf16*)pQ;
        const size_t plane = (size_t)(SEQ + NMEM) * HD;
        f_gate<<<SEQ, 32, 0, st>>>(x, gate_w);
        for (int i = 0; i < 3; i++) f_gemm<<<dim3(HD / 256, SEQ / 8), 256, 0, st>>>(x, (const bf16*)d_in[2 + i], qkv + i * plane, DM, HD);
        for (int s = 0; s < NSEG; s++) {
            for (int i = 0; i < 3; i++)
                f_gemm<<<dim3(HD / 256, 1), 256, 0, st>>>(s ? (const bf16*)pM : mem0, (const bf16*)d_in[2 + i], qkv + i * plane + (size_t)SEQ * HD, DM, HD);
            f_attn<<<dim3(NH, NMEM + SEG), 128, 0, st>>>(s);
            f_gemm<<<dim3(DM / 256, 1), 256, 0, st>>>((const bf16*)pOm, (const bf16*)d_in[5], (bf16*)pM, HD, DM);
        }
    } else {
        cudaLaunchConfig_t cfg = {};
        cfg.gridDim = dim3(96); cfg.blockDim = dim3(384); cfg.dynamicSmemBytes = R_SMEM; cfg.stream = st;
        cudaLaunchAttribute at[1];
        at[0].id = cudaLaunchAttributeClusterDimension; at[0].val.clusterDim.x = 3; at[0].val.clusterDim.y = 1; at[0].val.clusterDim.z = 1;
        cfg.attrs = at; cfg.numAttrs = 1;
        cudaLaunchKernelEx(&cfg, r_kernel, rm, mem0, x, gate_w);
    }
    {
        cudaLaunchConfig_t cfg = {};
        cfg.gridDim = dim3(n_sm - 96 > 32 ? n_sm - 96 : 32); cfg.blockDim = dim3(384); cfg.dynamicSmemBytes = G_SMEM; cfg.stream = st;
        cudaLaunchAttribute at[1];
        at[0].id = cudaLaunchAttributeProgrammaticStreamSerialization; at[0].val.programmaticStreamSerializationAllowed = 1;
        cfg.attrs = at; cfg.numAttrs = n_clusters < NH ? 0 : 1;
        cudaLaunchKernelEx(&cfg, g1_kernel, m1, (bf16*)d_out, 0);
    }
    {
        cudaLaunchConfig_t cfg = {};
        cfg.gridDim = dim3((64 - T_LATE) * 16); cfg.blockDim = dim3(384); cfg.dynamicSmemBytes = G_SMEM; cfg.stream = st;
        cudaLaunchAttribute at[1];
        at[0].id = cudaLaunchAttributeProgrammaticStreamSerialization; at[0].val.programmaticStreamSerializationAllowed = 1;
        cfg.attrs = at; cfg.numAttrs = 1;
        cudaLaunchKernelEx(&cfg, g1_kernel, m1, (bf16*)d_out, 1);
    }
}
```

```cpp
#include <cuda_runtime.h>
#include <cuda_bf16.h>
#include <cuda.h>
#include <stdint.h>

typedef __nv_bfloat16 bf16;

constexpr int SEQ = 2048, DM = 1024, NH = 32, DH = 128, NMEM = 8, SEG = 32, NSEG = 64, FF = 3584;
constexpr int HD = NH * DH;

__device__ bf16 g_O[SEQ * HD];
__device__ bf16 g_H[SEQ * FF];
__device__ uint32_t g_gate[SEQ];
__device__ uint32_t g_part[4][128 * 32 * 32];
__device__ uint32_t g_mem[4][DM * 4];
#define TLATE 52
constexpr int NFULL = 36, T_MID = 44, T_MID2 = 48, T_LATE = TLATE;
constexpr int NPRE = 64 - NFULL;
__device__ float4 g_pre[NPRE * 32 * 256];
__device__ uint4 g_sk[(64 - T_MID) * 8 * 16 * 256];
__device__ uint32_t g_skcnt[64], g_pcnt[64], g_ticket;
__device__ uint32_t g_hcnt[32], g_ocnt[16];
#define KT(k, i)
#define PT(i)

#define DEVINL __device__ __forceinline__

DEVINL uint32_t smem_u32(const void* p) { return (uint32_t)__cvta_generic_to_shared(p); }
DEVINL void mbar_init(uint32_t bar, uint32_t cnt) { asm volatile("mbarrier.init.shared::cta.b64 [%0], %1;" ::"r"(bar), "r"(cnt) : "memory"); }
DEVINL void mbar_arrive(uint32_t bar) { asm volatile("mbarrier.arrive.shared::cta.b64 _, [%0];" ::"r"(bar) : "memory"); }
DEVINL void mbar_expect(uint32_t bar, uint32_t bytes) { asm volatile("mbarrier.arrive.expect_tx.shared::cta.b64 _, [%0], %1;" ::"r"(bar), "r"(bytes) : "memory"); }
DEVINL void mbar_arrive_remote(uint32_t cbar) { asm volatile("mbarrier.arrive.relaxed.cluster.shared::cluster.b64 _, [%0];" ::"r"(cbar) : "memory"); }
DEVINL bool mbar_try(uint32_t bar, uint32_t par) {
    uint32_t ok;
    asm volatile("{ .reg .pred p; mbarrier.try_wait.parity.shared::cta.b64 p, [%1], %2; selp.u32 %0, 1, 0, p; }" : "=r"(ok) : "r"(bar), "r"(par) : "memory");
    return ok;
}
DEVINL void mbar_wait(uint32_t bar, uint32_t par) {
    uint32_t n = 0;
    while (!mbar_try(bar, par)) { if (++n > 50000000u) __trap(); }
}
DEVINL uint32_t mapa(uint32_t a, uint32_t r) { uint32_t o; asm volatile("mapa.shared::cluster.u32 %0, %1, %2;" : "=r"(o) : "r"(a), "r"(r)); return o; }
DEVINL void fence_async() { asm volatile("fence.proxy.async.shared::cta;" ::: "memory"); }
DEVINL void bar_sync(int id, int n) { asm volatile("bar.sync %0, %1;" ::"r"(id), "r"(n) : "memory"); }
DEVINL void cluster_sync() { asm volatile("barrier.cluster.arrive.aligned; barrier.cluster.wait.aligned;" ::: "memory"); }
DEVINL void tma_load(uint32_t dst, const CUtensorMap* tm, int c0, int c1, uint32_t bar) {
    asm volatile("cp.async.bulk.tensor.2d.shared::cluster.global.mbarrier::complete_tx::bytes [%0], [%1, {%3, %4}], [%2];"
                 ::"r"(dst), "l"(tm), "r"(bar), "r"(c0), "r"(c1) : "memory");
}
DEVINL void tma_prefetch(const CUtensorMap* tm, int c0, int c1) {
    asm volatile("cp.async.bulk.prefetch.tensor.2d.L2.global [%0, {%1, %2}];" ::"l"(tm), "r"(c0), "r"(c1) : "memory");
}
DEVINL void tma_store(const CUtensorMap* tm, uint32_t src, int c0, int c1) {
    asm volatile("cp.async.bulk.tensor.2d.global.shared::cta.bulk_group [%0, {%2, %3}], [%1];" ::"l"(tm), "r"(src), "r"(c0), "r"(c1) : "memory");
}
DEVINL void bulk_commit() { asm volatile("cp.async.bulk.commit_group;" ::: "memory"); }
DEVINL void bulk_wait_read() { asm volatile("cp.async.bulk.wait_group.read 0;" ::: "memory"); }
DEVINL void bulk_wait_all() { asm volatile("cp.async.bulk.wait_group 0;" ::: "memory"); }
DEVINL void bulk_s2s(uint32_t cdst, uint32_t src, uint32_t bytes, uint32_t cbar) {
    asm volatile("cp.async.bulk.shared::cluster.shared::cta.mbarrier::complete_tx::bytes [%0], [%1], %2, [%3];" ::"r"(cdst), "r"(src), "r"(bytes), "r"(cbar) : "memory");
}
DEVINL void st_async16(uint32_t cdst, uint4 v, uint32_t cbar) {
    asm volatile("st.async.shared::cluster.mbarrier::complete_tx::bytes.v4.b32 [%0], {%1,%2,%3,%4}, [%5];" ::"r"(cdst), "r"(v.x), "r"(v.y), "r"(v.z), "r"(v.w), "r"(cbar) : "memory");
}
DEVINL uint64_t mkdesc(uint32_t addr, uint32_t lbo, uint32_t sbo, uint32_t swz) {
    return (uint64_t)((addr & 0x3FFFF) >> 4) | ((uint64_t)(lbo >> 4) << 16) | ((uint64_t)(sbo >> 4) << 32) | ((uint64_t)swz << 62);
}
constexpr uint32_t SB0 = 1024;
__host__ __device__ constexpr uint64_t cdesc(uint32_t off, uint32_t lbo, uint32_t sbo, uint32_t swz) {
    return (uint64_t)(((SB0 + off) & 0x3FFFF) >> 4) | ((uint64_t)(lbo >> 4) << 16) | ((uint64_t)(sbo >> 4) << 32) | ((uint64_t)swz << 62);
}
DEVINL float rcp(float x) { float y; asm("rcp.approx.ftz.f32 %0, %1;" : "=f"(y) : "f"(x)); return y; }
DEVINL float ex2(float x) { float y; asm("ex2.approx.ftz.f32 %0, %1;" : "=f"(y) : "f"(x)); return y; }
#define OPAQUE(x) asm volatile("" : "+r"(x))
DEVINL void wg_fence() { asm volatile("wgmma.fence.sync.aligned;" ::: "memory"); }
DEVINL void wg_commit() { asm volatile("wgmma.commit_group.sync.aligned;" ::: "memory"); }
template <int N> DEVINL void wg_wait() { asm volatile("wgmma.wait_group.sync.aligned %0;" ::"n"(N) : "memory"); }
DEVINL uint32_t pack_bf16(float lo, float hi) { uint32_t r; asm("cvt.rn.bf16x2.f32 %0, %1, %2;" : "=r"(r) : "f"(hi), "f"(lo)); return r; }
DEVINL void ldsm4(uint32_t* r, uint32_t a) { asm volatile("ldmatrix.sync.aligned.m8n8.x4.shared.b16 {%0,%1,%2,%3}, [%4];" : "=r"(r[0]), "=r"(r[1]), "=r"(r[2]), "=r"(r[3]) : "r"(a) : "memory"); }
DEVINL void ldsm4t(uint32_t* r, uint32_t a) { asm volatile("ldmatrix.sync.aligned.m8n8.x4.trans.shared.b16 {%0,%1,%2,%3}, [%4];" : "=r"(r[0]), "=r"(r[1]), "=r"(r[2]), "=r"(r[3]) : "r"(a) : "memory"); }
DEVINL void ldsm4_if(uint32_t* r, uint32_t a, int c) { asm volatile("{ .reg .pred p; setp.ne.s32 p, %5, 0; @p ldmatrix.sync.aligned.m8n8.x4.shared.b16 {%0,%1,%2,%3}, [%4]; }" : "+r"(r[0]), "+r"(r[1]), "+r"(r[2]), "+r"(r[3]) : "r"(a), "r"(c) : "memory"); }
DEVINL void ldsm4t_if(uint32_t* r, uint32_t a, int c) { asm volatile("{ .reg .pred p; setp.ne.s32 p, %5, 0; @p ldmatrix.sync.aligned.m8n8.x4.trans.shared.b16 {%0,%1,%2,%3}, [%4]; }" : "+r"(r[0]), "+r"(r[1]), "+r"(r[2]), "+r"(r[3]) : "r"(a), "r"(c) : "memory"); }
DEVINL void stsm4(uint32_t a, uint32_t r0, uint32_t r1, uint32_t r2, uint32_t r3) { asm volatile("stmatrix.sync.aligned.m8n8.x4.shared.b16 [%0], {%1,%2,%3,%4};" ::"r"(a), "r"(r0), "r"(r1), "r"(r2), "r"(r3) : "memory"); }
DEVINL void stsm4t(uint32_t a, uint32_t r0, uint32_t r1, uint32_t r2, uint32_t r3) { asm volatile("stmatrix.sync.aligned.m8n8.x4.trans.shared.b16 [%0], {%1,%2,%3,%4};" ::"r"(a), "r"(r0), "r"(r1), "r"(r2), "r"(r3) : "memory"); }
DEVINL void sts32(uint32_t a, uint32_t v) { asm volatile("st.shared.b32 [%0], %1;" ::"r"(a), "r"(v) : "memory"); }
DEVINL void sts128(uint32_t a, uint4 v) { asm volatile("st.shared.v4.b32 [%0], {%1,%2,%3,%4};" ::"r"(a), "r"(v.x), "r"(v.y), "r"(v.z), "r"(v.w) : "memory"); }
DEVINL uint4 lds128(uint32_t a) { uint4 v; asm volatile("ld.shared.v4.b32 {%0,%1,%2,%3}, [%4];" : "=r"(v.x), "=r"(v.y), "=r"(v.z), "=r"(v.w) : "r"(a) : "memory"); return v; }
DEVINL uint4 ld_strong16(const void* p) { uint4 v; asm volatile("ld.relaxed.gpu.global.v4.u32 {%0,%1,%2,%3}, [%4];" : "=r"(v.x), "=r"(v.y), "=r"(v.z), "=r"(v.w) : "l"(p) : "memory"); return v; }
DEVINL void st_strong8(void* p, uint32_t a, uint32_t b) { asm volatile("st.relaxed.gpu.global.v2.u32 [%0], {%1,%2};" ::"l"(p), "r"(a), "r"(b) : "memory"); }
DEVINL void st_strong4(void* p, uint32_t a) { asm volatile("st.relaxed.gpu.global.u32 [%0], %1;" ::"l"(p), "r"(a) : "memory"); }
DEVINL void st_strong16(void* p, uint4 v) { asm volatile("st.relaxed.gpu.global.v4.u32 [%0], {%1,%2,%3,%4};" ::"l"(p), "r"(v.x), "r"(v.y), "r"(v.z), "r"(v.w) : "memory"); }
DEVINL uint32_t pack_nz(float lo, float hi) { uint32_t r = pack_bf16(lo, hi); return r == 0u ? 0x8000u : r; }
DEVINL uint32_t min4(uint4 v, uint32_t m) { return __vimin3_u32(__vimin3_u32(v.x, v.y, m), v.z, v.w); }
DEVINL void mma16816(float* d, uint32_t a0, uint32_t a1, uint32_t a2, uint32_t a3, uint32_t b0, uint32_t b1) {
    asm volatile("mma.sync.aligned.m16n8k16.row.col.f32.bf16.bf16.f32 {%0,%1,%2,%3}, {%4,%5,%6,%7}, {%8,%9}, {%0,%1,%2,%3};"
                 : "+f"(d[0]), "+f"(d[1]), "+f"(d[2]), "+f"(d[3]) : "r"(a0), "r"(a1), "r"(a2), "r"(a3), "r"(b0), "r"(b1));
}
DEVINL void mma1688(float* d, uint32_t a0, uint32_t a1, uint32_t b0) {
    asm volatile("mma.sync.aligned.m16n8k8.row.col.f32.bf16.bf16.f32 {%0,%1,%2,%3}, {%4,%5}, {%6}, {%0,%1,%2,%3};"
                 : "+f"(d[0]), "+f"(d[1]), "+f"(d[2]), "+f"(d[3]) : "r"(a0), "r"(a1), "r"(b0));
}
template <int TA, int TB> DEVINL void wg_ss8(float* d, uint64_t da, uint64_t db, int sc) {
    asm volatile("{ .reg .pred p; setp.ne.b32 p, %6, 0; wgmma.mma_async.sync.aligned.m64n8k16.f32.bf16.bf16 {%0,%1,%2,%3}, %4, %5, p, 1, 1, %7, %8; }"
                 : "+f"(d[0]), "+f"(d[1]), "+f"(d[2]), "+f"(d[3]) : "l"(da), "l"(db), "r"(sc), "n"(TA), "n"(TB));
}
template <int TB> DEVINL void wg_rs8(float* d, const uint32_t* a, uint64_t db, int sc) {
    asm volatile("{ .reg .pred p; setp.ne.b32 p, %9, 0; wgmma.mma_async.sync.aligned.m64n8k16.f32.bf16.bf16 {%0,%1,%2,%3}, {%4,%5,%6,%7}, %8, p, 1, 1, %10; }"
                 : "+f"(d[0]), "+f"(d[1]), "+f"(d[2]), "+f"(d[3]) : "r"(a[0]), "r"(a[1]), "r"(a[2]), "r"(a[3]), "l"(db), "r"(sc), "n"(TB));
}
#define ACC16(d) "+f"(d[0]), "+f"(d[1]), "+f"(d[2]), "+f"(d[3]), "+f"(d[4]), "+f"(d[5]), "+f"(d[6]), "+f"(d[7]), "+f"(d[8]), "+f"(d[9]), "+f"(d[10]), "+f"(d[11]), "+f"(d[12]), "+f"(d[13]), "+f"(d[14]), "+f"(d[15])
template <int TA> DEVINL void wg_ss32(float* d, uint64_t da, uint64_t db, int sc) {
    asm volatile("{ .reg .pred p; setp.ne.b32 p, %18, 0; wgmma.mma_async.sync.aligned.m64n32k16.f32.bf16.bf16 {%0,%1,%2,%3,%4,%5,%6,%7,%8,%9,%10,%11,%12,%13,%14,%15}, %16, %17, p, 1, 1, %19, 0; }"
                 : ACC16(d) : "l"(da), "l"(db), "r"(sc), "n"(TA));
}
DEVINL void wg_rs32(float* d, const uint32_t* a, uint64_t db, int sc) {
    asm volatile("{ .reg .pred p; setp.ne.b32 p, %21, 0; wgmma.mma_async.sync.aligned.m64n32k16.f32.bf16.bf16 {%0,%1,%2,%3,%4,%5,%6,%7,%8,%9,%10,%11,%12,%13,%14,%15}, {%16,%17,%18,%19}, %20, p, 1, 1, 0; }"
                 : ACC16(d) : "r"(a[0]), "r"(a[1]), "r"(a[2]), "r"(a[3]), "l"(db), "r"(sc));
}
DEVINL void wg_ss40(float* d, uint64_t da, uint64_t db, int sc) {
    asm volatile("{ .reg .pred p; setp.ne.b32 p, %22, 0; wgmma.mma_async.sync.aligned.m64n40k16.f32.bf16.bf16 {%0,%1,%2,%3,%4,%5,%6,%7,%8,%9,%10,%11,%12,%13,%14,%15,%16,%17,%18,%19}, %20, %21, p, 1, 1, 1, 1; }"
                 : ACC16(d), "+f"(d[16]), "+f"(d[17]), "+f"(d[18]), "+f"(d[19]) : "l"(da), "l"(db), "r"(sc));
}
#define A8(d, o) "+f"(d[o]), "+f"(d[o + 1]), "+f"(d[o + 2]), "+f"(d[o + 3]), "+f"(d[o + 4]), "+f"(d[o + 5]), "+f"(d[o + 6]), "+f"(d[o + 7])
#define A32(d, o) A8(d, o), A8(d, o + 8), A8(d, o + 16), A8(d, o + 24)
DEVINL void wg_ss256(float* d, uint64_t da, uint64_t db, int sc) {
    asm volatile(
        "{ .reg .pred p; setp.ne.b32 p, %130, 0;\n"
        "wgmma.mma_async.sync.aligned.m64n256k16.f32.bf16.bf16 {"
        "%0,%1,%2,%3,%4,%5,%6,%7,%8,%9,%10,%11,%12,%13,%14,%15,%16,%17,%18,%19,%20,%21,%22,%23,%24,%25,%26,%27,%28,%29,%30,%31,"
        "%32,%33,%34,%35,%36,%37,%38,%39,%40,%41,%42,%43,%44,%45,%46,%47,%48,%49,%50,%51,%52,%53,%54,%55,%56,%57,%58,%59,%60,%61,%62,%63,"
        "%64,%65,%66,%67,%68,%69,%70,%71,%72,%73,%74,%75,%76,%77,%78,%79,%80,%81,%82,%83,%84,%85,%86,%87,%88,%89,%90,%91,%92,%93,%94,%95,"
        "%96,%97,%98,%99,%100,%101,%102,%103,%104,%105,%106,%107,%108,%109,%110,%111,%112,%113,%114,%115,%116,%117,%118,%119,%120,%121,%122,%123,%124,%125,%126,%127"
        "}, %128, %129, p, 1, 1, 0, 1; }"
        : A32(d, 0), A32(d, 32), A32(d, 64), A32(d, 96) : "l"(da), "l"(db), "r"(sc));
}

DEVINL float gate_row(const uint4 (&xv)[4], const uint4 (&gv)[4]) {
    float acc = 0.f;
#pragma unroll
    for (int i = 0; i < 4; i++) {
        const uint32_t xa[4] = {xv[i].x, xv[i].y, xv[i].z, xv[i].w}, ga[4] = {gv[i].x, gv[i].y, gv[i].z, gv[i].w};
#pragma unroll
        for (int e = 0; e < 4; e++) {
            acc = fmaf(__uint_as_float(xa[e] << 16), __uint_as_float(ga[e] << 16), acc);
            acc = fmaf(__uint_as_float(xa[e] & 0xffff0000u), __uint_as_float(ga[e] & 0xffff0000u), acc);
        }
    }
#pragma unroll
    for (int o = 16; o > 0; o >>= 1) acc += __shfl_xor_sync(0xffffffffu, acc, o);
    return 1.0f / (1.0f + __expf(-acc));
}
DEVINL uint4 ldg_nc(const void* p) { uint4 v; asm volatile("ld.global.nc.v4.u32 {%0,%1,%2,%3}, [%4];" : "=r"(v.x), "=r"(v.y), "=r"(v.z), "=r"(v.w) : "l"(p) : "memory"); return v; }
DEVINL uint32_t ld_strong4(const void* p) { uint32_t v; asm volatile("ld.relaxed.gpu.global.u32 %0, [%1];" : "=r"(v) : "l"(p) : "memory"); return v; }
DEVINL void wait_count(const uint32_t* p, uint32_t want) {
    uint32_t v, n = 0;
    while (true) {
        asm volatile("ld.acquire.gpu.global.u32 %0, [%1];" : "=r"(v) : "l"(p) : "memory");
        if (v >= want) break;
        __nanosleep(100);
        if (++n > 20000000u) __trap();
    }
}

constexpr int KR = 44;
constexpr int KS = 64 - KR;
constexpr int R_W = 0;
constexpr int R_WO = KS * 4096;
constexpr int R_QX = R_WO + 65536;
constexpr int R_RING = R_WO + 98304;
constexpr int R_K = R_RING + 24576;
constexpr int R_V = R_K + 10240;
constexpr int R_QM = R_V + 10240;
constexpr int R_O = R_QM + 2048;
constexpr int R_BAR = R_O + 2048;
constexpr int R_G = R_BAR + 256 + 512 + 256 + 128;
constexpr int R_Z = R_G + 256;
constexpr int R_SMEM = R_Z + 1024;
enum { B_FULL = 0, B_EMPTY = 5, B_MEM = 8, B_HOP1 = 12, B_XT, B_TFREE, B_O, B_AFREE0, B_AFREE1, B_PRO0, B_PRO1, B_XRECV, B_XDONE, B_HOPV };
#define D2_BASE 900
#define D2_STEP 200
#define DQ 1700
#define PVD 400
#define ELD 700
constexpr int QD = 3;

DEVINL uint32_t clk32() { uint32_t c_; asm volatile("mov.u32 %0, %%clock;" : "=r"(c_)); return c_; }
DEVINL void spin_until(uint32_t t) { while ((uint32_t)(t - clk32() - 1u) < 100000u) {} }
#define PROF(i)
#define PROF2(i)
#define PROF3(i, val)
DEVINL void e_arrive(uint32_t bar) { asm volatile("{ .reg .pred p; elect.sync _|p, 0xffffffff; @p mbarrier.arrive.shared::cta.b64 _, [%0]; }" ::"r"(bar) : "memory"); }
DEVINL void e_arrive_remote(uint32_t cbar) { asm volatile("{ .reg .pred p; elect.sync _|p, 0xffffffff; @p mbarrier.arrive.relaxed.cluster.shared::cluster.b64 _, [%0]; }" ::"r"(cbar) : "memory"); }
DEVINL void e_count(uint32_t* p) { asm volatile("{ .reg .pred p; elect.sync _|p, 0xffffffff; @p red.relaxed.gpu.global.add.u32 [%0], 1; }" ::"l"(p) : "memory"); }
DEVINL void e_expect(uint32_t bar, uint32_t bytes) { asm volatile("{ .reg .pred p; elect.sync _|p, 0xffffffff; @p mbarrier.arrive.expect_tx.shared::cta.b64 _, [%0], %1; }" ::"r"(bar), "r"(bytes) : "memory"); }
DEVINL void e_tma_load(uint32_t dst, const CUtensorMap* tm, int c0, int c1, uint32_t bar) {
    asm volatile("{ .reg .pred p; elect.sync _|p, 0xffffffff; @p cp.async.bulk.tensor.2d.shared::cluster.global.mbarrier::complete_tx::bytes [%0], [%1, {%3, %4}], [%2]; }"
                 ::"r"(dst), "l"(tm), "r"(bar), "r"(c0), "r"(c1) : "memory");
}
DEVINL void e_tma_store(const CUtensorMap* tm, uint32_t src, int c0, int c1) {
    asm volatile("{ .reg .pred p; elect.sync _|p, 0xffffffff; @p cp.async.bulk.tensor.2d.global.shared::cta.bulk_group [%0, {%2, %3}], [%1]; }" ::"l"(tm), "r"(src), "r"(c0), "r"(c1) : "memory");
}
DEVINL void e_bulk_s2g(void* dst, uint32_t src, uint32_t bytes) {
    asm volatile("{ .reg .pred p; elect.sync _|p, 0xffffffff; @p cp.async.bulk.global.shared::cta.bulk_group [%0], [%1], %2; }" ::"l"(dst), "r"(src), "r"(bytes) : "memory");
}
DEVINL void e_bulk_s2s(uint32_t cdst, uint32_t src, uint32_t bytes, uint32_t cbar) {
    asm volatile("{ .reg .pred p; elect.sync _|p, 0xffffffff; @p cp.async.bulk.shared::cluster.shared::cta.mbarrier::complete_tx::bytes [%0], [%1], %2, [%3]; }" ::"r"(cdst), "r"(src), "r"(bytes), "r"(cbar) : "memory");
}

template <int N> DEVINL uint32_t poll_set(uint4 (&v)[N], const uint32_t* rp, int stride) {
#pragma unroll
    for (int i = 0; i < N; i++) v[i] = ld_strong16(rp + i * stride);
    uint32_t n = 0;
    while (true) {
        uint32_t m = 0xffffffffu;
#pragma unroll
        for (int i = 0; i < N; i++) m = min4(v[i], m);
        if (__all_sync(0xffffffffu, m != 0u)) return n;
#pragma unroll
        for (int i = 0; i < N; i++)
            asm volatile("{ .reg .pred p; setp.eq.u32 p, %5, 0; @p ld.relaxed.gpu.global.v4.u32 {%0,%1,%2,%3}, [%4]; }"
                         : "+r"(v[i].x), "+r"(v[i].y), "+r"(v[i].z), "+r"(v[i].w) : "l"(rp + i * stride), "r"(min4(v[i], 0xffffffffu)) : "memory");
        if (++n > 5000000u) __trap();
    }
}

struct RMaps { CUtensorMap x, w[3], wo, o; };
#define KC(c) ((c) * 64)

__host__ __device__ constexpr int xo(int i) { return i < 10 ? ((i & 1) ? i / 2 : 11 + i / 2) : i - 5; }
#define XC(i) (xo(i) * 64)
DEVINL void x_load_pair(uint32_t dst, const CUtensorMap* tmx, int h, int p, int seg, uint32_t fbar) {
    e_expect(fbar, 8192);
    e_tma_load(dst, tmx, XC(2 * p), seg * SEG, fbar);
    e_tma_load(dst + 4096, tmx, XC(2 * p + 1), seg * SEG, fbar);
}
__host__ __device__ constexpr int wo_tile(int role, int i) {
    return role == 0 ? (i < 2 ? 8 + i : 12 + i) : (i < 4 ? (i >> 1) * 4 : 10) + (role - 1) * 2 + (i & 1);
}

template <int NT> DEVINL void wo_phase(uint32_t sb, int tb, uint32_t* pp, uint32_t obar, uint32_t opar) {
    const int lane = tb & 31, krow = (lane & 7) + ((lane >> 4) << 3), chunk = ((tb >> 5) & 3) * 2 + ((lane >> 3) & 1);
    uint32_t wa = sb + R_WO + (tb >> 7) * 16384 + krow * 128 + ((chunk ^ (krow & 7)) << 4);
    uint32_t af[4][4], of[4][4];
#pragma unroll
    for (int g = 0; g < 4; g++) ldsm4t(af[g], wa + g * 2048);
    mbar_wait(obar, opar);
#pragma unroll
    for (int g = 0; g < 4; g++) ldsm4t(of[g], sb + R_O + g * 512 + lane * 16);
#pragma unroll 1
    for (int i = 0; i < NT; i++) {
        float w0[4] = {0.f, 0.f, 0.f, 0.f}, w1[4] = {0.f, 0.f, 0.f, 0.f};
        const int more = NT - 1 - i, yes = NT - i;
        mma16816(w0, af[0][0], af[0][1], af[0][2], af[0][3], of[0][0], of[0][1]);
        ldsm4t_if(af[0], wa + 4 * 2048, yes);
        mma16816(w1, af[1][0], af[1][1], af[1][2], af[1][3], of[0][2], of[0][3]);
        ldsm4t_if(af[1], wa + 5 * 2048, yes);
        mma16816(w0, af[2][0], af[2][1], af[2][2], af[2][3], of[1][0], of[1][1]);
        ldsm4t_if(af[2], wa + 6 * 2048, yes);
        mma16816(w1, af[3][0], af[3][1], af[3][2], af[3][3], of[1][2], of[1][3]);
        ldsm4t_if(af[3], wa + 7 * 2048, yes);
        wa += 32768;
        mma16816(w0, af[0][0], af[0][1], af[0][2], af[0][3], of[2][0], of[2][1]);
        ldsm4t_if(af[0], wa, more);
        mma16816(w1, af[1][0], af[1][1], af[1][2], af[1][3], of[2][2], of[2][3]);
        ldsm4t_if(af[1], wa + 2048, more);
        mma16816(w0, af[2][0], af[2][1], af[2][2], af[2][3], of[3][0], of[3][1]);
        ldsm4t_if(af[2], wa + 2 * 2048, more);
        mma16816(w1, af[3][0], af[3][1], af[3][2], af[3][3], of[3][2], of[3][3]);
        ldsm4t_if(af[3], wa + 3 * 2048, more);
        st_strong4(pp, pack_nz(w0[0] + w1[0], w0[1] + w1[1]));
        st_strong4(pp + 1024, pack_nz(w0[2] + w1[2], w0[3] + w1[3]));
        pp += (NT == 3 && i == 0) ? 4 * 8192 : 6 * 8192;
    }
}

template <uint32_t role> DEVINL void r_big(const RMaps& tm, const int wid) {
    extern __shared__ __align__(1024) unsigned char smem_raw[];
    const uint32_t sb = smem_u32(smem_raw);
    const uint32_t bar = sb + R_BAR;
    const int tid = threadIdx.x;
    int h; asm("mov.u32 %0, %%clusterid.x;" : "=r"(h));
        uint32_t a[KR][4];
        {
            const int lane = tid & 31;
            const int krow = (lane & 7) + ((lane >> 4) << 3);
            const int chunk = (wid & 3) * 2 + ((lane >> 3) & 1);
            const uint32_t la = sb + (wid >> 2) * 8192 + krow * 128 + ((chunk ^ (krow & 7)) << 4);
            const CUtensorMap* tw = &tm.w[role];
#pragma unroll
            for (int b = 0; b < KR / 4; b++) {
                mbar_wait(sb + R_O + 8 * b, 0);
                if (b == 0) PT(0);
#pragma unroll
                for (int k = 0; k < 4; k++) ldsm4t(a[b * 4 + k], la + b * 16384 + k * 2048);
                bar_sync(1, 256);
                if (wid == (b & 7)) {
                    fence_async();
                    if (b < 5) {
#pragma unroll
                        for (int q = 2 * b; q < 2 * b + 2; q++) e_tma_load(sb + R_W + q * 8192, tw, h * DH + (q / 5) * 64, KC(KR / 4 + q % 5), bar + 8 * B_PRO1);
                    } else if (b - 5 < (role == 0 ? 4 : 6)) {
                        e_tma_load(sb + R_WO + (b - 5) * 16384, &tm.wo, wo_tile(role, b - 5) * 64, h * DH, bar + 8 * B_PRO0);
                    }
                }
            }
        }
        constexpr uint32_t e0 = role == 0 ? R_QX + 16384 : R_K + 2048, e1 = role == 0 ? R_QX + 24576 : R_V + 2048;
        if (wid == 6) x_load_pair(sb + e0, &tm.x, h, 3, 0, bar + 8 * (B_FULL + 3));
        if (wid == 7) x_load_pair(sb + e1, &tm.x, h, 4, 0, bar + 8 * (B_FULL + 4));
        PT(1);
        mbar_wait(bar + 8 * B_PRO1, 0);
        PT(2);

        constexpr uint64_t dW0 = cdesc(R_W, 1024, 1024, 1);
        constexpr uint64_t dM = cdesc(R_RING, 128, 128, 0);
        constexpr uint64_t dX = cdesc(R_RING, 16, 1024, 1);
        constexpr uint64_t dX0 = cdesc(0, 16, 1024, 1);
        int tb = tid;
        int wq = wid;

        for (int seg = 0; seg < NSEG; seg++) {
            {
            const int s = seg - 1; (void)s;
            float d[16];
            OPAQUE(wq);
            const uint64_t dW = dW0 + (uint64_t)((wq >> 2) * (KS * 128));
#pragma unroll
            for (int p = 0; p < 8; p++) {
                const int slot = p % 5;
                mbar_wait(bar + 8 * (B_FULL + slot), slot < 3 ? (uint32_t)(p / 5) : (uint32_t)(seg & 1));
                PROF2(p);
                const uint64_t db = slot < 3 ? dX + (uint64_t)(slot * 512) : dX0 + (uint64_t)((slot == 3 ? e0 : e1) >> 4);
                wg_fence();
#pragma unroll
                for (int kk = 0; kk < 8; kk++) {
                    const int k = (kk & 1) * 4 + (kk >> 1);
                    const int ks = xo(2 * p + (k >> 2)) * 4 + (k & 3);
                    if (ks >= KR) wg_ss32<1>(d, dW + (uint64_t)((ks - KR) * 128), db + (uint64_t)((k >> 2) * 256 + (k & 3) * 2), p + k);
                    else wg_rs32(d, a[ks < KR ? ks : 0], db + (uint64_t)((k >> 2) * 256 + (k & 3) * 2), p + k);
                }
                wg_commit();
                if (p >= 1) {
                    wg_wait<1>();
                    if (p <= 3) { if ((wq & 3) == p) e_arrive(bar + 8 * (B_EMPTY + p - 1)); }
                    if (p <= 3) {
                        const int q = p;
                        if (wq == q + (q & 1) * 4) {
                            mbar_wait(bar + 8 * (B_EMPTY + q - 1), seg & 1);
                            x_load_pair(sb + R_RING + (q - 1) * 8192, &tm.x, h, q + 4, seg, bar + 8 * (B_FULL + q - 1));
                        }
                    }
                    if (p == 5 && role != 0 && (wq & 3) < 3) e_arrive_remote(mapa(bar + 8 * B_TFREE, wq & 3));
                    if (p == 6 && (wq & 3) == 1) e_arrive(bar + 8 * B_AFREE0);
                    if (p == 7 && (wq & 3) == 2) e_arrive(bar + 8 * B_AFREE1);
                }
            }
            mbar_wait(bar + 8 * B_TFREE, seg & 1);
            asm volatile("wgmma.wait_group.sync.aligned 0;" : ACC16(d)::"memory");
            PROF2(16);
            const uint32_t tilex = sb + (role == 0 ? R_QX + 2048 : (role == 1 ? R_K + 2048 : R_V + 2048));
            {
                OPAQUE(tb);
                const uint32_t gs = role == 0 ? 4096 : 2048;
                const uint32_t sa = tilex + ((tb >> 4) & 1) * gs + (tb >> 5) * 256 + (tb & 15) * 16;
                stsm4(sa, pack_bf16(d[0], d[1]), pack_bf16(d[2], d[3]), pack_bf16(d[4], d[5]), pack_bf16(d[6], d[7]));
                stsm4(sa + 2 * gs, pack_bf16(d[8], d[9]), pack_bf16(d[10], d[11]), pack_bf16(d[12], d[13]), pack_bf16(d[14], d[15]));
            }
            __syncwarp();
            e_arrive(bar + 8 * B_XDONE);
            if (role != 0 && (wq & 3) == 0) {
                mbar_wait(bar + 8 * B_XDONE, seg & 1);
                fence_async();
                uint32_t pr = role + 1 + (wq >> 2); pr = pr >= 3 ? pr - 3 : pr;
                e_bulk_s2s(mapa(tilex, pr), tilex, 8192, mapa(bar + 8 * B_XT, pr));
            }
            }
            {
                const int s = seg;
                OPAQUE(wq);
                const uint64_t dW = dW0 + (uint64_t)((wq >> 2) * (KS * 128));
                float y[4] = {0.f, 0.f, 0.f, 0.f};
                {
                    OPAQUE(tb);
                    const uint32_t ma = sb + R_RING + (tb & 31) * 16;
                    float z[4] = {0.f, 0.f, 0.f, 0.f}, u[4] = {0.f, 0.f, 0.f, 0.f};
                    uint32_t b[QD][4];
                    const int yes = s + 1;
                    mbar_wait(bar + 8 * B_MEM, s & 1);
                    PROF((wq >> 2) * 4 + 0);
                    if (s == 0) PT(3);
                    if (s == 1) PT(4);
#pragma unroll
                    for (int g = 0; g < QD; g++) ldsm4t(b[g], ma + g * 512);
#pragma unroll
                    for (int g = 0; g < KR / 2; g++) {
                        float* c0 = (g % 3 == 0) ? y : (g % 3 == 1) ? u : z;
                        float* c1 = (g % 3 == 0) ? z : (g % 3 == 1) ? y : u;
                        mma16816(c0, a[2 * g][0], a[2 * g][1], a[2 * g][2], a[2 * g][3], b[g % QD][0], b[g % QD][1]);
                        mma16816(c1, a[2 * g + 1][0], a[2 * g + 1][1], a[2 * g + 1][2], a[2 * g + 1][3], b[g % QD][2], b[g % QD][3]);
                        if (g + QD < KR / 2) {
                            if ((g + QD) % 8 == 0) mbar_wait(bar + 8 * (B_MEM + (g + QD) / 8), s & 1);
                            ldsm4t_if(b[g % QD], ma + (g + QD) * 512, yes);
                        }
                    }
                    y[0] += z[0] + u[0]; y[1] += z[1] + u[1]; y[2] += z[2] + u[2]; y[3] += z[3] + u[3];
                }
                PROF2(8);
                mbar_wait(bar + 8 * (B_MEM + 3), s & 1);
                wg_fence();
#pragma unroll
                for (int k = KR; k < 64; k++) {
                    wg_ss8<1, 1>(y, dW + (uint64_t)((k - KR) * 128), dM + (uint64_t)(k * 16), 1);
                }
                wg_commit();
                asm volatile("wgmma.wait_group.sync.aligned 0;" : "+f"(y[0]), "+f"(y[1]), "+f"(y[2]), "+f"(y[3])::"memory");
                OPAQUE(tb);
                {
                    const uint32_t wo_ = (tb >> 5) * 256;
                    const uint32_t tile = sb + (role == 0 ? R_QX : (role == 1 ? R_K : R_V)) + wo_;
                    const uint32_t u0 = pack_bf16(y[0], y[1]), u1 = pack_bf16(y[2], y[3]);
                    sts32(tile + (tb & 31) * 4, u0);
                    sts32(tile + (tb & 31) * 4 + 128, u1);
                    __syncwarp();
                    uint4 v = lds128(tile + (tb & 15) * 16);
                    uint32_t peer = role + 1 + ((tb >> 4) & 1);
                    peer = peer >= 3 ? peer - 3 : peer;
                    const uint32_t rt = sb + (role == 0 ? R_QM : (role == 1 ? R_K : R_V)) + wo_ + (tb & 15) * 16;
                    st_async16(mapa(rt, peer), v, mapa(bar + 8 * (role == 2 ? B_HOPV : B_HOP1), peer));
                    if (role == 0) {
                        sts128(tile + 4096 + ((tb >> 4) & 1) * 4096 + (tb & 15) * 16, v);
                        sts32(tile + 12288 + (tb & 31) * 4, u0);
                        sts32(tile + 12288 + (tb & 31) * 4 + 128, u1);
                        __syncwarp();
                    }
                    e_arrive(bar + 8 * (role == 2 ? B_HOPV : B_HOP1));
                }
                PROF((wq >> 2) * 4 + 1);
                if (s < NSEG - 1) {
                    bar_sync(1, 256);
                    if (wq < 3) { fence_async(); x_load_pair(sb + R_RING + wq * 8192, &tm.x, h, wq, s + 1, bar + 8 * (B_FULL + wq)); }
                    else if (role == 0 && wq < 5) x_load_pair(sb + (wq == 3 ? e0 : e1), &tm.x, h, wq, s + 1, bar + 8 * (B_FULL + wq));
                    OPAQUE(tb);
                }
                uint32_t* pp = g_part[s & 3] + (h * 32 + (wo_tile(role, 0) + (tb >> 7)) * 8192 + ((tb >> 5) & 3) * 2048 + (tb & 31));
                asm volatile("" : "+l"(pp));
                if (s == NSEG - 1) break;
                if (s == 0) mbar_wait(bar + 8 * B_PRO0, 0);
                wo_phase<role == 0 ? 2 : 3>(sb, tb, pp, bar + 8 * B_O, s & 1);
                if (wq == 0) PROF(10);
            }
        }
}

#define CLEAR(st) do { if (role != 0) { \
                const int w_ = wid & 3; \
                uint32_t* zp = g_part[(st) & 3] + ((rg0 + (w_ >> 1) * 64) * 1024 + (w_ & 1) * 512); \
                e_bulk_s2g(zp, sb + R_Z, 1024); \
                e_bulk_s2g(zp + 256, sb + R_Z, 1024); \
                e_bulk_s2g(&g_mem[(st) & 3][(rg0 + (w_ >> 1) * 64) * 32 + (w_ & 1) * 16], sb + R_Z, 64); \
                bulk_commit(); } } while (0)
template <uint32_t role> DEVINL void r_chain(const RMaps& tm, const bf16* __restrict__ mem0, const int wid) {
    extern __shared__ __align__(1024) unsigned char smem_raw[];
    const uint32_t sb = smem_u32(smem_raw);
    const uint32_t bar = sb + R_BAR;
    const int tid = threadIdx.x;
    int h; asm("mov.u32 %0, %%clusterid.x;" : "=r"(h));
        int t = tid & 127;
        const float sl2 = 0.08838834764831845f * 1.4426950408889634f;
        const float NEGRAW = -1000000000.0f / 0.08838834764831845f;
        const int rg0 = ((int)role - 1) * 32 + h;
        if (role != 0) {
#pragma unroll 1
            for (int r = 0; r < 4; r++) {
                uint32_t* zp = g_part[r] + ((rg0 + (t >> 6) * 64) * 1024 + (t & 63) * 4);
#pragma unroll
                for (int i = 0; i < 4; i++) if (r) st_strong16(zp + i * 256, make_uint4(0u, 0u, 0u, 0u));
                if ((t & 63) < 8) st_strong16(&g_mem[r][(rg0 + (t >> 6) * 64) * 32 + (t & 63) * 4], make_uint4(0u, 0u, 0u, 0u));
            }
            __threadfence();
        }
        if (role == 0 && (wid & 3) < 3) e_arrive_remote(mapa(bar + 8 * B_TFREE, wid & 3));
        if (t < 64) sts128(sb + R_Z + t * 16, make_uint4(0u, 0u, 0u, 0u));
        if (role == 0) sts128(sb + R_QM + t * 16, make_uint4(0u, 0u, 0u, 0u));
        {
            uint4 v[8];
#pragma unroll
            for (int r = 0; r < 8; r++) v[r] = __ldg((const uint4*)(mem0 + r * DM) + t);
            mbar_wait(bar + 8 * B_AFREE0, 0);
            mbar_wait(bar + 8 * B_AFREE1, 0);
#define TR2(f, c) \
            sts128(sb + R_RING + t * 128 + (c) * 16, make_uint4(__byte_perm(v[0].f, v[1].f, 0x5410), __byte_perm(v[2].f, v[3].f, 0x5410), __byte_perm(v[4].f, v[5].f, 0x5410), __byte_perm(v[6].f, v[7].f, 0x5410))); \
            sts128(sb + R_RING + t * 128 + (c) * 16 + 16, make_uint4(__byte_perm(v[0].f, v[1].f, 0x7632), __byte_perm(v[2].f, v[3].f, 0x7632), __byte_perm(v[4].f, v[5].f, 0x7632), __byte_perm(v[6].f, v[7].f, 0x7632)));
            TR2(x, 0) TR2(y, 2) TR2(z, 4) TR2(w, 6)
            fence_async();
            __syncwarp();
            e_arrive(bar + 8 * B_MEM + (t >> 5) * 8);
        }
        constexpr uint64_t dQ = role == 0 ? cdesc(R_QX, 128, 2048, 0) : cdesc(R_QM, 128, 0, 0);
        constexpr uint64_t dK = cdesc(R_K, 128, 2048, 0);

        for (int s = 0; s < NSEG; s++) {
            if (role == 0) {
                uint32_t n = 0, gate;
                do { gate = ld_strong4(&g_gate[s * SEG + (t >> 2)]); if (++n > 20000000u) __trap(); } while (gate == 0u);
                sts32(sb + R_G + (t >> 2) * 4, gate);
                __syncwarp();
            }
            mbar_wait(bar + 8 * B_XDONE, s & 1);
            mbar_wait(bar + 8 * B_XT, s & 1);
            if (t >= 1 && t < 3) { uint32_t pr = role + t; pr = pr >= 3 ? pr - 3 : pr; mbar_arrive_remote(mapa(bar + 8 * B_XRECV, pr)); }
            __syncwarp();
            mbar_wait(bar + 8 * B_HOP1, s & 1);
            PROF(8);
            fence_async();
            OPAQUE(t);
            if (s == NSEG - 1 && role != 0) { mbar_wait(bar + 8 * B_HOPV, s & 1); bulk_wait_all(); break; }
            float sc[20];
            wg_fence();
#pragma unroll
            for (int k = 0; k < 8; k++) wg_ss40(sc, dQ + (uint64_t)(k * 16), dK + (uint64_t)(k * 16), k);
            wg_commit();
            uint32_t t_o = clk32() + 500;
            {
                const uint32_t va = sb + R_V + 2048 + (t >> 5) * 512 + ((t >> 4) & 1) * 2048 + (t & 15) * 16;
                uint32_t v0[4], v1[4];
                ldsm4(v0, va); ldsm4(v1, va + 256);
                uint32_t vm[4];
                const bool v_here = role != 0 && mbar_try(bar + 8 * B_HOPV, s & 1);
                if (v_here) ldsm4(vm, sb + R_V + t * 16);
                wg_wait<0>();
                if (role == 0) {
#pragma unroll
                    for (int j = 0; j < 5; j++)
                        asm volatile("st.shared.v2.f32 [%0], {%1,%2};" ::"r"(sb + R_QX + 768 + (t >> 5) * 4096 + j * 256 + (t & 31) * 8), "f"(sc[4 * j + 2]), "f"(sc[4 * j + 3]) : "memory");
                }
                float m = fmaxf(sc[0], sc[1]);
#pragma unroll
                for (int j = 1; j < 5; j++) m = fmaxf(m, fmaxf(sc[4 * j], sc[4 * j + 1]));
                m = fmaxf(m, __shfl_xor_sync(0xffffffffu, m, 1));
                m = fmaxf(m, __shfl_xor_sync(0xffffffffu, m, 2));
                const float mb = m * sl2;
                uint32_t pk[5];
#pragma unroll
                for (int j = 0; j < 5; j++) pk[j] = pack_bf16(ex2(fmaf(sc[4 * j], sl2, -mb)), ex2(fmaf(sc[4 * j + 1], sl2, -mb)));
                float o0[4] = {0.f, 0.f, 0.f, 0.f}, o1[4] = {0.f, 0.f, 0.f, 0.f}, ls[4] = {0.f, 0.f, 0.f, 0.f};
                constexpr uint32_t ONE = 0x3F803F80u;
                mma16816(o0, v0[0], v0[1], v0[2], v0[3], pk[1], pk[2]);
                mma16816(o1, v1[0], v1[1], v1[2], v1[3], pk[1], pk[2]);
                if (role == 0) { ldsm4_if(v0, va + 4096, s + 1); ldsm4_if(v1, va + 4096 + 256, s + 1); }
                else { ldsm4(v0, va + 4096); ldsm4(v1, va + 4096 + 256); }
                mma16816(ls, ONE, ONE, ONE, ONE, pk[1], pk[2]);
                mma16816(ls, ONE, ONE, ONE, ONE, pk[3], pk[4]);
                mma1688(ls, ONE, ONE, pk[0]);
                mma16816(o0, v0[0], v0[1], v0[2], v0[3], pk[3], pk[4]);
                mma16816(o1, v1[0], v1[1], v1[2], v1[3], pk[3], pk[4]);
                if (!v_here) { mbar_wait(bar + 8 * B_HOPV, s & 1); ldsm4(vm, sb + R_V + t * 16); }
                mma1688(o0, vm[0], vm[1], pk[0]);
                mma1688(o1, vm[2], vm[3], pk[0]);
                const float i0 = rcp(ls[0]), i1 = rcp(ls[1]);
                const uint32_t oa = sb + R_O + (t >> 5) * 512 + (t & 31) * 4;
                sts32(oa, pack_bf16(o0[0] * i0, o0[1] * i1));
                sts32(oa + 128, pack_bf16(o0[2] * i0, o0[3] * i1));
                sts32(oa + 256, pack_bf16(o1[0] * i0, o1[1] * i1));
                sts32(oa + 384, pack_bf16(o1[2] * i0, o1[3] * i1));
                __syncwarp();
                e_arrive(bar + 8 * B_O);
                PROF(9);
                if (role == 0) {
                    OPAQUE(t);
                    const int lim = (t >> 2) - (t & 3) * 2 + 8;
                    float z[10];
#pragma unroll
                    for (int j = 0; j < 5; j++)
                        asm volatile("ld.shared.v2.f32 {%0,%1}, [%2];" : "=f"(z[2 * j]), "=f"(z[2 * j + 1]) : "r"(sb + R_QX + 768 + (t >> 5) * 4096 + j * 256 + (t & 31) * 8) : "memory");
                    float gate; asm volatile("ld.shared.f32 %0, [%1];" : "=f"(gate) : "r"(sb + R_G + (t >> 2) * 4) : "memory");
                    float m1 = fmaxf(z[0], z[1]);
#pragma unroll
                    for (int j = 1; j < 5; j++) {
                        z[2 * j] = 8 * j <= lim ? z[2 * j] : NEGRAW;
                        z[2 * j + 1] = 8 * j + 1 <= lim ? z[2 * j + 1] : NEGRAW;
                        m1 = fmaxf(m1, fmaxf(z[2 * j], z[2 * j + 1]));
                    }
                    m1 = fmaxf(m1, __shfl_xor_sync(0xffffffffu, m1, 1));
                    m1 = fmaxf(m1, __shfl_xor_sync(0xffffffffu, m1, 2));
                    const float mb1 = m1 * sl2;
                    float l1 = 0.f;
                    const uint32_t pa = sb + R_QX + (t >> 5) * 4096 + (t & 31) * 4;
#pragma unroll
                    for (int j = 0; j < 5; j++) {
                        const uint32_t pw = pack_bf16(ex2(fmaf(z[2 * j], sl2, -mb1)), ex2(fmaf(z[2 * j + 1], sl2, -mb1)));
                        l1 += __uint_as_float(pw << 16) + __uint_as_float(pw & 0xffff0000u);
                        sts32(pa + j * 128, pw);
                    }
                    sts32(pa + 5 * 128, 0u);
                    l1 += __shfl_xor_sync(0xffffffffu, l1, 1);
                    l1 += __shfl_xor_sync(0xffffffffu, l1, 2);
                    sts32(sb + R_G + 128 + (t >> 2) * 4, __float_as_uint(gate * rcp(l1)));
                    if (s < NSEG - 1) spin_until(t_o + PVD);
                    if ((wid & 3) == 0 && s >= 1) { bulk_wait_all(); e_count(&g_ocnt[(s - 1) >> 2]); }
                    fence_async();
                    bar_sync(2, 128);
                    constexpr uint64_t dV = cdesc(R_V, 2048, 128, 0);
                    constexpr uint64_t dP = cdesc(R_QX, 128, 4096, 0);
                    float sf[8];
#pragma unroll
                    for (int j = 0; j < 4; j++) asm volatile("ld.shared.v2.f32 {%0,%1}, [%2];" : "=f"(sf[2 * j]), "=f"(sf[2 * j + 1]) : "r"(sb + R_G + 128 + j * 32 + (t & 3) * 8) : "memory");
                    const uint32_t r = ((t >> 4) & 1) * 8 + (t & 7), ch = (t >> 5) * 2 + ((t >> 3) & 1);
                    const uint32_t sa = sb + R_QX + 2048 + r * 128 + ((ch ^ (r & 7)) << 4);
#pragma unroll
                    for (int hf = 0; hf < 2; hf++) {
                        float d[16];
                        wg_fence();
#pragma unroll
                        for (int k = 0; k < 3; k++) wg_ss32<0>(d, dV + (uint64_t)(hf * 64 + k * 256), dP + (uint64_t)(k * 16), k);
                        wg_commit();
                        asm volatile("wgmma.wait_group.sync.aligned 0;" : ACC16(d)::"memory");
                        stsm4t(sa + hf * 8192, pack_bf16(d[0] * sf[0], d[1] * sf[1]), pack_bf16(d[2] * sf[0], d[3] * sf[1]), pack_bf16(d[4] * sf[2], d[5] * sf[3]), pack_bf16(d[6] * sf[2], d[7] * sf[3]));
                        stsm4t(sa + hf * 8192 + 4096, pack_bf16(d[8] * sf[4], d[9] * sf[5]), pack_bf16(d[10] * sf[4], d[11] * sf[5]), pack_bf16(d[12] * sf[6], d[13] * sf[7]), pack_bf16(d[14] * sf[6], d[15] * sf[7]));
                    }
                    fence_async();
                    bar_sync(2, 128);
                    if ((wid & 3) == 0) {
#pragma unroll
                        for (int q = 0; q < 4; q++) e_tma_store(&tm.o, sb + R_QX + 2048 + q * 4096, h * DH + (q >> 1) * 64, s * SEG + (q & 1) * 16);
                        bulk_commit();
                        bulk_wait_read();
                    }
                    if ((wid & 3) < 3) e_arrive_remote(mapa(bar + 8 * B_TFREE, wid & 3));
                }
            }
            if (t < 32) { e_expect(bar + 8 * B_HOP1, role == 2 ? 4096 : 2048); if (role != 2) e_expect(bar + 8 * B_HOPV, 2048); e_expect(bar + 8 * B_XT, role == 0 ? 16384 : 8192); }
            if (s == NSEG - 1) { bulk_wait_all(); if ((wid & 3) == 0) e_count(&g_ocnt[s >> 2]); break; }
            if (role != 0 && (wid & 3) >= 2) {
                mbar_wait(bar + 8 * B_XRECV, s & 1);
                mbar_wait(bar + 8 * B_O, s & 1);
                fence_async();
                spin_until(t_o + ELD);
                x_load_pair(sb + ((wid & 1) ? R_V + 2048 : R_K + 2048), &tm.x, h, 3 + (wid & 1), s + 1, bar + 8 * (B_FULL + 3 + (wid & 1)));
            }
            OPAQUE(t);
            PROF(11);
            if (role != 0) {
                const int grp = rg0 + (t >> 6) * 64;
                const uint32_t* rp = g_part[s & 3] + (grp * 1024 + ((t >> 2) & 7) * 32 + ((t >> 5) & 1) * 16 + (t & 3) * 4);
                uint32_t* wp = &g_mem[(s + 1) & 3][grp * 32 + ((t >> 5) & 1) * 16 + (t & 3) * 4 + ((t >> 3) & 3)];
                bulk_wait_all();
                spin_until(t_o + D2_BASE + (role - 1 + (t >> 6) * 2) * D2_STEP);
                PROF3(0, clk32());
#define LO(u) __uint_as_float((u) << 16)
#define HI(u) __uint_as_float((u) & 0xffff0000u)
                uint4 v[4];
                uint32_t n = poll_set<4>(v, rp, 256);
                {
                    PROF3(1, clk32());
                    float f[8];
                    f[0] = (LO(v[0].x) + LO(v[1].x)) + (LO(v[2].x) + LO(v[3].x)); f[1] = (HI(v[0].x) + HI(v[1].x)) + (HI(v[2].x) + HI(v[3].x));
                    f[2] = (LO(v[0].y) + LO(v[1].y)) + (LO(v[2].y) + LO(v[3].y)); f[3] = (HI(v[0].y) + HI(v[1].y)) + (HI(v[2].y) + HI(v[3].y));
                    f[4] = (LO(v[0].z) + LO(v[1].z)) + (LO(v[2].z) + LO(v[3].z)); f[5] = (HI(v[0].z) + HI(v[1].z)) + (HI(v[2].z) + HI(v[3].z));
                    f[6] = (LO(v[0].w) + LO(v[1].w)) + (LO(v[2].w) + LO(v[3].w)); f[7] = (HI(v[0].w) + HI(v[1].w)) + (HI(v[2].w) + HI(v[3].w));
                    const bool b4 = t & 16, b3 = t & 8;
                    float g4[4], g2[2];
#pragma unroll
                    for (int i = 0; i < 4; i++) g4[i] = (b4 ? f[4 + i] : f[i]) + __shfl_xor_sync(0xffffffffu, b4 ? f[i] : f[4 + i], 16);
#pragma unroll
                    for (int i = 0; i < 2; i++) g2[i] = (b3 ? g4[2 + i] : g4[i]) + __shfl_xor_sync(0xffffffffu, b3 ? g4[i] : g4[2 + i], 8);
                    g2[0] += __shfl_xor_sync(0xffffffffu, g2[0], 4);
                    g2[1] += __shfl_xor_sync(0xffffffffu, g2[1], 4);
                    st_strong4(wp, pack_nz(g2[0], g2[1]));
                }
                PROF3(8, n); (void)n;
            }
            t_o += D2_BASE + DQ + (t >> 5) * D2_STEP;
            OPAQUE(t);
            PROF(12);
            {
                const uint32_t* rp = &g_mem[(s + 1) & 3][((t >> 5) * 256 + (t & 31)) * 4];
                const uint32_t da = sb + R_RING + ((t >> 5) * 256 + (t & 31)) * 16;
                uint4 v[8];
                spin_until(t_o);
                PROF3(2, clk32());
                uint32_t n = poll_set<8>(v, rp, 128);
                PROF(13);
                PROF3(3, clk32()); PROF3(9, n); (void)n;
                mbar_wait(bar + 8 * B_AFREE0 + (t >> 6) * 8, (s + 1) & 1);
                PROF3(4, clk32());
#pragma unroll
                for (int i = 0; i < 8; i++) sts128(da + i * 512, v[i]);
                if (t >= 64) fence_async();
                __syncwarp();
                e_arrive(bar + 8 * B_MEM + (t >> 5) * 8);
                PROF(14);
                PROF3(5, clk32());
            }
            CLEAR(s + 3);
        }
}

__global__ void __launch_bounds__(384, 1) r_kernel(const __grid_constant__ RMaps tm, const bf16* __restrict__ mem0, const bf16* __restrict__ x, const bf16* __restrict__ gate_w) {
    extern __shared__ __align__(1024) unsigned char smem_raw[];
    const uint32_t sb = smem_u32(smem_raw);
    if ((sb & 0x3FFFFu) != SB0) __trap();
    const int tid = threadIdx.x;
    const int wid = __shfl_sync(0xffffffffu, tid >> 5, 0);
    uint32_t role; asm("mov.u32 %0, %%cluster_ctarank;" : "=r"(role));
    int h; asm("mov.u32 %0, %%clusterid.x;" : "=r"(h));
    const uint32_t bar = sb + R_BAR;
    asm volatile("griddepcontrol.launch_dependents;");
    KT(0, 0);
    const int gr = blockIdx.x * 12 + wid;
    uint4 gx0[4], gx1[4], gw[4];
#pragma unroll
    for (int i = 0; i < 4; i++) {
        gx0[i] = ldg_nc((const uint4*)(x + gr * DM) + i * 32 + (tid & 31));
        gx1[i] = ldg_nc((const uint4*)(x + min(gr + 1152, SEQ - 1) * DM) + i * 32 + (tid & 31));
        gw[i] = ldg_nc((const uint4*)gate_w + i * 32 + (tid & 31));
    }

    if (tid == 0) {
        for (int i = 0; i < 5; i++) mbar_init(bar + 8 * (B_FULL + i), 1);
        for (int i = 0; i < 3; i++) mbar_init(bar + 8 * (B_EMPTY + i), 2);
        for (int i = 0; i < 4; i++) mbar_init(bar + 8 * (B_MEM + i), 1);
        mbar_init(bar + 8 * B_HOP1, role == 2 ? 1 : 9);
        mbar_init(bar + 8 * B_HOPV, role == 2 ? 8 : 1);
        mbar_init(bar + 8 * B_XT, 1);
        mbar_init(bar + 8 * B_TFREE, 5);
        mbar_init(bar + 8 * B_XDONE, 8);
        mbar_init(bar + 8 * B_XRECV, 2);
        mbar_init(bar + 8 * B_O, 4);
        mbar_init(bar + 8 * B_AFREE0, 2);
        mbar_init(bar + 8 * B_AFREE1, 2);
        mbar_init(bar + 8 * B_PRO0, 1);
        mbar_init(bar + 8 * B_PRO1, 1);
        for (int i = 0; i < KR / 4; i++) mbar_init(sb + R_O + 8 * i, 1);
        asm volatile("fence.mbarrier_init.release.cluster;" ::: "memory");
        fence_async();
        for (int i = 0; i < KR / 4; i++) mbar_expect(sb + R_O + 8 * i, 16384);
        mbar_expect(bar + 8 * B_PRO1, KS * 4096);
        mbar_expect(bar + 8 * B_PRO0, (role == 0 ? 4 : 6) * 16384);
        for (int i = 0; i < 3; i++) mbar_expect(bar + 8 * (B_FULL + i), 8192);
        mbar_expect(bar + 8 * B_HOP1, role == 2 ? 4096 : 2048);
        if (role != 2) mbar_expect(bar + 8 * B_HOPV, 2048);
        mbar_expect(bar + 8 * B_XT, role == 0 ? 16384 : 8192);
    }
    __syncthreads();
    asm volatile("barrier.cluster.arrive.relaxed.aligned;" ::: "memory");
    {
        const CUtensorMap* tw = &tm.w[role];
        if (wid < 11) {
            e_tma_load(sb + wid * 16384, tw, h * DH, KC(wid), sb + R_O + 8 * wid);
            e_tma_load(sb + wid * 16384 + 8192, tw, h * DH + 64, KC(wid), sb + R_O + 8 * wid);
        }
        if (wid < 6) e_tma_load(sb + R_RING + wid * 4096, &tm.x, XC(wid), 0, bar + 8 * (B_FULL + (wid >> 1)));
        __syncwarp();
        const uint32_t g0 = __float_as_uint(gate_row(gx0, gw)), g1 = __float_as_uint(gate_row(gx1, gw));
        if ((tid & 31) == 0) {
            st_strong4(&g_gate[gr], g0 ? g0 : 0x80000000u);
            if (gr + 1152 < SEQ) st_strong4(&g_gate[gr + 1152], g1 ? g1 : 0x80000000u);
        }
        __syncwarp();
    }
    asm volatile("barrier.cluster.wait.aligned;" ::: "memory");

    if (wid < 8) {
        asm volatile("setmaxnreg.inc.sync.aligned.u32 224;");
        if (role == 0) r_big<0>(tm, wid); else if (role == 1) r_big<1>(tm, wid); else r_big<2>(tm, wid);
    } else {
        asm volatile("setmaxnreg.dec.sync.aligned.u32 56;");
        if (role == 0) r_chain<0>(tm, mem0, wid); else if (role == 1) r_chain<1>(tm, mem0, wid); else r_chain<2>(tm, mem0, wid);
    }
    __syncwarp();
    asm volatile("barrier.cluster.arrive; barrier.cluster.wait;" ::: "memory");
    KT(0, 1);
}

constexpr int G_ST = 4;
constexpr int G_STAGE = 16384 + 32768;
constexpr int G_EPI = G_ST * G_STAGE;
constexpr int G_GATE = G_EPI + 32768;
constexpr int G_BAR = G_GATE + 1024;
constexpr int G_SMEM = G_BAR + 128 + 1024;

struct G1Maps { CUtensorMap x, wg, wu, hs, o, h, wo, wd, out; };
constexpr int G1_NB = FF / 128;
constexpr int G1_TILES = 16 * G1_NB;

DEVINL void g_mma_block(float* d, uint32_t sb, uint32_t bar, int it, int wg, int tid, bool first) {
    const int st = it % G_ST;
    mbar_wait(bar + 8 * st, (it / G_ST) & 1);
    const uint64_t da = mkdesc(sb + st * G_STAGE + wg * 8192, 16, 1024, 1);
    const uint64_t db = mkdesc(sb + st * G_STAGE + 16384, 8192, 1024, 1);
    wg_fence();
#pragma unroll
    for (int k = 0; k < 4; k++) wg_ss256(d, da + (uint64_t)(k * 2), db + (uint64_t)(k * 128), (first ? 0 : 1) | k);
    wg_commit();
    if (!first) { wg_wait<1>(); if ((tid & 127) == 0) mbar_arrive(bar + 8 * (G_ST + (it - 1) % G_ST)); }
}
DEVINL void g_load_block(uint32_t sb, uint32_t bar, int it, const CUtensorMap* ta, int k0, int m0, const CUtensorMap* tb, int n0) {
    const int st = it % G_ST;
    mbar_wait(bar + 8 * (G_ST + st), ((it / G_ST) & 1) ^ 1);
    const uint32_t fb = bar + 8 * st, sa = sb + st * G_STAGE;
    mbar_expect(fb, G_STAGE);
    tma_load(sa, ta, k0, m0, fb);
#pragma unroll
    for (int q = 0; q < 4; q++) tma_load(sa + 16384 + q * 8192, tb, n0 + q * 64, k0, fb);
}

DEVINL void g_store_tile(const float* d, const CUtensorMap* tout, uint32_t epi, int mb, int nb, int wg, int tid) {
    const int lane = tid & 31, row = ((tid >> 5) & 3) * 16 + ((lane >> 3) & 1) * 8 + (lane & 7);
#pragma unroll
    for (int half = 0; half < 2; half++) {
        if ((tid & 127) == 0) bulk_wait_read();
        bar_sync(1 + wg, 128);
#pragma unroll
        for (int j = 0; j < 16; j += 2) {
            const float* e = d + half * 64 + 4 * j;
            const int cgp = j + (lane >> 4);
            stsm4(epi + (cgp >> 3) * 8192 + row * 128 + (((cgp & 7) ^ (row & 7)) << 4),
                  pack_bf16(e[0], e[1]), pack_bf16(e[2], e[3]), pack_bf16(e[4], e[5]), pack_bf16(e[6], e[7]));
        }
        fence_async();
        bar_sync(1 + wg, 128);
        if ((tid & 127) == 0) {
            tma_store(tout, epi, nb * 256 + half * 128, mb * 128 + wg * 64);
            tma_store(tout, epi + 8192, nb * 256 + half * 128 + 64, mb * 128 + wg * 64);
            bulk_commit();
        }
    }
}
template <int NS> DEVINL void g_split_finish(const float* d, float4 (&r)[32 / NS], uint4* sk, int tile, int ks, bf16* __restrict__ out, int tid) {
    constexpr int Q = 32 / NS;
    uint4* mine = sk + ks * (16 * 256) + tid;
#pragma unroll
    for (int c = 0; c < NS; c++) {
        if (c != ks) {
#pragma unroll
            for (int q = c * Q / 2; q < (c + 1) * Q / 2; q++)
                __stcg(mine + q * 256, make_uint4(pack_bf16(d[8 * q], d[8 * q + 1]), pack_bf16(d[8 * q + 2], d[8 * q + 3]), pack_bf16(d[8 * q + 4], d[8 * q + 5]), pack_bf16(d[8 * q + 6], d[8 * q + 7])));
        } else {
#pragma unroll
            for (int q = 0; q < Q; q++) { const float* e = d + (c * Q + q) * 4; r[q].x += e[0]; r[q].y += e[1]; r[q].z += e[2]; r[q].w += e[3]; }
        }
    }
    __threadfence();
    bar_sync(3, 256);
    if (tile >= T_LATE) PT(20);
    if (tid == 0) {
        atomicAdd(&g_skcnt[tile], 1u);
        uint32_t v, n = 0;
        do {
            asm volatile("ld.acquire.gpu.global.u32 %0, [%1];" : "=r"(v) : "l"(&g_skcnt[tile]) : "memory");
            if (++n > 200000000u) __trap();
        } while (v < NS);
        if (atomicAdd(&g_skcnt[tile], 1u) == 2 * NS - 1) g_skcnt[tile] = 0u;
    }
    bar_sync(3, 256);
    if (tile >= T_LATE) PT(21);
#pragma unroll
    for (int c = 1; c < NS; c++) {
        const uint4* th = sk + (((ks + c) & (NS - 1)) * 16 + ks * (Q / 2)) * 256 + tid;
#pragma unroll
        for (int q = 0; q < Q / 2; q++) {
            const uint4 u = __ldcg(th + q * 256);
            r[2 * q].x += __uint_as_float(u.x << 16); r[2 * q].y += __uint_as_float(u.x & 0xffff0000u);
            r[2 * q].z += __uint_as_float(u.y << 16); r[2 * q].w += __uint_as_float(u.y & 0xffff0000u);
            r[2 * q + 1].x += __uint_as_float(u.z << 16); r[2 * q + 1].y += __uint_as_float(u.z & 0xffff0000u);
            r[2 * q + 1].z += __uint_as_float(u.w << 16); r[2 * q + 1].w += __uint_as_float(u.w & 0xffff0000u);
        }
    }
    const int lane = tid & 31;
    uint32_t* op = (uint32_t*)(out + ((tile >> 2) * 128 + (tid >> 5) * 16 + (lane >> 2)) * DM + (tile & 3) * 256 + ks * Q * 8 + (lane & 3) * 2);
#pragma unroll
    for (int q = 0; q < Q; q++) { op[q * 4] = pack_bf16(r[q].x, r[q].y); op[q * 4 + 4 * DM] = pack_bf16(r[q].z, r[q].w); }
}
DEVINL int g1_count(int pass, int tail) {
    return pass == 0 ? NPRE : pass == 1 ? NFULL : pass == 2 ? T_MID - NFULL : pass == 3 ? (T_MID2 - T_MID) * 4 : tail ? (64 - T_LATE) * 8 : (T_LATE - T_MID2) * 8;
}
DEVINL int g1_first(int pass, int tail) {
    const int b = blockIdx.x, n = gridDim.x;
    return (pass < 2 || tail) ? b : pass == 2 ? n - 1 - b : (b + n - (pass == 3 ? 16 : 32)) % n;
}
DEVINL int g1_tile(int pass, int tail, int i) {
    return pass == 1 ? i : pass == 3 ? T_MID + (i >> 2) : pass == 4 ? (tail ? T_LATE : T_MID2) + (i >> 3) : NFULL + i;
}
constexpr int H_EARLY = 24;

__global__ void __launch_bounds__(384, 1) g1_kernel(const __grid_constant__ G1Maps tm, bf16* __restrict__ out, const int tail) {
    extern __shared__ __align__(1024) unsigned char smem_raw[];
    const uint32_t sb = (smem_u32(smem_raw) + 1023) & ~1023u;
    const int tid = threadIdx.x, lane = tid & 31;
    const int wg = __shfl_sync(0xffffffffu, tid >> 7, 0);
    const int warp = __shfl_sync(0xffffffffu, (tid >> 5) & 3, 0);
    const uint32_t bar = sb + G_BAR;
    asm volatile("griddepcontrol.launch_dependents;");
    KT(1 + tail, 0);
    if (tail && (tid == 32 || tid == 64)) asm volatile("prefetch.tensormap [%0];" ::"l"(tid == 32 ? &tm.o : &tm.wo) : "memory");
    const int ntiles = tail ? 0 : G1_TILES;
    if (tid == 0) {
        for (int i = 0; i < G_ST; i++) { mbar_init(bar + 8 * i, 1); mbar_init(bar + 8 * (G_ST + i), 2); }
        fence_async();
    }
    __syncthreads();
    if (tail) PT(16);
    if (tail) PT(17);
    if (tail) PT(22);
    if (wg == 2) {
        asm volatile("setmaxnreg.dec.sync.aligned.u32 40;");
        if (tail) {
            const int tile = T_LATE + (blockIdx.x >> 3), k0 = ((blockIdx.x & 7) * 8 + warp) * 64;
            e_expect(bar + 8 * warp, G_STAGE);
#pragma unroll
            for (int q = 0; q < 4; q++) e_tma_load(sb + warp * G_STAGE + 16384 + q * 8192, &tm.wo, (tile & 3) * 256 + q * 64, k0, bar + 8 * warp);
            wait_count(&g_ocnt[tile >> 2], NH * 4);
            asm volatile("fence.proxy.async;" ::: "memory");
            e_tma_load(sb + warp * G_STAGE, &tm.o, k0, (tile >> 2) * 128, bar + 8 * warp);
        }
        if (warp == 0) {
            if (lane == 0) {
                int it = 0;
                for (int tile = blockIdx.x; tile < ntiles; tile += gridDim.x) {
                    const int mb = tile & 15, nb = tile >> 4;
                    for (int kb = 0; kb < 16; kb++, it++) {
                        const int st = it % G_ST;
                        mbar_wait(bar + 8 * (G_ST + st), ((it / G_ST) & 1) ^ 1);
                        const uint32_t fb = bar + 8 * st, sa = sb + st * G_STAGE;
                        mbar_expect(fb, G_STAGE);
                        tma_load(sa, &tm.x, kb * 64, mb * 128, fb);
                        tma_load(sa + 16384, &tm.wg, nb * 128, kb * 64, fb);
                        tma_load(sa + 16384 + 8192, &tm.wg, nb * 128 + 64, kb * 64, fb);
                        tma_load(sa + 16384 + 16384, &tm.wu, nb * 128, kb * 64, fb);
                        tma_load(sa + 16384 + 24576, &tm.wu, nb * 128 + 64, kb * 64, fb);
                    }
                }
                for (int pass = tail ? 4 : 0; pass < 5; pass++) {
                    for (int i = g1_first(pass, tail); i < g1_count(pass, tail); i += gridDim.x) {
                        const int tile = g1_tile(pass, tail, i), mb = tile >> 2, nb = tile & 3;
                        if (pass < 2) {
                            for (int kb = 0; kb < FF / 64; kb++, it++) {
                                if (kb == 0 || kb == 2 * H_EARLY) {
                                    wait_count(&g_hcnt[kb ? 16 + mb : mb], kb ? 2 * (G1_NB - H_EARLY) : 2 * H_EARLY);
                                    asm volatile("fence.proxy.async;" ::: "memory");
                                }
                                g_load_block(sb, bar, it, &tm.h, kb * 64, mb * 128, &tm.wd, nb * 256);
                            }
                        }
                        if (pass > 0) {
                            const int k0 = pass == 3 ? (i & 3) * 16 : pass == 4 ? (i & 7) * 8 : 0, k1 = pass == 3 ? k0 + 16 : pass == 4 ? k0 + 8 : HD / 64;
                            if (!tail) wait_count(&g_ocnt[mb], NH * 4);
                            asm volatile("fence.proxy.async;" ::: "memory");
                            for (int kb = k0; kb < k1; kb++, it++) if (!tail || it >= G_ST) g_load_block(sb, bar, it, &tm.o, kb * 64, mb * 128, &tm.wo, nb * 256);
                        }
                    }
                }
            }
        }
    } else {
        asm volatile("setmaxnreg.inc.sync.aligned.u32 232;");
        float d[128];
        int it = 0;
        const uint32_t epi = sb + G_EPI + wg * 16384;
        const int row = warp * 16 + ((lane >> 3) & 1) * 8 + (lane & 7);
        for (int tile = blockIdx.x; tile < ntiles; tile += gridDim.x) {
            const int mb = tile & 15, nb = tile >> 4;
            const uint32_t* gp = &g_gate[mb * 128 + wg * 64 + warp * 16 + (lane >> 2)];
            uint32_t u0 = ld_strong4(gp), u1 = ld_strong4(gp + 8);
            for (int kb = 0; kb < 16; kb++, it++) g_mma_block(d, sb, bar, it, wg, tid, kb == 0);
            wg_wait<0>();
            for (uint32_t n = 0; u0 == 0u || u1 == 0u; n++) { u0 = ld_strong4(gp); u1 = ld_strong4(gp + 8); if (n > 20000000u) __trap(); }
            __syncwarp();
            const float s0 = 1.0f - __uint_as_float(u0), s1 = 1.0f - __uint_as_float(u1);
            if ((tid & 127) == 0) {
                mbar_arrive(bar + 8 * (G_ST + (it - 1) % G_ST));
                bulk_wait_all();
                const int pt = tile - (int)gridDim.x;
                if (pt >= 0) atomicAdd(&g_hcnt[(pt & 15) + ((pt >> 4) >= H_EARLY ? 16 : 0)], 1u);
            }
            bar_sync(1 + wg, 128);
#pragma unroll
            for (int j = 0; j < 16; j += 2) {
                uint32_t p[4];
#pragma unroll
                for (int q = 0; q < 4; q++) {
                    const int i = (j + (q >> 1)) * 4 + (q & 1) * 2;
                    const float sc = (q & 1) ? s1 : s0;
                    const float g0 = d[i], g1 = d[i + 1];
                    const float a0 = 1.0f + ex2(fminf(g0 * -1.4426950408889634f, 62.0f)), a1 = 1.0f + ex2(fminf(g1 * -1.4426950408889634f, 62.0f));
                    const float rr = rcp(a0 * a1) * sc;
                    const float h0 = (g0 * d[64 + i]) * (rr * a1);
                    const float h1 = (g1 * d[64 + i + 1]) * (rr * a0);
                    p[q] = pack_bf16(h0, h1);
                }
                const int cgp = j + (lane >> 4);
                stsm4(epi + (cgp >> 3) * 8192 + row * 128 + (((cgp & 7) ^ (row & 7)) << 4), p[0], p[1], p[2], p[3]);
            }
            fence_async();
            bar_sync(1 + wg, 128);
            if ((tid & 127) == 0) {
                tma_store(&tm.hs, epi, nb * 128, mb * 128 + wg * 64);
                tma_store(&tm.hs, epi + 8192, nb * 128 + 64, mb * 128 + wg * 64);
                bulk_commit();
            }
        }
        if ((tid & 127) == 0 && !tail) {
            bulk_wait_all();
            const int pt = blockIdx.x + (G1_TILES - 1 - blockIdx.x) / gridDim.x * gridDim.x;
            atomicAdd(&g_hcnt[(pt & 15) + ((pt >> 4) >= H_EARLY ? 16 : 0)], 1u);
        }
        for (int pass = tail ? 4 : 0; pass < 5; pass++) {
            for (int i = g1_first(pass, tail); i < g1_count(pass, tail); i += gridDim.x) {
                const int tile = g1_tile(pass, tail, i);
                const int nkb = pass == 0 ? FF / 64 : pass == 1 ? (FF + HD) / 64 : pass == 2 ? HD / 64 : pass == 3 ? 16 : 8;
                float4* pre = g_pre + (tile - NFULL) * (32 * 256) + tid;
                if (tail) PT(23);
                if (tail) asm volatile("prefetch.global.L2 [%0];" ::"l"(pre - tid + (i & 7) * 1024 + tid * 4));
                for (int kb = 0; kb < nkb; kb++, it++) { g_mma_block(d, sb, bar, it, wg, tid, kb == 0); if (tail && kb == 0) PT(18); }
                wg_wait<0>();
                if (tail) PT(19);
                if ((tid & 127) == 0) mbar_arrive(bar + 8 * (G_ST + (it - 1) % G_ST));
                if (pass >= 2) { if ((tid & 31) == 0) wait_count(&g_pcnt[tile], 8); __syncwarp(); }
                if (pass == 0) {
#pragma unroll
                    for (int q = 0; q < 32; q++) __stcg(pre + q * 256, make_float4(d[4 * q], d[4 * q + 1], d[4 * q + 2], d[4 * q + 3]));
                    __threadfence();
                    __syncwarp();
                    if ((tid & 31) == 0) atomicAdd(&g_pcnt[tile], 1u);
                } else if (pass == 3) {
                    float4 r[8];
#pragma unroll
                    for (int q = 0; q < 8; q++) r[q] = __ldcg(pre + ((i & 3) * 8 + q) * 256);
                    g_split_finish<4>(d, r, g_sk + (tile - T_MID) * 8 * (16 * 256), tile, i & 3, out, tid);
                } else if (pass == 4) {
                    float4 r[4];
#pragma unroll
                    for (int q = 0; q < 4; q++) r[q] = __ldcg(pre + ((i & 7) * 4 + q) * 256);
                    g_split_finish<8>(d, r, g_sk + (tile - T_MID) * 8 * (16 * 256), tile, i & 7, out, tid);
                } else {
                    if (pass == 2) {
#pragma unroll
                        for (int q = 0; q < 32; q++) {
                            const float4 u = __ldcg(pre + q * 256); d[4 * q] += u.x; d[4 * q + 1] += u.y; d[4 * q + 2] += u.z; d[4 * q + 3] += u.w;
                            if ((q & 7) == 7) __syncwarp();
                        }
                    }
                    g_store_tile(d, &tm.out, epi, tile >> 2, tile & 3, wg, tid);
                }
            }
        }
        if ((tid & 127) == 0) bulk_wait_all();
        KT(1 + tail, 1);
        if (wg == 0) {
            uint32_t last = blockIdx.x == 0;
            if (tail) {
                if (tid == 0) sts32(bar + 64, atomicAdd(&g_ticket, 1u) == gridDim.x - 1);
                bar_sync(1, 128);
                asm volatile("ld.shared.b32 %0, [%1];" : "=r"(last) : "r"(bar + 64) : "memory");
            }
            if (last) {
                asm volatile("griddepcontrol.wait;" ::: "memory");
                if (tail) {
                    for (int i = tid; i < SEQ; i += 128) g_gate[i] = 0u;
                    if (tid < 64) g_pcnt[tid] = 0u;
                    if (tid < 32) g_hcnt[tid] = 0u;
                    if (tid < 16) g_ocnt[tid] = 0u;
                    if (tid == 0) g_ticket = 0u;
                }
            }
        }
    }
}

__device__ bf16 f_qkv[3][(SEQ + NMEM) * HD];
__device__ bf16 f_mem[NMEM * DM], f_om[NMEM * HD];

__global__ void __launch_bounds__(256) f_gemm(const bf16* __restrict__ A, const bf16* __restrict__ B, bf16* __restrict__ C, int K, int N) {
    __shared__ float sa[8][256];
    const int n = blockIdx.x * 256 + threadIdx.x, m0 = blockIdx.y * 8;
    float acc[8] = {0.f, 0.f, 0.f, 0.f, 0.f, 0.f, 0.f, 0.f};
    for (int k0 = 0; k0 < K; k0 += 256) {
        __syncthreads();
        for (int r = 0; r < 8; r++) sa[r][threadIdx.x] = __bfloat162float(A[(size_t)(m0 + r) * K + k0 + threadIdx.x]);
        __syncthreads();
        for (int k = 0; k < 256; k++) {
            const float b = __bfloat162float(B[(size_t)(k0 + k) * N + n]);
#pragma unroll
            for (int r = 0; r < 8; r++) acc[r] = fmaf(sa[r][k], b, acc[r]);
        }
    }
    for (int r = 0; r < 8; r++) C[(size_t)(m0 + r) * N + n] = __float2bfloat16(acc[r]);
}
__global__ void __launch_bounds__(32) f_gate(const bf16* __restrict__ x, const bf16* __restrict__ gate_w) {
    uint4 xv[4], gv[4];
    for (int i = 0; i < 4; i++) { xv[i] = ldg_nc((const uint4*)(x + blockIdx.x * DM) + i * 32 + threadIdx.x); gv[i] = ldg_nc((const uint4*)gate_w + i * 32 + threadIdx.x); }
    const uint32_t g = __float_as_uint(gate_row(xv, gv));
    if (threadIdx.x == 0) { g_gate[blockIdx.x] = g ? g : 0x80000000u; if (blockIdx.x < 16) g_ocnt[blockIdx.x] = NH * 4; }
}
__global__ void __launch_bounds__(128) f_attn(int s) {
    __shared__ float sq[DH], sp[NMEM + SEG];
    const int h = blockIdx.x, i = blockIdx.y, t = threadIdx.x;
    auto row = [&](int r) { return (size_t)(r < NMEM ? SEQ + r : s * SEG + r - NMEM) * HD + h * DH; };
    sq[t] = __bfloat162float(f_qkv[0][row(i) + t]);
    __syncthreads();
    if (t < NMEM + SEG) {
        float a = 0.f;
        for (int e = 0; e < DH; e++) a = fmaf(sq[e], __bfloat162float(f_qkv[1][row(t) + e]), a);
        sp[t] = (i < NMEM || i >= t) ? a * 0.08838834764831845f : -1000000000.0f;
    }
    __syncthreads();
    float m = sp[0], l = 0.f, o = 0.f;
    for (int j = 1; j < NMEM + SEG; j++) m = fmaxf(m, sp[j]);
    for (int j = 0; j < NMEM + SEG; j++) { const float p = __expf(sp[j] - m); l += p; o = fmaf(p, __bfloat162float(f_qkv[2][row(j) + t]), o); }
    if (i < NMEM) f_om[i * HD + h * DH + t] = __float2bfloat16(o / l);
    else g_O[(size_t)(s * SEG + i - NMEM) * HD + h * DH + t] = __float2bfloat16(o / l * __uint_as_float(g_gate[s * SEG + i - NMEM]));
}

typedef CUresult (*EncodeFn)(CUtensorMap*, CUtensorMapDataType, cuuint32_t, void*, const cuuint64_t*, const cuuint64_t*, const cuuint32_t*,
                             const cuuint32_t*, CUtensorMapInterleave, CUtensorMapSwizzle, CUtensorMapL2promotion, CUtensorMapFloatOOBfill);

static void make_map(EncodeFn enc, CUtensorMap* m, const void* ptr, uint64_t rows, uint64_t cols, uint32_t box_rows) {
    cuuint64_t dims[2] = {cols, rows};
    cuuint64_t strides[1] = {cols * 2};
    cuuint32_t box[2] = {64, box_rows};
    cuuint32_t es[2] = {1, 1};
    enc(m, CU_TENSOR_MAP_DATA_TYPE_BFLOAT16, 2, (void*)ptr, dims, strides, box, es, CU_TENSOR_MAP_INTERLEAVE_NONE,
        CU_TENSOR_MAP_SWIZZLE_128B, CU_TENSOR_MAP_L2_PROMOTION_L2_256B, CU_TENSOR_MAP_FLOAT_OOB_FILL_NONE);
}

extern "C" void kernel_launch(void* const* d_in, const int* in_sizes, int n_in, void* d_out, int out_size) {
    (void)in_sizes; (void)n_in; (void)out_size;
    const bf16* x = (const bf16*)d_in[0];
    const bf16* mem0 = (const bf16*)d_in[1];
    const bf16* gate_w = (const bf16*)d_in[11];
    static EncodeFn enc = nullptr;
    static int n_sm = 0;
    static void *pO = nullptr, *pH = nullptr, *pQ = nullptr, *pM = nullptr, *pOm = nullptr;
    static int n_clusters = 0;
    if (!enc) {
        void* fn = nullptr;
        cudaDriverEntryPointQueryResult qr;
        cudaGetDriverEntryPoint("cuTensorMapEncodeTiled", &fn, cudaEnableDefault, &qr);
        enc = (EncodeFn)fn;
        cudaDeviceGetAttribute(&n_sm, cudaDevAttrMultiProcessorCount, 0);
        cudaFuncSetAttribute(r_kernel, cudaFuncAttributeMaxDynamicSharedMemorySize, R_SMEM);
        cudaFuncSetAttribute(g1_kernel, cudaFuncAttributeMaxDynamicSharedMemorySize, G_SMEM);
        cudaGetSymbolAddress(&pO, g_O);
        cudaGetSymbolAddress(&pH, g_H);
        cudaGetSymbolAddress(&pQ, f_qkv);
        cudaGetSymbolAddress(&pM, f_mem);
        cudaGetSymbolAddress(&pOm, f_om);
        cudaLaunchConfig_t cfg = {};
        cfg.gridDim = dim3(96); cfg.blockDim = dim3(384); cfg.dynamicSmemBytes = R_SMEM;
        cudaLaunchAttribute at[1];
        at[0].id = cudaLaunchAttributeClusterDimension; at[0].val.clusterDim.x = 3; at[0].val.clusterDim.y = 1; at[0].val.clusterDim.z = 1;
        cfg.attrs = at; cfg.numAttrs = 1;
        if (cudaOccupancyMaxActiveClusters(&n_clusters, r_kernel, &cfg) != cudaSuccess) { n_clusters = 0; (void)cudaGetLastError(); }
    }
    RMaps rm; G1Maps m1;
    make_map(enc, &rm.x, x, SEQ, DM, 32);
    for (int i = 0; i < 3; i++) make_map(enc, &rm.w[i], d_in[2 + i], DM, HD, 64);
    make_map(enc, &rm.wo, d_in[5], HD, DM, 128);
    make_map(enc, &rm.o, pO, SEQ, HD, 16);
    make_map(enc, &m1.x, x, SEQ, DM, 128);
    make_map(enc, &m1.wg, d_in[8], DM, FF, 64);
    make_map(enc, &m1.wu, d_in[9], DM, FF, 64);
    make_map(enc, &m1.hs, pH, SEQ, FF, 64);
    make_map(enc, &m1.o, pO, SEQ, HD, 128);
    make_map(enc, &m1.h, pH, SEQ, FF, 128);
    make_map(enc, &m1.wo, d_in[5], HD, DM, 64);
    make_map(enc, &m1.wd, d_in[10], FF, DM, 64);
    make_map(enc, &m1.out, d_out, SEQ, DM, 64);

    cudaStream_t st = cudaStreamPerThread;
    if (n_clusters < NH) {
        bf16* qkv = (bf16*)pQ;
        const size_t plane = (size_t)(SEQ + NMEM) * HD;
        f_gate<<<SEQ, 32, 0, st>>>(x, gate_w);
        for (int i = 0; i < 3; i++) f_gemm<<<dim3(HD / 256, SEQ / 8), 256, 0, st>>>(x, (const bf16*)d_in[2 + i], qkv + i * plane, DM, HD);
        for (int s = 0; s < NSEG; s++) {
            for (int i = 0; i < 3; i++)
                f_gemm<<<dim3(HD / 256, 1), 256, 0, st>>>(s ? (const bf16*)pM : mem0, (const bf16*)d_in[2 + i], qkv + i * plane + (size_t)SEQ * HD, DM, HD);
            f_attn<<<dim3(NH, NMEM + SEG), 128, 0, st>>>(s);
            f_gemm<<<dim3(DM / 256, 1), 256, 0, st>>>((const bf16*)pOm, (const bf16*)d_in[5], (bf16*)pM, HD, DM);
        }
    } else {
        cudaLaunchConfig_t cfg = {};
        cfg.gridDim = dim3(96); cfg.blockDim = dim3(384); cfg.dynamicSmemBytes = R_SMEM; cfg.stream = st;
        cudaLaunchAttribute at[1];
        at[0].id = cudaLaunchAttributeClusterDimension; at[0].val.clusterDim.x = 3; at[0].val.clusterDim.y = 1; at[0].val.clusterDim.z = 1;
        cfg.attrs = at; cfg.numAttrs = 1;
        cudaLaunchKernelEx(&cfg, r_kernel, rm, mem0, x, gate_w);
    }
    {
        cudaLaunchConfig_t cfg = {};
        cfg.gridDim = dim3(n_sm - 96 > 32 ? n_sm - 96 : 32); cfg.blockDim = dim3(384); cfg.dynamicSmemBytes = G_SMEM; cfg.stream = st;
        cudaLaunchAttribute at[1];
        at[0].id = cudaLaunchAttributeProgrammaticStreamSerialization; at[0].val.programmaticStreamSerializationAllowed = 1;
        cfg.attrs = at; cfg.numAttrs = n_clusters < NH ? 0 : 1;
        cudaLaunchKernelEx(&cfg, g1_kernel, m1, (bf16*)d_out, 0);
    }
    {
        cudaLaunchConfig_t cfg = {};
        cfg.gridDim = dim3((64 - T_LATE) * 8); cfg.blockDim = dim3(384); cfg.dynamicSmemBytes = G_SMEM; cfg.stream = st;
        cudaLaunchAttribute at[1];
        at[0].id = cudaLaunchAttributeProgrammaticStreamSerialization; at[0].val.programmaticStreamSerializationAllowed = 1;
        cfg.attrs = at; cfg.numAttrs = 1;
        cudaLaunchKernelEx(&cfg, g1_kernel, m1, (bf16*)d_out, 1);
    }
}
```

```cpp
#include <cuda_runtime.h>
#include <cuda_bf16.h>
#include <cuda.h>
#include <stdint.h>

typedef __nv_bfloat16 bf16;

constexpr int SEQ = 2048, DM = 1024, NH = 32, DH = 128, NMEM = 8, SEG = 32, NSEG = 64, FF = 3584;
constexpr int HD = NH * DH;

__device__ bf16 g_O[SEQ * HD];
__device__ bf16 g_H[SEQ * FF];
__device__ uint32_t g_gate[SEQ];
__device__ uint32_t g_part[4][128 * 32 * 32];
__device__ uint32_t g_mem[4][DM * 4];
#define TLATE 52
constexpr int NFULL = 36, T_MID = 44, T_MID2 = 48, T_LATE = TLATE;
constexpr int NPRE = 64 - NFULL;
__device__ float4 g_pre[NPRE * 32 * 256];
__device__ uint4 g_sk[(64 - T_MID) * 8 * 16 * 256];
__device__ uint32_t g_skcnt[64], g_pcnt[64], g_ticket;
__device__ uint32_t g_hcnt[32], g_ocnt[16];
#define KT(k, i)
#define PT(i)

#define DEVINL __device__ __forceinline__

DEVINL uint32_t smem_u32(const void* p) { return (uint32_t)__cvta_generic_to_shared(p); }
DEVINL void mbar_init(uint32_t bar, uint32_t cnt) { asm volatile("mbarrier.init.shared::cta.b64 [%0], %1;" ::"r"(bar), "r"(cnt) : "memory"); }
DEVINL void mbar_arrive(uint32_t bar) { asm volatile("mbarrier.arrive.shared::cta.b64 _, [%0];" ::"r"(bar) : "memory"); }
DEVINL void mbar_expect(uint32_t bar, uint32_t bytes) { asm volatile("mbarrier.arrive.expect_tx.shared::cta.b64 _, [%0], %1;" ::"r"(bar), "r"(bytes) : "memory"); }
DEVINL void mbar_arrive_remote(uint32_t cbar) { asm volatile("mbarrier.arrive.relaxed.cluster.shared::cluster.b64 _, [%0];" ::"r"(cbar) : "memory"); }
DEVINL bool mbar_try(uint32_t bar, uint32_t par) {
    uint32_t ok;
    asm volatile("{ .reg .pred p; mbarrier.try_wait.parity.shared::cta.b64 p, [%1], %2; selp.u32 %0, 1, 0, p; }" : "=r"(ok) : "r"(bar), "r"(par) : "memory");
    return ok;
}
DEVINL void mbar_wait(uint32_t bar, uint32_t par) {
    uint32_t n = 0;
    while (!mbar_try(bar, par)) { if (++n > 50000000u) __trap(); }
}
DEVINL uint32_t mapa(uint32_t a, uint32_t r) { uint32_t o; asm volatile("mapa.shared::cluster.u32 %0, %1, %2;" : "=r"(o) : "r"(a), "r"(r)); return o; }
DEVINL void fence_async() { asm volatile("fence.proxy.async.shared::cta;" ::: "memory"); }
DEVINL void bar_sync(int id, int n) { asm volatile("bar.sync %0, %1;" ::"r"(id), "r"(n) : "memory"); }
DEVINL void cluster_sync() { asm volatile("barrier.cluster.arrive.aligned; barrier.cluster.wait.aligned;" ::: "memory"); }
DEVINL void tma_load(uint32_t dst, const CUtensorMap* tm, int c0, int c1, uint32_t bar) {
    asm volatile("cp.async.bulk.tensor.2d.shared::cluster.global.mbarrier::complete_tx::bytes [%0], [%1, {%3, %4}], [%2];"
                 ::"r"(dst), "l"(tm), "r"(bar), "r"(c0), "r"(c1) : "memory");
}
DEVINL void tma_prefetch(const CUtensorMap* tm, int c0, int c1) {
    asm volatile("cp.async.bulk.prefetch.tensor.2d.L2.global [%0, {%1, %2}];" ::"l"(tm), "r"(c0), "r"(c1) : "memory");
}
DEVINL void tma_store(const CUtensorMap* tm, uint32_t src, int c0, int c1) {
    asm volatile("cp.async.bulk.tensor.2d.global.shared::cta.bulk_group [%0, {%2, %3}], [%1];" ::"l"(tm), "r"(src), "r"(c0), "r"(c1) : "memory");
}
DEVINL void bulk_commit() { asm volatile("cp.async.bulk.commit_group;" ::: "memory"); }
DEVINL void bulk_wait_read() { asm volatile("cp.async.bulk.wait_group.read 0;" ::: "memory"); }
DEVINL void bulk_wait_all() { asm volatile("cp.async.bulk.wait_group 0;" ::: "memory"); }
DEVINL void bulk_s2s(uint32_t cdst, uint32_t src, uint32_t bytes, uint32_t cbar) {
    asm volatile("cp.async.bulk.shared::cluster.shared::cta.mbarrier::complete_tx::bytes [%0], [%1], %2, [%3];" ::"r"(cdst), "r"(src), "r"(bytes), "r"(cbar) : "memory");
}
DEVINL void st_async16(uint32_t cdst, uint4 v, uint32_t cbar) {
    asm volatile("st.async.shared::cluster.mbarrier::complete_tx::bytes.v4.b32 [%0], {%1,%2,%3,%4}, [%5];" ::"r"(cdst), "r"(v.x), "r"(v.y), "r"(v.z), "r"(v.w), "r"(cbar) : "memory");
}
DEVINL uint64_t mkdesc(uint32_t addr, uint32_t lbo, uint32_t sbo, uint32_t swz) {
    return (uint64_t)((addr & 0x3FFFF) >> 4) | ((uint64_t)(lbo >> 4) << 16) | ((uint64_t)(sbo >> 4) << 32) | ((uint64_t)swz << 62);
}
constexpr uint32_t SB0 = 1024;
__host__ __device__ constexpr uint64_t cdesc(uint32_t off, uint32_t lbo, uint32_t sbo, uint32_t swz) {
    return (uint64_t)(((SB0 + off) & 0x3FFFF) >> 4) | ((uint64_t)(lbo >> 4) << 16) | ((uint64_t)(sbo >> 4) << 32) | ((uint64_t)swz << 62);
}
DEVINL float rcp(float x) { float y; asm("rcp.approx.ftz.f32 %0, %1;" : "=f"(y) : "f"(x)); return y; }
DEVINL float ex2(float x) { float y; asm("ex2.approx.ftz.f32 %0, %1;" : "=f"(y) : "f"(x)); return y; }
#define OPAQUE(x) asm volatile("" : "+r"(x))
DEVINL void wg_fence() { asm volatile("wgmma.fence.sync.aligned;" ::: "memory"); }
DEVINL void wg_commit() { asm volatile("wgmma.commit_group.sync.aligned;" ::: "memory"); }
template <int N> DEVINL void wg_wait() { asm volatile("wgmma.wait_group.sync.aligned %0;" ::"n"(N) : "memory"); }
DEVINL uint32_t pack_bf16(float lo, float hi) { uint32_t r; asm("cvt.rn.bf16x2.f32 %0, %1, %2;" : "=r"(r) : "f"(hi), "f"(lo)); return r; }
DEVINL void ldsm4(uint32_t* r, uint32_t a) { asm volatile("ldmatrix.sync.aligned.m8n8.x4.shared.b16 {%0,%1,%2,%3}, [%4];" : "=r"(r[0]), "=r"(r[1]), "=r"(r[2]), "=r"(r[3]) : "r"(a) : "memory"); }
DEVINL void ldsm4t(uint32_t* r, uint32_t a) { asm volatile("ldmatrix.sync.aligned.m8n8.x4.trans.shared.b16 {%0,%1,%2,%3}, [%4];" : "=r"(r[0]), "=r"(r[1]), "=r"(r[2]), "=r"(r[3]) : "r"(a) : "memory"); }
DEVINL void ldsm4_if(uint32_t* r, uint32_t a, int c) { asm volatile("{ .reg .pred p; setp.ne.s32 p, %5, 0; @p ldmatrix.sync.aligned.m8n8.x4.shared.b16 {%0,%1,%2,%3}, [%4]; }" : "+r"(r[0]), "+r"(r[1]), "+r"(r[2]), "+r"(r[3]) : "r"(a), "r"(c) : "memory"); }
DEVINL void ldsm4t_if(uint32_t* r, uint32_t a, int c) { asm volatile("{ .reg .pred p; setp.ne.s32 p, %5, 0; @p ldmatrix.sync.aligned.m8n8.x4.trans.shared.b16 {%0,%1,%2,%3}, [%4]; }" : "+r"(r[0]), "+r"(r[1]), "+r"(r[2]), "+r"(r[3]) : "r"(a), "r"(c) : "memory"); }
DEVINL void stsm4(uint32_t a, uint32_t r0, uint32_t r1, uint32_t r2, uint32_t r3) { asm volatile("stmatrix.sync.aligned.m8n8.x4.shared.b16 [%0], {%1,%2,%3,%4};" ::"r"(a), "r"(r0), "r"(r1), "r"(r2), "r"(r3) : "memory"); }
DEVINL void stsm4t(uint32_t a, uint32_t r0, uint32_t r1, uint32_t r2, uint32_t r3) { asm volatile("stmatrix.sync.aligned.m8n8.x4.trans.shared.b16 [%0], {%1,%2,%3,%4};" ::"r"(a), "r"(r0), "r"(r1), "r"(r2), "r"(r3) : "memory"); }
DEVINL void sts32(uint32_t a, uint32_t v) { asm volatile("st.shared.b32 [%0], %1;" ::"r"(a), "r"(v) : "memory"); }
DEVINL void sts128(uint32_t a, uint4 v) { asm volatile("st.shared.v4.b32 [%0], {%1,%2,%3,%4};" ::"r"(a), "r"(v.x), "r"(v.y), "r"(v.z), "r"(v.w) : "memory"); }
DEVINL uint4 lds128(uint32_t a) { uint4 v; asm volatile("ld.shared.v4.b32 {%0,%1,%2,%3}, [%4];" : "=r"(v.x), "=r"(v.y), "=r"(v.z), "=r"(v.w) : "r"(a) : "memory"); return v; }
DEVINL uint4 ld_strong16(const void* p) { uint4 v; asm volatile("ld.relaxed.gpu.global.v4.u32 {%0,%1,%2,%3}, [%4];" : "=r"(v.x), "=r"(v.y), "=r"(v.z), "=r"(v.w) : "l"(p) : "memory"); return v; }
DEVINL void st_strong8(void* p, uint32_t a, uint32_t b) { asm volatile("st.relaxed.gpu.global.v2.u32 [%0], {%1,%2};" ::"l"(p), "r"(a), "r"(b) : "memory"); }
DEVINL void st_strong4(void* p, uint32_t a) { asm volatile("st.relaxed.gpu.global.u32 [%0], %1;" ::"l"(p), "r"(a) : "memory"); }
DEVINL void st_strong16(void* p, uint4 v) { asm volatile("st.relaxed.gpu.global.v4.u32 [%0], {%1,%2,%3,%4};" ::"l"(p), "r"(v.x), "r"(v.y), "r"(v.z), "r"(v.w) : "memory"); }
DEVINL uint32_t pack_nz(float lo, float hi) { uint32_t r = pack_bf16(lo, hi); return r == 0u ? 0x8000u : r; }
DEVINL uint32_t min4(uint4 v, uint32_t m) { return __vimin3_u32(__vimin3_u32(v.x, v.y, m), v.z, v.w); }
DEVINL void mma16816(float* d, uint32_t a0, uint32_t a1, uint32_t a2, uint32_t a3, uint32_t b0, uint32_t b1) {
    asm volatile("mma.sync.aligned.m16n8k16.row.col.f32.bf16.bf16.f32 {%0,%1,%2,%3}, {%4,%5,%6,%7}, {%8,%9}, {%0,%1,%2,%3};"
                 : "+f"(d[0]), "+f"(d[1]), "+f"(d[2]), "+f"(d[3]) : "r"(a0), "r"(a1), "r"(a2), "r"(a3), "r"(b0), "r"(b1));
}
DEVINL void mma1688(float* d, uint32_t a0, uint32_t a1, uint32_t b0) {
    asm volatile("mma.sync.aligned.m16n8k8.row.col.f32.bf16.bf16.f32 {%0,%1,%2,%3}, {%4,%5}, {%6}, {%0,%1,%2,%3};"
                 : "+f"(d[0]), "+f"(d[1]), "+f"(d[2]), "+f"(d[3]) : "r"(a0), "r"(a1), "r"(b0));
}
template <int TA, int TB> DEVINL void wg_ss8(float* d, uint64_t da, uint64_t db, int sc) {
    asm volatile("{ .reg .pred p; setp.ne.b32 p, %6, 0; wgmma.mma_async.sync.aligned.m64n8k16.f32.bf16.bf16 {%0,%1,%2,%3}, %4, %5, p, 1, 1, %7, %8; }"
                 : "+f"(d[0]), "+f"(d[1]), "+f"(d[2]), "+f"(d[3]) : "l"(da), "l"(db), "r"(sc), "n"(TA), "n"(TB));
}
template <int TB> DEVINL void wg_rs8(float* d, const uint32_t* a, uint64_t db, int sc) {
    asm volatile("{ .reg .pred p; setp.ne.b32 p, %9, 0; wgmma.mma_async.sync.aligned.m64n8k16.f32.bf16.bf16 {%0,%1,%2,%3}, {%4,%5,%6,%7}, %8, p, 1, 1, %10; }"
                 : "+f"(d[0]), "+f"(d[1]), "+f"(d[2]), "+f"(d[3]) : "r"(a[0]), "r"(a[1]), "r"(a[2]), "r"(a[3]), "l"(db), "r"(sc), "n"(TB));
}
#define ACC16(d) "+f"(d[0]), "+f"(d[1]), "+f"(d[2]), "+f"(d[3]), "+f"(d[4]), "+f"(d[5]), "+f"(d[6]), "+f"(d[7]), "+f"(d[8]), "+f"(d[9]), "+f"(d[10]), "+f"(d[11]), "+f"(d[12]), "+f"(d[13]), "+f"(d[14]), "+f"(d[15])
template <int TA> DEVINL void wg_ss32(float* d, uint64_t da, uint64_t db, int sc) {
    asm volatile("{ .reg .pred p; setp.ne.b32 p, %18, 0; wgmma.mma_async.sync.aligned.m64n32k16.f32.bf16.bf16 {%0,%1,%2,%3,%4,%5,%6,%7,%8,%9,%10,%11,%12,%13,%14,%15}, %16, %17, p, 1, 1, %19, 0; }"
                 : ACC16(d) : "l"(da), "l"(db), "r"(sc), "n"(TA));
}
DEVINL void wg_rs32(float* d, const uint32_t* a, uint64_t db, int sc) {
    asm volatile("{ .reg .pred p; setp.ne.b32 p, %21, 0; wgmma.mma_async.sync.aligned.m64n32k16.f32.bf16.bf16 {%0,%1,%2,%3,%4,%5,%6,%7,%8,%9,%10,%11,%12,%13,%14,%15}, {%16,%17,%18,%19}, %20, p, 1, 1, 0; }"
                 : ACC16(d) : "r"(a[0]), "r"(a[1]), "r"(a[2]), "r"(a[3]), "l"(db), "r"(sc));
}
DEVINL void wg_ss40(float* d, uint64_t da, uint64_t db, int sc) {
    asm volatile("{ .reg .pred p; setp.ne.b32 p, %22, 0; wgmma.mma_async.sync.aligned.m64n40k16.f32.bf16.bf16 {%0,%1,%2,%3,%4,%5,%6,%7,%8,%9,%10,%11,%12,%13,%14,%15,%16,%17,%18,%19}, %20, %21, p, 1, 1, 1, 1; }"
                 : ACC16(d), "+f"(d[16]), "+f"(d[17]), "+f"(d[18]), "+f"(d[19]) : "l"(da), "l"(db), "r"(sc));
}
#define A8(d, o) "+f"(d[o]), "+f"(d[o + 1]), "+f"(d[o + 2]), "+f"(d[o + 3]), "+f"(d[o + 4]), "+f"(d[o + 5]), "+f"(d[o + 6]), "+f"(d[o + 7])
#define A32(d, o) A8(d, o), A8(d, o + 8), A8(d, o + 16), A8(d, o + 24)
DEVINL void wg_ss256(float* d, uint64_t da, uint64_t db, int sc) {
    asm volatile(
        "{ .reg .pred p; setp.ne.b32 p, %130, 0;\n"
        "wgmma.mma_async.sync.aligned.m64n256k16.f32.bf16.bf16 {"
        "%0,%1,%2,%3,%4,%5,%6,%7,%8,%9,%10,%11,%12,%13,%14,%15,%16,%17,%18,%19,%20,%21,%22,%23,%24,%25,%26,%27,%28,%29,%30,%31,"
        "%32,%33,%34,%35,%36,%37,%38,%39,%40,%41,%42,%43,%44,%45,%46,%47,%48,%49,%50,%51,%52,%53,%54,%55,%56,%57,%58,%59,%60,%61,%62,%63,"
        "%64,%65,%66,%67,%68,%69,%70,%71,%72,%73,%74,%75,%76,%77,%78,%79,%80,%81,%82,%83,%84,%85,%86,%87,%88,%89,%90,%91,%92,%93,%94,%95,"
        "%96,%97,%98,%99,%100,%101,%102,%103,%104,%105,%106,%107,%108,%109,%110,%111,%112,%113,%114,%115,%116,%117,%118,%119,%120,%121,%122,%123,%124,%125,%126,%127"
        "}, %128, %129, p, 1, 1, 0, 1; }"
        : A32(d, 0), A32(d, 32), A32(d, 64), A32(d, 96) : "l"(da), "l"(db), "r"(sc));
}

DEVINL float gate_row(const uint4 (&xv)[4], const uint4 (&gv)[4]) {
    float acc = 0.f;
#pragma unroll
    for (int i = 0; i < 4; i++) {
        const uint32_t xa[4] = {xv[i].x, xv[i].y, xv[i].z, xv[i].w}, ga[4] = {gv[i].x, gv[i].y, gv[i].z, gv[i].w};
#pragma unroll
        for (int e = 0; e < 4; e++) {
            acc = fmaf(__uint_as_float(xa[e] << 16), __uint_as_float(ga[e] << 16), acc);
            acc = fmaf(__uint_as_float(xa[e] & 0xffff0000u), __uint_as_float(ga[e] & 0xffff0000u), acc);
        }
    }
#pragma unroll
    for (int o = 16; o > 0; o >>= 1) acc += __shfl_xor_sync(0xffffffffu, acc, o);
    return 1.0f / (1.0f + __expf(-acc));
}
DEVINL uint4 ldg_nc(const void* p) { uint4 v; asm volatile("ld.global.nc.v4.u32 {%0,%1,%2,%3}, [%4];" : "=r"(v.x), "=r"(v.y), "=r"(v.z), "=r"(v.w) : "l"(p) : "memory"); return v; }
DEVINL uint32_t ld_strong4(const void* p) { uint32_t v; asm volatile("ld.relaxed.gpu.global.u32 %0, [%1];" : "=r"(v) : "l"(p) : "memory"); return v; }
DEVINL void wait_count(const uint32_t* p, uint32_t want) {
    uint32_t v, n = 0;
    while (true) {
        asm volatile("ld.acquire.gpu.global.u32 %0, [%1];" : "=r"(v) : "l"(p) : "memory");
        if (v >= want) break;
        __nanosleep(100);
        if (++n > 20000000u) __trap();
    }
}

constexpr int KR = 44;
constexpr int KS = 64 - KR;
constexpr int R_W = 0;
constexpr int R_WO = KS * 4096;
constexpr int R_QX = R_WO + 65536;
constexpr int R_RING = R_WO + 98304;
constexpr int R_K = R_RING + 24576;
constexpr int R_V = R_K + 10240;
constexpr int R_QM = R_V + 10240;
constexpr int R_O = R_QM + 2048;
constexpr int R_BAR = R_O + 2048;
constexpr int R_G = R_BAR + 256 + 512 + 256 + 128;
constexpr int R_Z = R_G + 256;
constexpr int R_SMEM = R_Z + 1024;
enum { B_FULL = 0, B_EMPTY = 5, B_MEM = 8, B_HOP1 = 12, B_XT, B_TFREE, B_O, B_AFREE0, B_AFREE1, B_PRO0, B_PRO1, B_XRECV, B_XDONE, B_HOPV };
#define D2_BASE 950
#define D2_STEP 180
#define DQ 1800
#define PVD 400
#define ELD 700
constexpr int QD = 3;

DEVINL uint32_t clk32() { uint32_t c_; asm volatile("mov.u32 %0, %%clock;" : "=r"(c_)); return c_; }
DEVINL void spin_until(uint32_t t) { while ((uint32_t)(t - clk32() - 1u) < 100000u) {} }
#define PROF(i)
#define PROF2(i)
#define PROF3(i, val)
DEVINL void e_arrive(uint32_t bar) { asm volatile("{ .reg .pred p; elect.sync _|p, 0xffffffff; @p mbarrier.arrive.shared::cta.b64 _, [%0]; }" ::"r"(bar) : "memory"); }
DEVINL void e_arrive_remote(uint32_t cbar) { asm volatile("{ .reg .pred p; elect.sync _|p, 0xffffffff; @p mbarrier.arrive.relaxed.cluster.shared::cluster.b64 _, [%0]; }" ::"r"(cbar) : "memory"); }
DEVINL void e_count(uint32_t* p) { asm volatile("{ .reg .pred p; elect.sync _|p, 0xffffffff; @p red.relaxed.gpu.global.add.u32 [%0], 1; }" ::"l"(p) : "memory"); }
DEVINL void e_expect(uint32_t bar, uint32_t bytes) { asm volatile("{ .reg .pred p; elect.sync _|p, 0xffffffff; @p mbarrier.arrive.expect_tx.shared::cta.b64 _, [%0], %1; }" ::"r"(bar), "r"(bytes) : "memory"); }
DEVINL void e_tma_load(uint32_t dst, const CUtensorMap* tm, int c0, int c1, uint32_t bar) {
    asm volatile("{ .reg .pred p; elect.sync _|p, 0xffffffff; @p cp.async.bulk.tensor.2d.shared::cluster.global.mbarrier::complete_tx::bytes [%0], [%1, {%3, %4}], [%2]; }"
                 ::"r"(dst), "l"(tm), "r"(bar), "r"(c0), "r"(c1) : "memory");
}
DEVINL void e_tma_store(const CUtensorMap* tm, uint32_t src, int c0, int c1) {
    asm volatile("{ .reg .pred p; elect.sync _|p, 0xffffffff; @p cp.async.bulk.tensor.2d.global.shared::cta.bulk_group [%0, {%2, %3}], [%1]; }" ::"l"(tm), "r"(src), "r"(c0), "r"(c1) : "memory");
}
DEVINL void e_bulk_s2g(void* dst, uint32_t src, uint32_t bytes) {
    asm volatile("{ .reg .pred p; elect.sync _|p, 0xffffffff; @p cp.async.bulk.global.shared::cta.bulk_group [%0], [%1], %2; }" ::"l"(dst), "r"(src), "r"(bytes) : "memory");
}
DEVINL void e_bulk_s2s(uint32_t cdst, uint32_t src, uint32_t bytes, uint32_t cbar) {
    asm volatile("{ .reg .pred p; elect.sync _|p, 0xffffffff; @p cp.async.bulk.shared::cluster.shared::cta.mbarrier::complete_tx::bytes [%0], [%1], %2, [%3]; }" ::"r"(cdst), "r"(src), "r"(bytes), "r"(cbar) : "memory");
}

template <int N> DEVINL uint32_t poll_set(uint4 (&v)[N], const uint32_t* rp, int stride) {
#pragma unroll
    for (int i = 0; i < N; i++) v[i] = ld_strong16(rp + i * stride);
    uint32_t n = 0;
    while (true) {
        uint32_t m = 0xffffffffu;
#pragma unroll
        for (int i = 0; i < N; i++) m = min4(v[i], m);
        if (__all_sync(0xffffffffu, m != 0u)) return n;
#pragma unroll
        for (int i = 0; i < N; i++)
            asm volatile("{ .reg .pred p; setp.eq.u32 p, %5, 0; @p ld.relaxed.gpu.global.v4.u32 {%0,%1,%2,%3}, [%4]; }"
                         : "+r"(v[i].x), "+r"(v[i].y), "+r"(v[i].z), "+r"(v[i].w) : "l"(rp + i * stride), "r"(min4(v[i], 0xffffffffu)) : "memory");
        if (++n > 5000000u) __trap();
    }
}

struct RMaps { CUtensorMap x, w[3], wo, o; };
#define KC(c) ((c) * 64)

__host__ __device__ constexpr int xo(int i) { return i < 10 ? ((i & 1) ? i / 2 : 11 + i / 2) : i - 5; }
#define XC(i) (xo(i) * 64)
DEVINL void x_load_pair(uint32_t dst, const CUtensorMap* tmx, int h, int p, int seg, uint32_t fbar) {
    e_expect(fbar, 8192);
    e_tma_load(dst, tmx, XC(2 * p), seg * SEG, fbar);
    e_tma_load(dst + 4096, tmx, XC(2 * p + 1), seg * SEG, fbar);
}
__host__ __device__ constexpr int wo_tile(int role, int i) {
    return role == 0 ? (i < 2 ? 8 + i : 12 + i) : (i < 4 ? (i >> 1) * 4 : 10) + (role - 1) * 2 + (i & 1);
}

template <int NT> DEVINL void wo_phase(uint32_t sb, int tb, uint32_t* pp, uint32_t obar, uint32_t opar) {
    const int lane = tb & 31, krow = (lane & 7) + ((lane >> 4) << 3), chunk = ((tb >> 5) & 3) * 2 + ((lane >> 3) & 1);
    uint32_t wa = sb + R_WO + (tb >> 7) * 16384 + krow * 128 + ((chunk ^ (krow & 7)) << 4);
    uint32_t af[4][4], of[4][4];
#pragma unroll
    for (int g = 0; g < 4; g++) ldsm4t(af[g], wa + g * 2048);
    mbar_wait(obar, opar);
#pragma unroll
    for (int g = 0; g < 4; g++) ldsm4t(of[g], sb + R_O + g * 512 + lane * 16);
#pragma unroll 1
    for (int i = 0; i < NT; i++) {
        float w0[4] = {0.f, 0.f, 0.f, 0.f}, w1[4] = {0.f, 0.f, 0.f, 0.f};
        const int more = NT - 1 - i, yes = NT - i;
        mma16816(w0, af[0][0], af[0][1], af[0][2], af[0][3], of[0][0], of[0][1]);
        ldsm4t_if(af[0], wa + 4 * 2048, yes);
        mma16816(w1, af[1][0], af[1][1], af[1][2], af[1][3], of[0][2], of[0][3]);
        ldsm4t_if(af[1], wa + 5 * 2048, yes);
        mma16816(w0, af[2][0], af[2][1], af[2][2], af[2][3], of[1][0], of[1][1]);
        ldsm4t_if(af[2], wa + 6 * 2048, yes);
        mma16816(w1, af[3][0], af[3][1], af[3][2], af[3][3], of[1][2], of[1][3]);
        ldsm4t_if(af[3], wa + 7 * 2048, yes);
        wa += 32768;
        mma16816(w0, af[0][0], af[0][1], af[0][2], af[0][3], of[2][0], of[2][1]);
        ldsm4t_if(af[0], wa, more);
        mma16816(w1, af[1][0], af[1][1], af[1][2], af[1][3], of[2][2], of[2][3]);
        ldsm4t_if(af[1], wa + 2048, more);
        mma16816(w0, af[2][0], af[2][1], af[2][2], af[2][3], of[3][0], of[3][1]);
        ldsm4t_if(af[2], wa + 2 * 2048, more);
        mma16816(w1, af[3][0], af[3][1], af[3][2], af[3][3], of[3][2], of[3][3]);
        ldsm4t_if(af[3], wa + 3 * 2048, more);
        st_strong4(pp, pack_nz(w0[0] + w1[0], w0[1] + w1[1]));
        st_strong4(pp + 1024, pack_nz(w0[2] + w1[2], w0[3] + w1[3]));
        pp += (NT == 3 && i == 0) ? 4 * 8192 : 6 * 8192;
    }
}

template <uint32_t role> DEVINL void r_big(const RMaps& tm, const int wid) {
    extern __shared__ __align__(1024) unsigned char smem_raw[];
    const uint32_t sb = smem_u32(smem_raw);
    const uint32_t bar = sb + R_BAR;
    const int tid = threadIdx.x;
    int h; asm("mov.u32 %0, %%clusterid.x;" : "=r"(h));
        uint32_t a[KR][4];
        {
            const int lane = tid & 31;
            const int krow = (lane & 7) + ((lane >> 4) << 3);
            const int chunk = (wid & 3) * 2 + ((lane >> 3) & 1);
            const uint32_t la = sb + (wid >> 2) * 8192 + krow * 128 + ((chunk ^ (krow & 7)) << 4);
            const CUtensorMap* tw = &tm.w[role];
#pragma unroll
            for (int b = 0; b < KR / 4; b++) {
                mbar_wait(sb + R_O + 8 * b, 0);
                if (b == 0) PT(0);
#pragma unroll
                for (int k = 0; k < 4; k++) ldsm4t(a[b * 4 + k], la + b * 16384 + k * 2048);
                if (b < 5 || b == KR / 4 - 1) bar_sync(1, 256);
                if (wid == b) {
                    fence_async();
                    if (b < 5) {
#pragma unroll
                        for (int q = 2 * b; q < 2 * b + 2; q++) e_tma_load(sb + R_W + q * 8192, tw, h * DH + (q / 5) * 64, KC(KR / 4 + q % 5), bar + 8 * B_PRO1);
                    }
                }
            }
        }
        constexpr uint32_t e0 = role == 0 ? R_QX + 16384 : R_K + 2048, e1 = role == 0 ? R_QX + 24576 : R_V + 2048;
        if (wid == 6) x_load_pair(sb + e0, &tm.x, h, 3, 0, bar + 8 * (B_FULL + 3));
        if (wid == 7) x_load_pair(sb + e1, &tm.x, h, 4, 0, bar + 8 * (B_FULL + 4));
        PT(1);
        mbar_wait(bar + 8 * B_PRO1, 0);
        PT(2);
        if (wid < (role == 0 ? 4 : 6)) { fence_async(); e_tma_load(sb + R_WO + wid * 16384, &tm.wo, wo_tile(role, wid) * 64, h * DH, bar + 8 * B_PRO0); }

        constexpr uint64_t dW0 = cdesc(R_W, 1024, 1024, 1);
        constexpr uint64_t dM = cdesc(R_RING, 128, 128, 0);
        constexpr uint64_t dX = cdesc(R_RING, 16, 1024, 1);
        constexpr uint64_t dX0 = cdesc(0, 16, 1024, 1);
        int tb = tid;
        int wq = wid;

        for (int seg = 0; seg < NSEG; seg++) {
            {
            const int s = seg - 1; (void)s;
            float d[16];
            OPAQUE(wq);
            const uint64_t dW = dW0 + (uint64_t)((wq >> 2) * (KS * 128));
#pragma unroll
            for (int p = 0; p < 8; p++) {
                const int slot = p % 5;
                mbar_wait(bar + 8 * (B_FULL + slot), slot < 3 ? (uint32_t)(p / 5) : (uint32_t)(seg & 1));
                PROF2(p);
                const uint64_t db = slot < 3 ? dX + (uint64_t)(slot * 512) : dX0 + (uint64_t)((slot == 3 ? e0 : e1) >> 4);
                wg_fence();
#pragma unroll
                for (int kk = 0; kk < 8; kk++) {
                    const int k = (kk & 1) * 4 + (kk >> 1);
                    const int ks = xo(2 * p + (k >> 2)) * 4 + (k & 3);
                    if (ks >= KR) wg_ss32<1>(d, dW + (uint64_t)((ks - KR) * 128), db + (uint64_t)((k >> 2) * 256 + (k & 3) * 2), p + k);
                    else wg_rs32(d, a[ks < KR ? ks : 0], db + (uint64_t)((k >> 2) * 256 + (k & 3) * 2), p + k);
                }
                wg_commit();
                if (p >= 1) {
                    wg_wait<1>();
                    if (p <= 3) { if ((wq & 3) == p) e_arrive(bar + 8 * (B_EMPTY + p - 1)); }
                    if (p <= 3) {
                        const int q = p;
                        if (wq == q + (q & 1) * 4) {
                            mbar_wait(bar + 8 * (B_EMPTY + q - 1), seg & 1);
                            x_load_pair(sb + R_RING + (q - 1) * 8192, &tm.x, h, q + 4, seg, bar + 8 * (B_FULL + q - 1));
                        }
                    }
                    if (p == 5 && role != 0 && (wq & 3) < 3) e_arrive_remote(mapa(bar + 8 * B_TFREE, wq & 3));
                    if (p == 6 && (wq & 3) == 1) e_arrive(bar + 8 * B_AFREE0);
                    if (p == 7 && (wq & 3) == 2) e_arrive(bar + 8 * B_AFREE1);
                }
            }
            mbar_wait(bar + 8 * B_TFREE, seg & 1);
            asm volatile("wgmma.wait_group.sync.aligned 0;" : ACC16(d)::"memory");
            PROF2(16);
            const uint32_t tilex = sb + (role == 0 ? R_QX + 2048 : (role == 1 ? R_K + 2048 : R_V + 2048));
            {
                OPAQUE(tb);
                const uint32_t gs = role == 0 ? 4096 : 2048;
                const uint32_t sa = tilex + ((tb >> 4) & 1) * gs + (tb >> 5) * 256 + (tb & 15) * 16;
                stsm4(sa, pack_bf16(d[0], d[1]), pack_bf16(d[2], d[3]), pack_bf16(d[4], d[5]), pack_bf16(d[6], d[7]));
                stsm4(sa + 2 * gs, pack_bf16(d[8], d[9]), pack_bf16(d[10], d[11]), pack_bf16(d[12], d[13]), pack_bf16(d[14], d[15]));
            }
            __syncwarp();
            e_arrive(bar + 8 * B_XDONE);
            if (role != 0 && (wq & 3) == 0) {
                mbar_wait(bar + 8 * B_XDONE, seg & 1);
                fence_async();
                uint32_t pr = role + 1 + (wq >> 2); pr = pr >= 3 ? pr - 3 : pr;
                e_bulk_s2s(mapa(tilex, pr), tilex, 8192, mapa(bar + 8 * B_XT, pr));
            }
            }
            {
                const int s = seg;
                OPAQUE(wq);
                const uint64_t dW = dW0 + (uint64_t)((wq >> 2) * (KS * 128));
                float y[4] = {0.f, 0.f, 0.f, 0.f};
                {
                    OPAQUE(tb);
                    const uint32_t ma = sb + R_RING + (tb & 31) * 16;
                    float z[4] = {0.f, 0.f, 0.f, 0.f}, u[4] = {0.f, 0.f, 0.f, 0.f};
                    uint32_t b[QD][4];
                    const int yes = s + 1;
                    mbar_wait(bar + 8 * B_MEM, s & 1);
                    PROF((wq >> 2) * 4 + 0);
                    if (s == 0) PT(3);
                    if (s == 1) PT(4);
#pragma unroll
                    for (int g = 0; g < QD; g++) ldsm4t(b[g], ma + g * 512);
#pragma unroll
                    for (int g = 0; g < KR / 2; g++) {
                        float* c0 = (g % 3 == 0) ? y : (g % 3 == 1) ? u : z;
                        float* c1 = (g % 3 == 0) ? z : (g % 3 == 1) ? y : u;
                        mma16816(c0, a[2 * g][0], a[2 * g][1], a[2 * g][2], a[2 * g][3], b[g % QD][0], b[g % QD][1]);
                        mma16816(c1, a[2 * g + 1][0], a[2 * g + 1][1], a[2 * g + 1][2], a[2 * g + 1][3], b[g % QD][2], b[g % QD][3]);
                        if (g + QD < KR / 2) {
                            if ((g + QD) % 8 == 0) mbar_wait(bar + 8 * (B_MEM + (g + QD) / 8), s & 1);
                            ldsm4t_if(b[g % QD], ma + (g + QD) * 512, yes);
                        }
                    }
                    y[0] += z[0] + u[0]; y[1] += z[1] + u[1]; y[2] += z[2] + u[2]; y[3] += z[3] + u[3];
                }
                PROF2(8);
                mbar_wait(bar + 8 * (B_MEM + 3), s & 1);
                wg_fence();
#pragma unroll
                for (int k = KR; k < 64; k++) {
                    wg_ss8<1, 1>(y, dW + (uint64_t)((k - KR) * 128), dM + (uint64_t)(k * 16), 1);
                }
                wg_commit();
                asm volatile("wgmma.wait_group.sync.aligned 0;" : "+f"(y[0]), "+f"(y[1]), "+f"(y[2]), "+f"(y[3])::"memory");
                OPAQUE(tb);
                {
                    const uint32_t wo_ = (tb >> 5) * 256;
                    const uint32_t tile = sb + (role == 0 ? R_QX : (role == 1 ? R_K : R_V)) + wo_;
                    const uint32_t u0 = pack_bf16(y[0], y[1]), u1 = pack_bf16(y[2], y[3]);
                    sts32(tile + (tb & 31) * 4, u0);
                    sts32(tile + (tb & 31) * 4 + 128, u1);
                    __syncwarp();
                    uint4 v = lds128(tile + (tb & 15) * 16);
                    uint32_t peer = role + 1 + ((tb >> 4) & 1);
                    peer = peer >= 3 ? peer - 3 : peer;
                    const uint32_t rt = sb + (role == 0 ? R_QM : (role == 1 ? R_K : R_V)) + wo_ + (tb & 15) * 16;
                    st_async16(mapa(rt, peer), v, mapa(bar + 8 * (role == 2 ? B_HOPV : B_HOP1), peer));
                    if (role == 0) {
                        sts128(tile + 4096 + ((tb >> 4) & 1) * 4096 + (tb & 15) * 16, v);
                        sts32(tile + 12288 + (tb & 31) * 4, u0);
                        sts32(tile + 12288 + (tb & 31) * 4 + 128, u1);
                        __syncwarp();
                    }
                    e_arrive(bar + 8 * (role == 2 ? B_HOPV : B_HOP1));
                }
                PROF((wq >> 2) * 4 + 1);
                if (s < NSEG - 1) {
                    bar_sync(1, 256);
                    if (wq < 3) { fence_async(); x_load_pair(sb + R_RING + wq * 8192, &tm.x, h, wq, s + 1, bar + 8 * (B_FULL + wq)); }
                    else if (role == 0 && wq < 5) x_load_pair(sb + (wq == 3 ? e0 : e1), &tm.x, h, wq, s + 1, bar + 8 * (B_FULL + wq));
                    OPAQUE(tb);
                }
                uint32_t* pp = g_part[s & 3] + (h * 32 + (wo_tile(role, 0) + (tb >> 7)) * 8192 + ((tb >> 5) & 3) * 2048 + (tb & 31));
                asm volatile("" : "+l"(pp));
                if (s == NSEG - 1) break;
                if (s == 0) mbar_wait(bar + 8 * B_PRO0, 0);
                wo_phase<role == 0 ? 2 : 3>(sb, tb, pp, bar + 8 * B_O, s & 1);
                if (wq == 0) PROF(10);
            }
        }
}

#define CLEAR(st) do { if (role != 0) { \
                const int w_ = wid & 3; \
                uint32_t* zp = g_part[(st) & 3] + ((rg0 + (w_ >> 1) * 64) * 1024 + (w_ & 1) * 512); \
                e_bulk_s2g(zp, sb + R_Z, 1024); \
                e_bulk_s2g(zp + 256, sb + R_Z, 1024); \
                e_bulk_s2g(&g_mem[(st) & 3][(rg0 + (w_ >> 1) * 64) * 32 + (w_ & 1) * 16], sb + R_Z, 64); \
                bulk_commit(); } } while (0)
template <uint32_t role> DEVINL void r_chain(const RMaps& tm, const bf16* __restrict__ mem0, const int wid) {
    extern __shared__ __align__(1024) unsigned char smem_raw[];
    const uint32_t sb = smem_u32(smem_raw);
    const uint32_t bar = sb + R_BAR;
    const int tid = threadIdx.x;
    int h; asm("mov.u32 %0, %%clusterid.x;" : "=r"(h));
        int t = tid & 127;
        const float sl2 = 0.08838834764831845f * 1.4426950408889634f;
        const float NEGRAW = -1000000000.0f / 0.08838834764831845f;
        const int rg0 = ((int)role - 1) * 32 + h;
        if (role != 0) {
#pragma unroll 1
            for (int r = 0; r < 4; r++) {
                uint32_t* zp = g_part[r] + ((rg0 + (t >> 6) * 64) * 1024 + (t & 63) * 4);
#pragma unroll
                for (int i = 0; i < 4; i++) if (r) st_strong16(zp + i * 256, make_uint4(0u, 0u, 0u, 0u));
                if ((t & 63) < 8) st_strong16(&g_mem[r][(rg0 + (t >> 6) * 64) * 32 + (t & 63) * 4], make_uint4(0u, 0u, 0u, 0u));
            }
            __threadfence();
        }
        if (role == 0 && (wid & 3) < 3) e_arrive_remote(mapa(bar + 8 * B_TFREE, wid & 3));
        if (t < 64) sts128(sb + R_Z + t * 16, make_uint4(0u, 0u, 0u, 0u));
        if (role == 0) sts128(sb + R_QM + t * 16, make_uint4(0u, 0u, 0u, 0u));
        {
            uint4 v[8];
#pragma unroll
            for (int r = 0; r < 8; r++) v[r] = __ldg((const uint4*)(mem0 + r * DM) + t);
            mbar_wait(bar + 8 * B_AFREE0, 0);
            mbar_wait(bar + 8 * B_AFREE1, 0);
#define TR2(f, c) \
            sts128(sb + R_RING + t * 128 + (c) * 16, make_uint4(__byte_perm(v[0].f, v[1].f, 0x5410), __byte_perm(v[2].f, v[3].f, 0x5410), __byte_perm(v[4].f, v[5].f, 0x5410), __byte_perm(v[6].f, v[7].f, 0x5410))); \
            sts128(sb + R_RING + t * 128 + (c) * 16 + 16, make_uint4(__byte_perm(v[0].f, v[1].f, 0x7632), __byte_perm(v[2].f, v[3].f, 0x7632), __byte_perm(v[4].f, v[5].f, 0x7632), __byte_perm(v[6].f, v[7].f, 0x7632)));
            TR2(x, 0) TR2(y, 2) TR2(z, 4) TR2(w, 6)
            fence_async();
            __syncwarp();
            e_arrive(bar + 8 * B_MEM + (t >> 5) * 8);
        }
        constexpr uint64_t dQ = role == 0 ? cdesc(R_QX, 128, 2048, 0) : cdesc(R_QM, 128, 0, 0);
        constexpr uint64_t dK = cdesc(R_K, 128, 2048, 0);

        for (int s = 0; s < NSEG; s++) {
            if (role == 0) {
                uint32_t n = 0, gate;
                do { gate = ld_strong4(&g_gate[s * SEG + (t >> 2)]); if (++n > 20000000u) __trap(); } while (gate == 0u);
                sts32(sb + R_G + (t >> 2) * 4, gate);
                __syncwarp();
            }
            mbar_wait(bar + 8 * B_XDONE, s & 1);
            mbar_wait(bar + 8 * B_XT, s & 1);
            if (t >= 1 && t < 3 && s < NSEG - 1) { uint32_t pr = role + t; pr = pr >= 3 ? pr - 3 : pr; mbar_arrive_remote(mapa(bar + 8 * B_XRECV, pr)); }
            __syncwarp();
            mbar_wait(bar + 8 * B_HOP1, s & 1);
            PROF(8);
            fence_async();
            OPAQUE(t);
            if (s == NSEG - 1 && role != 0) { mbar_wait(bar + 8 * B_HOPV, s & 1); bulk_wait_all(); break; }
            float sc[20];
            wg_fence();
#pragma unroll
            for (int k = 0; k < 8; k++) wg_ss40(sc, dQ + (uint64_t)(k * 16), dK + (uint64_t)(k * 16), k);
            wg_commit();
            uint32_t t_o = clk32() + 500;
            {
                const uint32_t va = sb + R_V + 2048 + (t >> 5) * 512 + ((t >> 4) & 1) * 2048 + (t & 15) * 16;
                uint32_t v0[4], v1[4];
                ldsm4(v0, va); ldsm4(v1, va + 256);
                uint32_t vm[4];
                const bool v_here = role != 0 && mbar_try(bar + 8 * B_HOPV, s & 1);
                if (v_here) ldsm4(vm, sb + R_V + t * 16);
                wg_wait<0>();
                if (role == 0) {
#pragma unroll
                    for (int j = 0; j < 5; j++)
                        asm volatile("st.shared.v2.f32 [%0], {%1,%2};" ::"r"(sb + R_QX + 768 + (t >> 5) * 4096 + j * 256 + (t & 31) * 8), "f"(sc[4 * j + 2]), "f"(sc[4 * j + 3]) : "memory");
                }
                float m = fmaxf(sc[0], sc[1]);
#pragma unroll
                for (int j = 1; j < 5; j++) m = fmaxf(m, fmaxf(sc[4 * j], sc[4 * j + 1]));
                m = fmaxf(m, __shfl_xor_sync(0xffffffffu, m, 1));
                m = fmaxf(m, __shfl_xor_sync(0xffffffffu, m, 2));
                const float mb = m * sl2;
                uint32_t pk[5];
#pragma unroll
                for (int j = 0; j < 5; j++) pk[j] = pack_bf16(ex2(fmaf(sc[4 * j], sl2, -mb)), ex2(fmaf(sc[4 * j + 1], sl2, -mb)));
                float o0[4] = {0.f, 0.f, 0.f, 0.f}, o1[4] = {0.f, 0.f, 0.f, 0.f}, ls[4] = {0.f, 0.f, 0.f, 0.f};
                constexpr uint32_t ONE = 0x3F803F80u;
                mma16816(o0, v0[0], v0[1], v0[2], v0[3], pk[1], pk[2]);
                mma16816(o1, v1[0], v1[1], v1[2], v1[3], pk[1], pk[2]);
                if (role == 0) { ldsm4_if(v0, va + 4096, s + 1); ldsm4_if(v1, va + 4096 + 256, s + 1); }
                else { ldsm4(v0, va + 4096); ldsm4(v1, va + 4096 + 256); }
                mma16816(ls, ONE, ONE, ONE, ONE, pk[1], pk[2]);
                mma16816(ls, ONE, ONE, ONE, ONE, pk[3], pk[4]);
                mma1688(ls, ONE, ONE, pk[0]);
                mma16816(o0, v0[0], v0[1], v0[2], v0[3], pk[3], pk[4]);
                mma16816(o1, v1[0], v1[1], v1[2], v1[3], pk[3], pk[4]);
                if (!v_here) { mbar_wait(bar + 8 * B_HOPV, s & 1); ldsm4(vm, sb + R_V + t * 16); }
                mma1688(o0, vm[0], vm[1], pk[0]);
                mma1688(o1, vm[2], vm[3], pk[0]);
                const float i0 = rcp(ls[0]), i1 = rcp(ls[1]);
                const uint32_t oa = sb + R_O + (t >> 5) * 512 + (t & 31) * 4;
                sts32(oa, pack_bf16(o0[0] * i0, o0[1] * i1));
                sts32(oa + 128, pack_bf16(o0[2] * i0, o0[3] * i1));
                sts32(oa + 256, pack_bf16(o1[0] * i0, o1[1] * i1));
                sts32(oa + 384, pack_bf16(o1[2] * i0, o1[3] * i1));
                __syncwarp();
                e_arrive(bar + 8 * B_O);
                PROF(9);
                if (role == 0) {
                    OPAQUE(t);
                    const int lim = (t >> 2) - (t & 3) * 2 + 8;
                    float z[10];
#pragma unroll
                    for (int j = 0; j < 5; j++)
                        asm volatile("ld.shared.v2.f32 {%0,%1}, [%2];" : "=f"(z[2 * j]), "=f"(z[2 * j + 1]) : "r"(sb + R_QX + 768 + (t >> 5) * 4096 + j * 256 + (t & 31) * 8) : "memory");
                    float gate; asm volatile("ld.shared.f32 %0, [%1];" : "=f"(gate) : "r"(sb + R_G + (t >> 2) * 4) : "memory");
                    float m1 = fmaxf(z[0], z[1]);
#pragma unroll
                    for (int j = 1; j < 5; j++) {
                        z[2 * j] = 8 * j <= lim ? z[2 * j] : NEGRAW;
                        z[2 * j + 1] = 8 * j + 1 <= lim ? z[2 * j + 1] : NEGRAW;
                        m1 = fmaxf(m1, fmaxf(z[2 * j], z[2 * j + 1]));
                    }
                    m1 = fmaxf(m1, __shfl_xor_sync(0xffffffffu, m1, 1));
                    m1 = fmaxf(m1, __shfl_xor_sync(0xffffffffu, m1, 2));
                    const float mb1 = m1 * sl2;
                    float l1 = 0.f;
                    const uint32_t pa = sb + R_QX + (t >> 5) * 4096 + (t & 31) * 4;
#pragma unroll
                    for (int j = 0; j < 5; j++) {
                        const uint32_t pw = pack_bf16(ex2(fmaf(z[2 * j], sl2, -mb1)), ex2(fmaf(z[2 * j + 1], sl2, -mb1)));
                        l1 += __uint_as_float(pw << 16) + __uint_as_float(pw & 0xffff0000u);
                        sts32(pa + j * 128, pw);
                    }
                    sts32(pa + 5 * 128, 0u);
                    l1 += __shfl_xor_sync(0xffffffffu, l1, 1);
                    l1 += __shfl_xor_sync(0xffffffffu, l1, 2);
                    sts32(sb + R_G + 128 + (t >> 2) * 4, __float_as_uint(gate * rcp(l1)));
                    if (s < NSEG - 1) spin_until(t_o + PVD);
                    if ((wid & 3) == 0 && s >= 1) { bulk_wait_all(); e_count(&g_ocnt[(s - 1) >> 2]); }
                    fence_async();
                    bar_sync(2, 128);
                    constexpr uint64_t dV = cdesc(R_V, 2048, 128, 0);
                    constexpr uint64_t dP = cdesc(R_QX, 128, 4096, 0);
                    float sf[8];
#pragma unroll
                    for (int j = 0; j < 4; j++) asm volatile("ld.shared.v2.f32 {%0,%1}, [%2];" : "=f"(sf[2 * j]), "=f"(sf[2 * j + 1]) : "r"(sb + R_G + 128 + j * 32 + (t & 3) * 8) : "memory");
                    const uint32_t r = ((t >> 4) & 1) * 8 + (t & 7), ch = (t >> 5) * 2 + ((t >> 3) & 1);
                    const uint32_t sa = sb + R_QX + 2048 + r * 128 + ((ch ^ (r & 7)) << 4);
#pragma unroll
                    for (int hf = 0; hf < 2; hf++) {
                        float d[16];
                        wg_fence();
#pragma unroll
                        for (int k = 0; k < 3; k++) wg_ss32<0>(d, dV + (uint64_t)(hf * 64 + k * 256), dP + (uint64_t)(k * 16), k);
                        wg_commit();
                        asm volatile("wgmma.wait_group.sync.aligned 0;" : ACC16(d)::"memory");
                        stsm4t(sa + hf * 8192, pack_bf16(d[0] * sf[0], d[1] * sf[1]), pack_bf16(d[2] * sf[0], d[3] * sf[1]), pack_bf16(d[4] * sf[2], d[5] * sf[3]), pack_bf16(d[6] * sf[2], d[7] * sf[3]));
                        stsm4t(sa + hf * 8192 + 4096, pack_bf16(d[8] * sf[4], d[9] * sf[5]), pack_bf16(d[10] * sf[4], d[11] * sf[5]), pack_bf16(d[12] * sf[6], d[13] * sf[7]), pack_bf16(d[14] * sf[6], d[15] * sf[7]));
                    }
                    fence_async();
                    bar_sync(2, 128);
                    if ((wid & 3) == 0) {
#pragma unroll
                        for (int q = 0; q < 4; q++) e_tma_store(&tm.o, sb + R_QX + 2048 + q * 4096, h * DH + (q >> 1) * 64, s * SEG + (q & 1) * 16);
                        bulk_commit();
                        bulk_wait_read();
                    }
                    if ((wid & 3) < 3 && s < NSEG - 1) e_arrive_remote(mapa(bar + 8 * B_TFREE, wid & 3));
                }
            }
            if (t < 32) { e_expect(bar + 8 * B_HOP1, role == 2 ? 4096 : 2048); if (role != 2) e_expect(bar + 8 * B_HOPV, 2048); e_expect(bar + 8 * B_XT, role == 0 ? 16384 : 8192); }
            if (s == NSEG - 1) { bulk_wait_all(); if ((wid & 3) == 0) e_count(&g_ocnt[s >> 2]); break; }
            if (role != 0 && (wid & 3) >= 2) {
                mbar_wait(bar + 8 * B_XRECV, s & 1);
                mbar_wait(bar + 8 * B_O, s & 1);
                fence_async();
                spin_until(t_o + ELD);
                x_load_pair(sb + ((wid & 1) ? R_V + 2048 : R_K + 2048), &tm.x, h, 3 + (wid & 1), s + 1, bar + 8 * (B_FULL + 3 + (wid & 1)));
            }
            OPAQUE(t);
            PROF(11);
            if (role != 0) {
                const int grp = rg0 + (t >> 6) * 64;
                const uint32_t* rp = g_part[s & 3] + (grp * 1024 + ((t >> 2) & 7) * 32 + ((t >> 5) & 1) * 16 + (t & 3) * 4);
                uint32_t* wp = &g_mem[(s + 1) & 3][grp * 32 + ((t >> 5) & 1) * 16 + (t & 3) * 4 + ((t >> 3) & 3)];
                bulk_wait_all();
                spin_until(t_o + D2_BASE + (role - 1 + (t >> 6) * 2) * D2_STEP);
                PROF3(0, clk32());
#define LO(u) __uint_as_float((u) << 16)
#define HI(u) __uint_as_float((u) & 0xffff0000u)
                uint4 v[4];
                uint32_t n = poll_set<4>(v, rp, 256);
                {
                    PROF3(1, clk32());
                    float f[8];
                    f[0] = (LO(v[0].x) + LO(v[1].x)) + (LO(v[2].x) + LO(v[3].x)); f[1] = (HI(v[0].x) + HI(v[1].x)) + (HI(v[2].x) + HI(v[3].x));
                    f[2] = (LO(v[0].y) + LO(v[1].y)) + (LO(v[2].y) + LO(v[3].y)); f[3] = (HI(v[0].y) + HI(v[1].y)) + (HI(v[2].y) + HI(v[3].y));
                    f[4] = (LO(v[0].z) + LO(v[1].z)) + (LO(v[2].z) + LO(v[3].z)); f[5] = (HI(v[0].z) + HI(v[1].z)) + (HI(v[2].z) + HI(v[3].z));
                    f[6] = (LO(v[0].w) + LO(v[1].w)) + (LO(v[2].w) + LO(v[3].w)); f[7] = (HI(v[0].w) + HI(v[1].w)) + (HI(v[2].w) + HI(v[3].w));
                    const bool b4 = t & 16, b3 = t & 8;
                    float g4[4], g2[2];
#pragma unroll
                    for (int i = 0; i < 4; i++) g4[i] = (b4 ? f[4 + i] : f[i]) + __shfl_xor_sync(0xffffffffu, b4 ? f[i] : f[4 + i], 16);
#pragma unroll
                    for (int i = 0; i < 2; i++) g2[i] = (b3 ? g4[2 + i] : g4[i]) + __shfl_xor_sync(0xffffffffu, b3 ? g4[i] : g4[2 + i], 8);
                    g2[0] += __shfl_xor_sync(0xffffffffu, g2[0], 4);
                    g2[1] += __shfl_xor_sync(0xffffffffu, g2[1], 4);
                    st_strong4(wp, pack_nz(g2[0], g2[1]));
                }
                PROF3(8, n); (void)n;
            }
            t_o += D2_BASE + DQ + (t >> 5) * D2_STEP;
            OPAQUE(t);
            PROF(12);
            {
                const uint32_t* rp = &g_mem[(s + 1) & 3][((t >> 5) * 256 + (t & 31)) * 4];
                const uint32_t da = sb + R_RING + ((t >> 5) * 256 + (t & 31)) * 16;
                uint4 v[8];
                spin_until(t_o);
                PROF3(2, clk32());
                uint32_t n = poll_set<8>(v, rp, 128);
                PROF(13);
                PROF3(3, clk32()); PROF3(9, n); (void)n;
                mbar_wait(bar + 8 * B_AFREE0 + (t >> 6) * 8, (s + 1) & 1);
                PROF3(4, clk32());
#pragma unroll
                for (int i = 0; i < 8; i++) sts128(da + i * 512, v[i]);
                if (t >= 64) fence_async();
                __syncwarp();
                e_arrive(bar + 8 * B_MEM + (t >> 5) * 8);
                PROF(14);
                PROF3(5, clk32());
            }
            CLEAR(s + 3);
        }
}

__global__ void __launch_bounds__(384, 1) r_kernel(const __grid_constant__ RMaps tm, const bf16* __restrict__ mem0, const bf16* __restrict__ x, const bf16* __restrict__ gate_w) {
    extern __shared__ __align__(1024) unsigned char smem_raw[];
    const uint32_t sb = smem_u32(smem_raw);
    if ((sb & 0x3FFFFu) != SB0) __trap();
    const int tid = threadIdx.x;
    const int wid = __shfl_sync(0xffffffffu, tid >> 5, 0);
    uint32_t role; asm("mov.u32 %0, %%cluster_ctarank;" : "=r"(role));
    int h; asm("mov.u32 %0, %%clusterid.x;" : "=r"(h));
    const uint32_t bar = sb + R_BAR;
    asm volatile("griddepcontrol.launch_dependents;");
    KT(0, 0);
    const int gr = blockIdx.x * 12 + wid;
    uint4 gx0[4], gx1[4], gw[4];
#pragma unroll
    for (int i = 0; i < 4; i++) {
        gx0[i] = ldg_nc((const uint4*)(x + gr * DM) + i * 32 + (tid & 31));
        gx1[i] = ldg_nc((const uint4*)(x + min(gr + 1152, SEQ - 1) * DM) + i * 32 + (tid & 31));
        gw[i] = ldg_nc((const uint4*)gate_w + i * 32 + (tid & 31));
    }

    if (tid == 0) {
        for (int i = 0; i < 5; i++) mbar_init(bar + 8 * (B_FULL + i), 1);
        for (int i = 0; i < 3; i++) mbar_init(bar + 8 * (B_EMPTY + i), 2);
        for (int i = 0; i < 4; i++) mbar_init(bar + 8 * (B_MEM + i), 1);
        mbar_init(bar + 8 * B_HOP1, role == 2 ? 1 : 9);
        mbar_init(bar + 8 * B_HOPV, role == 2 ? 8 : 1);
        mbar_init(bar + 8 * B_XT, 1);
        mbar_init(bar + 8 * B_TFREE, 5);
        mbar_init(bar + 8 * B_XDONE, 8);
        mbar_init(bar + 8 * B_XRECV, 2);
        mbar_init(bar + 8 * B_O, 4);
        mbar_init(bar + 8 * B_AFREE0, 2);
        mbar_init(bar + 8 * B_AFREE1, 2);
        mbar_init(bar + 8 * B_PRO0, 1);
        mbar_init(bar + 8 * B_PRO1, 1);
        for (int i = 0; i < KR / 4; i++) mbar_init(sb + R_O + 8 * i, 1);
        asm volatile("fence.mbarrier_init.release.cluster;" ::: "memory");
        fence_async();
        for (int i = 0; i < KR / 4; i++) mbar_expect(sb + R_O + 8 * i, 16384);
        mbar_expect(bar + 8 * B_PRO1, KS * 4096);
        mbar_expect(bar + 8 * B_PRO0, (role == 0 ? 4 : 6) * 16384);
        for (int i = 0; i < 3; i++) mbar_expect(bar + 8 * (B_FULL + i), 8192);
        mbar_expect(bar + 8 * B_HOP1, role == 2 ? 4096 : 2048);
        if (role != 2) mbar_expect(bar + 8 * B_HOPV, 2048);
        mbar_expect(bar + 8 * B_XT, role == 0 ? 16384 : 8192);
    }
    __syncthreads();
    asm volatile("barrier.cluster.arrive.relaxed.aligned;" ::: "memory");
    {
        const CUtensorMap* tw = &tm.w[role];
        if (wid < 11) {
            e_tma_load(sb + wid * 16384, tw, h * DH, KC(wid), sb + R_O + 8 * wid);
            e_tma_load(sb + wid * 16384 + 8192, tw, h * DH + 64, KC(wid), sb + R_O + 8 * wid);
        }
        if (wid < 6) e_tma_load(sb + R_RING + wid * 4096, &tm.x, XC(wid), 0, bar + 8 * (B_FULL + (wid >> 1)));
        __syncwarp();
        const uint32_t g0 = __float_as_uint(gate_row(gx0, gw)), g1 = __float_as_uint(gate_row(gx1, gw));
        if ((tid & 31) == 0) {
            st_strong4(&g_gate[gr], g0 ? g0 : 0x80000000u);
            if (gr + 1152 < SEQ) st_strong4(&g_gate[gr + 1152], g1 ? g1 : 0x80000000u);
        }
        __syncwarp();
    }
    asm volatile("barrier.cluster.wait.aligned;" ::: "memory");

    if (wid < 8) {
        asm volatile("setmaxnreg.inc.sync.aligned.u32 224;");
        if (role == 0) r_big<0>(tm, wid); else if (role == 1) r_big<1>(tm, wid); else r_big<2>(tm, wid);
    } else {
        asm volatile("setmaxnreg.dec.sync.aligned.u32 56;");
        if (role == 0) r_chain<0>(tm, mem0, wid); else if (role == 1) r_chain<1>(tm, mem0, wid); else r_chain<2>(tm, mem0, wid);
    }
    KT(0, 1);
}

constexpr int G_ST = 4;
constexpr int G_STAGE = 16384 + 32768;
constexpr int G_EPI = G_ST * G_STAGE;
constexpr int G_GATE = G_EPI + 32768;
constexpr int G_BAR = G_GATE + 1024;
constexpr int G_SMEM = G_BAR + 128 + 1024;

struct G1Maps { CUtensorMap x, wg, wu, hs, o, h, wo, wd, out; };
constexpr int G1_NB = FF / 128;
constexpr int G1_TILES = 16 * G1_NB;

DEVINL void g_mma_block(float* d, uint32_t sb, uint32_t bar, int it, int wg, int tid, bool first) {
    const int st = it % G_ST;
    mbar_wait(bar + 8 * st, (it / G_ST) & 1);
    const uint64_t da = mkdesc(sb + st * G_STAGE + wg * 8192, 16, 1024, 1);
    const uint64_t db = mkdesc(sb + st * G_STAGE + 16384, 8192, 1024, 1);
    wg_fence();
#pragma unroll
    for (int k = 0; k < 4; k++) wg_ss256(d, da + (uint64_t)(k * 2), db + (uint64_t)(k * 128), (first ? 0 : 1) | k);
    wg_commit();
    if (!first) { wg_wait<1>(); if ((tid & 127) == 0) mbar_arrive(bar + 8 * (G_ST + (it - 1) % G_ST)); }
}
DEVINL void g_load_block(uint32_t sb, uint32_t bar, int it, const CUtensorMap* ta, int k0, int m0, const CUtensorMap* tb, int n0) {
    const int st = it % G_ST;
    mbar_wait(bar + 8 * (G_ST + st), ((it / G_ST) & 1) ^ 1);
    const uint32_t fb = bar + 8 * st, sa = sb + st * G_STAGE;
    mbar_expect(fb, G_STAGE);
    tma_load(sa, ta, k0, m0, fb);
#pragma unroll
    for (int q = 0; q < 4; q++) tma_load(sa + 16384 + q * 8192, tb, n0 + q * 64, k0, fb);
}

DEVINL void g_store_tile(const float* d, const CUtensorMap* tout, uint32_t epi, int mb, int nb, int wg, int tid) {
    const int lane = tid & 31, row = ((tid >> 5) & 3) * 16 + ((lane >> 3) & 1) * 8 + (lane & 7);
#pragma unroll
    for (int half = 0; half < 2; half++) {
        if ((tid & 127) == 0) bulk_wait_read();
        bar_sync(1 + wg, 128);
#pragma unroll
        for (int j = 0; j < 16; j += 2) {
            const float* e = d + half * 64 + 4 * j;
            const int cgp = j + (lane >> 4);
            stsm4(epi + (cgp >> 3) * 8192 + row * 128 + (((cgp & 7) ^ (row & 7)) << 4),
                  pack_bf16(e[0], e[1]), pack_bf16(e[2], e[3]), pack_bf16(e[4], e[5]), pack_bf16(e[6], e[7]));
        }
        fence_async();
        bar_sync(1 + wg, 128);
        if ((tid & 127) == 0) {
            tma_store(tout, epi, nb * 256 + half * 128, mb * 128 + wg * 64);
            tma_store(tout, epi + 8192, nb * 256 + half * 128 + 64, mb * 128 + wg * 64);
            bulk_commit();
        }
    }
}
template <int NS> DEVINL void g_split_finish(const float* d, float4 (&r)[32 / NS], uint4* sk, int tile, int ks, bf16* __restrict__ out, int tid) {
    constexpr int Q = 32 / NS;
    uint4* mine = sk + ks * (16 * 256) + tid;
#pragma unroll
    for (int c = 0; c < NS; c++) {
        if (c != ks) {
#pragma unroll
            for (int q = c * Q / 2; q < (c + 1) * Q / 2; q++)
                __stcg(mine + q * 256, make_uint4(pack_bf16(d[8 * q], d[8 * q + 1]), pack_bf16(d[8 * q + 2], d[8 * q + 3]), pack_bf16(d[8 * q + 4], d[8 * q + 5]), pack_bf16(d[8 * q + 6], d[8 * q + 7])));
        } else {
#pragma unroll
            for (int q = 0; q < Q; q++) { const float* e = d + (c * Q + q) * 4; r[q].x += e[0]; r[q].y += e[1]; r[q].z += e[2]; r[q].w += e[3]; }
        }
    }
    __threadfence();
    bar_sync(3, 256);
    if (tile >= T_LATE) PT(20);
    if (tid == 0) {
        atomicAdd(&g_skcnt[tile], 1u);
        uint32_t v, n = 0;
        do {
            asm volatile("ld.acquire.gpu.global.u32 %0, [%1];" : "=r"(v) : "l"(&g_skcnt[tile]) : "memory");
            if (++n > 200000000u) __trap();
        } while (v < NS);
        if (atomicAdd(&g_skcnt[tile], 1u) == 2 * NS - 1) g_skcnt[tile] = 0u;
    }
    bar_sync(3, 256);
    if (tile >= T_LATE) PT(21);
#pragma unroll
    for (int c = 1; c < NS; c++) {
        const uint4* th = sk + (((ks + c) & (NS - 1)) * 16 + ks * (Q / 2)) * 256 + tid;
#pragma unroll
        for (int q = 0; q < Q / 2; q++) {
            const uint4 u = __ldcg(th + q * 256);
            r[2 * q].x += __uint_as_float(u.x << 16); r[2 * q].y += __uint_as_float(u.x & 0xffff0000u);
            r[2 * q].z += __uint_as_float(u.y << 16); r[2 * q].w += __uint_as_float(u.y & 0xffff0000u);
            r[2 * q + 1].x += __uint_as_float(u.z << 16); r[2 * q + 1].y += __uint_as_float(u.z & 0xffff0000u);
            r[2 * q + 1].z += __uint_as_float(u.w << 16); r[2 * q + 1].w += __uint_as_float(u.w & 0xffff0000u);
        }
    }
    const int lane = tid & 31;
    uint32_t* op = (uint32_t*)(out + ((tile >> 2) * 128 + (tid >> 5) * 16 + (lane >> 2)) * DM + (tile & 3) * 256 + ks * Q * 8 + (lane & 3) * 2);
#pragma unroll
    for (int q = 0; q < Q; q++) { op[q * 4] = pack_bf16(r[q].x, r[q].y); op[q * 4 + 4 * DM] = pack_bf16(r[q].z, r[q].w); }
}
DEVINL int g1_count(int pass, int tail) {
    return pass == 0 ? NPRE : pass == 1 ? NFULL : pass == 2 ? T_MID - NFULL : pass == 3 ? (T_MID2 - T_MID) * 4 : tail ? (64 - T_LATE) * 8 : (T_LATE - T_MID2) * 8;
}
DEVINL int g1_first(int pass, int tail) {
    const int b = blockIdx.x, n = gridDim.x;
    return (pass < 2 || tail) ? b : pass == 2 ? n - 1 - b : (b + n - (pass == 3 ? 16 : 32)) % n;
}
DEVINL int g1_tile(int pass, int tail, int i) {
    return pass == 1 ? i : pass == 3 ? T_MID + (i >> 2) : pass == 4 ? (tail ? T_LATE : T_MID2) + (i >> 3) : NFULL + i;
}
constexpr int H_EARLY = 24;

__global__ void __launch_bounds__(384, 1) g1_kernel(const __grid_constant__ G1Maps tm, bf16* __restrict__ out, const int tail) {
    extern __shared__ __align__(1024) unsigned char smem_raw[];
    const uint32_t sb = (smem_u32(smem_raw) + 1023) & ~1023u;
    const int tid = threadIdx.x, lane = tid & 31;
    const int wg = __shfl_sync(0xffffffffu, tid >> 7, 0);
    const int warp = __shfl_sync(0xffffffffu, (tid >> 5) & 3, 0);
    const uint32_t bar = sb + G_BAR;
    asm volatile("griddepcontrol.launch_dependents;");
    KT(1 + tail, 0);
    if (tail && (tid == 32 || tid == 64)) asm volatile("prefetch.tensormap [%0];" ::"l"(tid == 32 ? &tm.o : &tm.wo) : "memory");
    const int ntiles = tail ? 0 : G1_TILES;
    if (tid == 0) {
        for (int i = 0; i < G_ST; i++) { mbar_init(bar + 8 * i, 1); mbar_init(bar + 8 * (G_ST + i), 2); }
        fence_async();
    }
    __syncthreads();
    if (tail) PT(16);
    if (tail) PT(17);
    if (tail) PT(22);
    if (wg == 2) {
        asm volatile("setmaxnreg.dec.sync.aligned.u32 40;");
        if (tail) {
            const int tile = T_LATE + (blockIdx.x >> 3), k0 = ((blockIdx.x & 7) * 8 + warp) * 64;
            e_expect(bar + 8 * warp, G_STAGE);
#pragma unroll
            for (int q = 0; q < 4; q++) e_tma_load(sb + warp * G_STAGE + 16384 + q * 8192, &tm.wo, (tile & 3) * 256 + q * 64, k0, bar + 8 * warp);
            wait_count(&g_ocnt[tile >> 2], NH * 4);
            asm volatile("fence.proxy.async;" ::: "memory");
            e_tma_load(sb + warp * G_STAGE, &tm.o, k0, (tile >> 2) * 128, bar + 8 * warp);
        }
        if (warp == 0) {
            if (lane == 0) {
                int it = 0;
                for (int tile = blockIdx.x; tile < ntiles; tile += gridDim.x) {
                    const int mb = tile & 15, nb = tile >> 4;
                    for (int kb = 0; kb < 16; kb++, it++) {
                        const int st = it % G_ST;
                        mbar_wait(bar + 8 * (G_ST + st), ((it / G_ST) & 1) ^ 1);
                        const uint32_t fb = bar + 8 * st, sa = sb + st * G_STAGE;
                        mbar_expect(fb, G_STAGE);
                        tma_load(sa, &tm.x, kb * 64, mb * 128, fb);
                        tma_load(sa + 16384, &tm.wg, nb * 128, kb * 64, fb);
                        tma_load(sa + 16384 + 8192, &tm.wg, nb * 128 + 64, kb * 64, fb);
                        tma_load(sa + 16384 + 16384, &tm.wu, nb * 128, kb * 64, fb);
                        tma_load(sa + 16384 + 24576, &tm.wu, nb * 128 + 64, kb * 64, fb);
                    }
                }
                for (int pass = tail ? 4 : 0; pass < 5; pass++) {
                    for (int i = g1_first(pass, tail); i < g1_count(pass, tail); i += gridDim.x) {
                        const int tile = g1_tile(pass, tail, i), mb = tile >> 2, nb = tile & 3;
                        if (pass < 2) {
                            for (int kb = 0; kb < FF / 64; kb++, it++) {
                                if (kb == 0 || kb == 2 * H_EARLY) {
                                    wait_count(&g_hcnt[kb ? 16 + mb : mb], kb ? 2 * (G1_NB - H_EARLY) : 2 * H_EARLY);
                                    asm volatile("fence.proxy.async;" ::: "memory");
                                }
                                g_load_block(sb, bar, it, &tm.h, kb * 64, mb * 128, &tm.wd, nb * 256);
                            }
                        }
                        if (pass > 0) {
                            const int k0 = pass == 3 ? (i & 3) * 16 : pass == 4 ? (i & 7) * 8 : 0, k1 = pass == 3 ? k0 + 16 : pass == 4 ? k0 + 8 : HD / 64;
                            if (!tail) wait_count(&g_ocnt[mb], NH * 4);
                            asm volatile("fence.proxy.async;" ::: "memory");
                            for (int kb = k0; kb < k1; kb++, it++) if (!tail || it >= G_ST) g_load_block(sb, bar, it, &tm.o, kb * 64, mb * 128, &tm.wo, nb * 256);
                        }
                    }
                }
            }
        }
    } else {
        asm volatile("setmaxnreg.inc.sync.aligned.u32 232;");
        float d[128];
        int it = 0;
        const uint32_t epi = sb + G_EPI + wg * 16384;
        const int row = warp * 16 + ((lane >> 3) & 1) * 8 + (lane & 7);
        for (int tile = blockIdx.x; tile < ntiles; tile += gridDim.x) {
            const int mb = tile & 15, nb = tile >> 4;
            const uint32_t* gp = &g_gate[mb * 128 + wg * 64 + warp * 16 + (lane >> 2)];
            uint32_t u0 = ld_strong4(gp), u1 = ld_strong4(gp + 8);
            for (int kb = 0; kb < 16; kb++, it++) g_mma_block(d, sb, bar, it, wg, tid, kb == 0);
            wg_wait<0>();
            for (uint32_t n = 0; u0 == 0u || u1 == 0u; n++) { u0 = ld_strong4(gp); u1 = ld_strong4(gp + 8); if (n > 20000000u) __trap(); }
            __syncwarp();
            const float s0 = 1.0f - __uint_as_float(u0), s1 = 1.0f - __uint_as_float(u1);
            if ((tid & 127) == 0) {
                mbar_arrive(bar + 8 * (G_ST + (it - 1) % G_ST));
                bulk_wait_all();
                const int pt = tile - (int)gridDim.x;
                if (pt >= 0) atomicAdd(&g_hcnt[(pt & 15) + ((pt >> 4) >= H_EARLY ? 16 : 0)], 1u);
            }
            bar_sync(1 + wg, 128);
#pragma unroll
            for (int j = 0; j < 16; j += 2) {
                uint32_t p[4];
#pragma unroll
                for (int q = 0; q < 4; q++) {
                    const int i = (j + (q >> 1)) * 4 + (q & 1) * 2;
                    const float sc = (q & 1) ? s1 : s0;
                    const float g0 = d[i], g1 = d[i + 1];
                    const float a0 = 1.0f + ex2(fminf(g0 * -1.4426950408889634f, 62.0f)), a1 = 1.0f + ex2(fminf(g1 * -1.4426950408889634f, 62.0f));
                    const float rr = rcp(a0 * a1) * sc;
                    const float h0 = (g0 * d[64 + i]) * (rr * a1);
                    const float h1 = (g1 * d[64 + i + 1]) * (rr * a0);
                    p[q] = pack_bf16(h0, h1);
                }
                const int cgp = j + (lane >> 4);
                stsm4(epi + (cgp >> 3) * 8192 + row * 128 + (((cgp & 7) ^ (row & 7)) << 4), p[0], p[1], p[2], p[3]);
            }
            fence_async();
            bar_sync(1 + wg, 128);
            if ((tid & 127) == 0) {
                tma_store(&tm.hs, epi, nb * 128, mb * 128 + wg * 64);
                tma_store(&tm.hs, epi + 8192, nb * 128 + 64, mb * 128 + wg * 64);
                bulk_commit();
            }
        }
        if ((tid & 127) == 0 && !tail) {
            bulk_wait_all();
            const int pt = blockIdx.x + (G1_TILES - 1 - blockIdx.x) / gridDim.x * gridDim.x;
            atomicAdd(&g_hcnt[(pt & 15) + ((pt >> 4) >= H_EARLY ? 16 : 0)], 1u);
        }
        for (int pass = tail ? 4 : 0; pass < 5; pass++) {
            for (int i = g1_first(pass, tail); i < g1_count(pass, tail); i += gridDim.x) {
                const int tile = g1_tile(pass, tail, i);
                const int nkb = pass == 0 ? FF / 64 : pass == 1 ? (FF + HD) / 64 : pass == 2 ? HD / 64 : pass == 3 ? 16 : 8;
                float4* pre = g_pre + (tile - NFULL) * (32 * 256) + tid;
                if (tail) PT(23);
                if (tail) asm volatile("prefetch.global.L2 [%0];" ::"l"(pre - tid + (i & 7) * 1024 + tid * 4));
                for (int kb = 0; kb < nkb; kb++, it++) { g_mma_block(d, sb, bar, it, wg, tid, kb == 0); if (tail && kb == 0) PT(18); }
                wg_wait<0>();
                if (tail) PT(19);
                if ((tid & 127) == 0) mbar_arrive(bar + 8 * (G_ST + (it - 1) % G_ST));
                if (pass >= 2) { if ((tid & 31) == 0) wait_count(&g_pcnt[tile], 8); __syncwarp(); }
                if (pass == 0) {
#pragma unroll
                    for (int q = 0; q < 32; q++) __stcg(pre + q * 256, make_float4(d[4 * q], d[4 * q + 1], d[4 * q + 2], d[4 * q + 3]));
                    __threadfence();
                    __syncwarp();
                    if ((tid & 31) == 0) atomicAdd(&g_pcnt[tile], 1u);
                } else if (pass == 3) {
                    float4 r[8];
#pragma unroll
                    for (int q = 0; q < 8; q++) r[q] = __ldcg(pre + ((i & 3) * 8 + q) * 256);
                    g_split_finish<4>(d, r, g_sk + (tile - T_MID) * 8 * (16 * 256), tile, i & 3, out, tid);
                } else if (pass == 4) {
                    float4 r[4];
#pragma unroll
                    for (int q = 0; q < 4; q++) r[q] = __ldcg(pre + ((i & 7) * 4 + q) * 256);
                    g_split_finish<8>(d, r, g_sk + (tile - T_MID) * 8 * (16 * 256), tile, i & 7, out, tid);
                } else {
                    if (pass == 2) {
#pragma unroll
                        for (int q = 0; q < 32; q++) {
                            const float4 u = __ldcg(pre + q * 256); d[4 * q] += u.x; d[4 * q + 1] += u.y; d[4 * q + 2] += u.z; d[4 * q + 3] += u.w;
                            if ((q & 7) == 7) __syncwarp();
                        }
                    }
                    g_store_tile(d, &tm.out, epi, tile >> 2, tile & 3, wg, tid);
                }
            }
        }
        if ((tid & 127) == 0) bulk_wait_all();
        KT(1 + tail, 1);
        if (wg == 0) {
            uint32_t last = blockIdx.x == 0;
            if (tail) {
                if (tid == 0) sts32(bar + 64, atomicAdd(&g_ticket, 1u) == gridDim.x - 1);
                bar_sync(1, 128);
                asm volatile("ld.shared.b32 %0, [%1];" : "=r"(last) : "r"(bar + 64) : "memory");
            }
            if (last) {
                asm volatile("griddepcontrol.wait;" ::: "memory");
                if (tail) {
                    for (int i = tid; i < SEQ; i += 128) g_gate[i] = 0u;
                    if (tid < 64) g_pcnt[tid] = 0u;
                    if (tid < 32) g_hcnt[tid] = 0u;
                    if (tid < 16) g_ocnt[tid] = 0u;
                    if (tid == 0) g_ticket = 0u;
                }
            }
        }
    }
}

__device__ bf16 f_qkv[3][(SEQ + NMEM) * HD];
__device__ bf16 f_mem[NMEM * DM], f_om[NMEM * HD];

__global__ void __launch_bounds__(256) f_gemm(const bf16* __restrict__ A, const bf16* __restrict__ B, bf16* __restrict__ C, int K, int N) {
    __shared__ float sa[8][256];
    const int n = blockIdx.x * 256 + threadIdx.x, m0 = blockIdx.y * 8;
    float acc[8] = {0.f, 0.f, 0.f, 0.f, 0.f, 0.f, 0.f, 0.f};
    for (int k0 = 0; k0 < K; k0 += 256) {
        __syncthreads();
        for (int r = 0; r < 8; r++) sa[r][threadIdx.x] = __bfloat162float(A[(size_t)(m0 + r) * K + k0 + threadIdx.x]);
        __syncthreads();
        for (int k = 0; k < 256; k++) {
            const float b = __bfloat162float(B[(size_t)(k0 + k) * N + n]);
#pragma unroll
            for (int r = 0; r < 8; r++) acc[r] = fmaf(sa[r][k], b, acc[r]);
        }
    }
    for (int r = 0; r < 8; r++) C[(size_t)(m0 + r) * N + n] = __float2bfloat16(acc[r]);
}
__global__ void __launch_bounds__(32) f_gate(const bf16* __restrict__ x, const bf16* __restrict__ gate_w) {
    uint4 xv[4], gv[4];
    for (int i = 0; i < 4; i++) { xv[i] = ldg_nc((const uint4*)(x + blockIdx.x * DM) + i * 32 + threadIdx.x); gv[i] = ldg_nc((const uint4*)gate_w + i * 32 + threadIdx.x); }
    const uint32_t g = __float_as_uint(gate_row(xv, gv));
    if (threadIdx.x == 0) { g_gate[blockIdx.x] = g ? g : 0x80000000u; if (blockIdx.x < 16) g_ocnt[blockIdx.x] = NH * 4; }
}
__global__ void __launch_bounds__(128) f_attn(int s) {
    __shared__ float sq[DH], sp[NMEM + SEG];
    const int h = blockIdx.x, i = blockIdx.y, t = threadIdx.x;
    auto row = [&](int r) { return (size_t)(r < NMEM ? SEQ + r : s * SEG + r - NMEM) * HD + h * DH; };
    sq[t] = __bfloat162float(f_qkv[0][row(i) + t]);
    __syncthreads();
    if (t < NMEM + SEG) {
        float a = 0.f;
        for (int e = 0; e < DH; e++) a = fmaf(sq[e], __bfloat162float(f_qkv[1][row(t) + e]), a);
        sp[t] = (i < NMEM || i >= t) ? a * 0.08838834764831845f : -1000000000.0f;
    }
    __syncthreads();
    float m = sp[0], l = 0.f, o = 0.f;
    for (int j = 1; j < NMEM + SEG; j++) m = fmaxf(m, sp[j]);
    for (int j = 0; j < NMEM + SEG; j++) { const float p = __expf(sp[j] - m); l += p; o = fmaf(p, __bfloat162float(f_qkv[2][row(j) + t]), o); }
    if (i < NMEM) f_om[i * HD + h * DH + t] = __float2bfloat16(o / l);
    else g_O[(size_t)(s * SEG + i - NMEM) * HD + h * DH + t] = __float2bfloat16(o / l * __uint_as_float(g_gate[s * SEG + i - NMEM]));
}

typedef CUresult (*EncodeFn)(CUtensorMap*, CUtensorMapDataType, cuuint32_t, void*, const cuuint64_t*, const cuuint64_t*, const cuuint32_t*,
                             const cuuint32_t*, CUtensorMapInterleave, CUtensorMapSwizzle, CUtensorMapL2promotion, CUtensorMapFloatOOBfill);

static void make_map(EncodeFn enc, CUtensorMap* m, const void* ptr, uint64_t rows, uint64_t cols, uint32_t box_rows) {
    cuuint64_t dims[2] = {cols, rows};
    cuuint64_t strides[1] = {cols * 2};
    cuuint32_t box[2] = {64, box_rows};
    cuuint32_t es[2] = {1, 1};
    enc(m, CU_TENSOR_MAP_DATA_TYPE_BFLOAT16, 2, (void*)ptr, dims, strides, box, es, CU_TENSOR_MAP_INTERLEAVE_NONE,
        CU_TENSOR_MAP_SWIZZLE_128B, CU_TENSOR_MAP_L2_PROMOTION_L2_256B, CU_TENSOR_MAP_FLOAT_OOB_FILL_NONE);
}

extern "C" void kernel_launch(void* const* d_in, const int* in_sizes, int n_in, void* d_out, int out_size) {
    (void)in_sizes; (void)n_in; (void)out_size;
    const bf16* x = (const bf16*)d_in[0];
    const bf16* mem0 = (const bf16*)d_in[1];
    const bf16* gate_w = (const bf16*)d_in[11];
    static EncodeFn enc = nullptr;
    static int n_sm = 0;
    static void *pO = nullptr, *pH = nullptr, *pQ = nullptr, *pM = nullptr, *pOm = nullptr;
    static int n_clusters = 0;
    if (!enc) {
        void* fn = nullptr;
        cudaDriverEntryPointQueryResult qr;
        cudaGetDriverEntryPoint("cuTensorMapEncodeTiled", &fn, cudaEnableDefault, &qr);
        enc = (EncodeFn)fn;
        cudaDeviceGetAttribute(&n_sm, cudaDevAttrMultiProcessorCount, 0);
        cudaFuncSetAttribute(r_kernel, cudaFuncAttributeMaxDynamicSharedMemorySize, R_SMEM);
        cudaFuncSetAttribute(g1_kernel, cudaFuncAttributeMaxDynamicSharedMemorySize, G_SMEM);
        cudaGetSymbolAddress(&pO, g_O);
        cudaGetSymbolAddress(&pH, g_H);
        cudaGetSymbolAddress(&pQ, f_qkv);
        cudaGetSymbolAddress(&pM, f_mem);
        cudaGetSymbolAddress(&pOm, f_om);
        cudaLaunchConfig_t cfg = {};
        cfg.gridDim = dim3(96); cfg.blockDim = dim3(384); cfg.dynamicSmemBytes = R_SMEM;
        cudaLaunchAttribute at[1];
        at[0].id = cudaLaunchAttributeClusterDimension; at[0].val.clusterDim.x = 3; at[0].val.clusterDim.y = 1; at[0].val.clusterDim.z = 1;
        cfg.attrs = at; cfg.numAttrs = 1;
        if (cudaOccupancyMaxActiveClusters(&n_clusters, r_kernel, &cfg) != cudaSuccess) { n_clusters = 0; (void)cudaGetLastError(); }
    }
    RMaps rm; G1Maps m1;
    make_map(enc, &rm.x, x, SEQ, DM, 32);
    for (int i = 0; i < 3; i++) make_map(enc, &rm.w[i], d_in[2 + i], DM, HD, 64);
    make_map(enc, &rm.wo, d_in[5], HD, DM, 128);
    make_map(enc, &rm.o, pO, SEQ, HD, 16);
    make_map(enc, &m1.x, x, SEQ, DM, 128);
    make_map(enc, &m1.wg, d_in[8], DM, FF, 64);
    make_map(enc, &m1.wu, d_in[9], DM, FF, 64);
    make_map(enc, &m1.hs, pH, SEQ, FF, 64);
    make_map(enc, &m1.o, pO, SEQ, HD, 128);
    make_map(enc, &m1.h, pH, SEQ, FF, 128);
    make_map(enc, &m1.wo, d_in[5], HD, DM, 64);
    make_map(enc, &m1.wd, d_in[10], FF, DM, 64);
    make_map(enc, &m1.out, d_out, SEQ, DM, 64);

    cudaStream_t st = cudaStreamPerThread;
    if (n_clusters < NH) {
        bf16* qkv = (bf16*)pQ;
        const size_t plane = (size_t)(SEQ + NMEM) * HD;
        f_gate<<<SEQ, 32, 0, st>>>(x, gate_w);
        for (int i = 0; i < 3; i++) f_gemm<<<dim3(HD / 256, SEQ / 8), 256, 0, st>>>(x, (const bf16*)d_in[2 + i], qkv + i * plane, DM, HD);
        for (int s = 0; s < NSEG; s++) {
            for (int i = 0; i < 3; i++)
                f_gemm<<<dim3(HD / 256, 1), 256, 0, st>>>(s ? (const bf16*)pM : mem0, (const bf16*)d_in[2 + i], qkv + i * plane + (size_t)SEQ * HD, DM, HD);
            f_attn<<<dim3(NH, NMEM + SEG), 128, 0, st>>>(s);
            f_gemm<<<dim3(DM / 256, 1), 256, 0, st>>>((const bf16*)pOm, (const bf16*)d_in[5], (bf16*)pM, HD, DM);
        }
    } else {
        cudaLaunchConfig_t cfg = {};
        cfg.gridDim = dim3(96); cfg.blockDim = dim3(384); cfg.dynamicSmemBytes = R_SMEM; cfg.stream = st;
        cudaLaunchAttribute at[1];
        at[0].id = cudaLaunchAttributeClusterDimension; at[0].val.clusterDim.x = 3; at[0].val.clusterDim.y = 1; at[0].val.clusterDim.z = 1;
        cfg.attrs = at; cfg.numAttrs = 1;
        cudaLaunchKernelEx(&cfg, r_kernel, rm, mem0, x, gate_w);
    }
    {
        cudaLaunchConfig_t cfg = {};
        cfg.gridDim = dim3(n_sm - 96 > 32 ? n_sm - 96 : 32); cfg.blockDim = dim3(384); cfg.dynamicSmemBytes = G_SMEM; cfg.stream = st;
        cudaLaunchAttribute at[1];
        at[0].id = cudaLaunchAttributeProgrammaticStreamSerialization; at[0].val.programmaticStreamSerializationAllowed = 1;
        cfg.attrs = at; cfg.numAttrs = n_clusters < NH ? 0 : 1;
        cudaLaunchKernelEx(&cfg, g1_kernel, m1, (bf16*)d_out, 0);
    }
    {
        cudaLaunchConfig_t cfg = {};
        cfg.gridDim = dim3((64 - T_LATE) * 8); cfg.blockDim = dim3(384); cfg.dynamicSmemBytes = G_SMEM; cfg.stream = st;
        cudaLaunchAttribute at[1];
        at[0].id = cudaLaunchAttributeProgrammaticStreamSerialization; at[0].val.programmaticStreamSerializationAllowed = 1;
        cfg.attrs = at; cfg.numAttrs = 1;
        cudaLaunchKernelEx(&cfg, g1_kernel, m1, (bf16*)d_out, 1);
    }
}
```
